```python
import torch

def _softmax(x, axis=-1):
    return torch.softmax(x, dim=axis)
def _gelu(x):
    return torch.nn.functional.gelu(x, approximate="tanh")
def _silu(x):
    return torch.nn.functional.silu(x)
def _sigmoid(x):
    return torch.sigmoid(x)
def _layernorm(x, axis=-1, eps=1e-5):
    m = x.mean(dim=axis, keepdim=True)
    v = x.var(dim=axis, keepdim=True, unbiased=False)
    return (x - m) / torch.sqrt(v + eps)
def _scatter_add(tgt, idx, src, axis=0):
    return tgt.clone().index_add_(axis, idx, src)
def _segment_sum(src, seg, n):
    out = torch.zeros((n,) + src.shape[1:], dtype=src.dtype)
    return out.index_add_(0, seg, src)
def _pad(x, pw):
    flat = tuple(v for pair in reversed(pw) for v in pair)
    return torch.nn.functional.pad(x, flat)

kernel_name = 'sequential_preLN__grouped_kv_mqa__dense_activation_silu__prompt'

def setup_inputs():

    _w = (lambda a: (lambda t: t.to(torch.bfloat16) if t.is_floating_point() else t)(torch.as_tensor(a)))
    def _A_setup():
        B, S, D, H = 1, 2048, 576, 32
        Dh = D // H
        return {
            "x": _w((lambda *s: torch.randn(*s, dtype=torch.bfloat16) * 0.05)(B, S, D)),
            "wq": _w((lambda *s: torch.randn(*s, dtype=torch.bfloat16) * 0.05)(D, H * Dh)),
            "wk": _w((lambda *s: torch.randn(*s, dtype=torch.bfloat16) * 0.05)(D, Dh)),
            "wv": _w((lambda *s: torch.randn(*s, dtype=torch.bfloat16) * 0.05)(D, Dh)),
            "wo": _w((lambda *s: torch.randn(*s, dtype=torch.bfloat16) * 0.05)(H * Dh, D)),
        }
    _A_in = _A_setup()

    def _B_setup():
        B, S, D, F = 1, 2048, 576, 4608
        return {
            "x": _w((lambda *s: torch.randn(*s, dtype=torch.bfloat16) * 0.05)(B, S, D)),
            "w1": _w((lambda *s: torch.randn(*s, dtype=torch.bfloat16) * 1.6)(D, F) * (D ** -0.5)),
            "w2": _w((lambda *s: torch.randn(*s, dtype=torch.bfloat16) * 0.2)(F, D) * (F ** -0.5)),
        }
    _B_in = _B_setup()

    return {
        "A_x": _A_in["x"],
        "A_wq": _A_in["wq"],
        "A_wk": _A_in["wk"],
        "A_wv": _A_in["wv"],
        "A_wo": _A_in["wo"],
        "B_x": _B_in["x"],
        "B_w1": _B_in["w1"],
        "B_w2": _B_in["w2"],
    }

def reference(A_x, A_wq, A_wk, A_wv, A_wo, B_x, B_w1, B_w2):
    def _A_ref(x, wq, wk, wv, wo):
        B, S, D = x.shape
        H = 32
        Dh = D // H
        q = (lambda x, *d: x.permute(*d))((x @ wq).reshape(B, S, H, Dh), 0, 2, 1, 3)
        k = x @ wk
        v = x @ wv
        scores = torch.einsum("bhqd,bkd->bhqk", q, k) * (Dh ** -0.5)
        p = _softmax(scores, axis=-1)
        o = torch.einsum("bhqk,bkd->bhqd", p, v)
        return (lambda x, *d: x.permute(*d))(o, 0, 2, 1, 3).reshape(B, S, H * Dh) @ wo

    def _B_ref(x, w1, w2):
        h = torch.einsum("bsd,df->bsf", x, w1)
        h = _silu(h)
        out = torch.einsum("bsf,fd->bsd", h, w2)
        return out

    x = A_x
    h = x + _A_ref(_layernorm(x, axis=-1), A_wq, A_wk, A_wv, A_wo)
    h2 = h + _B_ref(_layernorm(h, axis=-1), B_w1, B_w2)
    return h2
```

```cpp
#include <cuda_runtime.h>
#include <cuda_bf16.h>
#include <cuda.h>
#include <stdint.h>

namespace {

constexpr int SEQ = 2048, DM = 576, FF = 4608;
constexpr int KV_BYTES = SEQ * 48;
constexpr float LN_EPS = 1e-5f;
constexpr float LOG2E = 1.4426950408889634f;
constexpr float Q_SCALE = 0.23570226039551584f * LOG2E;

constexpr uint32_t POLY_MASK = 0xB5B5u;
constexpr float FAST_BOUND = 60.0f;

__device__ __align__(1024) __nv_bfloat16 g_q[SEQ * DM];
__device__ __align__(1024) uint4 g_kc[KV_BYTES / 16];
__device__ __align__(1024) uint4 g_vc[KV_BYTES / 16];
__device__ float g_kmax[32];
__device__ __align__(1024) __nv_bfloat16 g_o[SEQ * DM];
__device__ __align__(1024) __nv_bfloat16 g_h[SEQ * DM];
__device__ float2 g_stat[6 * SEQ];
__device__ __align__(16) float g_cs1[FF];

#define TS(k, i)

__device__ __forceinline__ uint32_t smem_u32(const void* p) { return (uint32_t)__cvta_generic_to_shared(p); }
__device__ __forceinline__ void wg_fence() { asm volatile("wgmma.fence.sync.aligned;" ::: "memory"); }
__device__ __forceinline__ void wg_commit() { asm volatile("wgmma.commit_group.sync.aligned;" ::: "memory"); }
template <int N> __device__ __forceinline__ void wg_wait() { asm volatile("wgmma.wait_group.sync.aligned %0;" ::"n"(N) : "memory"); }
template <int N> __device__ __forceinline__ void pin(float (&r)[N]) {
#pragma unroll
    for (int i = 0; i < N; i++) asm volatile("" : "+f"(r[i])::"memory");
}
template <int N> __device__ __forceinline__ void pin(uint32_t (&r)[N]) {
#pragma unroll
    for (int i = 0; i < N; i++) asm volatile("" : "+r"(r[i])::"memory");
}
__device__ __forceinline__ constexpr uint32_t desc_hi(uint32_t sbo, uint32_t swz) { return (sbo >> 4) | (swz << 30); }
__device__ __forceinline__ uint32_t desc_lo(uint32_t addr, uint32_t lbo) { return ((addr & 0x3FFFF) >> 4) | ((lbo >> 4) << 16); }
__device__ __forceinline__ uint64_t desc64(uint32_t lo, uint32_t hi) { return ((uint64_t)hi << 32) | lo; }
constexpr uint32_t SMEM0 = 0x400;
__host__ __device__ constexpr uint64_t cdesc(uint32_t off, uint32_t lbo, uint32_t sbo, uint32_t swz) {
    return (uint64_t)(((SMEM0 + off) & 0x3FFFF) >> 4) | ((uint64_t)(lbo >> 4) << 16) | ((uint64_t)(sbo >> 4) << 32) | ((uint64_t)swz << 62);
}
__device__ __forceinline__ void check_smem_base(uint32_t base) { if ((base & 0x3FFFF) != SMEM0) __trap(); }

__device__ __forceinline__ void mbar_init(uint32_t bar, int cnt) { asm volatile("mbarrier.init.shared::cta.b64 [%0], %1;" ::"r"(bar), "r"(cnt) : "memory"); }
__device__ __forceinline__ void mbar_expect(uint32_t bar, int bytes) { asm volatile("mbarrier.arrive.expect_tx.shared::cta.b64 _, [%0], %1;" ::"r"(bar), "r"(bytes) : "memory"); }
__device__ __forceinline__ void mbar_arrive(uint32_t bar) { asm volatile("mbarrier.arrive.shared::cta.b64 _, [%0];" ::"r"(bar) : "memory"); }
__device__ __forceinline__ void mbar_wait(uint32_t bar, uint32_t parity) {
    asm volatile(
        "{\n.reg .pred p;\n.reg .u32 n;\nmov.u32 n, 0;\n"
        "LAB_WAIT:\n"
        "mbarrier.try_wait.parity.shared::cta.b64 p, [%0], %1;\n"
        "@p bra DONE;\n"
        "add.u32 n, n, 1;\n"
        "setp.lt.u32 p, n, 4000000;\n"
        "@p bra LAB_WAIT;\n"
        "trap;\n"
        "DONE:\n}\n" ::"r"(bar), "r"(parity) : "memory");
}
__device__ __forceinline__ void bar_init_fence() {
    asm volatile("fence.mbarrier_init.release.cluster;" ::: "memory");
    asm volatile("fence.proxy.async.shared::cta;" ::: "memory");
}
__device__ __forceinline__ void proxy_fence() { asm volatile("fence.proxy.async.shared::cta;" ::: "memory"); }
__device__ __forceinline__ void named_sync(int id, int n) { asm volatile("bar.sync %0, %1;" ::"r"(id), "r"(n) : "memory"); }
__device__ __forceinline__ void bulk_g2s(uint32_t dst, const void* src, int bytes, uint32_t bar) {
    asm volatile("cp.async.bulk.shared::cluster.global.mbarrier::complete_tx::bytes [%0], [%1], %2, [%3];" ::"r"(dst), "l"(src), "r"(bytes), "r"(bar) : "memory");
}
__device__ __forceinline__ void tma_2d(uint32_t dst, const CUtensorMap* tm, int c0, int c1, uint32_t bar) {
    asm volatile("cp.async.bulk.tensor.2d.shared::cluster.global.mbarrier::complete_tx::bytes [%0], [%1, {%3, %4}], [%2];" ::"r"(dst), "l"(tm), "r"(bar), "r"(c0), "r"(c1) : "memory");
}
__device__ __forceinline__ void tma_red_2d(const CUtensorMap* tm, int c0, int c1, uint32_t src) {
    asm volatile("cp.reduce.async.bulk.tensor.2d.global.shared::cta.add.tile.bulk_group [%0, {%2, %3}], [%1];" ::"l"(tm), "r"(src), "r"(c0), "r"(c1) : "memory");
}
__device__ __forceinline__ void tma_st_2d(const CUtensorMap* tm, int c0, int c1, uint32_t src) {
    asm volatile("cp.async.bulk.tensor.2d.global.shared::cta.tile.bulk_group [%0, {%2, %3}], [%1];" ::"l"(tm), "r"(src), "r"(c0), "r"(c1) : "memory");
}
__device__ __forceinline__ void bulk_commit() { asm volatile("cp.async.bulk.commit_group;" ::: "memory"); }
__device__ __forceinline__ void bulk_wait_all() { asm volatile("cp.async.bulk.wait_group 0;" ::: "memory"); }
__device__ __forceinline__ bool elect_one() {
    uint32_t p;
    asm volatile("{\n.reg .pred P;\nelect.sync _|P, 0xffffffff;\nselp.b32 %0, 1, 0, P;\n}\n" : "=r"(p));
    return p != 0;
}
__device__ __forceinline__ void prefetch_l2(const void* p, int bytes) { asm volatile("cp.async.bulk.prefetch.L2.global [%0], %1;" ::"l"(p), "r"(bytes) : "memory"); }
__device__ __forceinline__ void pdl_launch() { asm volatile("griddepcontrol.launch_dependents;" ::: "memory"); }
__device__ __forceinline__ void pdl_wait() { asm volatile("griddepcontrol.wait;" ::: "memory"); }
__device__ __forceinline__ float ex2(float x) { float y; asm("ex2.approx.ftz.f32 %0, %1;" : "=f"(y) : "f"(x)); return y; }
__device__ __forceinline__ float rcp(float x) { float y; asm("rcp.approx.ftz.f32 %0, %1;" : "=f"(y) : "f"(x)); return y; }
__device__ __forceinline__ uint32_t pack_bf16(float lo, float hi) { uint32_t r; asm("cvt.rn.bf16x2.f32 %0, %1, %2;" : "=r"(r) : "f"(hi), "f"(lo)); return r; }
__device__ __forceinline__ float bf_lo(uint32_t v) { return __uint_as_float(v << 16); }
__device__ __forceinline__ float bf_hi(uint32_t v) { return __uint_as_float(v & 0xFFFF0000u); }
__device__ __forceinline__ uint32_t hfma2(uint32_t a, uint32_t b, uint32_t c) { uint32_t r; asm("fma.rn.f16x2 %0, %1, %2, %3;" : "=r"(r) : "r"(a), "r"(b), "r"(c)); return r; }
__device__ __forceinline__ void stmatrix_x4(uint32_t addr, uint32_t r0, uint32_t r1, uint32_t r2, uint32_t r3) {
    asm volatile("stmatrix.sync.aligned.m8n8.x4.shared.b16 [%0], {%1, %2, %3, %4};" ::"r"(addr), "r"(r0), "r"(r1), "r"(r2), "r"(r3) : "memory");
}

template <int TB> __device__ __forceinline__ void wgmma_ss_n24(float (&d)[12], uint64_t da, uint64_t db, int sc) {
    asm volatile("{\n.reg .pred p;\nsetp.ne.b32 p, %14, 0;\n"
        "wgmma.mma_async.sync.aligned.m64n24k16.f32.bf16.bf16 {%0, %1, %2, %3, %4, %5, %6, %7, %8, %9, %10, %11}, %12, %13, p, 1, 1, 0, %15;\n}\n"
        : "+f"(d[0]), "+f"(d[1]), "+f"(d[2]), "+f"(d[3]), "+f"(d[4]), "+f"(d[5]), "+f"(d[6]), "+f"(d[7]), "+f"(d[8]), "+f"(d[9]), "+f"(d[10]), "+f"(d[11])
        : "l"(da), "l"(db), "r"(sc), "n"(TB));
}
template <int TB> __device__ __forceinline__ void wgmma_ss_n64(float (&d)[32], uint64_t da, uint64_t db, int sc) {
    asm volatile("{\n.reg .pred p;\nsetp.ne.b32 p, %34, 0;\n"
        "wgmma.mma_async.sync.aligned.m64n64k16.f32.bf16.bf16 {%0, %1, %2, %3, %4, %5, %6, %7, %8, %9, %10, %11, %12, %13, %14, %15, %16, %17, %18, %19, %20, %21, %22, %23, %24, %25, %26, %27, %28, %29, %30, %31}, %32, %33, p, 1, 1, 0, %35;\n}\n"
        : "+f"(d[0]), "+f"(d[1]), "+f"(d[2]), "+f"(d[3]), "+f"(d[4]), "+f"(d[5]), "+f"(d[6]), "+f"(d[7]), "+f"(d[8]), "+f"(d[9]), "+f"(d[10]), "+f"(d[11]), "+f"(d[12]), "+f"(d[13]), "+f"(d[14]), "+f"(d[15]), "+f"(d[16]), "+f"(d[17]), "+f"(d[18]), "+f"(d[19]), "+f"(d[20]), "+f"(d[21]), "+f"(d[22]), "+f"(d[23]), "+f"(d[24]), "+f"(d[25]), "+f"(d[26]), "+f"(d[27]), "+f"(d[28]), "+f"(d[29]), "+f"(d[30]), "+f"(d[31])
        : "l"(da), "l"(db), "r"(sc), "n"(TB));
}
template <int TB> __device__ __forceinline__ void wgmma_ss_n128(float (&d)[64], uint64_t da, uint64_t db, int sc) {
    asm volatile("{\n.reg .pred p;\nsetp.ne.b32 p, %66, 0;\n"
        "wgmma.mma_async.sync.aligned.m64n128k16.f32.bf16.bf16 {%0, %1, %2, %3, %4, %5, %6, %7, %8, %9, %10, %11, %12, %13, %14, %15, %16, %17, %18, %19, %20, %21, %22, %23, %24, %25, %26, %27, %28, %29, %30, %31, %32, %33, %34, %35, %36, %37, %38, %39, %40, %41, %42, %43, %44, %45, %46, %47, %48, %49, %50, %51, %52, %53, %54, %55, %56, %57, %58, %59, %60, %61, %62, %63}, %64, %65, p, 1, 1, 0, %67;\n}\n"
        : "+f"(d[0]), "+f"(d[1]), "+f"(d[2]), "+f"(d[3]), "+f"(d[4]), "+f"(d[5]), "+f"(d[6]), "+f"(d[7]), "+f"(d[8]), "+f"(d[9]), "+f"(d[10]), "+f"(d[11]), "+f"(d[12]), "+f"(d[13]), "+f"(d[14]), "+f"(d[15]), "+f"(d[16]), "+f"(d[17]), "+f"(d[18]), "+f"(d[19]), "+f"(d[20]), "+f"(d[21]), "+f"(d[22]), "+f"(d[23]), "+f"(d[24]), "+f"(d[25]), "+f"(d[26]), "+f"(d[27]), "+f"(d[28]), "+f"(d[29]), "+f"(d[30]), "+f"(d[31]), "+f"(d[32]), "+f"(d[33]), "+f"(d[34]), "+f"(d[35]), "+f"(d[36]), "+f"(d[37]), "+f"(d[38]), "+f"(d[39]), "+f"(d[40]), "+f"(d[41]), "+f"(d[42]), "+f"(d[43]), "+f"(d[44]), "+f"(d[45]), "+f"(d[46]), "+f"(d[47]), "+f"(d[48]), "+f"(d[49]), "+f"(d[50]), "+f"(d[51]), "+f"(d[52]), "+f"(d[53]), "+f"(d[54]), "+f"(d[55]), "+f"(d[56]), "+f"(d[57]), "+f"(d[58]), "+f"(d[59]), "+f"(d[60]), "+f"(d[61]), "+f"(d[62]), "+f"(d[63])
        : "l"(da), "l"(db), "r"(sc), "n"(TB));
}
template <int TB> __device__ __forceinline__ void wgmma_rs_n24(float (&d)[12], uint32_t a0, uint32_t a1, uint32_t a2, uint32_t a3, uint64_t db, int sc) {
    asm volatile("{\n.reg .pred p;\nsetp.ne.b32 p, %17, 0;\n"
        "wgmma.mma_async.sync.aligned.m64n24k16.f32.bf16.bf16 {%0, %1, %2, %3, %4, %5, %6, %7, %8, %9, %10, %11}, {%12, %13, %14, %15}, %16, p, 1, 1, %18;\n}\n"
        : "+f"(d[0]), "+f"(d[1]), "+f"(d[2]), "+f"(d[3]), "+f"(d[4]), "+f"(d[5]), "+f"(d[6]), "+f"(d[7]), "+f"(d[8]), "+f"(d[9]), "+f"(d[10]), "+f"(d[11])
        : "r"(a0), "r"(a1), "r"(a2), "r"(a3), "l"(db), "r"(sc), "n"(TB));
}
template <int TB> __device__ __forceinline__ void wgmma_rs_n64(float (&d)[32], uint32_t a0, uint32_t a1, uint32_t a2, uint32_t a3, uint64_t db, int sc) {
    asm volatile("{\n.reg .pred p;\nsetp.ne.b32 p, %37, 0;\n"
        "wgmma.mma_async.sync.aligned.m64n64k16.f32.bf16.bf16 {%0, %1, %2, %3, %4, %5, %6, %7, %8, %9, %10, %11, %12, %13, %14, %15, %16, %17, %18, %19, %20, %21, %22, %23, %24, %25, %26, %27, %28, %29, %30, %31}, {%32, %33, %34, %35}, %36, p, 1, 1, %38;\n}\n"
        : "+f"(d[0]), "+f"(d[1]), "+f"(d[2]), "+f"(d[3]), "+f"(d[4]), "+f"(d[5]), "+f"(d[6]), "+f"(d[7]), "+f"(d[8]), "+f"(d[9]), "+f"(d[10]), "+f"(d[11]), "+f"(d[12]), "+f"(d[13]), "+f"(d[14]), "+f"(d[15]), "+f"(d[16]), "+f"(d[17]), "+f"(d[18]), "+f"(d[19]), "+f"(d[20]), "+f"(d[21]), "+f"(d[22]), "+f"(d[23]), "+f"(d[24]), "+f"(d[25]), "+f"(d[26]), "+f"(d[27]), "+f"(d[28]), "+f"(d[29]), "+f"(d[30]), "+f"(d[31])
        : "r"(a0), "r"(a1), "r"(a2), "r"(a3), "l"(db), "r"(sc), "n"(TB));
}
template <int TB> __device__ __forceinline__ void wgmma_rs_n128(float (&d)[64], uint32_t a0, uint32_t a1, uint32_t a2, uint32_t a3, uint64_t db, int sc) {
    asm volatile("{\n.reg .pred p;\nsetp.ne.b32 p, %69, 0;\n"
        "wgmma.mma_async.sync.aligned.m64n128k16.f32.bf16.bf16 {%0, %1, %2, %3, %4, %5, %6, %7, %8, %9, %10, %11, %12, %13, %14, %15, %16, %17, %18, %19, %20, %21, %22, %23, %24, %25, %26, %27, %28, %29, %30, %31, %32, %33, %34, %35, %36, %37, %38, %39, %40, %41, %42, %43, %44, %45, %46, %47, %48, %49, %50, %51, %52, %53, %54, %55, %56, %57, %58, %59, %60, %61, %62, %63}, {%64, %65, %66, %67}, %68, p, 1, 1, %70;\n}\n"
        : "+f"(d[0]), "+f"(d[1]), "+f"(d[2]), "+f"(d[3]), "+f"(d[4]), "+f"(d[5]), "+f"(d[6]), "+f"(d[7]), "+f"(d[8]), "+f"(d[9]), "+f"(d[10]), "+f"(d[11]), "+f"(d[12]), "+f"(d[13]), "+f"(d[14]), "+f"(d[15]), "+f"(d[16]), "+f"(d[17]), "+f"(d[18]), "+f"(d[19]), "+f"(d[20]), "+f"(d[21]), "+f"(d[22]), "+f"(d[23]), "+f"(d[24]), "+f"(d[25]), "+f"(d[26]), "+f"(d[27]), "+f"(d[28]), "+f"(d[29]), "+f"(d[30]), "+f"(d[31]), "+f"(d[32]), "+f"(d[33]), "+f"(d[34]), "+f"(d[35]), "+f"(d[36]), "+f"(d[37]), "+f"(d[38]), "+f"(d[39]), "+f"(d[40]), "+f"(d[41]), "+f"(d[42]), "+f"(d[43]), "+f"(d[44]), "+f"(d[45]), "+f"(d[46]), "+f"(d[47]), "+f"(d[48]), "+f"(d[49]), "+f"(d[50]), "+f"(d[51]), "+f"(d[52]), "+f"(d[53]), "+f"(d[54]), "+f"(d[55]), "+f"(d[56]), "+f"(d[57]), "+f"(d[58]), "+f"(d[59]), "+f"(d[60]), "+f"(d[61]), "+f"(d[62]), "+f"(d[63])
        : "r"(a0), "r"(a1), "r"(a2), "r"(a3), "l"(db), "r"(sc), "n"(TB));
}

constexpr int P_THREADS = 288;
constexpr int P_NST = 6;
constexpr int P_A_BYTES = 9 * 8192;
constexpr int P_B_STAGE = 3 * 8192;
constexpr int P_SMEM = P_A_BYTES + P_NST * P_B_STAGE + 256;
constexpr uint32_t HI_SW128 = (1024u >> 4) | (1u << 30);

template <int NCOL, bool WAIT_A>
__device__ __forceinline__ void proj_mma(float (&acc)[NCOL / 2], uint32_t sA, uint32_t sB, uint32_t colofs, uint32_t fullB, uint32_t emptyB, uint32_t fullA, int lane) {
#pragma unroll 1
    for (int kb = 0; kb < 9; kb++) {
        const int s = kb >= P_NST ? kb - P_NST : kb;
        if (WAIT_A) mbar_wait(fullA + kb * 8, 0);
        mbar_wait(fullB + s * 8, kb >= P_NST ? 1 : 0);
        const uint32_t alo = desc_lo(sA + kb * 8192, 16), blo = desc_lo(sB + s * P_B_STAGE + colofs, 8192);
        wg_fence();
#pragma unroll
        for (int ks = 0; ks < 4; ks++) {
            const uint64_t da = desc64(alo + ks * 2, HI_SW128), db = desc64(blo + ks * 128, HI_SW128);
            if constexpr (NCOL == 128) wgmma_ss_n128<1>(acc, da, db, (kb | ks) != 0);
            else wgmma_ss_n64<1>(acc, da, db, (kb | ks) != 0);
        }
        wg_commit();
        if (kb + P_NST < 9 + 1) {
            wg_wait<1>();
            if (kb >= 1 && kb - 1 + P_NST < 9 && lane == 0) mbar_arrive(emptyB + (kb - 1) * 8);
        }
    }
    wg_wait<0>();
    pin(acc);
}

template <int NB>
__device__ __forceinline__ void stage_tile(const uint32_t (&pk)[NB * 2], uint32_t base, int w, int lane) {
    const int r = w * 16 + (lane & 7) + ((lane >> 3) & 1) * 8;
#pragma unroll
    for (int b = 0; b < NB; b += 2) {
        const uint32_t a = base + (b >> 3) * 8192 + r * 128 + ((((b & 7) + (lane >> 4)) ^ (r & 7)) << 4);
        stmatrix_x4(a, pk[2 * b], pk[2 * b + 1], pk[2 * b + 2], pk[2 * b + 3]);
    }
}

__global__ void __launch_bounds__(P_THREADS, 1)
k_qkv(const __grid_constant__ CUtensorMap tmWq, const __grid_constant__ CUtensorMap tmQ, const __nv_bfloat16* __restrict__ x, const __nv_bfloat16* __restrict__ wk, const __nv_bfloat16* __restrict__ wv) {
    extern __shared__ __align__(1024) uint8_t smem[];
    const uint32_t sA = smem_u32(smem), sB = sA + P_A_BYTES, bars = sB + P_NST * P_B_STAGE;
    const uint32_t fullB = bars, emptyB = bars + 64;
    const int tid = threadIdx.x, warp = __shfl_sync(~0u, tid >> 5, 0), lane = tid & 31;
    const bool isQ = blockIdx.x < 96;
    const int m = isQ ? blockIdx.x / 3 : blockIdx.x - 96, cg = blockIdx.x % 3;
    if (tid == 0) TS(0, 0);
    if (tid == 0) {
        for (int i = 0; i < P_NST; i++) { mbar_init(fullB + i * 8, 1); mbar_init(emptyB + i * 8, 8); }
        bar_init_fence();
    }
    __syncthreads();
    pdl_launch();
    if (warp == 8) {
        if (isQ && elect_one()) {
            for (int kb = 0; kb < 9; kb++) {
                const int s = kb >= P_NST ? kb - P_NST : kb;
                if (kb >= P_NST) mbar_wait(emptyB + s * 8, 0);
                mbar_expect(fullB + s * 8, P_B_STAGE);
                for (int a = 0; a < 3; a++) tma_2d(sB + s * P_B_STAGE + a * 8192, &tmWq, cg * 192 + a * 64, kb * 64, fullB + s * 8);
            }
        }
        return;
    }
    {
        const int row = tid >> 2, q = tid & 3;
        const uint4* src = reinterpret_cast<const uint4*>(x + (size_t)(m * 64 + row) * DM) + q;
        uint4 v[18];
#pragma unroll
        for (int i = 0; i < 18; i++) v[i] = __ldg(src + 4 * i);
        if (!isQ) {
            const uint32_t* wk32 = reinterpret_cast<const uint32_t*>(wk);
            const uint32_t* wv32 = reinterpret_cast<const uint32_t*>(wv);
            uint32_t wreg[41];
#pragma unroll
            for (int i = 0; i < 41; i++) {
                const int idx = tid + i * 256;
                wreg[i] = idx < DM * 9 ? __ldg(wk32 + idx) : (idx < 2 * DM * 9 ? __ldg(wv32 + idx - DM * 9) : 0u);
            }
#pragma unroll
            for (int i = 0; i < 41; i++) {
                const int idx = tid + i * 256;
                if (idx < 2 * DM * 9) {
                    const int sel = idx >= DM * 9, j = idx - sel * DM * 9, k = j / 9, n = (j - k * 9) * 2;
                    const uint32_t a = sB + (sel * 3 + (n >> 3)) * 9216 + (k >> 3) * 128 + (n & 7) * 16 + (k & 7) * 2;
                    asm volatile("st.shared.u16 [%0], %1;" ::"r"(a), "h"((uint16_t)(wreg[i] & 0xFFFF)) : "memory");
                    asm volatile("st.shared.u16 [%0], %1;" ::"r"(a + 16), "h"((uint16_t)(wreg[i] >> 16)) : "memory");
                }
            }
        }
        float sum = 0.f;
#pragma unroll
        for (int i = 0; i < 18; i++) {
            sum += (bf_lo(v[i].x) + bf_hi(v[i].x)) + (bf_lo(v[i].y) + bf_hi(v[i].y)) + (bf_lo(v[i].z) + bf_hi(v[i].z)) + (bf_lo(v[i].w) + bf_hi(v[i].w));
        }
        sum += __shfl_xor_sync(~0u, sum, 1); sum += __shfl_xor_sync(~0u, sum, 2);
        const float mean = sum * (1.0f / DM);
        float sq = 0.f;
#pragma unroll
        for (int i = 0; i < 18; i++) {
            const uint32_t w[4] = {v[i].x, v[i].y, v[i].z, v[i].w};
#pragma unroll
            for (int j = 0; j < 4; j++) { const float a = bf_lo(w[j]) - mean, b = bf_hi(w[j]) - mean; sq = fmaf(a, a, sq); sq = fmaf(b, b, sq); }
        }
        sq += __shfl_xor_sync(~0u, sq, 1); sq += __shfl_xor_sync(~0u, sq, 2);
        const float rstd = rsqrtf(sq * (1.0f / DM) + LN_EPS), nmr = -mean * rstd;
#pragma unroll
        for (int i = 0; i < 18; i++) {
            const int c = q + 4 * i;
            const uint32_t w[4] = {v[i].x, v[i].y, v[i].z, v[i].w};
            uint32_t o[4];
#pragma unroll
            for (int j = 0; j < 4; j++) o[j] = pack_bf16(fmaf(bf_lo(w[j]), rstd, nmr), fmaf(bf_hi(w[j]), rstd, nmr));
            const uint32_t a = sA + (c >> 3) * 8192 + row * 128 + (((c & 7) ^ (row & 7)) << 4);
            asm volatile("st.shared.v4.b32 [%0], {%1, %2, %3, %4};" ::"r"(a), "r"(o[0]), "r"(o[1]), "r"(o[2]), "r"(o[3]) : "memory");
        }
    }
    proxy_fence();
    named_sync(1, 256);
    if (tid == 0) TS(0, 1);
    const int wg = warp >> 2, w = warp & 3, g = lane >> 2, t = lane & 3;
    const int r0 = m * 64 + w * 16 + g;
    if (isQ) {
        if (wg == 0) {
            float acc[64];
            proj_mma<128, false>(acc, sA, sB, 0, fullB, emptyB, 0, lane);
            if (tid == 0) TS(0, 2);
            named_sync(1, 256);
            uint32_t pk[32];
#pragma unroll
            for (int i = 0; i < 32; i++) pk[i] = pack_bf16(acc[2 * i] * Q_SCALE, acc[2 * i + 1] * Q_SCALE);
            stage_tile<16>(pk, sA, w, lane);
        } else {
            float acc[32];
            proj_mma<64, false>(acc, sA, sB, 2 * 8192, fullB, emptyB, 0, lane);
            named_sync(1, 256);
            uint32_t pk[16];
#pragma unroll
            for (int i = 0; i < 16; i++) pk[i] = pack_bf16(acc[2 * i] * Q_SCALE, acc[2 * i + 1] * Q_SCALE);
            stage_tile<8>(pk, sA + 2 * 8192, w, lane);
        }
        proxy_fence();
        named_sync(1, 256);
        if (warp == 0 && elect_one()) {
            for (int a = 0; a < 3; a++) tma_st_2d(&tmQ, cg * 192 + a * 64, m * 64, sA + a * 8192);
            bulk_commit();
            bulk_wait_all();
        }
    } else {
        float acc[12];
        const uint32_t blo = desc_lo(sB + wg * 3 * 9216, 128);
#pragma unroll 1
        for (int kb = 0; kb < 9; kb++) {
            const uint32_t alo = desc_lo(sA + kb * 8192, 16);
            wg_fence();
#pragma unroll
            for (int ks = 0; ks < 4; ks++)
                wgmma_ss_n24<0>(acc, desc64(alo + ks * 2, HI_SW128), desc64(blo + (kb * 4 + ks) * 16, desc_hi(9216, 0)), (kb | ks) != 0);
        }
        wg_commit();
        wg_wait<0>();
        pin(acc);
        uint32_t pk[6];
#pragma unroll
        for (int i = 0; i < 6; i++) pk[i] = pack_bf16(acc[2 * i], acc[2 * i + 1]);
        float n0 = 0.f, n1 = 0.f, vm = 0.f;
#pragma unroll
        for (int b = 0; b < 3; b++) {
            if (b < 2 || t == 0) {
                const float a = bf_lo(pk[2 * b]), c = bf_hi(pk[2 * b]), d = bf_lo(pk[2 * b + 1]), e = bf_hi(pk[2 * b + 1]);
                n0 = fmaf(a, a, fmaf(c, c, n0)); n1 = fmaf(d, d, fmaf(e, e, n1));
            }
        }
        n0 += __shfl_xor_sync(~0u, n0, 1); n0 += __shfl_xor_sync(~0u, n0, 2);
        n1 += __shfl_xor_sync(~0u, n1, 1); n1 += __shfl_xor_sync(~0u, n1, 2);
        vm = fmaxf(n0, n1);
        if (!(vm == vm)) vm = __int_as_float(0x7F800000);
#pragma unroll
        for (int o = 4; o < 32; o <<= 1) vm = fmaxf(vm, __shfl_xor_sync(~0u, vm, o));
        if (t != 0) {
            uint32_t lo, hi;
            if (wg == 0) {
                const int grp = m * 8 + w * 2;
                const uint32_t c = t == 1 ? 0x42FE3F80u   : (t == 2 ? 0x00003BC0u   : 0u);
                lo = ((POLY_MASK >> (grp & 15)) & 1) ? c : 0u;
                hi = ((POLY_MASK >> ((grp + 1) & 15)) & 1) ? c : 0u;
            } else {
                lo = hi = t == 1 ? 0x00003F80u : 0u;
            }
            pk[4] = lo; pk[5] = hi;
        }
        uint32_t* dst = reinterpret_cast<uint32_t*>(wg == 0 ? g_kc : g_vc) + (m * 8 + w * 2) * 96 + g * 4 + t;
#pragma unroll
        for (int b = 0; b < 3; b++) { dst[b * 32] = pk[2 * b]; dst[96 + b * 32] = pk[2 * b + 1]; }
        float* red = reinterpret_cast<float*>(smem + P_A_BYTES + 6 * 9216);
        if (lane == 0) red[warp] = (wg == 0) ? vm : (vm <= 1e24f ? 0.f : __int_as_float(0x7F800000));
        named_sync(1, 256);
        if (tid == 0) {
            float mx = red[0];
#pragma unroll
            for (int i = 1; i < 8; i++) mx = fmaxf(mx, red[i]);
            g_kmax[m] = mx;
        }
    }
    if (tid == 0) TS(0, 3);
}

constexpr int A_THREADS = 512;
constexpr int A_NPIECE = 8;
constexpr int A_SMEM = 2 * KV_BYTES + 128;

__device__ __forceinline__ uint32_t exp2_pair_fixed(float lo, float hi) {
    const uint32_t G = __byte_perm(__float_as_uint(lo), __float_as_uint(hi), 0x5410);
    const uint32_t Hh = G & 0x007F007Fu;
    const uint32_t tt = hfma2(Hh, 0xF96BF96Bu, 0x358C358Cu);
    return G - hfma2(tt, Hh, 0u);
}

__device__ __forceinline__ void attn_side_job(const __nv_bfloat16* __restrict__ w1, const __nv_bfloat16* __restrict__ w2, const __nv_bfloat16* __restrict__ wo, uint8_t* smem) {
    const int e = blockIdx.x - 128, tid = threadIdx.x;
    if (tid < 32) {
        const char* p = reinterpret_cast<const char*>(wo) + e * (DM * DM * 2 / 4);
        for (int i = tid; i < DM * DM * 2 / 4 / 4608; i += 32) prefetch_l2(p + i * 4608, 4608);
    }
    float* red = reinterpret_cast<float*>(smem);
    if (tid < 432) {
        const int c = tid % 144, rg = tid / 144;
        const uint4* src = reinterpret_cast<const uint4*>(w1 + (size_t)rg * 192 * FF + e * 1152) + c;
        float s[8] = {0.f, 0.f, 0.f, 0.f, 0.f, 0.f, 0.f, 0.f};
#pragma unroll 8
        for (int r = 0; r < 192; r++) {
            const uint4 v = __ldg(src + (size_t)r * (FF / 8));
            s[0] += bf_lo(v.x); s[1] += bf_hi(v.x); s[2] += bf_lo(v.y); s[3] += bf_hi(v.y);
            s[4] += bf_lo(v.z); s[5] += bf_hi(v.z); s[6] += bf_lo(v.w); s[7] += bf_hi(v.w);
        }
#pragma unroll
        for (int i = 0; i < 8; i++) red[rg * 1152 + c * 8 + i] = s[i];
    }
    __syncthreads();
    for (int i = tid; i < 1152; i += A_THREADS) g_cs1[e * 1152 + i] = red[i] + red[1152 + i] + red[2304 + i];
    if (tid < 32) {
        const char* p = reinterpret_cast<const char*>(w2) + (size_t)e * (FF * DM * 2 / 4);
        for (int i = tid; i < FF * DM * 2 / 4 / 9216; i += 32) prefetch_l2(p + (size_t)i * 9216, 9216);
    }
}

__global__ void __launch_bounds__(A_THREADS, 1)
k_attn(const __nv_bfloat16* __restrict__ w1, const __nv_bfloat16* __restrict__ w2, const __nv_bfloat16* __restrict__ wo) {
    extern __shared__ __align__(1024) uint8_t smem[];
    pdl_launch();
    if (blockIdx.x >= 128) { attn_side_job(w1, w2, wo, smem); return; }
    const uint32_t sK = smem_u32(smem), sV = sK + KV_BYTES, bars = sV + KV_BYTES;
    const int tid = threadIdx.x;
    if (tid == 0) TS(1, 0);
    if (tid == 0) {
        for (int i = 0; i < A_NPIECE; i++) mbar_init(bars + i * 8, 1);
        bar_init_fence();
    }
    __syncthreads();
    pdl_wait();
    if (tid == 0) TS(1, 1);
    if (tid < 32 && elect_one()) {
        constexpr int PB = KV_BYTES / A_NPIECE;
        for (int i = 0; i < A_NPIECE; i++) {
            mbar_expect(bars + i * 8, 2 * PB);
            bulk_g2s(sK + i * PB, reinterpret_cast<const char*>(g_kc) + i * PB, PB, bars + i * 8);
            bulk_g2s(sV + i * PB, reinterpret_cast<const char*>(g_vc) + i * PB, PB, bars + i * 8);
        }
    }
    const int wg = __shfl_sync(~0u, tid >> 7, 0), w = (tid >> 5) & 3, lane = tid & 31, g = lane >> 2, t = lane & 3;
    const uint32_t* q32 = reinterpret_cast<const uint32_t*>(g_q);
    uint32_t* o32 = reinterpret_cast<uint32_t*>(g_o);
    float kmax2 = g_kmax[lane];
#pragma unroll
    for (int o = 1; o < 32; o <<= 1) kmax2 = fmaxf(kmax2, __shfl_xor_sync(~0u, kmax2, o));
    constexpr uint32_t HI_K = desc_hi(384, 0), HI_V = desc_hi(128, 0);
    const uint32_t k0lo = desc_lo(sK, 128), k1lo = desc_lo(sK + 256, 0), vlo = desc_lo(sV, 384);

    int row = (blockIdx.x * 8 + wg) * 64 + w * 16 + g;
    uint32_t nq[6];
    nq[0] = q32[row * 9 + t]; nq[1] = q32[(row + 8) * 9 + t]; nq[2] = q32[row * 9 + 4 + t]; nq[3] = q32[(row + 8) * 9 + 4 + t];
    nq[4] = q32[row * 9 + 8]; nq[5] = q32[(row + 8) * 9 + 8];
#pragma unroll 1
    for (int rep = 0; rep < 2; rep++, row += 256) {
        uint32_t qa[4] = {nq[0], nq[1], nq[2], nq[3]}, qb[4];
        float n0, n1;
        {
            const float a0 = bf_lo(qa[0]), a1 = bf_hi(qa[0]), a2 = bf_lo(qa[2]), a3 = bf_hi(qa[2]);
            const float b0 = bf_lo(qa[1]), b1 = bf_hi(qa[1]), b2 = bf_lo(qa[3]), b3 = bf_hi(qa[3]);
            n0 = a0 * a0 + a1 * a1 + a2 * a2 + a3 * a3; n1 = b0 * b0 + b1 * b1 + b2 * b2 + b3 * b3;
            if (t == 0) {
                const float c0 = bf_lo(nq[4]), c1 = bf_hi(nq[4]), d0 = bf_lo(nq[5]), d1 = bf_hi(nq[5]);
                n0 += c0 * c0 + c1 * c1; n1 += d0 * d0 + d1 * d1;
            }
            n0 += __shfl_xor_sync(~0u, n0, 1); n0 += __shfl_xor_sync(~0u, n0, 2);
            n1 += __shfl_xor_sync(~0u, n1, 1); n1 += __shfl_xor_sync(~0u, n1, 2);
        }
        const uint32_t x0 = nq[4], x1 = nq[5];
        if (rep == 0) {
            const int nr = row + 256;
            nq[0] = q32[nr * 9 + t]; nq[1] = q32[(nr + 8) * 9 + t]; nq[2] = q32[nr * 9 + 4 + t]; nq[3] = q32[(nr + 8) * 9 + 4 + t];
            nq[4] = q32[nr * 9 + 8]; nq[5] = q32[(nr + 8) * 9 + 8];
        }
        const bool unsafe = !(fmaxf(n0, n1) * kmax2 <= FAST_BOUND * FAST_BOUND);
        uint32_t any_unsafe;
        asm volatile("{\n.reg .pred p, q;\nsetp.ne.u32 p, %1, 0;\nbar.red.or.pred q, %2, 128, p;\nselp.u32 %0, 1, 0, q;\n}\n" : "=r"(any_unsafe) : "r"((uint32_t)unsafe), "r"(wg + 1) : "memory");
        if (tid == 0) TS(1, 2 + rep * 2);
        float o[12];
#pragma unroll
        for (int i = 0; i < 12; i++) o[i] = 0.f;
        if (!any_unsafe) {
            float s[64];
            const uint32_t cst = t == 1 ? 0x3F804780u   : (t == 2 ? 0x00003F80u   : 0u);
            qb[0] = t == 0 ? x0 : cst; qb[1] = t == 0 ? x1 : cst; qb[2] = 0; qb[3] = 0;
            pin(qa); pin(qb); pin(o);
#pragma unroll 1
            for (int j = 0; j < 16; j++) {
                if (rep == 0 && (j & 1) == 0) mbar_wait(bars + (j >> 1) * 8, 0);
                const uint32_t off = j * (16 * 384 >> 4);
                wg_fence();
                wgmma_rs_n128<0>(s, qa[0], qa[1], qa[2], qa[3], desc64(k0lo + off, HI_K), 0);
                wgmma_rs_n128<0>(s, qb[0], qb[1], qb[2], qb[3], desc64(k1lo + off, HI_K), 1);
                wg_commit();
                wg_wait<0>();
                pin(s);
                uint32_t p[32];
#pragma unroll
                for (int i = 0; i < 32; i++) {
                    if ((POLY_MASK >> (i >> 1)) & 1) p[i] = exp2_pair_fixed(s[2 * i], s[2 * i + 1]);
                    else p[i] = pack_bf16(ex2(s[2 * i]), ex2(s[2 * i + 1]));
                }
                pin(p);
                wg_fence();
#pragma unroll
                for (int k = 0; k < 8; k++) wgmma_rs_n24<1>(o, p[4 * k], p[4 * k + 1], p[4 * k + 2], p[4 * k + 3], desc64(vlo + off + k * 48, HI_V), 1);
                wg_commit();
                wg_wait<0>();
            }
        } else {
            float s[64];
            qb[0] = t == 0 ? x0 : 0u; qb[1] = t == 0 ? x1 : 0u; qb[2] = 0; qb[3] = 0;
            pin(qa); pin(qb); pin(o);
            float m0 = -INFINITY, m1 = -INFINITY;
#pragma unroll 1
            for (int j = 0; j < 16; j++) {
                if (rep == 0 && (j & 1) == 0) mbar_wait(bars + (j >> 1) * 8, 0);
                const uint32_t off = j * (16 * 384 >> 4);
                wg_fence();
                wgmma_rs_n128<0>(s, qa[0], qa[1], qa[2], qa[3], desc64(k0lo + off, HI_K), 0);
                wgmma_rs_n128<0>(s, qb[0], qb[1], qb[2], qb[3], desc64(k1lo + off, HI_K), 1);
                wg_commit();
                wg_wait<0>();
                pin(s);
                float x0m = m0, x1m = m1;
#pragma unroll
                for (int b = 0; b < 16; b++) { x0m = fmaxf(x0m, fmaxf(s[4 * b], s[4 * b + 1])); x1m = fmaxf(x1m, fmaxf(s[4 * b + 2], s[4 * b + 3])); }
                x0m = fmaxf(x0m, __shfl_xor_sync(~0u, x0m, 1)); x0m = fmaxf(x0m, __shfl_xor_sync(~0u, x0m, 2));
                x1m = fmaxf(x1m, __shfl_xor_sync(~0u, x1m, 1)); x1m = fmaxf(x1m, __shfl_xor_sync(~0u, x1m, 2));
                const float c0 = ex2(m0 - x0m), c1 = ex2(m1 - x1m);
                m0 = x0m; m1 = x1m;
#pragma unroll
                for (int b = 0; b < 3; b++) { o[4 * b] *= c0; o[4 * b + 1] *= c0; o[4 * b + 2] *= c1; o[4 * b + 3] *= c1; }
                uint32_t p[32];
#pragma unroll
                for (int b = 0; b < 16; b++) {
                    p[2 * b] = pack_bf16(ex2(s[4 * b] - m0), ex2(s[4 * b + 1] - m0));
                    p[2 * b + 1] = pack_bf16(ex2(s[4 * b + 2] - m1), ex2(s[4 * b + 3] - m1));
                }
                pin(p); pin(o);
                wg_fence();
#pragma unroll
                for (int k = 0; k < 8; k++) wgmma_rs_n24<1>(o, p[4 * k], p[4 * k + 1], p[4 * k + 2], p[4 * k + 3], desc64(vlo + off + k * 48, HI_V), 1);
                wg_commit();
                wg_wait<0>();
            }
        }
        pin(o);
        if (tid == 0) TS(1, 3 + rep * 2);
        const float l0 = __shfl_sync(~0u, o[8], (lane & ~3) | 1), l1 = __shfl_sync(~0u, o[10], (lane & ~3) | 1);
        const float i0 = 1.0f / l0, i1 = 1.0f / l1;
        o32[row * 9 + t] = pack_bf16(o[0] * i0, o[1] * i0);
        o32[(row + 8) * 9 + t] = pack_bf16(o[2] * i1, o[3] * i1);
        o32[row * 9 + 4 + t] = pack_bf16(o[4] * i0, o[5] * i0);
        o32[(row + 8) * 9 + 4 + t] = pack_bf16(o[6] * i1, o[7] * i1);
        if (t == 0) { o32[row * 9 + 8] = pack_bf16(o[8] * i0, o[9] * i0); o32[(row + 8) * 9 + 8] = pack_bf16(o[10] * i1, o[11] * i1); }
    }
    if (tid == 0) TS(1, 6);
}

template <int NB>
__device__ __forceinline__ void oproj_load_x(uint32_t (&xr)[NB * 2], const uint32_t* __restrict__ x32, int r0, int col0, int t) {
#pragma unroll
    for (int b = 0; b < NB; b++) {
        const int i0 = (r0 * DM + col0 + b * 8 + 2 * t) >> 1;
        xr[2 * b] = __ldg(x32 + i0); xr[2 * b + 1] = __ldg(x32 + i0 + 4 * DM);
    }
}
template <int NB>
__device__ __forceinline__ void oproj_epilogue(const float (&acc)[NB * 4], uint32_t (&xr)[NB * 2], uint32_t stg, int r0, int part, int w, int lane) {
    float s0 = 0.f, q0 = 0.f, s1 = 0.f, q1 = 0.f;
#pragma unroll
    for (int b = 0; b < NB; b++) {
        const uint32_t xa = xr[2 * b], xb = xr[2 * b + 1];
        const uint32_t ha = pack_bf16(acc[4 * b] + bf_lo(xa), acc[4 * b + 1] + bf_hi(xa));
        const uint32_t hb = pack_bf16(acc[4 * b + 2] + bf_lo(xb), acc[4 * b + 3] + bf_hi(xb));
        xr[2 * b] = ha; xr[2 * b + 1] = hb;
        const float a = bf_lo(ha), c = bf_hi(ha), d = bf_lo(hb), e = bf_hi(hb);
        s0 += a + c; q0 = fmaf(a, a, fmaf(c, c, q0));
        s1 += d + e; q1 = fmaf(d, d, fmaf(e, e, q1));
    }
    stage_tile<NB>(xr, stg, w, lane);
    s0 += __shfl_xor_sync(~0u, s0, 1); s0 += __shfl_xor_sync(~0u, s0, 2);
    q0 += __shfl_xor_sync(~0u, q0, 1); q0 += __shfl_xor_sync(~0u, q0, 2);
    s1 += __shfl_xor_sync(~0u, s1, 1); s1 += __shfl_xor_sync(~0u, s1, 2);
    q1 += __shfl_xor_sync(~0u, q1, 1); q1 += __shfl_xor_sync(~0u, q1, 2);
    if ((lane & 3) == 0) { g_stat[part * SEQ + r0] = make_float2(s0, q0); g_stat[part * SEQ + r0 + 8] = make_float2(s1, q1); }
}

__global__ void __launch_bounds__(P_THREADS, 1)
k_oproj(const __grid_constant__ CUtensorMap tmO, const __grid_constant__ CUtensorMap tmWo, const __grid_constant__ CUtensorMap tmH, const __grid_constant__ CUtensorMap tmOut, const __nv_bfloat16* __restrict__ x) {
    extern __shared__ __align__(1024) uint8_t smem[];
    const uint32_t sA = smem_u32(smem), sB = sA + P_A_BYTES, bars = sB + P_NST * P_B_STAGE;
    const uint32_t fullB = bars, emptyB = bars + 64, fullA = bars + 128;
    const int tid = threadIdx.x, warp = __shfl_sync(~0u, tid >> 5, 0), lane = tid & 31;
    const int m = blockIdx.x / 3, cg = blockIdx.x % 3;
    if (tid == 0) TS(2, 0);
    if (tid == 0) {
        for (int i = 0; i < P_NST; i++) { mbar_init(fullB + i * 8, 1); mbar_init(emptyB + i * 8, 8); }
        for (int i = 0; i < 9; i++) mbar_init(fullA + i * 8, 1);
        bar_init_fence();
    }
    __syncthreads();
    pdl_launch();
    if (warp == 8) {
        if (elect_one()) {
            for (int kb = 0; kb < P_NST; kb++) {
                mbar_expect(fullB + kb * 8, P_B_STAGE);
                for (int a = 0; a < 3; a++) tma_2d(sB + kb * P_B_STAGE + a * 8192, &tmWo, cg * 192 + a * 64, kb * 64, fullB + kb * 8);
            }
            pdl_wait();
            for (int kb = 0; kb < 9; kb++) {
                mbar_expect(fullA + kb * 8, 8192);
                tma_2d(sA + kb * 8192, &tmO, kb * 64, m * 64, fullA + kb * 8);
            }
            for (int kb = P_NST; kb < 9; kb++) {
                const int s = kb - P_NST;
                mbar_wait(emptyB + s * 8, 0);
                mbar_expect(fullB + s * 8, P_B_STAGE);
                for (int a = 0; a < 3; a++) tma_2d(sB + s * P_B_STAGE + a * 8192, &tmWo, cg * 192 + a * 64, kb * 64, fullB + s * 8);
            }
        }
        return;
    }
    const int wg = warp >> 2, w = warp & 3, g = lane >> 2, t = lane & 3;
    const int r0 = m * 64 + w * 16 + g;
    const uint32_t* x32 = reinterpret_cast<const uint32_t*>(x);
    if (wg == 0) {
        uint32_t xr[32];
        oproj_load_x<16>(xr, x32, r0, cg * 192, t);
        float acc[64];
        proj_mma<128, true>(acc, sA, sB, 0, fullB, emptyB, fullA, lane);
        if (tid == 0) TS(2, 2);
        named_sync(1, 256);
        pdl_wait();
        oproj_epilogue<16>(acc, xr, sA, r0, cg * 2, w, lane);
    } else {
        uint32_t xr[16];
        oproj_load_x<8>(xr, x32, r0, cg * 192 + 128, t);
        float acc[32];
        proj_mma<64, true>(acc, sA, sB, 2 * 8192, fullB, emptyB, fullA, lane);
        named_sync(1, 256);
        pdl_wait();
        oproj_epilogue<8>(acc, xr, sA + 2 * 8192, r0, cg * 2 + 1, w, lane);
    }
    proxy_fence();
    named_sync(1, 256);
    if (warp == 0 && elect_one()) {
        for (int a = 0; a < 3; a++) {
            tma_st_2d(&tmH, cg * 192 + a * 64, m * 64, sA + a * 8192);
            tma_st_2d(&tmOut, cg * 192 + a * 64, m * 64, sA + a * 8192);
        }
        bulk_commit();
        bulk_wait_all();
        TS(2, 3);
    }
}

constexpr int F_THREADS = 384;
constexpr int F_NST = 6;
constexpr int F_STAGE = 96 * 128;
constexpr int F_X_BYTES = 9 * 16384;
constexpr int F_OFF_ST = F_X_BYTES;
constexpr int F_OFF_CS = F_OFF_ST + F_NST * F_STAGE;
constexpr int F_OFF_BAR = F_OFF_CS + 576 * 4;
constexpr int F_SMEM = F_OFF_BAR + 256;

struct RowStat { float nmean0, c0, istd0, nmean1, c1, istd1; };

__device__ __forceinline__ float silu_ln(float acc, float cs, float nmean, float c, float istd) {
    const float u = fmaf(nmean, cs, acc);
    const float e = ex2(u * c);
    return u * rcp(fmaf(e, istd, istd));
}

template <int C>
__device__ __forceinline__ void ffn_silu_piece(const float (&acc)[32], uint32_t (&h1)[144], uint32_t cs_addr, const RowStat& st, int b) {
    float cs0, cs1;
    asm volatile("ld.shared.v2.f32 {%0, %1}, [%2];" : "=f"(cs0), "=f"(cs1) : "r"(cs_addr + (C * 64 + b * 8) * 4));
    h1[C * 16 + 2 * b] = pack_bf16(silu_ln(acc[4 * b], cs0, st.nmean0, st.c0, st.istd0), silu_ln(acc[4 * b + 1], cs1, st.nmean0, st.c0, st.istd0));
    h1[C * 16 + 2 * b + 1] = pack_bf16(silu_ln(acc[4 * b + 2], cs0, st.nmean1, st.c1, st.istd1), silu_ln(acc[4 * b + 3], cs1, st.nmean1, st.c1, st.istd1));
}

struct FfnPipe {
    uint32_t full, empty;
    int lane;
    __device__ __forceinline__ void acquire(int s, uint32_t ph) const { mbar_wait(full + s * 8, ph); }
    __device__ __forceinline__ void release(int s) const { if (lane == 0) mbar_arrive(empty + s * 8); }
};

template <int C>
__device__ __forceinline__ void ffn_phase1_chunk(float (&cur)[32], float (&prev)[32], uint32_t (&h1)[144], const FfnPipe& pp, uint64_t dx, uint32_t fullX, uint32_t cs_addr, const RowStat& st) {
    dx += blockIdx.y * C;
#pragma unroll
    for (int j = 0; j < 6; j++) {
        if (C == 0) { mbar_wait(fullX + ((6 * j) >> 2) * 8, 0); mbar_wait(fullX + ((6 * j + 5) >> 2) * 8, 0); }
        pp.acquire(j, C & 1);
        if (j == 0) pin(cur);
        wg_fence();
#pragma unroll
        for (int i = 0; i < 6; i++) {
            const int ks = 6 * j + i;
            wgmma_ss_n64<1>(cur, dx + ((ks >> 2) * 1024 + (ks & 3) * 2), cdesc(F_OFF_ST + j * F_STAGE + i * 2048, 8192, 1024, 1), ks != 0);
        }
        wg_commit();
        if (C > 0 || j > 0) { wg_wait<1>(); pp.release((j + 5) % 6); }
        if (C > 0) {
            if (j == 0) pin(prev);
            if (j < 2) { ffn_silu_piece<(C > 0 ? C - 1 : 0)>(prev, h1, cs_addr, st, 2 * j); ffn_silu_piece<(C > 0 ? C - 1 : 0)>(prev, h1, cs_addr, st, 2 * j + 1); }
            else ffn_silu_piece<(C > 0 ? C - 1 : 0)>(prev, h1, cs_addr, st, j + 2);
        }
    }
}

__device__ __forceinline__ void ffn_store_chunk(const float (&acc)[32], const CUtensorMap* tmOut, uint32_t stg, int col, int row, int w, int lane, int wgid) {
    uint32_t pk[16];
#pragma unroll
    for (int i = 0; i < 16; i++) pk[i] = pack_bf16(acc[2 * i], acc[2 * i + 1]);
    stage_tile<8>(pk, stg, w, lane);
    proxy_fence();
    named_sync(2 + wgid, 128);
    if (w == 0 && elect_one()) {
        tma_red_2d(tmOut, col, row, stg);
        bulk_commit();
    }
}

__device__ __forceinline__ void ffn_phase2_chunk(float (&cur)[32], float (&prev)[32], uint32_t (&h1)[144], const FfnPipe& pp, uint32_t ph, bool store_prev, const CUtensorMap* tmOut, uint32_t stg_prev, int col_prev, int row, int w, int lane, int wgid) {
#pragma unroll
    for (int j = 0; j < 6; j++) {
        pp.acquire(j, ph);
        if (j == 0) pin(cur);
        wg_fence();
#pragma unroll
        for (int i = 0; i < 6; i++) {
            const int f = (6 * j + i) * 4;
            wgmma_rs_n64<1>(cur, h1[f], h1[f + 1], h1[f + 2], h1[f + 3], cdesc(F_OFF_ST + j * F_STAGE + i * 2048, 8192, 1024, 1), (j | i) != 0);
        }
        wg_commit();
        if (j > 0 || store_prev) { wg_wait<1>(); pp.release((j + 5) % 6); }
        if (j == 0 && store_prev) { pin(prev); ffn_store_chunk(prev, tmOut, stg_prev, col_prev, row, w, lane, wgid); }
    }
}

__global__ void __launch_bounds__(F_THREADS, 1)
k_ffn(const __grid_constant__ CUtensorMap tmH, const __grid_constant__ CUtensorMap tmW1, const __grid_constant__ CUtensorMap tmW2, const __grid_constant__ CUtensorMap tmOut) {
    extern __shared__ __align__(1024) uint8_t smem[];
    const uint32_t sX = smem_u32(smem), sSt = sX + F_OFF_ST, sCs = sX + F_OFF_CS, bars = sX + F_OFF_BAR;
    const uint32_t full = bars, empty = bars + 64, fullX = bars + 128;
    const int tid = threadIdx.x, warp = __shfl_sync(~0u, tid >> 5, 0), lane = tid & 31;
    const int m = blockIdx.x & 15, fs = blockIdx.x >> 4;
    if (tid == 0) TS(3, 0);
    check_smem_base(sX);
    if (tid == 0) {
        for (int i = 0; i < F_NST; i++) { mbar_init(full + i * 8, 1); mbar_init(empty + i * 8, 8); }
        for (int i = 0; i < 9; i++) mbar_init(fullX + i * 8, 1);
        bar_init_fence();
    }
    __syncthreads();
    if (warp < 4) {
        asm volatile("setmaxnreg.dec.sync.aligned.u32 24;");
        if (warp == 0 && elect_one()) {
            int s = 0; uint32_t ph = 1;
            int c = 0, j = 0;
#pragma unroll 1
            for (int i = 0; i < 108; i++) {
                if (i == F_NST) {
                    pdl_wait();
                    for (int kb = 0; kb < 9; kb++) {
                        mbar_expect(fullX + kb * 8, 16384);
                        tma_2d(sX + kb * 16384, &tmH, kb * 64, m * 128, fullX + kb * 8);
                    }
                }
                if (i == 54) c = fs;
                mbar_wait(empty + s * 8, ph);
                mbar_expect(full + s * 8, F_STAGE);
                if (i < 54) tma_2d(sSt + s * F_STAGE, &tmW1, fs * 576 + c * 64, j * 96, full + s * 8);
                else tma_2d(sSt + s * F_STAGE, &tmW2, c * 64, fs * 576 + j * 96, full + s * 8);
                if (++j == 6) { j = 0; if (++c == 9) c = 0; }
                if (++s == F_NST) { s = 0; ph ^= 1; }
            }
        }
    } else {
        asm volatile("setmaxnreg.inc.sync.aligned.u32 240;");
        const int wgid = (warp >> 2) - 1, w = warp & 3, g = lane >> 2;
        pdl_wait();
        if (tid == 128) TS(3, 1);
        for (int i = tid - 128; i < 576; i += 256) reinterpret_cast<float*>(smem + F_OFF_CS)[i] = g_cs1[fs * 576 + i];
        RowStat st;
        {
            const int r0 = m * 128 + wgid * 64 + w * 16 + g;
            float s0 = 0.f, q0 = 0.f, s1 = 0.f, q1 = 0.f;
#pragma unroll
            for (int p = 0; p < 6; p++) {
                const float2 a = g_stat[p * SEQ + r0], b = g_stat[p * SEQ + r0 + 8];
                s0 += a.x; q0 += a.y; s1 += b.x; q1 += b.y;
            }
            const float m0 = s0 * (1.0f / DM), m1 = s1 * (1.0f / DM);
            const float v0 = fmaxf(q0 * (1.0f / DM) - m0 * m0, 0.f) + LN_EPS, v1 = fmaxf(q1 * (1.0f / DM) - m1 * m1, 0.f) + LN_EPS;
            st.istd0 = sqrtf(v0); st.istd1 = sqrtf(v1);
            st.nmean0 = -m0; st.nmean1 = -m1;
            st.c0 = -LOG2E / st.istd0; st.c1 = -LOG2E / st.istd1;
        }
        FfnPipe pp{full, empty, lane};
        const uint32_t cs_addr = sCs + (lane & 3) * 8;
        const uint64_t xlo = cdesc(0, 16, 1024, 1) + wgid * 512;
        uint32_t h1[144];
        float acc0[32], acc1[32];
        ffn_phase1_chunk<0>(acc0, acc1, h1, pp, xlo, fullX, cs_addr, st);
        named_sync(1, 256);
        if (tid == 128) TS(3, 2);
        ffn_phase1_chunk<1>(acc1, acc0, h1, pp, xlo, fullX, cs_addr, st);
        ffn_phase1_chunk<2>(acc0, acc1, h1, pp, xlo, fullX, cs_addr, st);
        ffn_phase1_chunk<3>(acc1, acc0, h1, pp, xlo, fullX, cs_addr, st);
        ffn_phase1_chunk<4>(acc0, acc1, h1, pp, xlo, fullX, cs_addr, st);
        ffn_phase1_chunk<5>(acc1, acc0, h1, pp, xlo, fullX, cs_addr, st);
        ffn_phase1_chunk<6>(acc0, acc1, h1, pp, xlo, fullX, cs_addr, st);
        ffn_phase1_chunk<7>(acc1, acc0, h1, pp, xlo, fullX, cs_addr, st);
        ffn_phase1_chunk<8>(acc0, acc1, h1, pp, xlo, fullX, cs_addr, st);
        wg_wait<0>();
        pp.release(5);
        pin(acc0);
#pragma unroll
        for (int b = 0; b < 8; b++) ffn_silu_piece<8>(acc0, h1, cs_addr, st, b);
        pin(h1);
        if (tid == 128) TS(3, 3);
        const int row = m * 128 + wgid * 64;
        const uint32_t stg = sX + wgid * 8192;
        int c = fs, cprev = 0;
#pragma unroll 1
        for (int j = 0; j < 8; j += 2) {
            ffn_phase2_chunk(acc1, acc0, h1, pp, 1, j > 0, &tmOut, stg + (j - 1) * 16384, cprev * 64, row, w, lane, wgid);
            cprev = c; if (++c == 9) c = 0;
            ffn_phase2_chunk(acc0, acc1, h1, pp, 0, true, &tmOut, stg + j * 16384, cprev * 64, row, w, lane, wgid);
            cprev = c; if (++c == 9) c = 0;
        }
        ffn_phase2_chunk(acc1, acc0, h1, pp, 1, true, &tmOut, stg + 7 * 16384, cprev * 64, row, w, lane, wgid);
        wg_wait<0>();
        pin(acc1);
        ffn_store_chunk(acc1, &tmOut, stg + 8 * 16384, c * 64, row, w, lane, wgid);
        if (tid == 128) TS(3, 4);
        if (w == 0) bulk_wait_all();
        if (tid == 128) TS(3, 5);
    }
}

typedef CUresult (*EncodeFn)(CUtensorMap*, CUtensorMapDataType, cuuint32_t, void*, const cuuint64_t*, const cuuint64_t*, const cuuint32_t*, const cuuint32_t*,
                             CUtensorMapInterleave, CUtensorMapSwizzle, CUtensorMapL2promotion, CUtensorMapFloatOOBfill);

CUtensorMap make_map(EncodeFn enc, const void* base, int rows, int cols, int box_rows) {
    CUtensorMap tm;
    cuuint64_t dims[2] = {(cuuint64_t)cols, (cuuint64_t)rows};
    cuuint64_t strides[1] = {(cuuint64_t)cols * 2};
    cuuint32_t box[2] = {64, (cuuint32_t)box_rows};
    cuuint32_t es[2] = {1, 1};
    enc(&tm, CU_TENSOR_MAP_DATA_TYPE_BFLOAT16, 2, const_cast<void*>(base), dims, strides, box, es, CU_TENSOR_MAP_INTERLEAVE_NONE,
        CU_TENSOR_MAP_SWIZZLE_128B, CU_TENSOR_MAP_L2_PROMOTION_L2_256B, CU_TENSOR_MAP_FLOAT_OOB_FILL_NONE);
    return tm;
}

template <typename... KArgs, typename... Args>
void launch(void (*kern)(KArgs...), int grid, int block, int smem, bool pdl, Args... args) {
    cudaLaunchConfig_t cfg = {};
    cfg.gridDim = dim3(grid); cfg.blockDim = dim3(block); cfg.dynamicSmemBytes = smem; cfg.stream = cudaStreamPerThread;
    cudaLaunchAttribute at[1];
    at[0].id = cudaLaunchAttributeProgrammaticStreamSerialization;
    at[0].val.programmaticStreamSerializationAllowed = 1;
    cfg.attrs = at; cfg.numAttrs = pdl ? 1 : 0;
    cudaLaunchKernelEx(&cfg, kern, KArgs(args)...);
}

}

#define USE_PDL 1

extern "C" void kernel_launch(void* const* d_in, const int* in_sizes, int n_in, void* d_out, int out_size) {
    const __nv_bfloat16* x = (const __nv_bfloat16*)d_in[0];
    const __nv_bfloat16* wq = (const __nv_bfloat16*)d_in[1];
    const __nv_bfloat16* wk = (const __nv_bfloat16*)d_in[2];
    const __nv_bfloat16* wv = (const __nv_bfloat16*)d_in[3];
    const __nv_bfloat16* wo = (const __nv_bfloat16*)d_in[4];
    const __nv_bfloat16* w1 = (const __nv_bfloat16*)d_in[6];
    const __nv_bfloat16* w2 = (const __nv_bfloat16*)d_in[7];
    __nv_bfloat16* out = (__nv_bfloat16*)d_out;

    static EncodeFn enc = nullptr;
    static void *p_o = nullptr, *p_h = nullptr, *p_q = nullptr;
    if (!enc) {
        cudaDriverEntryPointQueryResult qr;
        cudaGetDriverEntryPoint("cuTensorMapEncodeTiled", (void**)&enc, cudaEnableDefault, &qr);
        cudaGetSymbolAddress(&p_o, g_o);
        cudaGetSymbolAddress(&p_h, g_h);
        cudaGetSymbolAddress(&p_q, g_q);
        cudaFuncSetAttribute(k_qkv, cudaFuncAttributeMaxDynamicSharedMemorySize, P_SMEM);
        cudaFuncSetAttribute(k_attn, cudaFuncAttributeMaxDynamicSharedMemorySize, A_SMEM);
        cudaFuncSetAttribute(k_oproj, cudaFuncAttributeMaxDynamicSharedMemorySize, P_SMEM);
        cudaFuncSetAttribute(k_ffn, cudaFuncAttributeMaxDynamicSharedMemorySize, F_SMEM);
    }
    const CUtensorMap tmWq = make_map(enc, wq, DM, DM, 64);
    const CUtensorMap tmWo = make_map(enc, wo, DM, DM, 64);
    const CUtensorMap tmO = make_map(enc, p_o, SEQ, DM, 64);
    const CUtensorMap tmH = make_map(enc, p_h, SEQ, DM, 128);
    const CUtensorMap tmH64 = make_map(enc, p_h, SEQ, DM, 64);
    const CUtensorMap tmQ = make_map(enc, p_q, SEQ, DM, 64);
    const CUtensorMap tmW1 = make_map(enc, w1, DM, FF, 96);
    const CUtensorMap tmW2 = make_map(enc, w2, FF, DM, 96);
    const CUtensorMap tmOut = make_map(enc, out, SEQ, DM, 64);

    launch(k_qkv, 128, P_THREADS, P_SMEM, false, tmWq, tmQ, x, wk, wv);
    launch(k_attn, 132, A_THREADS, A_SMEM, USE_PDL, w1, w2, wo);
    launch(k_oproj, 96, P_THREADS, P_SMEM, USE_PDL, tmO, tmWo, tmH64, tmOut, x);
    launch(k_ffn, 128, F_THREADS, F_SMEM, USE_PDL, tmH, tmW1, tmW2, tmOut);
}
```

```cpp
#include <cuda_runtime.h>
#include <cuda_bf16.h>
#include <cuda.h>
#include <stdint.h>

namespace {

constexpr int SEQ = 2048, DM = 576, FF = 4608;
constexpr int KV_BYTES = SEQ * 48;
constexpr float LN_EPS = 1e-5f;
constexpr float LOG2E = 1.4426950408889634f;
constexpr float Q_SCALE = 0.23570226039551584f * LOG2E;

constexpr uint32_t POLY_MASK = 0xB5B5u;
constexpr float FAST_BOUND = 60.0f;

__device__ __align__(1024) __nv_bfloat16 g_q[SEQ * DM];
__device__ __align__(1024) uint4 g_kc[KV_BYTES / 16];
__device__ __align__(1024) uint4 g_vc[KV_BYTES / 16];
__device__ float g_kmax[32];
__device__ __align__(1024) __nv_bfloat16 g_o[SEQ * DM];
__device__ __align__(1024) __nv_bfloat16 g_h[SEQ * DM];
__device__ float2 g_stat[6 * SEQ];
__device__ __align__(16) float g_cs1[FF];

#define TS(k, i)

__device__ __forceinline__ uint32_t smem_u32(const void* p) { return (uint32_t)__cvta_generic_to_shared(p); }
__device__ __forceinline__ void wg_fence() { asm volatile("wgmma.fence.sync.aligned;" ::: "memory"); }
__device__ __forceinline__ void wg_commit() { asm volatile("wgmma.commit_group.sync.aligned;" ::: "memory"); }
template <int N> __device__ __forceinline__ void wg_wait() { asm volatile("wgmma.wait_group.sync.aligned %0;" ::"n"(N) : "memory"); }
template <int N> __device__ __forceinline__ void pin(float (&r)[N]) {
#pragma unroll
    for (int i = 0; i < N; i++) asm volatile("" : "+f"(r[i])::"memory");
}
template <int N> __device__ __forceinline__ void pin(uint32_t (&r)[N]) {
#pragma unroll
    for (int i = 0; i < N; i++) asm volatile("" : "+r"(r[i])::"memory");
}
__device__ __forceinline__ constexpr uint32_t desc_hi(uint32_t sbo, uint32_t swz) { return (sbo >> 4) | (swz << 30); }
__device__ __forceinline__ uint32_t desc_lo(uint32_t addr, uint32_t lbo) { return ((addr & 0x3FFFF) >> 4) | ((lbo >> 4) << 16); }
__device__ __forceinline__ uint64_t desc64(uint32_t lo, uint32_t hi) { return ((uint64_t)hi << 32) | lo; }
constexpr uint32_t SMEM0 = 0x400;
__host__ __device__ constexpr uint64_t cdesc(uint32_t off, uint32_t lbo, uint32_t sbo, uint32_t swz) {
    return (uint64_t)(((SMEM0 + off) & 0x3FFFF) >> 4) | ((uint64_t)(lbo >> 4) << 16) | ((uint64_t)(sbo >> 4) << 32) | ((uint64_t)swz << 62);
}
__device__ __forceinline__ void check_smem_base(uint32_t base) { if ((base & 0x3FFFF) != SMEM0) __trap(); }

__device__ __forceinline__ void mbar_init(uint32_t bar, int cnt) { asm volatile("mbarrier.init.shared::cta.b64 [%0], %1;" ::"r"(bar), "r"(cnt) : "memory"); }
__device__ __forceinline__ void mbar_expect(uint32_t bar, int bytes) { asm volatile("mbarrier.arrive.expect_tx.shared::cta.b64 _, [%0], %1;" ::"r"(bar), "r"(bytes) : "memory"); }
__device__ __forceinline__ void mbar_arrive(uint32_t bar) { asm volatile("mbarrier.arrive.shared::cta.b64 _, [%0];" ::"r"(bar) : "memory"); }
__device__ __forceinline__ void mbar_wait(uint32_t bar, uint32_t parity) {
    asm volatile(
        "{\n.reg .pred p;\n.reg .u32 n;\nmov.u32 n, 0;\n"
        "LAB_WAIT:\n"
        "mbarrier.try_wait.parity.shared::cta.b64 p, [%0], %1;\n"
        "@p bra DONE;\n"
        "add.u32 n, n, 1;\n"
        "setp.lt.u32 p, n, 4000000;\n"
        "@p bra LAB_WAIT;\n"
        "trap;\n"
        "DONE:\n}\n" ::"r"(bar), "r"(parity) : "memory");
}
__device__ __forceinline__ void bar_init_fence() {
    asm volatile("fence.mbarrier_init.release.cluster;" ::: "memory");
    asm volatile("fence.proxy.async.shared::cta;" ::: "memory");
}
__device__ __forceinline__ void proxy_fence() { asm volatile("fence.proxy.async.shared::cta;" ::: "memory"); }
__device__ __forceinline__ void named_sync(int id, int n) { asm volatile("bar.sync %0, %1;" ::"r"(id), "r"(n) : "memory"); }
__device__ __forceinline__ void bulk_g2s(uint32_t dst, const void* src, int bytes, uint32_t bar) {
    asm volatile("cp.async.bulk.shared::cluster.global.mbarrier::complete_tx::bytes [%0], [%1], %2, [%3];" ::"r"(dst), "l"(src), "r"(bytes), "r"(bar) : "memory");
}
__device__ __forceinline__ void tma_2d(uint32_t dst, const CUtensorMap* tm, int c0, int c1, uint32_t bar) {
    asm volatile("cp.async.bulk.tensor.2d.shared::cluster.global.mbarrier::complete_tx::bytes [%0], [%1, {%3, %4}], [%2];" ::"r"(dst), "l"(tm), "r"(bar), "r"(c0), "r"(c1) : "memory");
}
__device__ __forceinline__ void tma_red_2d(const CUtensorMap* tm, int c0, int c1, uint32_t src) {
    asm volatile("cp.reduce.async.bulk.tensor.2d.global.shared::cta.add.tile.bulk_group [%0, {%2, %3}], [%1];" ::"l"(tm), "r"(src), "r"(c0), "r"(c1) : "memory");
}
__device__ __forceinline__ void tma_st_2d(const CUtensorMap* tm, int c0, int c1, uint32_t src) {
    asm volatile("cp.async.bulk.tensor.2d.global.shared::cta.tile.bulk_group [%0, {%2, %3}], [%1];" ::"l"(tm), "r"(src), "r"(c0), "r"(c1) : "memory");
}
__device__ __forceinline__ void bulk_commit() { asm volatile("cp.async.bulk.commit_group;" ::: "memory"); }
__device__ __forceinline__ void bulk_wait_all() { asm volatile("cp.async.bulk.wait_group 0;" ::: "memory"); }
__device__ __forceinline__ bool elect_one() {
    uint32_t p;
    asm volatile("{\n.reg .pred P;\nelect.sync _|P, 0xffffffff;\nselp.b32 %0, 1, 0, P;\n}\n" : "=r"(p));
    return p != 0;
}
__device__ __forceinline__ void prefetch_l2(const void* p, int bytes) { asm volatile("cp.async.bulk.prefetch.L2.global [%0], %1;" ::"l"(p), "r"(bytes) : "memory"); }
__device__ __forceinline__ void pdl_launch() { asm volatile("griddepcontrol.launch_dependents;" ::: "memory"); }
__device__ __forceinline__ void pdl_wait() { asm volatile("griddepcontrol.wait;" ::: "memory"); }
__device__ __forceinline__ float ex2(float x) { float y; asm("ex2.approx.ftz.f32 %0, %1;" : "=f"(y) : "f"(x)); return y; }
__device__ __forceinline__ float rcp(float x) { float y; asm("rcp.approx.ftz.f32 %0, %1;" : "=f"(y) : "f"(x)); return y; }
__device__ __forceinline__ uint32_t pack_bf16(float lo, float hi) { uint32_t r; asm("cvt.rn.bf16x2.f32 %0, %1, %2;" : "=r"(r) : "f"(hi), "f"(lo)); return r; }
__device__ __forceinline__ float bf_lo(uint32_t v) { return __uint_as_float(v << 16); }
__device__ __forceinline__ float bf_hi(uint32_t v) { return __uint_as_float(v & 0xFFFF0000u); }
__device__ __forceinline__ uint32_t hfma2(uint32_t a, uint32_t b, uint32_t c) { uint32_t r; asm("fma.rn.f16x2 %0, %1, %2, %3;" : "=r"(r) : "r"(a), "r"(b), "r"(c)); return r; }
__device__ __forceinline__ void stmatrix_x4(uint32_t addr, uint32_t r0, uint32_t r1, uint32_t r2, uint32_t r3) {
    asm volatile("stmatrix.sync.aligned.m8n8.x4.shared.b16 [%0], {%1, %2, %3, %4};" ::"r"(addr), "r"(r0), "r"(r1), "r"(r2), "r"(r3) : "memory");
}

template <int TB> __device__ __forceinline__ void wgmma_ss_n24(float (&d)[12], uint64_t da, uint64_t db, int sc) {
    asm volatile("{\n.reg .pred p;\nsetp.ne.b32 p, %14, 0;\n"
        "wgmma.mma_async.sync.aligned.m64n24k16.f32.bf16.bf16 {%0, %1, %2, %3, %4, %5, %6, %7, %8, %9, %10, %11}, %12, %13, p, 1, 1, 0, %15;\n}\n"
        : "+f"(d[0]), "+f"(d[1]), "+f"(d[2]), "+f"(d[3]), "+f"(d[4]), "+f"(d[5]), "+f"(d[6]), "+f"(d[7]), "+f"(d[8]), "+f"(d[9]), "+f"(d[10]), "+f"(d[11])
        : "l"(da), "l"(db), "r"(sc), "n"(TB));
}
template <int TB> __device__ __forceinline__ void wgmma_ss_n64(float (&d)[32], uint64_t da, uint64_t db, int sc) {
    asm volatile("{\n.reg .pred p;\nsetp.ne.b32 p, %34, 0;\n"
        "wgmma.mma_async.sync.aligned.m64n64k16.f32.bf16.bf16 {%0, %1, %2, %3, %4, %5, %6, %7, %8, %9, %10, %11, %12, %13, %14, %15, %16, %17, %18, %19, %20, %21, %22, %23, %24, %25, %26, %27, %28, %29, %30, %31}, %32, %33, p, 1, 1, 0, %35;\n}\n"
        : "+f"(d[0]), "+f"(d[1]), "+f"(d[2]), "+f"(d[3]), "+f"(d[4]), "+f"(d[5]), "+f"(d[6]), "+f"(d[7]), "+f"(d[8]), "+f"(d[9]), "+f"(d[10]), "+f"(d[11]), "+f"(d[12]), "+f"(d[13]), "+f"(d[14]), "+f"(d[15]), "+f"(d[16]), "+f"(d[17]), "+f"(d[18]), "+f"(d[19]), "+f"(d[20]), "+f"(d[21]), "+f"(d[22]), "+f"(d[23]), "+f"(d[24]), "+f"(d[25]), "+f"(d[26]), "+f"(d[27]), "+f"(d[28]), "+f"(d[29]), "+f"(d[30]), "+f"(d[31])
        : "l"(da), "l"(db), "r"(sc), "n"(TB));
}
template <int TB> __device__ __forceinline__ void wgmma_ss_n128(float (&d)[64], uint64_t da, uint64_t db, int sc) {
    asm volatile("{\n.reg .pred p;\nsetp.ne.b32 p, %66, 0;\n"
        "wgmma.mma_async.sync.aligned.m64n128k16.f32.bf16.bf16 {%0, %1, %2, %3, %4, %5, %6, %7, %8, %9, %10, %11, %12, %13, %14, %15, %16, %17, %18, %19, %20, %21, %22, %23, %24, %25, %26, %27, %28, %29, %30, %31, %32, %33, %34, %35, %36, %37, %38, %39, %40, %41, %42, %43, %44, %45, %46, %47, %48, %49, %50, %51, %52, %53, %54, %55, %56, %57, %58, %59, %60, %61, %62, %63}, %64, %65, p, 1, 1, 0, %67;\n}\n"
        : "+f"(d[0]), "+f"(d[1]), "+f"(d[2]), "+f"(d[3]), "+f"(d[4]), "+f"(d[5]), "+f"(d[6]), "+f"(d[7]), "+f"(d[8]), "+f"(d[9]), "+f"(d[10]), "+f"(d[11]), "+f"(d[12]), "+f"(d[13]), "+f"(d[14]), "+f"(d[15]), "+f"(d[16]), "+f"(d[17]), "+f"(d[18]), "+f"(d[19]), "+f"(d[20]), "+f"(d[21]), "+f"(d[22]), "+f"(d[23]), "+f"(d[24]), "+f"(d[25]), "+f"(d[26]), "+f"(d[27]), "+f"(d[28]), "+f"(d[29]), "+f"(d[30]), "+f"(d[31]), "+f"(d[32]), "+f"(d[33]), "+f"(d[34]), "+f"(d[35]), "+f"(d[36]), "+f"(d[37]), "+f"(d[38]), "+f"(d[39]), "+f"(d[40]), "+f"(d[41]), "+f"(d[42]), "+f"(d[43]), "+f"(d[44]), "+f"(d[45]), "+f"(d[46]), "+f"(d[47]), "+f"(d[48]), "+f"(d[49]), "+f"(d[50]), "+f"(d[51]), "+f"(d[52]), "+f"(d[53]), "+f"(d[54]), "+f"(d[55]), "+f"(d[56]), "+f"(d[57]), "+f"(d[58]), "+f"(d[59]), "+f"(d[60]), "+f"(d[61]), "+f"(d[62]), "+f"(d[63])
        : "l"(da), "l"(db), "r"(sc), "n"(TB));
}
template <int TB> __device__ __forceinline__ void wgmma_rs_n24(float (&d)[12], uint32_t a0, uint32_t a1, uint32_t a2, uint32_t a3, uint64_t db, int sc) {
    asm volatile("{\n.reg .pred p;\nsetp.ne.b32 p, %17, 0;\n"
        "wgmma.mma_async.sync.aligned.m64n24k16.f32.bf16.bf16 {%0, %1, %2, %3, %4, %5, %6, %7, %8, %9, %10, %11}, {%12, %13, %14, %15}, %16, p, 1, 1, %18;\n}\n"
        : "+f"(d[0]), "+f"(d[1]), "+f"(d[2]), "+f"(d[3]), "+f"(d[4]), "+f"(d[5]), "+f"(d[6]), "+f"(d[7]), "+f"(d[8]), "+f"(d[9]), "+f"(d[10]), "+f"(d[11])
        : "r"(a0), "r"(a1), "r"(a2), "r"(a3), "l"(db), "r"(sc), "n"(TB));
}
template <int TB> __device__ __forceinline__ void wgmma_rs_n64(float (&d)[32], uint32_t a0, uint32_t a1, uint32_t a2, uint32_t a3, uint64_t db, int sc) {
    asm volatile("{\n.reg .pred p;\nsetp.ne.b32 p, %37, 0;\n"
        "wgmma.mma_async.sync.aligned.m64n64k16.f32.bf16.bf16 {%0, %1, %2, %3, %4, %5, %6, %7, %8, %9, %10, %11, %12, %13, %14, %15, %16, %17, %18, %19, %20, %21, %22, %23, %24, %25, %26, %27, %28, %29, %30, %31}, {%32, %33, %34, %35}, %36, p, 1, 1, %38;\n}\n"
        : "+f"(d[0]), "+f"(d[1]), "+f"(d[2]), "+f"(d[3]), "+f"(d[4]), "+f"(d[5]), "+f"(d[6]), "+f"(d[7]), "+f"(d[8]), "+f"(d[9]), "+f"(d[10]), "+f"(d[11]), "+f"(d[12]), "+f"(d[13]), "+f"(d[14]), "+f"(d[15]), "+f"(d[16]), "+f"(d[17]), "+f"(d[18]), "+f"(d[19]), "+f"(d[20]), "+f"(d[21]), "+f"(d[22]), "+f"(d[23]), "+f"(d[24]), "+f"(d[25]), "+f"(d[26]), "+f"(d[27]), "+f"(d[28]), "+f"(d[29]), "+f"(d[30]), "+f"(d[31])
        : "r"(a0), "r"(a1), "r"(a2), "r"(a3), "l"(db), "r"(sc), "n"(TB));
}
template <int TB> __device__ __forceinline__ void wgmma_rs_n128(float (&d)[64], uint32_t a0, uint32_t a1, uint32_t a2, uint32_t a3, uint64_t db, int sc) {
    asm volatile("{\n.reg .pred p;\nsetp.ne.b32 p, %69, 0;\n"
        "wgmma.mma_async.sync.aligned.m64n128k16.f32.bf16.bf16 {%0, %1, %2, %3, %4, %5, %6, %7, %8, %9, %10, %11, %12, %13, %14, %15, %16, %17, %18, %19, %20, %21, %22, %23, %24, %25, %26, %27, %28, %29, %30, %31, %32, %33, %34, %35, %36, %37, %38, %39, %40, %41, %42, %43, %44, %45, %46, %47, %48, %49, %50, %51, %52, %53, %54, %55, %56, %57, %58, %59, %60, %61, %62, %63}, {%64, %65, %66, %67}, %68, p, 1, 1, %70;\n}\n"
        : "+f"(d[0]), "+f"(d[1]), "+f"(d[2]), "+f"(d[3]), "+f"(d[4]), "+f"(d[5]), "+f"(d[6]), "+f"(d[7]), "+f"(d[8]), "+f"(d[9]), "+f"(d[10]), "+f"(d[11]), "+f"(d[12]), "+f"(d[13]), "+f"(d[14]), "+f"(d[15]), "+f"(d[16]), "+f"(d[17]), "+f"(d[18]), "+f"(d[19]), "+f"(d[20]), "+f"(d[21]), "+f"(d[22]), "+f"(d[23]), "+f"(d[24]), "+f"(d[25]), "+f"(d[26]), "+f"(d[27]), "+f"(d[28]), "+f"(d[29]), "+f"(d[30]), "+f"(d[31]), "+f"(d[32]), "+f"(d[33]), "+f"(d[34]), "+f"(d[35]), "+f"(d[36]), "+f"(d[37]), "+f"(d[38]), "+f"(d[39]), "+f"(d[40]), "+f"(d[41]), "+f"(d[42]), "+f"(d[43]), "+f"(d[44]), "+f"(d[45]), "+f"(d[46]), "+f"(d[47]), "+f"(d[48]), "+f"(d[49]), "+f"(d[50]), "+f"(d[51]), "+f"(d[52]), "+f"(d[53]), "+f"(d[54]), "+f"(d[55]), "+f"(d[56]), "+f"(d[57]), "+f"(d[58]), "+f"(d[59]), "+f"(d[60]), "+f"(d[61]), "+f"(d[62]), "+f"(d[63])
        : "r"(a0), "r"(a1), "r"(a2), "r"(a3), "l"(db), "r"(sc), "n"(TB));
}

constexpr int P_THREADS = 288;
constexpr int P_NST = 6;
constexpr int P_A_BYTES = 9 * 8192;
constexpr int P_B_STAGE = 3 * 8192;
constexpr int P_SMEM = P_A_BYTES + P_NST * P_B_STAGE + 256;
constexpr uint32_t HI_SW128 = (1024u >> 4) | (1u << 30);

template <int NCOL, bool WAIT_A>
__device__ __forceinline__ void proj_mma(float (&acc)[NCOL / 2], uint32_t sA, uint32_t sB, uint32_t colofs, uint32_t fullB, uint32_t emptyB, uint32_t fullA, int lane) {
#pragma unroll 1
    for (int kb = 0; kb < 9; kb++) {
        const int s = kb >= P_NST ? kb - P_NST : kb;
        if (WAIT_A) mbar_wait(fullA + kb * 8, 0);
        mbar_wait(fullB + s * 8, kb >= P_NST ? 1 : 0);
        const uint32_t alo = desc_lo(sA + kb * 8192, 16), blo = desc_lo(sB + s * P_B_STAGE + colofs, 8192);
        wg_fence();
#pragma unroll
        for (int ks = 0; ks < 4; ks++) {
            const uint64_t da = desc64(alo + ks * 2, HI_SW128), db = desc64(blo + ks * 128, HI_SW128);
            if constexpr (NCOL == 128) wgmma_ss_n128<1>(acc, da, db, (kb | ks) != 0);
            else wgmma_ss_n64<1>(acc, da, db, (kb | ks) != 0);
        }
        wg_commit();
        if (kb + P_NST < 9 + 1) {
            wg_wait<1>();
            if (kb >= 1 && kb - 1 + P_NST < 9 && lane == 0) mbar_arrive(emptyB + (kb - 1) * 8);
        }
    }
    wg_wait<0>();
    pin(acc);
}

template <int NB>
__device__ __forceinline__ void stage_tile(const uint32_t (&pk)[NB * 2], uint32_t base, int w, int lane) {
    const int r = w * 16 + (lane & 7) + ((lane >> 3) & 1) * 8;
#pragma unroll
    for (int b = 0; b < NB; b += 2) {
        const uint32_t a = base + (b >> 3) * 8192 + r * 128 + ((((b & 7) + (lane >> 4)) ^ (r & 7)) << 4);
        stmatrix_x4(a, pk[2 * b], pk[2 * b + 1], pk[2 * b + 2], pk[2 * b + 3]);
    }
}

__global__ void __launch_bounds__(P_THREADS, 1)
k_qkv(const __grid_constant__ CUtensorMap tmWq, const __grid_constant__ CUtensorMap tmQ, const __nv_bfloat16* __restrict__ x, const __nv_bfloat16* __restrict__ wk, const __nv_bfloat16* __restrict__ wv) {
    extern __shared__ __align__(1024) uint8_t smem[];
    const uint32_t sA = smem_u32(smem), sB = sA + P_A_BYTES, bars = sB + P_NST * P_B_STAGE;
    const uint32_t fullB = bars, emptyB = bars + 64;
    const int tid = threadIdx.x, warp = __shfl_sync(~0u, tid >> 5, 0), lane = tid & 31;
    const bool isQ = blockIdx.x < 96;
    const int m = isQ ? blockIdx.x / 3 : blockIdx.x - 96, cg = blockIdx.x % 3;
    if (tid == 0) TS(0, 0);
    if (tid == 0) {
        for (int i = 0; i < P_NST; i++) { mbar_init(fullB + i * 8, 1); mbar_init(emptyB + i * 8, 8); }
        bar_init_fence();
    }
    __syncthreads();
    pdl_launch();
    if (warp == 8) {
        if (isQ && elect_one()) {
            for (int kb = 0; kb < 9; kb++) {
                const int s = kb >= P_NST ? kb - P_NST : kb;
                if (kb >= P_NST) mbar_wait(emptyB + s * 8, 0);
                mbar_expect(fullB + s * 8, P_B_STAGE);
                for (int a = 0; a < 3; a++) tma_2d(sB + s * P_B_STAGE + a * 8192, &tmWq, cg * 192 + a * 64, kb * 64, fullB + s * 8);
            }
        }
        return;
    }
    {
        const int row = tid >> 2, q = tid & 3;
        const uint4* src = reinterpret_cast<const uint4*>(x + (size_t)(m * 64 + row) * DM) + q;
        uint4 v[18];
#pragma unroll
        for (int i = 0; i < 18; i++) v[i] = __ldg(src + 4 * i);
        if (!isQ) {
            const uint32_t* wk32 = reinterpret_cast<const uint32_t*>(wk);
            const uint32_t* wv32 = reinterpret_cast<const uint32_t*>(wv);
            uint32_t wreg[41];
#pragma unroll
            for (int i = 0; i < 41; i++) {
                const int idx = tid + i * 256;
                wreg[i] = idx < DM * 9 ? __ldg(wk32 + idx) : (idx < 2 * DM * 9 ? __ldg(wv32 + idx - DM * 9) : 0u);
            }
#pragma unroll
            for (int i = 0; i < 41; i++) {
                const int idx = tid + i * 256;
                if (idx < 2 * DM * 9) {
                    const int sel = idx >= DM * 9, j = idx - sel * DM * 9, k = j / 9, n = (j - k * 9) * 2;
                    const uint32_t a = sB + (sel * 3 + (n >> 3)) * 9216 + (k >> 3) * 128 + (n & 7) * 16 + (k & 7) * 2;
                    asm volatile("st.shared.u16 [%0], %1;" ::"r"(a), "h"((uint16_t)(wreg[i] & 0xFFFF)) : "memory");
                    asm volatile("st.shared.u16 [%0], %1;" ::"r"(a + 16), "h"((uint16_t)(wreg[i] >> 16)) : "memory");
                }
            }
        }
        float sum = 0.f;
#pragma unroll
        for (int i = 0; i < 18; i++) {
            sum += (bf_lo(v[i].x) + bf_hi(v[i].x)) + (bf_lo(v[i].y) + bf_hi(v[i].y)) + (bf_lo(v[i].z) + bf_hi(v[i].z)) + (bf_lo(v[i].w) + bf_hi(v[i].w));
        }
        sum += __shfl_xor_sync(~0u, sum, 1); sum += __shfl_xor_sync(~0u, sum, 2);
        const float mean = sum * (1.0f / DM);
        float sq = 0.f;
#pragma unroll
        for (int i = 0; i < 18; i++) {
            const uint32_t w[4] = {v[i].x, v[i].y, v[i].z, v[i].w};
#pragma unroll
            for (int j = 0; j < 4; j++) { const float a = bf_lo(w[j]) - mean, b = bf_hi(w[j]) - mean; sq = fmaf(a, a, sq); sq = fmaf(b, b, sq); }
        }
        sq += __shfl_xor_sync(~0u, sq, 1); sq += __shfl_xor_sync(~0u, sq, 2);
        const float rstd = rsqrtf(sq * (1.0f / DM) + LN_EPS), nmr = -mean * rstd;
#pragma unroll
        for (int i = 0; i < 18; i++) {
            const int c = q + 4 * i;
            const uint32_t w[4] = {v[i].x, v[i].y, v[i].z, v[i].w};
            uint32_t o[4];
#pragma unroll
            for (int j = 0; j < 4; j++) o[j] = pack_bf16(fmaf(bf_lo(w[j]), rstd, nmr), fmaf(bf_hi(w[j]), rstd, nmr));
            const uint32_t a = sA + (c >> 3) * 8192 + row * 128 + (((c & 7) ^ (row & 7)) << 4);
            asm volatile("st.shared.v4.b32 [%0], {%1, %2, %3, %4};" ::"r"(a), "r"(o[0]), "r"(o[1]), "r"(o[2]), "r"(o[3]) : "memory");
        }
    }
    proxy_fence();
    named_sync(1, 256);
    if (tid == 0) TS(0, 1);
    const int wg = warp >> 2, w = warp & 3, g = lane >> 2, t = lane & 3;
    const int r0 = m * 64 + w * 16 + g;
    if (isQ) {
        if (wg == 0) {
            float acc[64];
            proj_mma<128, false>(acc, sA, sB, 0, fullB, emptyB, 0, lane);
            if (tid == 0) TS(0, 2);
            named_sync(1, 256);
            uint32_t pk[32];
#pragma unroll
            for (int i = 0; i < 32; i++) pk[i] = pack_bf16(acc[2 * i] * Q_SCALE, acc[2 * i + 1] * Q_SCALE);
            stage_tile<16>(pk, sA, w, lane);
        } else {
            float acc[32];
            proj_mma<64, false>(acc, sA, sB, 2 * 8192, fullB, emptyB, 0, lane);
            named_sync(1, 256);
            uint32_t pk[16];
#pragma unroll
            for (int i = 0; i < 16; i++) pk[i] = pack_bf16(acc[2 * i] * Q_SCALE, acc[2 * i + 1] * Q_SCALE);
            stage_tile<8>(pk, sA + 2 * 8192, w, lane);
        }
        proxy_fence();
        named_sync(1, 256);
        if (warp == 0 && elect_one()) {
            for (int a = 0; a < 3; a++) tma_st_2d(&tmQ, cg * 192 + a * 64, m * 64, sA + a * 8192);
            bulk_commit();
            bulk_wait_all();
        }
    } else {
        float acc[12];
        const uint32_t blo = desc_lo(sB + wg * 3 * 9216, 128);
#pragma unroll 1
        for (int kb = 0; kb < 9; kb++) {
            const uint32_t alo = desc_lo(sA + kb * 8192, 16);
            wg_fence();
#pragma unroll
            for (int ks = 0; ks < 4; ks++)
                wgmma_ss_n24<0>(acc, desc64(alo + ks * 2, HI_SW128), desc64(blo + (kb * 4 + ks) * 16, desc_hi(9216, 0)), (kb | ks) != 0);
        }
        wg_commit();
        wg_wait<0>();
        pin(acc);
        uint32_t pk[6];
#pragma unroll
        for (int i = 0; i < 6; i++) pk[i] = pack_bf16(acc[2 * i], acc[2 * i + 1]);
        float n0 = 0.f, n1 = 0.f, vm = 0.f;
#pragma unroll
        for (int b = 0; b < 3; b++) {
            if (b < 2 || t == 0) {
                const float a = bf_lo(pk[2 * b]), c = bf_hi(pk[2 * b]), d = bf_lo(pk[2 * b + 1]), e = bf_hi(pk[2 * b + 1]);
                n0 = fmaf(a, a, fmaf(c, c, n0)); n1 = fmaf(d, d, fmaf(e, e, n1));
            }
        }
        n0 += __shfl_xor_sync(~0u, n0, 1); n0 += __shfl_xor_sync(~0u, n0, 2);
        n1 += __shfl_xor_sync(~0u, n1, 1); n1 += __shfl_xor_sync(~0u, n1, 2);
        vm = fmaxf(n0, n1);
        if (!(vm == vm)) vm = __int_as_float(0x7F800000);
#pragma unroll
        for (int o = 4; o < 32; o <<= 1) vm = fmaxf(vm, __shfl_xor_sync(~0u, vm, o));
        if (t != 0) {
            uint32_t lo, hi;
            if (wg == 0) {
                const int grp = m * 8 + w * 2;
                const uint32_t c = t == 1 ? 0x42FE3F80u   : (t == 2 ? 0x00003BC0u   : 0u);
                lo = ((POLY_MASK >> (grp & 15)) & 1) ? c : 0u;
                hi = ((POLY_MASK >> ((grp + 1) & 15)) & 1) ? c : 0u;
            } else {
                lo = hi = t == 1 ? 0x00003F80u : 0u;
            }
            pk[4] = lo; pk[5] = hi;
        }
        uint32_t* dst = reinterpret_cast<uint32_t*>(wg == 0 ? g_kc : g_vc) + (m * 8 + w * 2) * 96 + g * 4 + t;
#pragma unroll
        for (int b = 0; b < 3; b++) { dst[b * 32] = pk[2 * b]; dst[96 + b * 32] = pk[2 * b + 1]; }
        float* red = reinterpret_cast<float*>(smem + P_A_BYTES + 6 * 9216);
        if (lane == 0) red[warp] = (wg == 0) ? vm : (vm <= 1e24f ? 0.f : __int_as_float(0x7F800000));
        named_sync(1, 256);
        if (tid == 0) {
            float mx = red[0];
#pragma unroll
            for (int i = 1; i < 8; i++) mx = fmaxf(mx, red[i]);
            g_kmax[m] = mx;
        }
    }
    if (tid == 0) TS(0, 3);
}

constexpr int A_THREADS = 512;
constexpr int A_NPIECE = 8;
constexpr int A_SMEM = 2 * KV_BYTES + 128;

__device__ __forceinline__ uint32_t exp2_pair_fixed(float lo, float hi) {
    const uint32_t G = __byte_perm(__float_as_uint(lo), __float_as_uint(hi), 0x5410);
    const uint32_t Hh = G & 0x007F007Fu;
    const uint32_t tt = hfma2(Hh, 0xF96BF96Bu, 0x358C358Cu);
    return G - hfma2(tt, Hh, 0u);
}

__device__ __forceinline__ void attn_side_job(const __nv_bfloat16* __restrict__ w1, const __nv_bfloat16* __restrict__ w2, const __nv_bfloat16* __restrict__ wo, uint8_t* smem) {
    const int e = blockIdx.x - 128, tid = threadIdx.x;
    if (tid < 32) {
        const char* p = reinterpret_cast<const char*>(wo) + e * (DM * DM * 2 / 4);
        for (int i = tid; i < DM * DM * 2 / 4 / 4608; i += 32) prefetch_l2(p + i * 4608, 4608);
    }
    float* red = reinterpret_cast<float*>(smem);
    if (tid < 432) {
        const int c = tid % 144, rg = tid / 144;
        const uint4* src = reinterpret_cast<const uint4*>(w1 + (size_t)rg * 192 * FF + e * 1152) + c;
        float s[8] = {0.f, 0.f, 0.f, 0.f, 0.f, 0.f, 0.f, 0.f};
#pragma unroll 8
        for (int r = 0; r < 192; r++) {
            const uint4 v = __ldg(src + (size_t)r * (FF / 8));
            s[0] += bf_lo(v.x); s[1] += bf_hi(v.x); s[2] += bf_lo(v.y); s[3] += bf_hi(v.y);
            s[4] += bf_lo(v.z); s[5] += bf_hi(v.z); s[6] += bf_lo(v.w); s[7] += bf_hi(v.w);
        }
#pragma unroll
        for (int i = 0; i < 8; i++) red[rg * 1152 + c * 8 + i] = s[i];
    }
    __syncthreads();
    for (int i = tid; i < 1152; i += A_THREADS) g_cs1[e * 1152 + i] = red[i] + red[1152 + i] + red[2304 + i];
    if (tid < 32) {
        const char* p = reinterpret_cast<const char*>(w2) + (size_t)e * (FF * DM * 2 / 4);
        for (int i = tid; i < FF * DM * 2 / 4 / 9216; i += 32) prefetch_l2(p + (size_t)i * 9216, 9216);
    }
}

__global__ void __launch_bounds__(A_THREADS, 1)
k_attn(const __nv_bfloat16* __restrict__ w1, const __nv_bfloat16* __restrict__ w2, const __nv_bfloat16* __restrict__ wo) {
    extern __shared__ __align__(1024) uint8_t smem[];
    pdl_launch();
    if (blockIdx.x >= 128) { attn_side_job(w1, w2, wo, smem); return; }
    const uint32_t sK = smem_u32(smem), sV = sK + KV_BYTES, bars = sV + KV_BYTES;
    const int tid = threadIdx.x;
    if (tid == 0) TS(1, 0);
    if (tid == 0) {
        for (int i = 0; i < A_NPIECE; i++) mbar_init(bars + i * 8, 1);
        bar_init_fence();
    }
    __syncthreads();
    pdl_wait();
    if (tid == 0) TS(1, 1);
    if (tid < 32 && elect_one()) {
        constexpr int PB = KV_BYTES / A_NPIECE;
        for (int i = 0; i < A_NPIECE; i++) {
            mbar_expect(bars + i * 8, 2 * PB);
            bulk_g2s(sK + i * PB, reinterpret_cast<const char*>(g_kc) + i * PB, PB, bars + i * 8);
            bulk_g2s(sV + i * PB, reinterpret_cast<const char*>(g_vc) + i * PB, PB, bars + i * 8);
        }
    }
    const int wg = __shfl_sync(~0u, tid >> 7, 0), w = (tid >> 5) & 3, lane = tid & 31, g = lane >> 2, t = lane & 3;
    const uint32_t* q32 = reinterpret_cast<const uint32_t*>(g_q);
    uint32_t* o32 = reinterpret_cast<uint32_t*>(g_o);
    float kmax2 = g_kmax[lane];
#pragma unroll
    for (int o = 1; o < 32; o <<= 1) kmax2 = fmaxf(kmax2, __shfl_xor_sync(~0u, kmax2, o));
    constexpr uint32_t HI_K = desc_hi(384, 0), HI_V = desc_hi(128, 0);
    const uint32_t k0lo = desc_lo(sK, 128), k1lo = desc_lo(sK + 256, 0), vlo = desc_lo(sV, 384);

    int row = (blockIdx.x * 8 + wg) * 64 + w * 16 + g;
    uint32_t nq[6];
    nq[0] = q32[row * 9 + t]; nq[1] = q32[(row + 8) * 9 + t]; nq[2] = q32[row * 9 + 4 + t]; nq[3] = q32[(row + 8) * 9 + 4 + t];
    nq[4] = q32[row * 9 + 8]; nq[5] = q32[(row + 8) * 9 + 8];
#pragma unroll 1
    for (int rep = 0; rep < 2; rep++, row += 256) {
        uint32_t qa[4] = {nq[0], nq[1], nq[2], nq[3]}, qb[4];
        float n0, n1;
        {
            const float a0 = bf_lo(qa[0]), a1 = bf_hi(qa[0]), a2 = bf_lo(qa[2]), a3 = bf_hi(qa[2]);
            const float b0 = bf_lo(qa[1]), b1 = bf_hi(qa[1]), b2 = bf_lo(qa[3]), b3 = bf_hi(qa[3]);
            n0 = a0 * a0 + a1 * a1 + a2 * a2 + a3 * a3; n1 = b0 * b0 + b1 * b1 + b2 * b2 + b3 * b3;
            if (t == 0) {
                const float c0 = bf_lo(nq[4]), c1 = bf_hi(nq[4]), d0 = bf_lo(nq[5]), d1 = bf_hi(nq[5]);
                n0 += c0 * c0 + c1 * c1; n1 += d0 * d0 + d1 * d1;
            }
            n0 += __shfl_xor_sync(~0u, n0, 1); n0 += __shfl_xor_sync(~0u, n0, 2);
            n1 += __shfl_xor_sync(~0u, n1, 1); n1 += __shfl_xor_sync(~0u, n1, 2);
        }
        const uint32_t x0 = nq[4], x1 = nq[5];
        if (rep == 0) {
            const int nr = row + 256;
            nq[0] = q32[nr * 9 + t]; nq[1] = q32[(nr + 8) * 9 + t]; nq[2] = q32[nr * 9 + 4 + t]; nq[3] = q32[(nr + 8) * 9 + 4 + t];
            nq[4] = q32[nr * 9 + 8]; nq[5] = q32[(nr + 8) * 9 + 8];
        }
        const bool unsafe = !(fmaxf(n0, n1) * kmax2 <= FAST_BOUND * FAST_BOUND);
        uint32_t any_unsafe;
        asm volatile("{\n.reg .pred p, q;\nsetp.ne.u32 p, %1, 0;\nbar.red.or.pred q, %2, 128, p;\nselp.u32 %0, 1, 0, q;\n}\n" : "=r"(any_unsafe) : "r"((uint32_t)unsafe), "r"(wg + 1) : "memory");
        if (tid == 0) TS(1, 2 + rep * 2);
        float o[12];
#pragma unroll
        for (int i = 0; i < 12; i++) o[i] = 0.f;
        if (!any_unsafe) {
            float s[64];
            const uint32_t cst = t == 1 ? 0x3F804780u   : (t == 2 ? 0x00003F80u   : 0u);
            qb[0] = t == 0 ? x0 : cst; qb[1] = t == 0 ? x1 : cst; qb[2] = 0; qb[3] = 0;
            pin(qa); pin(qb); pin(o);
#pragma unroll 1
            for (int j = 0; j < 16; j++) {
                if (rep == 0 && (j & 1) == 0) mbar_wait(bars + (j >> 1) * 8, 0);
                const uint32_t off = j * (16 * 384 >> 4);
                wg_fence();
                wgmma_rs_n128<0>(s, qa[0], qa[1], qa[2], qa[3], desc64(k0lo + off, HI_K), 0);
                wgmma_rs_n128<0>(s, qb[0], qb[1], qb[2], qb[3], desc64(k1lo + off, HI_K), 1);
                wg_commit();
                wg_wait<0>();
                pin(s);
                uint32_t p[32];
#pragma unroll
                for (int i = 0; i < 32; i++) {
                    if ((POLY_MASK >> (i >> 1)) & 1) p[i] = exp2_pair_fixed(s[2 * i], s[2 * i + 1]);
                    else p[i] = pack_bf16(ex2(s[2 * i]), ex2(s[2 * i + 1]));
                }
                pin(p);
                wg_fence();
#pragma unroll
                for (int k = 0; k < 8; k++) wgmma_rs_n24<1>(o, p[4 * k], p[4 * k + 1], p[4 * k + 2], p[4 * k + 3], desc64(vlo + off + k * 48, HI_V), 1);
                wg_commit();
                wg_wait<0>();
            }
        } else {
            float s[64];
            qb[0] = t == 0 ? x0 : 0u; qb[1] = t == 0 ? x1 : 0u; qb[2] = 0; qb[3] = 0;
            pin(qa); pin(qb); pin(o);
            float m0 = -INFINITY, m1 = -INFINITY;
#pragma unroll 1
            for (int j = 0; j < 16; j++) {
                if (rep == 0 && (j & 1) == 0) mbar_wait(bars + (j >> 1) * 8, 0);
                const uint32_t off = j * (16 * 384 >> 4);
                wg_fence();
                wgmma_rs_n128<0>(s, qa[0], qa[1], qa[2], qa[3], desc64(k0lo + off, HI_K), 0);
                wgmma_rs_n128<0>(s, qb[0], qb[1], qb[2], qb[3], desc64(k1lo + off, HI_K), 1);
                wg_commit();
                wg_wait<0>();
                pin(s);
                float x0m = m0, x1m = m1;
#pragma unroll
                for (int b = 0; b < 16; b++) { x0m = fmaxf(x0m, fmaxf(s[4 * b], s[4 * b + 1])); x1m = fmaxf(x1m, fmaxf(s[4 * b + 2], s[4 * b + 3])); }
                x0m = fmaxf(x0m, __shfl_xor_sync(~0u, x0m, 1)); x0m = fmaxf(x0m, __shfl_xor_sync(~0u, x0m, 2));
                x1m = fmaxf(x1m, __shfl_xor_sync(~0u, x1m, 1)); x1m = fmaxf(x1m, __shfl_xor_sync(~0u, x1m, 2));
                const float c0 = ex2(m0 - x0m), c1 = ex2(m1 - x1m);
                m0 = x0m; m1 = x1m;
#pragma unroll
                for (int b = 0; b < 3; b++) { o[4 * b] *= c0; o[4 * b + 1] *= c0; o[4 * b + 2] *= c1; o[4 * b + 3] *= c1; }
                uint32_t p[32];
#pragma unroll
                for (int b = 0; b < 16; b++) {
                    p[2 * b] = pack_bf16(ex2(s[4 * b] - m0), ex2(s[4 * b + 1] - m0));
                    p[2 * b + 1] = pack_bf16(ex2(s[4 * b + 2] - m1), ex2(s[4 * b + 3] - m1));
                }
                pin(p); pin(o);
                wg_fence();
#pragma unroll
                for (int k = 0; k < 8; k++) wgmma_rs_n24<1>(o, p[4 * k], p[4 * k + 1], p[4 * k + 2], p[4 * k + 3], desc64(vlo + off + k * 48, HI_V), 1);
                wg_commit();
                wg_wait<0>();
            }
        }
        pin(o);
        if (tid == 0) TS(1, 3 + rep * 2);
        const float l0 = __shfl_sync(~0u, o[8], (lane & ~3) | 1), l1 = __shfl_sync(~0u, o[10], (lane & ~3) | 1);
        const float i0 = 1.0f / l0, i1 = 1.0f / l1;
        o32[row * 9 + t] = pack_bf16(o[0] * i0, o[1] * i0);
        o32[(row + 8) * 9 + t] = pack_bf16(o[2] * i1, o[3] * i1);
        o32[row * 9 + 4 + t] = pack_bf16(o[4] * i0, o[5] * i0);
        o32[(row + 8) * 9 + 4 + t] = pack_bf16(o[6] * i1, o[7] * i1);
        if (t == 0) { o32[row * 9 + 8] = pack_bf16(o[8] * i0, o[9] * i0); o32[(row + 8) * 9 + 8] = pack_bf16(o[10] * i1, o[11] * i1); }
    }
    if (tid == 0) TS(1, 6);
}

template <int NB>
__device__ __forceinline__ void oproj_load_x(uint32_t (&xr)[NB * 2], const uint32_t* __restrict__ x32, int r0, int col0, int t) {
#pragma unroll
    for (int b = 0; b < NB; b++) {
        const int i0 = (r0 * DM + col0 + b * 8 + 2 * t) >> 1;
        xr[2 * b] = __ldg(x32 + i0); xr[2 * b + 1] = __ldg(x32 + i0 + 4 * DM);
    }
}
template <int NB>
__device__ __forceinline__ void oproj_epilogue(const float (&acc)[NB * 4], uint32_t (&xr)[NB * 2], uint32_t stg, int r0, int part, int w, int lane) {
    float s0 = 0.f, q0 = 0.f, s1 = 0.f, q1 = 0.f;
#pragma unroll
    for (int b = 0; b < NB; b++) {
        const uint32_t xa = xr[2 * b], xb = xr[2 * b + 1];
        const uint32_t ha = pack_bf16(acc[4 * b] + bf_lo(xa), acc[4 * b + 1] + bf_hi(xa));
        const uint32_t hb = pack_bf16(acc[4 * b + 2] + bf_lo(xb), acc[4 * b + 3] + bf_hi(xb));
        xr[2 * b] = ha; xr[2 * b + 1] = hb;
        const float a = bf_lo(ha), c = bf_hi(ha), d = bf_lo(hb), e = bf_hi(hb);
        s0 += a + c; q0 = fmaf(a, a, fmaf(c, c, q0));
        s1 += d + e; q1 = fmaf(d, d, fmaf(e, e, q1));
    }
    stage_tile<NB>(xr, stg, w, lane);
    s0 += __shfl_xor_sync(~0u, s0, 1); s0 += __shfl_xor_sync(~0u, s0, 2);
    q0 += __shfl_xor_sync(~0u, q0, 1); q0 += __shfl_xor_sync(~0u, q0, 2);
    s1 += __shfl_xor_sync(~0u, s1, 1); s1 += __shfl_xor_sync(~0u, s1, 2);
    q1 += __shfl_xor_sync(~0u, q1, 1); q1 += __shfl_xor_sync(~0u, q1, 2);
    if ((lane & 3) == 0) { g_stat[part * SEQ + r0] = make_float2(s0, q0); g_stat[part * SEQ + r0 + 8] = make_float2(s1, q1); }
}

__global__ void __launch_bounds__(P_THREADS, 1)
k_oproj(const __grid_constant__ CUtensorMap tmO, const __grid_constant__ CUtensorMap tmWo, const __grid_constant__ CUtensorMap tmH, const __grid_constant__ CUtensorMap tmOut, const __nv_bfloat16* __restrict__ x) {
    extern __shared__ __align__(1024) uint8_t smem[];
    const uint32_t sA = smem_u32(smem), sB = sA + P_A_BYTES, bars = sB + P_NST * P_B_STAGE;
    const uint32_t fullB = bars, emptyB = bars + 64, fullA = bars + 128;
    const int tid = threadIdx.x, warp = __shfl_sync(~0u, tid >> 5, 0), lane = tid & 31;
    const int m = blockIdx.x / 3, cg = blockIdx.x % 3;
    if (tid == 0) TS(2, 0);
    if (tid == 0) {
        for (int i = 0; i < P_NST; i++) { mbar_init(fullB + i * 8, 1); mbar_init(emptyB + i * 8, 8); }
        for (int i = 0; i < 9; i++) mbar_init(fullA + i * 8, 1);
        bar_init_fence();
    }
    __syncthreads();
    pdl_launch();
    if (warp == 8) {
        if (elect_one()) {
            for (int kb = 0; kb < P_NST; kb++) {
                mbar_expect(fullB + kb * 8, P_B_STAGE);
                for (int a = 0; a < 3; a++) tma_2d(sB + kb * P_B_STAGE + a * 8192, &tmWo, cg * 192 + a * 64, kb * 64, fullB + kb * 8);
            }
            pdl_wait();
            for (int kb = 0; kb < 9; kb++) {
                mbar_expect(fullA + kb * 8, 8192);
                tma_2d(sA + kb * 8192, &tmO, kb * 64, m * 64, fullA + kb * 8);
            }
            for (int kb = P_NST; kb < 9; kb++) {
                const int s = kb - P_NST;
                mbar_wait(emptyB + s * 8, 0);
                mbar_expect(fullB + s * 8, P_B_STAGE);
                for (int a = 0; a < 3; a++) tma_2d(sB + s * P_B_STAGE + a * 8192, &tmWo, cg * 192 + a * 64, kb * 64, fullB + s * 8);
            }
        }
        return;
    }
    const int wg = warp >> 2, w = warp & 3, g = lane >> 2, t = lane & 3;
    const int r0 = m * 64 + w * 16 + g;
    const uint32_t* x32 = reinterpret_cast<const uint32_t*>(x);
    if (wg == 0) {
        uint32_t xr[32];
        oproj_load_x<16>(xr, x32, r0, cg * 192, t);
        float acc[64];
        proj_mma<128, true>(acc, sA, sB, 0, fullB, emptyB, fullA, lane);
        if (tid == 0) TS(2, 2);
        named_sync(1, 256);
        pdl_wait();
        oproj_epilogue<16>(acc, xr, sA, r0, cg * 2, w, lane);
    } else {
        uint32_t xr[16];
        oproj_load_x<8>(xr, x32, r0, cg * 192 + 128, t);
        float acc[32];
        proj_mma<64, true>(acc, sA, sB, 2 * 8192, fullB, emptyB, fullA, lane);
        named_sync(1, 256);
        pdl_wait();
        oproj_epilogue<8>(acc, xr, sA + 2 * 8192, r0, cg * 2 + 1, w, lane);
    }
    proxy_fence();
    named_sync(1, 256);
    if (warp == 0 && elect_one()) {
        for (int a = 0; a < 3; a++) {
            tma_st_2d(&tmH, cg * 192 + a * 64, m * 64, sA + a * 8192);
            tma_st_2d(&tmOut, cg * 192 + a * 64, m * 64, sA + a * 8192);
        }
        bulk_commit();
        bulk_wait_all();
        TS(2, 3);
    }
}

constexpr int F_THREADS = 384;
constexpr int F_NST = 6;
constexpr int F_STAGE = 96 * 128;
constexpr int F_X_BYTES = 9 * 16384;
constexpr int F_OFF_ST = F_X_BYTES;
constexpr int F_OFF_CS = F_OFF_ST + F_NST * F_STAGE;
constexpr int F_OFF_BAR = F_OFF_CS + 576 * 4;
constexpr int F_SMEM = F_OFF_BAR + 256;

struct RowStat { float nmean0, c0, istd0, nmean1, c1, istd1; };

__device__ __forceinline__ void silu_s1(float (&acc)[32], float (&tmp)[8], int piece, uint32_t cs_addr, const RowStat& st) {
#pragma unroll
    for (int h = 0; h < 2; h++) {
        const int b = 2 * piece + h;
        float cs0, cs1;
        asm volatile("ld.shared.v2.f32 {%0, %1}, [%2];" : "=f"(cs0), "=f"(cs1) : "r"(cs_addr + b * 32));
        acc[4 * b] = fmaf(st.nmean0, cs0, acc[4 * b]); acc[4 * b + 1] = fmaf(st.nmean0, cs1, acc[4 * b + 1]);
        acc[4 * b + 2] = fmaf(st.nmean1, cs0, acc[4 * b + 2]); acc[4 * b + 3] = fmaf(st.nmean1, cs1, acc[4 * b + 3]);
        tmp[4 * h] = ex2(acc[4 * b] * st.c0); tmp[4 * h + 1] = ex2(acc[4 * b + 1] * st.c0);
        tmp[4 * h + 2] = ex2(acc[4 * b + 2] * st.c1); tmp[4 * h + 3] = ex2(acc[4 * b + 3] * st.c1);
    }
}
__device__ __forceinline__ void silu_s2(float (&tmp)[8], const RowStat& st) {
#pragma unroll
    for (int i = 0; i < 8; i++) { const float is = (i & 2) ? st.istd1 : st.istd0; tmp[i] = rcp(fmaf(tmp[i], is, is)); }
}
template <int C>
__device__ __forceinline__ void silu_s3(const float (&acc)[32], const float (&tmp)[8], uint32_t (&h1)[144], int piece) {
#pragma unroll
    for (int i = 0; i < 4; i++) h1[C * 16 + 4 * piece + i] = pack_bf16(acc[8 * piece + 2 * i] * tmp[2 * i], acc[8 * piece + 2 * i + 1] * tmp[2 * i + 1]);
}

struct FfnPipe {
    uint32_t full, empty;
    int lane;
    __device__ __forceinline__ void acquire(int s, uint32_t ph) const { mbar_wait(full + s * 8, ph); }
    __device__ __forceinline__ void release(int s) const { if (lane == 0) mbar_arrive(empty + s * 8); }
};

template <int C>
__device__ __forceinline__ void ffn_phase1_chunk(float (&cur)[32], float (&prev)[32], uint32_t (&h1)[144], const FfnPipe& pp, uint64_t dx, uint32_t fullX, uint32_t cs_addr, const RowStat& st) {
    float tmp[2][8];
    dx += blockIdx.y * C;
#pragma unroll
    for (int j = 0; j < 6; j++) {
        if (C == 0) { mbar_wait(fullX + ((6 * j) >> 2) * 8, 0); mbar_wait(fullX + ((6 * j + 5) >> 2) * 8, 0); }
        pp.acquire(j, C & 1);
        if (j == 0) pin(cur);
        wg_fence();
#pragma unroll
        for (int i = 0; i < 6; i++) {
            const int ks = 6 * j + i;
            wgmma_ss_n64<1>(cur, dx + ((ks >> 2) * 1024 + (ks & 3) * 2), cdesc(F_OFF_ST + j * F_STAGE + i * 2048, 8192, 1024, 1), ks != 0);
        }
        wg_commit();
        if (C > 0) {
            if (j == 0) pin(prev);
            if (j >= 2) silu_s3<(C > 0 ? C - 1 : 0)>(prev, tmp[j & 1], h1, j - 2);
            if (j >= 1 && j <= 4) { silu_s2(tmp[(j - 1) & 1], st); pin(tmp[(j - 1) & 1]); }
            if (j <= 3) { silu_s1(prev, tmp[j & 1], j, cs_addr + (C - 1) * 256, st); pin(tmp[j & 1]); }
        }
        wg_wait<0>();
        pp.release(j);
    }
}

__device__ __forceinline__ void ffn_store_chunk(const float (&acc)[32], const CUtensorMap* tmOut, uint32_t stg, int col, int row, int w, int lane, int wgid) {
    uint32_t pk[16];
#pragma unroll
    for (int i = 0; i < 16; i++) pk[i] = pack_bf16(acc[2 * i], acc[2 * i + 1]);
    stage_tile<8>(pk, stg, w, lane);
    proxy_fence();
    named_sync(2 + wgid, 128);
    if (w == 0 && elect_one()) {
        tma_red_2d(tmOut, col, row, stg);
        bulk_commit();
    }
}

__device__ __forceinline__ void ffn_phase2_chunk(float (&cur)[32], float (&prev)[32], uint32_t (&h1)[144], const FfnPipe& pp, uint32_t ph, bool store_prev, const CUtensorMap* tmOut, uint32_t stg_prev, int col_prev, int row, int w, int lane, int wgid) {
#pragma unroll
    for (int j = 0; j < 6; j++) {
        pp.acquire(j, ph);
        if (j == 0) pin(cur);
        wg_fence();
#pragma unroll
        for (int i = 0; i < 6; i++) {
            const int f = (6 * j + i) * 4;
            wgmma_rs_n64<1>(cur, h1[f], h1[f + 1], h1[f + 2], h1[f + 3], cdesc(F_OFF_ST + j * F_STAGE + i * 2048, 8192, 1024, 1), (j | i) != 0);
        }
        wg_commit();
        if (j == 0 && store_prev) { pin(prev); ffn_store_chunk(prev, tmOut, stg_prev, col_prev, row, w, lane, wgid); }
        wg_wait<0>();
        pp.release(j);
    }
}

__global__ void __launch_bounds__(F_THREADS, 1)
k_ffn(const __grid_constant__ CUtensorMap tmH, const __grid_constant__ CUtensorMap tmW1, const __grid_constant__ CUtensorMap tmW2, const __grid_constant__ CUtensorMap tmOut) {
    extern __shared__ __align__(1024) uint8_t smem[];
    const uint32_t sX = smem_u32(smem), sSt = sX + F_OFF_ST, sCs = sX + F_OFF_CS, bars = sX + F_OFF_BAR;
    const uint32_t full = bars, empty = bars + 64, fullX = bars + 128;
    const int tid = threadIdx.x, warp = __shfl_sync(~0u, tid >> 5, 0), lane = tid & 31;
    const int m = blockIdx.x & 15, fs = blockIdx.x >> 4;
    if (tid == 0) TS(3, 0);
    check_smem_base(sX);
    if (tid == 0) {
        for (int i = 0; i < F_NST; i++) { mbar_init(full + i * 8, 1); mbar_init(empty + i * 8, 8); }
        for (int i = 0; i < 9; i++) mbar_init(fullX + i * 8, 1);
        bar_init_fence();
    }
    __syncthreads();
    if (warp < 4) {
        asm volatile("setmaxnreg.dec.sync.aligned.u32 24;");
        if (warp == 0 && elect_one()) {
            int s = 0; uint32_t ph = 1;
            int c = 0, j = 0;
#pragma unroll 1
            for (int i = 0; i < 108; i++) {
                if (i == F_NST) {
                    pdl_wait();
                    for (int kb = 0; kb < 9; kb++) {
                        mbar_expect(fullX + kb * 8, 16384);
                        tma_2d(sX + kb * 16384, &tmH, kb * 64, m * 128, fullX + kb * 8);
                    }
                }
                if (i == 54) c = fs;
                mbar_wait(empty + s * 8, ph);
                mbar_expect(full + s * 8, F_STAGE);
                if (i < 54) tma_2d(sSt + s * F_STAGE, &tmW1, fs * 576 + c * 64, j * 96, full + s * 8);
                else tma_2d(sSt + s * F_STAGE, &tmW2, c * 64, fs * 576 + j * 96, full + s * 8);
                if (++j == 6) { j = 0; if (++c == 9) c = 0; }
                if (++s == F_NST) { s = 0; ph ^= 1; }
            }
        }
    } else {
        asm volatile("setmaxnreg.inc.sync.aligned.u32 240;");
        const int wgid = (warp >> 2) - 1, w = warp & 3, g = lane >> 2;
        pdl_wait();
        if (tid == 128) TS(3, 1);
        for (int i = tid - 128; i < 576; i += 256) reinterpret_cast<float*>(smem + F_OFF_CS)[i] = g_cs1[fs * 576 + i];
        RowStat st;
        {
            const int r0 = m * 128 + wgid * 64 + w * 16 + g;
            float s0 = 0.f, q0 = 0.f, s1 = 0.f, q1 = 0.f;
#pragma unroll
            for (int p = 0; p < 6; p++) {
                const float2 a = g_stat[p * SEQ + r0], b = g_stat[p * SEQ + r0 + 8];
                s0 += a.x; q0 += a.y; s1 += b.x; q1 += b.y;
            }
            const float m0 = s0 * (1.0f / DM), m1 = s1 * (1.0f / DM);
            const float v0 = fmaxf(q0 * (1.0f / DM) - m0 * m0, 0.f) + LN_EPS, v1 = fmaxf(q1 * (1.0f / DM) - m1 * m1, 0.f) + LN_EPS;
            st.istd0 = sqrtf(v0); st.istd1 = sqrtf(v1);
            st.nmean0 = -m0; st.nmean1 = -m1;
            st.c0 = -LOG2E / st.istd0; st.c1 = -LOG2E / st.istd1;
        }
        FfnPipe pp{full, empty, lane};
        const uint32_t cs_addr = sCs + (lane & 3) * 8;
        const uint64_t xlo = cdesc(0, 16, 1024, 1) + wgid * 512;
        uint32_t h1[144];
        float acc0[32], acc1[32];
        ffn_phase1_chunk<0>(acc0, acc1, h1, pp, xlo, fullX, cs_addr, st);
        named_sync(1, 256);
        if (tid == 128) TS(3, 2);
        ffn_phase1_chunk<1>(acc1, acc0, h1, pp, xlo, fullX, cs_addr, st);
        ffn_phase1_chunk<2>(acc0, acc1, h1, pp, xlo, fullX, cs_addr, st);
        ffn_phase1_chunk<3>(acc1, acc0, h1, pp, xlo, fullX, cs_addr, st);
        ffn_phase1_chunk<4>(acc0, acc1, h1, pp, xlo, fullX, cs_addr, st);
        ffn_phase1_chunk<5>(acc1, acc0, h1, pp, xlo, fullX, cs_addr, st);
        ffn_phase1_chunk<6>(acc0, acc1, h1, pp, xlo, fullX, cs_addr, st);
        ffn_phase1_chunk<7>(acc1, acc0, h1, pp, xlo, fullX, cs_addr, st);
        ffn_phase1_chunk<8>(acc0, acc1, h1, pp, xlo, fullX, cs_addr, st);
        pin(acc0);
        {
            float tmp[4][8];
#pragma unroll
            for (int p = 0; p < 4; p++) silu_s1(acc0, tmp[p], p, cs_addr + 8 * 256, st);
#pragma unroll
            for (int p = 0; p < 4; p++) silu_s2(tmp[p], st);
#pragma unroll
            for (int p = 0; p < 4; p++) silu_s3<8>(acc0, tmp[p], h1, p);
        }
        pin(h1);
        if (tid == 128) TS(3, 3);
        const int row = m * 128 + wgid * 64;
        const uint32_t stg = sX + wgid * 8192;
        int c = fs, cprev = 0;
#pragma unroll 1
        for (int j = 0; j < 8; j += 2) {
            ffn_phase2_chunk(acc1, acc0, h1, pp, 1, j > 0, &tmOut, stg + (j - 1) * 16384, cprev * 64, row, w, lane, wgid);
            cprev = c; if (++c == 9) c = 0;
            ffn_phase2_chunk(acc0, acc1, h1, pp, 0, true, &tmOut, stg + j * 16384, cprev * 64, row, w, lane, wgid);
            cprev = c; if (++c == 9) c = 0;
        }
        ffn_phase2_chunk(acc1, acc0, h1, pp, 1, true, &tmOut, stg + 7 * 16384, cprev * 64, row, w, lane, wgid);
        pin(acc1);
        ffn_store_chunk(acc1, &tmOut, stg + 8 * 16384, c * 64, row, w, lane, wgid);
        if (tid == 128) TS(3, 4);
        if (w == 0) bulk_wait_all();
        if (tid == 128) TS(3, 5);
    }
}

typedef CUresult (*EncodeFn)(CUtensorMap*, CUtensorMapDataType, cuuint32_t, void*, const cuuint64_t*, const cuuint64_t*, const cuuint32_t*, const cuuint32_t*,
                             CUtensorMapInterleave, CUtensorMapSwizzle, CUtensorMapL2promotion, CUtensorMapFloatOOBfill);

CUtensorMap make_map(EncodeFn enc, const void* base, int rows, int cols, int box_rows) {
    CUtensorMap tm;
    cuuint64_t dims[2] = {(cuuint64_t)cols, (cuuint64_t)rows};
    cuuint64_t strides[1] = {(cuuint64_t)cols * 2};
    cuuint32_t box[2] = {64, (cuuint32_t)box_rows};
    cuuint32_t es[2] = {1, 1};
    enc(&tm, CU_TENSOR_MAP_DATA_TYPE_BFLOAT16, 2, const_cast<void*>(base), dims, strides, box, es, CU_TENSOR_MAP_INTERLEAVE_NONE,
        CU_TENSOR_MAP_SWIZZLE_128B, CU_TENSOR_MAP_L2_PROMOTION_L2_256B, CU_TENSOR_MAP_FLOAT_OOB_FILL_NONE);
    return tm;
}

template <typename... KArgs, typename... Args>
void launch(void (*kern)(KArgs...), int grid, int block, int smem, bool pdl, Args... args) {
    cudaLaunchConfig_t cfg = {};
    cfg.gridDim = dim3(grid); cfg.blockDim = dim3(block); cfg.dynamicSmemBytes = smem; cfg.stream = cudaStreamPerThread;
    cudaLaunchAttribute at[1];
    at[0].id = cudaLaunchAttributeProgrammaticStreamSerialization;
    at[0].val.programmaticStreamSerializationAllowed = 1;
    cfg.attrs = at; cfg.numAttrs = pdl ? 1 : 0;
    cudaLaunchKernelEx(&cfg, kern, KArgs(args)...);
}

}

#define USE_PDL 1

extern "C" void kernel_launch(void* const* d_in, const int* in_sizes, int n_in, void* d_out, int out_size) {
    const __nv_bfloat16* x = (const __nv_bfloat16*)d_in[0];
    const __nv_bfloat16* wq = (const __nv_bfloat16*)d_in[1];
    const __nv_bfloat16* wk = (const __nv_bfloat16*)d_in[2];
    const __nv_bfloat16* wv = (const __nv_bfloat16*)d_in[3];
    const __nv_bfloat16* wo = (const __nv_bfloat16*)d_in[4];
    const __nv_bfloat16* w1 = (const __nv_bfloat16*)d_in[6];
    const __nv_bfloat16* w2 = (const __nv_bfloat16*)d_in[7];
    __nv_bfloat16* out = (__nv_bfloat16*)d_out;

    static EncodeFn enc = nullptr;
    static void *p_o = nullptr, *p_h = nullptr, *p_q = nullptr;
    if (!enc) {
        cudaDriverEntryPointQueryResult qr;
        cudaGetDriverEntryPoint("cuTensorMapEncodeTiled", (void**)&enc, cudaEnableDefault, &qr);
        cudaGetSymbolAddress(&p_o, g_o);
        cudaGetSymbolAddress(&p_h, g_h);
        cudaGetSymbolAddress(&p_q, g_q);
        cudaFuncSetAttribute(k_qkv, cudaFuncAttributeMaxDynamicSharedMemorySize, P_SMEM);
        cudaFuncSetAttribute(k_attn, cudaFuncAttributeMaxDynamicSharedMemorySize, A_SMEM);
        cudaFuncSetAttribute(k_oproj, cudaFuncAttributeMaxDynamicSharedMemorySize, P_SMEM);
        cudaFuncSetAttribute(k_ffn, cudaFuncAttributeMaxDynamicSharedMemorySize, F_SMEM);
    }
    const CUtensorMap tmWq = make_map(enc, wq, DM, DM, 64);
    const CUtensorMap tmWo = make_map(enc, wo, DM, DM, 64);
    const CUtensorMap tmO = make_map(enc, p_o, SEQ, DM, 64);
    const CUtensorMap tmH = make_map(enc, p_h, SEQ, DM, 128);
    const CUtensorMap tmH64 = make_map(enc, p_h, SEQ, DM, 64);
    const CUtensorMap tmQ = make_map(enc, p_q, SEQ, DM, 64);
    const CUtensorMap tmW1 = make_map(enc, w1, DM, FF, 96);
    const CUtensorMap tmW2 = make_map(enc, w2, FF, DM, 96);
    const CUtensorMap tmOut = make_map(enc, out, SEQ, DM, 64);

    launch(k_qkv, 128, P_THREADS, P_SMEM, false, tmWq, tmQ, x, wk, wv);
    launch(k_attn, 132, A_THREADS, A_SMEM, USE_PDL, w1, w2, wo);
    launch(k_oproj, 96, P_THREADS, P_SMEM, USE_PDL, tmO, tmWo, tmH64, tmOut, x);
    launch(k_ffn, 128, F_THREADS, F_SMEM, USE_PDL, tmH, tmW1, tmW2, tmOut);
}
```

```cpp
#include <cuda_runtime.h>
#include <cuda_bf16.h>
#include <cuda.h>
#include <stdint.h>

namespace {

constexpr int SEQ = 2048, DM = 576, FF = 4608;
constexpr int KV_BYTES = SEQ * 48;
constexpr float LN_EPS = 1e-5f;
constexpr float LOG2E = 1.4426950408889634f;
constexpr float Q_SCALE = 0.23570226039551584f * LOG2E;

constexpr uint32_t POLY_MASK = 0xB5B5u;
constexpr float FAST_BOUND = 60.0f;

__device__ __align__(1024) __nv_bfloat16 g_q[SEQ * DM];
__device__ __align__(1024) uint4 g_kc[KV_BYTES / 16];
__device__ __align__(1024) uint4 g_vc[KV_BYTES / 16];
__device__ float g_kmax[32];
__device__ __align__(1024) __nv_bfloat16 g_o[SEQ * DM];
__device__ __align__(1024) __nv_bfloat16 g_h[SEQ * DM];
__device__ float2 g_stat[6 * SEQ];
__device__ __align__(16) float g_cs1[FF];

#define TS(k, i)

__device__ __forceinline__ uint32_t smem_u32(const void* p) { return (uint32_t)__cvta_generic_to_shared(p); }
__device__ __forceinline__ void wg_fence() { asm volatile("wgmma.fence.sync.aligned;" ::: "memory"); }
__device__ __forceinline__ void wg_commit() { asm volatile("wgmma.commit_group.sync.aligned;" ::: "memory"); }
template <int N> __device__ __forceinline__ void wg_wait() { asm volatile("wgmma.wait_group.sync.aligned %0;" ::"n"(N) : "memory"); }
template <int N> __device__ __forceinline__ void pin(float (&r)[N]) {
#pragma unroll
    for (int i = 0; i < N; i++) asm volatile("" : "+f"(r[i])::"memory");
}
template <int N> __device__ __forceinline__ void pin(uint32_t (&r)[N]) {
#pragma unroll
    for (int i = 0; i < N; i++) asm volatile("" : "+r"(r[i])::"memory");
}
__device__ __forceinline__ constexpr uint32_t desc_hi(uint32_t sbo, uint32_t swz) { return (sbo >> 4) | (swz << 30); }
__device__ __forceinline__ uint32_t desc_lo(uint32_t addr, uint32_t lbo) { return ((addr & 0x3FFFF) >> 4) | ((lbo >> 4) << 16); }
__device__ __forceinline__ uint64_t desc64(uint32_t lo, uint32_t hi) { return ((uint64_t)hi << 32) | lo; }
constexpr uint32_t SMEM0 = 0x400;
__host__ __device__ constexpr uint64_t cdesc(uint32_t off, uint32_t lbo, uint32_t sbo, uint32_t swz) {
    return (uint64_t)(((SMEM0 + off) & 0x3FFFF) >> 4) | ((uint64_t)(lbo >> 4) << 16) | ((uint64_t)(sbo >> 4) << 32) | ((uint64_t)swz << 62);
}
__device__ __forceinline__ void check_smem_base(uint32_t base) { if ((base & 0x3FFFF) != SMEM0) __trap(); }

__device__ __forceinline__ void mbar_init(uint32_t bar, int cnt) { asm volatile("mbarrier.init.shared::cta.b64 [%0], %1;" ::"r"(bar), "r"(cnt) : "memory"); }
__device__ __forceinline__ void mbar_expect(uint32_t bar, int bytes) { asm volatile("mbarrier.arrive.expect_tx.shared::cta.b64 _, [%0], %1;" ::"r"(bar), "r"(bytes) : "memory"); }
__device__ __forceinline__ void mbar_arrive(uint32_t bar) { asm volatile("mbarrier.arrive.shared::cta.b64 _, [%0];" ::"r"(bar) : "memory"); }
__device__ __forceinline__ void mbar_wait(uint32_t bar, uint32_t parity) {
    asm volatile(
        "{\n.reg .pred p;\n.reg .u32 n;\nmov.u32 n, 0;\n"
        "LAB_WAIT:\n"
        "mbarrier.try_wait.parity.shared::cta.b64 p, [%0], %1;\n"
        "@p bra DONE;\n"
        "add.u32 n, n, 1;\n"
        "setp.lt.u32 p, n, 4000000;\n"
        "@p bra LAB_WAIT;\n"
        "trap;\n"
        "DONE:\n}\n" ::"r"(bar), "r"(parity) : "memory");
}
__device__ __forceinline__ void bar_init_fence() {
    asm volatile("fence.mbarrier_init.release.cluster;" ::: "memory");
    asm volatile("fence.proxy.async.shared::cta;" ::: "memory");
}
__device__ __forceinline__ void proxy_fence() { asm volatile("fence.proxy.async.shared::cta;" ::: "memory"); }
__device__ __forceinline__ void named_sync(int id, int n) { asm volatile("bar.sync %0, %1;" ::"r"(id), "r"(n) : "memory"); }
__device__ __forceinline__ void bulk_g2s(uint32_t dst, const void* src, int bytes, uint32_t bar) {
    asm volatile("cp.async.bulk.shared::cluster.global.mbarrier::complete_tx::bytes [%0], [%1], %2, [%3];" ::"r"(dst), "l"(src), "r"(bytes), "r"(bar) : "memory");
}
__device__ __forceinline__ void tma_2d(uint32_t dst, const CUtensorMap* tm, int c0, int c1, uint32_t bar) {
    asm volatile("cp.async.bulk.tensor.2d.shared::cluster.global.mbarrier::complete_tx::bytes [%0], [%1, {%3, %4}], [%2];" ::"r"(dst), "l"(tm), "r"(bar), "r"(c0), "r"(c1) : "memory");
}
__device__ __forceinline__ void tma_red_2d(const CUtensorMap* tm, int c0, int c1, uint32_t src) {
    asm volatile("cp.reduce.async.bulk.tensor.2d.global.shared::cta.add.tile.bulk_group [%0, {%2, %3}], [%1];" ::"l"(tm), "r"(src), "r"(c0), "r"(c1) : "memory");
}
__device__ __forceinline__ void tma_st_2d(const CUtensorMap* tm, int c0, int c1, uint32_t src) {
    asm volatile("cp.async.bulk.tensor.2d.global.shared::cta.tile.bulk_group [%0, {%2, %3}], [%1];" ::"l"(tm), "r"(src), "r"(c0), "r"(c1) : "memory");
}
__device__ __forceinline__ void bulk_commit() { asm volatile("cp.async.bulk.commit_group;" ::: "memory"); }
__device__ __forceinline__ void bulk_wait_all() { asm volatile("cp.async.bulk.wait_group 0;" ::: "memory"); }
__device__ __forceinline__ bool elect_one() {
    uint32_t p;
    asm volatile("{\n.reg .pred P;\nelect.sync _|P, 0xffffffff;\nselp.b32 %0, 1, 0, P;\n}\n" : "=r"(p));
    return p != 0;
}
__device__ __forceinline__ void prefetch_l2(const void* p, int bytes) { asm volatile("cp.async.bulk.prefetch.L2.global [%0], %1;" ::"l"(p), "r"(bytes) : "memory"); }
__device__ __forceinline__ void pdl_launch() { asm volatile("griddepcontrol.launch_dependents;" ::: "memory"); }
__device__ __forceinline__ void pdl_wait() { asm volatile("griddepcontrol.wait;" ::: "memory"); }
__device__ __forceinline__ float ex2(float x) { float y; asm("ex2.approx.ftz.f32 %0, %1;" : "=f"(y) : "f"(x)); return y; }
__device__ __forceinline__ float rcp(float x) { float y; asm("rcp.approx.ftz.f32 %0, %1;" : "=f"(y) : "f"(x)); return y; }
__device__ __forceinline__ uint32_t pack_bf16(float lo, float hi) { uint32_t r; asm("cvt.rn.bf16x2.f32 %0, %1, %2;" : "=r"(r) : "f"(hi), "f"(lo)); return r; }
__device__ __forceinline__ float bf_lo(uint32_t v) { return __uint_as_float(v << 16); }
__device__ __forceinline__ float bf_hi(uint32_t v) { return __uint_as_float(v & 0xFFFF0000u); }
__device__ __forceinline__ uint32_t hfma2(uint32_t a, uint32_t b, uint32_t c) { uint32_t r; asm("fma.rn.f16x2 %0, %1, %2, %3;" : "=r"(r) : "r"(a), "r"(b), "r"(c)); return r; }
__device__ __forceinline__ void stmatrix_x4(uint32_t addr, uint32_t r0, uint32_t r1, uint32_t r2, uint32_t r3) {
    asm volatile("stmatrix.sync.aligned.m8n8.x4.shared.b16 [%0], {%1, %2, %3, %4};" ::"r"(addr), "r"(r0), "r"(r1), "r"(r2), "r"(r3) : "memory");
}

template <int TB> __device__ __forceinline__ void wgmma_ss_n24(float (&d)[12], uint64_t da, uint64_t db, int sc) {
    asm volatile("{\n.reg .pred p;\nsetp.ne.b32 p, %14, 0;\n"
        "wgmma.mma_async.sync.aligned.m64n24k16.f32.bf16.bf16 {%0, %1, %2, %3, %4, %5, %6, %7, %8, %9, %10, %11}, %12, %13, p, 1, 1, 0, %15;\n}\n"
        : "+f"(d[0]), "+f"(d[1]), "+f"(d[2]), "+f"(d[3]), "+f"(d[4]), "+f"(d[5]), "+f"(d[6]), "+f"(d[7]), "+f"(d[8]), "+f"(d[9]), "+f"(d[10]), "+f"(d[11])
        : "l"(da), "l"(db), "r"(sc), "n"(TB));
}
template <int TB> __device__ __forceinline__ void wgmma_ss_n64(float (&d)[32], uint64_t da, uint64_t db, int sc) {
    asm volatile("{\n.reg .pred p;\nsetp.ne.b32 p, %34, 0;\n"
        "wgmma.mma_async.sync.aligned.m64n64k16.f32.bf16.bf16 {%0, %1, %2, %3, %4, %5, %6, %7, %8, %9, %10, %11, %12, %13, %14, %15, %16, %17, %18, %19, %20, %21, %22, %23, %24, %25, %26, %27, %28, %29, %30, %31}, %32, %33, p, 1, 1, 0, %35;\n}\n"
        : "+f"(d[0]), "+f"(d[1]), "+f"(d[2]), "+f"(d[3]), "+f"(d[4]), "+f"(d[5]), "+f"(d[6]), "+f"(d[7]), "+f"(d[8]), "+f"(d[9]), "+f"(d[10]), "+f"(d[11]), "+f"(d[12]), "+f"(d[13]), "+f"(d[14]), "+f"(d[15]), "+f"(d[16]), "+f"(d[17]), "+f"(d[18]), "+f"(d[19]), "+f"(d[20]), "+f"(d[21]), "+f"(d[22]), "+f"(d[23]), "+f"(d[24]), "+f"(d[25]), "+f"(d[26]), "+f"(d[27]), "+f"(d[28]), "+f"(d[29]), "+f"(d[30]), "+f"(d[31])
        : "l"(da), "l"(db), "r"(sc), "n"(TB));
}
template <int TB> __device__ __forceinline__ void wgmma_ss_n128(float (&d)[64], uint64_t da, uint64_t db, int sc) {
    asm volatile("{\n.reg .pred p;\nsetp.ne.b32 p, %66, 0;\n"
        "wgmma.mma_async.sync.aligned.m64n128k16.f32.bf16.bf16 {%0, %1, %2, %3, %4, %5, %6, %7, %8, %9, %10, %11, %12, %13, %14, %15, %16, %17, %18, %19, %20, %21, %22, %23, %24, %25, %26, %27, %28, %29, %30, %31, %32, %33, %34, %35, %36, %37, %38, %39, %40, %41, %42, %43, %44, %45, %46, %47, %48, %49, %50, %51, %52, %53, %54, %55, %56, %57, %58, %59, %60, %61, %62, %63}, %64, %65, p, 1, 1, 0, %67;\n}\n"
        : "+f"(d[0]), "+f"(d[1]), "+f"(d[2]), "+f"(d[3]), "+f"(d[4]), "+f"(d[5]), "+f"(d[6]), "+f"(d[7]), "+f"(d[8]), "+f"(d[9]), "+f"(d[10]), "+f"(d[11]), "+f"(d[12]), "+f"(d[13]), "+f"(d[14]), "+f"(d[15]), "+f"(d[16]), "+f"(d[17]), "+f"(d[18]), "+f"(d[19]), "+f"(d[20]), "+f"(d[21]), "+f"(d[22]), "+f"(d[23]), "+f"(d[24]), "+f"(d[25]), "+f"(d[26]), "+f"(d[27]), "+f"(d[28]), "+f"(d[29]), "+f"(d[30]), "+f"(d[31]), "+f"(d[32]), "+f"(d[33]), "+f"(d[34]), "+f"(d[35]), "+f"(d[36]), "+f"(d[37]), "+f"(d[38]), "+f"(d[39]), "+f"(d[40]), "+f"(d[41]), "+f"(d[42]), "+f"(d[43]), "+f"(d[44]), "+f"(d[45]), "+f"(d[46]), "+f"(d[47]), "+f"(d[48]), "+f"(d[49]), "+f"(d[50]), "+f"(d[51]), "+f"(d[52]), "+f"(d[53]), "+f"(d[54]), "+f"(d[55]), "+f"(d[56]), "+f"(d[57]), "+f"(d[58]), "+f"(d[59]), "+f"(d[60]), "+f"(d[61]), "+f"(d[62]), "+f"(d[63])
        : "l"(da), "l"(db), "r"(sc), "n"(TB));
}
template <int TB> __device__ __forceinline__ void wgmma_rs_n24(float (&d)[12], uint32_t a0, uint32_t a1, uint32_t a2, uint32_t a3, uint64_t db, int sc) {
    asm volatile("{\n.reg .pred p;\nsetp.ne.b32 p, %17, 0;\n"
        "wgmma.mma_async.sync.aligned.m64n24k16.f32.bf16.bf16 {%0, %1, %2, %3, %4, %5, %6, %7, %8, %9, %10, %11}, {%12, %13, %14, %15}, %16, p, 1, 1, %18;\n}\n"
        : "+f"(d[0]), "+f"(d[1]), "+f"(d[2]), "+f"(d[3]), "+f"(d[4]), "+f"(d[5]), "+f"(d[6]), "+f"(d[7]), "+f"(d[8]), "+f"(d[9]), "+f"(d[10]), "+f"(d[11])
        : "r"(a0), "r"(a1), "r"(a2), "r"(a3), "l"(db), "r"(sc), "n"(TB));
}
template <int TB> __device__ __forceinline__ void wgmma_rs_n64(float (&d)[32], uint32_t a0, uint32_t a1, uint32_t a2, uint32_t a3, uint64_t db, int sc) {
    asm volatile("{\n.reg .pred p;\nsetp.ne.b32 p, %37, 0;\n"
        "wgmma.mma_async.sync.aligned.m64n64k16.f32.bf16.bf16 {%0, %1, %2, %3, %4, %5, %6, %7, %8, %9, %10, %11, %12, %13, %14, %15, %16, %17, %18, %19, %20, %21, %22, %23, %24, %25, %26, %27, %28, %29, %30, %31}, {%32, %33, %34, %35}, %36, p, 1, 1, %38;\n}\n"
        : "+f"(d[0]), "+f"(d[1]), "+f"(d[2]), "+f"(d[3]), "+f"(d[4]), "+f"(d[5]), "+f"(d[6]), "+f"(d[7]), "+f"(d[8]), "+f"(d[9]), "+f"(d[10]), "+f"(d[11]), "+f"(d[12]), "+f"(d[13]), "+f"(d[14]), "+f"(d[15]), "+f"(d[16]), "+f"(d[17]), "+f"(d[18]), "+f"(d[19]), "+f"(d[20]), "+f"(d[21]), "+f"(d[22]), "+f"(d[23]), "+f"(d[24]), "+f"(d[25]), "+f"(d[26]), "+f"(d[27]), "+f"(d[28]), "+f"(d[29]), "+f"(d[30]), "+f"(d[31])
        : "r"(a0), "r"(a1), "r"(a2), "r"(a3), "l"(db), "r"(sc), "n"(TB));
}
template <int TB> __device__ __forceinline__ void wgmma_rs_n128(float (&d)[64], uint32_t a0, uint32_t a1, uint32_t a2, uint32_t a3, uint64_t db, int sc) {
    asm volatile("{\n.reg .pred p;\nsetp.ne.b32 p, %69, 0;\n"
        "wgmma.mma_async.sync.aligned.m64n128k16.f32.bf16.bf16 {%0, %1, %2, %3, %4, %5, %6, %7, %8, %9, %10, %11, %12, %13, %14, %15, %16, %17, %18, %19, %20, %21, %22, %23, %24, %25, %26, %27, %28, %29, %30, %31, %32, %33, %34, %35, %36, %37, %38, %39, %40, %41, %42, %43, %44, %45, %46, %47, %48, %49, %50, %51, %52, %53, %54, %55, %56, %57, %58, %59, %60, %61, %62, %63}, {%64, %65, %66, %67}, %68, p, 1, 1, %70;\n}\n"
        : "+f"(d[0]), "+f"(d[1]), "+f"(d[2]), "+f"(d[3]), "+f"(d[4]), "+f"(d[5]), "+f"(d[6]), "+f"(d[7]), "+f"(d[8]), "+f"(d[9]), "+f"(d[10]), "+f"(d[11]), "+f"(d[12]), "+f"(d[13]), "+f"(d[14]), "+f"(d[15]), "+f"(d[16]), "+f"(d[17]), "+f"(d[18]), "+f"(d[19]), "+f"(d[20]), "+f"(d[21]), "+f"(d[22]), "+f"(d[23]), "+f"(d[24]), "+f"(d[25]), "+f"(d[26]), "+f"(d[27]), "+f"(d[28]), "+f"(d[29]), "+f"(d[30]), "+f"(d[31]), "+f"(d[32]), "+f"(d[33]), "+f"(d[34]), "+f"(d[35]), "+f"(d[36]), "+f"(d[37]), "+f"(d[38]), "+f"(d[39]), "+f"(d[40]), "+f"(d[41]), "+f"(d[42]), "+f"(d[43]), "+f"(d[44]), "+f"(d[45]), "+f"(d[46]), "+f"(d[47]), "+f"(d[48]), "+f"(d[49]), "+f"(d[50]), "+f"(d[51]), "+f"(d[52]), "+f"(d[53]), "+f"(d[54]), "+f"(d[55]), "+f"(d[56]), "+f"(d[57]), "+f"(d[58]), "+f"(d[59]), "+f"(d[60]), "+f"(d[61]), "+f"(d[62]), "+f"(d[63])
        : "r"(a0), "r"(a1), "r"(a2), "r"(a3), "l"(db), "r"(sc), "n"(TB));
}

constexpr int P_THREADS = 288;
constexpr int P_NST = 6;
constexpr int P_A_BYTES = 9 * 8192;
constexpr int P_B_STAGE = 3 * 8192;
constexpr int P_SMEM = P_A_BYTES + P_NST * P_B_STAGE + 256;
constexpr uint32_t HI_SW128 = (1024u >> 4) | (1u << 30);

template <int NCOL, bool WAIT_A>
__device__ __forceinline__ void proj_mma(float (&acc)[NCOL / 2], uint32_t sA, uint32_t sB, uint32_t colofs, uint32_t fullB, uint32_t emptyB, uint32_t fullA, int lane) {
#pragma unroll 1
    for (int kb = 0; kb < 9; kb++) {
        const int s = kb >= P_NST ? kb - P_NST : kb;
        if (WAIT_A) mbar_wait(fullA + kb * 8, 0);
        mbar_wait(fullB + s * 8, kb >= P_NST ? 1 : 0);
        const uint32_t alo = desc_lo(sA + kb * 8192, 16), blo = desc_lo(sB + s * P_B_STAGE + colofs, 8192);
        wg_fence();
#pragma unroll
        for (int ks = 0; ks < 4; ks++) {
            const uint64_t da = desc64(alo + ks * 2, HI_SW128), db = desc64(blo + ks * 128, HI_SW128);
            if constexpr (NCOL == 128) wgmma_ss_n128<1>(acc, da, db, (kb | ks) != 0);
            else wgmma_ss_n64<1>(acc, da, db, (kb | ks) != 0);
        }
        wg_commit();
        if (kb + P_NST < 9 + 1) {
            wg_wait<1>();
            if (kb >= 1 && kb - 1 + P_NST < 9 && lane == 0) mbar_arrive(emptyB + (kb - 1) * 8);
        }
    }
    wg_wait<0>();
    pin(acc);
}

template <int NB>
__device__ __forceinline__ void stage_tile(const uint32_t (&pk)[NB * 2], uint32_t base, int w, int lane) {
    const int r = w * 16 + (lane & 7) + ((lane >> 3) & 1) * 8;
#pragma unroll
    for (int b = 0; b < NB; b += 2) {
        const uint32_t a = base + (b >> 3) * 8192 + r * 128 + ((((b & 7) + (lane >> 4)) ^ (r & 7)) << 4);
        stmatrix_x4(a, pk[2 * b], pk[2 * b + 1], pk[2 * b + 2], pk[2 * b + 3]);
    }
}

__global__ void __launch_bounds__(P_THREADS, 1)
k_qkv(const __grid_constant__ CUtensorMap tmWq, const __grid_constant__ CUtensorMap tmQ, const __nv_bfloat16* __restrict__ x, const __nv_bfloat16* __restrict__ wk, const __nv_bfloat16* __restrict__ wv) {
    extern __shared__ __align__(1024) uint8_t smem[];
    const uint32_t sA = smem_u32(smem), sB = sA + P_A_BYTES, bars = sB + P_NST * P_B_STAGE;
    const uint32_t fullB = bars, emptyB = bars + 64;
    const int tid = threadIdx.x, warp = __shfl_sync(~0u, tid >> 5, 0), lane = tid & 31;
    const bool isQ = blockIdx.x < 96;
    const int m = isQ ? blockIdx.x / 3 : blockIdx.x - 96, cg = blockIdx.x % 3;
    if (tid == 0) TS(0, 0);
    if (tid == 0) {
        for (int i = 0; i < P_NST; i++) { mbar_init(fullB + i * 8, 1); mbar_init(emptyB + i * 8, 8); }
        bar_init_fence();
    }
    __syncthreads();
    pdl_launch();
    if (warp == 8) {
        if (isQ && elect_one()) {
            for (int kb = 0; kb < 9; kb++) {
                const int s = kb >= P_NST ? kb - P_NST : kb;
                if (kb >= P_NST) mbar_wait(emptyB + s * 8, 0);
                mbar_expect(fullB + s * 8, P_B_STAGE);
                for (int a = 0; a < 3; a++) tma_2d(sB + s * P_B_STAGE + a * 8192, &tmWq, cg * 192 + a * 64, kb * 64, fullB + s * 8);
            }
        }
        return;
    }
    {
        const int row = tid >> 2, q = tid & 3;
        const uint4* src = reinterpret_cast<const uint4*>(x + (size_t)(m * 64 + row) * DM) + q;
        uint4 v[18];
#pragma unroll
        for (int i = 0; i < 18; i++) v[i] = __ldg(src + 4 * i);
        if (!isQ) {
            const uint32_t* wk32 = reinterpret_cast<const uint32_t*>(wk);
            const uint32_t* wv32 = reinterpret_cast<const uint32_t*>(wv);
            uint32_t wreg[41];
#pragma unroll
            for (int i = 0; i < 41; i++) {
                const int idx = tid + i * 256;
                wreg[i] = idx < DM * 9 ? __ldg(wk32 + idx) : (idx < 2 * DM * 9 ? __ldg(wv32 + idx - DM * 9) : 0u);
            }
#pragma unroll
            for (int i = 0; i < 41; i++) {
                const int idx = tid + i * 256;
                if (idx < 2 * DM * 9) {
                    const int sel = idx >= DM * 9, j = idx - sel * DM * 9, k = j / 9, n = (j - k * 9) * 2;
                    const uint32_t a = sB + (sel * 3 + (n >> 3)) * 9216 + (k >> 3) * 128 + (n & 7) * 16 + (k & 7) * 2;
                    asm volatile("st.shared.u16 [%0], %1;" ::"r"(a), "h"((uint16_t)(wreg[i] & 0xFFFF)) : "memory");
                    asm volatile("st.shared.u16 [%0], %1;" ::"r"(a + 16), "h"((uint16_t)(wreg[i] >> 16)) : "memory");
                }
            }
        }
        float sum = 0.f;
#pragma unroll
        for (int i = 0; i < 18; i++) {
            sum += (bf_lo(v[i].x) + bf_hi(v[i].x)) + (bf_lo(v[i].y) + bf_hi(v[i].y)) + (bf_lo(v[i].z) + bf_hi(v[i].z)) + (bf_lo(v[i].w) + bf_hi(v[i].w));
        }
        sum += __shfl_xor_sync(~0u, sum, 1); sum += __shfl_xor_sync(~0u, sum, 2);
        const float mean = sum * (1.0f / DM);
        float sq = 0.f;
#pragma unroll
        for (int i = 0; i < 18; i++) {
            const uint32_t w[4] = {v[i].x, v[i].y, v[i].z, v[i].w};
#pragma unroll
            for (int j = 0; j < 4; j++) { const float a = bf_lo(w[j]) - mean, b = bf_hi(w[j]) - mean; sq = fmaf(a, a, sq); sq = fmaf(b, b, sq); }
        }
        sq += __shfl_xor_sync(~0u, sq, 1); sq += __shfl_xor_sync(~0u, sq, 2);
        const float rstd = rsqrtf(sq * (1.0f / DM) + LN_EPS), nmr = -mean * rstd;
#pragma unroll
        for (int i = 0; i < 18; i++) {
            const int c = q + 4 * i;
            const uint32_t w[4] = {v[i].x, v[i].y, v[i].z, v[i].w};
            uint32_t o[4];
#pragma unroll
            for (int j = 0; j < 4; j++) o[j] = pack_bf16(fmaf(bf_lo(w[j]), rstd, nmr), fmaf(bf_hi(w[j]), rstd, nmr));
            const uint32_t a = sA + (c >> 3) * 8192 + row * 128 + (((c & 7) ^ (row & 7)) << 4);
            asm volatile("st.shared.v4.b32 [%0], {%1, %2, %3, %4};" ::"r"(a), "r"(o[0]), "r"(o[1]), "r"(o[2]), "r"(o[3]) : "memory");
        }
    }
    proxy_fence();
    named_sync(1, 256);
    if (tid == 0) TS(0, 1);
    const int wg = warp >> 2, w = warp & 3, g = lane >> 2, t = lane & 3;
    const int r0 = m * 64 + w * 16 + g;
    if (isQ) {
        if (wg == 0) {
            float acc[64];
            proj_mma<128, false>(acc, sA, sB, 0, fullB, emptyB, 0, lane);
            if (tid == 0) TS(0, 2);
            named_sync(1, 256);
            uint32_t pk[32];
#pragma unroll
            for (int i = 0; i < 32; i++) pk[i] = pack_bf16(acc[2 * i] * Q_SCALE, acc[2 * i + 1] * Q_SCALE);
            stage_tile<16>(pk, sA, w, lane);
        } else {
            float acc[32];
            proj_mma<64, false>(acc, sA, sB, 2 * 8192, fullB, emptyB, 0, lane);
            named_sync(1, 256);
            uint32_t pk[16];
#pragma unroll
            for (int i = 0; i < 16; i++) pk[i] = pack_bf16(acc[2 * i] * Q_SCALE, acc[2 * i + 1] * Q_SCALE);
            stage_tile<8>(pk, sA + 2 * 8192, w, lane);
        }
        proxy_fence();
        named_sync(1, 256);
        if (warp == 0 && elect_one()) {
            for (int a = 0; a < 3; a++) tma_st_2d(&tmQ, cg * 192 + a * 64, m * 64, sA + a * 8192);
            bulk_commit();
            bulk_wait_all();
        }
    } else {
        float acc[12];
        const uint32_t blo = desc_lo(sB + wg * 3 * 9216, 128);
#pragma unroll 1
        for (int kb = 0; kb < 9; kb++) {
            const uint32_t alo = desc_lo(sA + kb * 8192, 16);
            wg_fence();
#pragma unroll
            for (int ks = 0; ks < 4; ks++)
                wgmma_ss_n24<0>(acc, desc64(alo + ks * 2, HI_SW128), desc64(blo + (kb * 4 + ks) * 16, desc_hi(9216, 0)), (kb | ks) != 0);
        }
        wg_commit();
        wg_wait<0>();
        pin(acc);
        uint32_t pk[6];
#pragma unroll
        for (int i = 0; i < 6; i++) pk[i] = pack_bf16(acc[2 * i], acc[2 * i + 1]);
        float n0 = 0.f, n1 = 0.f, vm = 0.f;
#pragma unroll
        for (int b = 0; b < 3; b++) {
            if (b < 2 || t == 0) {
                const float a = bf_lo(pk[2 * b]), c = bf_hi(pk[2 * b]), d = bf_lo(pk[2 * b + 1]), e = bf_hi(pk[2 * b + 1]);
                n0 = fmaf(a, a, fmaf(c, c, n0)); n1 = fmaf(d, d, fmaf(e, e, n1));
            }
        }
        n0 += __shfl_xor_sync(~0u, n0, 1); n0 += __shfl_xor_sync(~0u, n0, 2);
        n1 += __shfl_xor_sync(~0u, n1, 1); n1 += __shfl_xor_sync(~0u, n1, 2);
        vm = fmaxf(n0, n1);
        if (!(vm == vm)) vm = __int_as_float(0x7F800000);
#pragma unroll
        for (int o = 4; o < 32; o <<= 1) vm = fmaxf(vm, __shfl_xor_sync(~0u, vm, o));
        if (t != 0) {
            uint32_t lo, hi;
            if (wg == 0) {
                const int grp = m * 8 + w * 2;
                const uint32_t c = t == 1 ? 0x42FE3F80u   : (t == 2 ? 0x00003BC0u   : 0u);
                lo = ((POLY_MASK >> (grp & 15)) & 1) ? c : 0u;
                hi = ((POLY_MASK >> ((grp + 1) & 15)) & 1) ? c : 0u;
            } else {
                lo = hi = t == 1 ? 0x00003F80u : 0u;
            }
            pk[4] = lo; pk[5] = hi;
        }
        uint32_t* dst = reinterpret_cast<uint32_t*>(wg == 0 ? g_kc : g_vc) + (m * 8 + w * 2) * 96 + g * 4 + t;
#pragma unroll
        for (int b = 0; b < 3; b++) { dst[b * 32] = pk[2 * b]; dst[96 + b * 32] = pk[2 * b + 1]; }
        float* red = reinterpret_cast<float*>(smem + P_A_BYTES + 6 * 9216);
        if (lane == 0) red[warp] = (wg == 0) ? vm : (vm <= 1e24f ? 0.f : __int_as_float(0x7F800000));
        named_sync(1, 256);
        if (tid == 0) {
            float mx = red[0];
#pragma unroll
            for (int i = 1; i < 8; i++) mx = fmaxf(mx, red[i]);
            g_kmax[m] = mx;
        }
    }
    if (tid == 0) TS(0, 3);
}

constexpr int A_THREADS = 512;
constexpr int A_NPIECE = 8;
constexpr int A_SMEM = 2 * KV_BYTES + 128;

__device__ __forceinline__ uint32_t exp2_pair_fixed(float lo, float hi) {
    const uint32_t G = __byte_perm(__float_as_uint(lo), __float_as_uint(hi), 0x5410);
    const uint32_t Hh = G & 0x007F007Fu;
    const uint32_t tt = hfma2(Hh, 0xF96BF96Bu, 0x358C358Cu);
    return G - hfma2(tt, Hh, 0u);
}

__device__ __forceinline__ void attn_side_job(const __nv_bfloat16* __restrict__ w1, const __nv_bfloat16* __restrict__ w2, const __nv_bfloat16* __restrict__ wo, uint8_t* smem) {
    const int e = blockIdx.x - 128, tid = threadIdx.x;
    if (tid < 32) {
        const char* p = reinterpret_cast<const char*>(wo) + e * (DM * DM * 2 / 4);
        for (int i = tid; i < DM * DM * 2 / 4 / 4608; i += 32) prefetch_l2(p + i * 4608, 4608);
    }
    float* red = reinterpret_cast<float*>(smem);
    if (tid < 432) {
        const int c = tid % 144, rg = tid / 144;
        const uint4* src = reinterpret_cast<const uint4*>(w1 + (size_t)rg * 192 * FF + e * 1152) + c;
        float s[8] = {0.f, 0.f, 0.f, 0.f, 0.f, 0.f, 0.f, 0.f};
#pragma unroll 8
        for (int r = 0; r < 192; r++) {
            const uint4 v = __ldg(src + (size_t)r * (FF / 8));
            s[0] += bf_lo(v.x); s[1] += bf_hi(v.x); s[2] += bf_lo(v.y); s[3] += bf_hi(v.y);
            s[4] += bf_lo(v.z); s[5] += bf_hi(v.z); s[6] += bf_lo(v.w); s[7] += bf_hi(v.w);
        }
#pragma unroll
        for (int i = 0; i < 8; i++) red[rg * 1152 + c * 8 + i] = s[i];
    }
    __syncthreads();
    for (int i = tid; i < 1152; i += A_THREADS) g_cs1[e * 1152 + i] = red[i] + red[1152 + i] + red[2304 + i];
    if (tid < 32) {
        const char* p = reinterpret_cast<const char*>(w2) + (size_t)e * (FF * DM * 2 / 4);
        for (int i = tid; i < FF * DM * 2 / 4 / 9216; i += 32) prefetch_l2(p + (size_t)i * 9216, 9216);
    }
}

__global__ void __launch_bounds__(A_THREADS, 1)
k_attn(const __nv_bfloat16* __restrict__ w1, const __nv_bfloat16* __restrict__ w2, const __nv_bfloat16* __restrict__ wo) {
    extern __shared__ __align__(1024) uint8_t smem[];
    pdl_launch();
    if (blockIdx.x >= 128) { attn_side_job(w1, w2, wo, smem); return; }
    const uint32_t sK = smem_u32(smem), sV = sK + KV_BYTES, bars = sV + KV_BYTES;
    const int tid = threadIdx.x;
    if (tid == 0) TS(1, 0);
    if (tid == 0) {
        for (int i = 0; i < A_NPIECE; i++) mbar_init(bars + i * 8, 1);
        bar_init_fence();
    }
    __syncthreads();
    pdl_wait();
    if (tid == 0) TS(1, 1);
    if (tid < 32 && elect_one()) {
        constexpr int PB = KV_BYTES / A_NPIECE;
        for (int i = 0; i < A_NPIECE; i++) {
            mbar_expect(bars + i * 8, 2 * PB);
            bulk_g2s(sK + i * PB, reinterpret_cast<const char*>(g_kc) + i * PB, PB, bars + i * 8);
            bulk_g2s(sV + i * PB, reinterpret_cast<const char*>(g_vc) + i * PB, PB, bars + i * 8);
        }
    }
    const int wg = __shfl_sync(~0u, tid >> 7, 0), w = (tid >> 5) & 3, lane = tid & 31, g = lane >> 2, t = lane & 3;
    const uint32_t* q32 = reinterpret_cast<const uint32_t*>(g_q);
    uint32_t* o32 = reinterpret_cast<uint32_t*>(g_o);
    float kmax2 = g_kmax[lane];
#pragma unroll
    for (int o = 1; o < 32; o <<= 1) kmax2 = fmaxf(kmax2, __shfl_xor_sync(~0u, kmax2, o));
    constexpr uint32_t HI_K = desc_hi(384, 0), HI_V = desc_hi(128, 0);
    const uint32_t k0lo = desc_lo(sK, 128), k1lo = desc_lo(sK + 256, 0), vlo = desc_lo(sV, 384);

    int row = (blockIdx.x * 8 + wg) * 64 + w * 16 + g;
    uint32_t nq[6];
    nq[0] = q32[row * 9 + t]; nq[1] = q32[(row + 8) * 9 + t]; nq[2] = q32[row * 9 + 4 + t]; nq[3] = q32[(row + 8) * 9 + 4 + t];
    nq[4] = q32[row * 9 + 8]; nq[5] = q32[(row + 8) * 9 + 8];
#pragma unroll 1
    for (int rep = 0; rep < 2; rep++, row += 256) {
        uint32_t qa[4] = {nq[0], nq[1], nq[2], nq[3]}, qb[4];
        float n0, n1;
        {
            const float a0 = bf_lo(qa[0]), a1 = bf_hi(qa[0]), a2 = bf_lo(qa[2]), a3 = bf_hi(qa[2]);
            const float b0 = bf_lo(qa[1]), b1 = bf_hi(qa[1]), b2 = bf_lo(qa[3]), b3 = bf_hi(qa[3]);
            n0 = a0 * a0 + a1 * a1 + a2 * a2 + a3 * a3; n1 = b0 * b0 + b1 * b1 + b2 * b2 + b3 * b3;
            if (t == 0) {
                const float c0 = bf_lo(nq[4]), c1 = bf_hi(nq[4]), d0 = bf_lo(nq[5]), d1 = bf_hi(nq[5]);
                n0 += c0 * c0 + c1 * c1; n1 += d0 * d0 + d1 * d1;
            }
            n0 += __shfl_xor_sync(~0u, n0, 1); n0 += __shfl_xor_sync(~0u, n0, 2);
            n1 += __shfl_xor_sync(~0u, n1, 1); n1 += __shfl_xor_sync(~0u, n1, 2);
        }
        const uint32_t x0 = nq[4], x1 = nq[5];
        if (rep == 0) {
            const int nr = row + 256;
            nq[0] = q32[nr * 9 + t]; nq[1] = q32[(nr + 8) * 9 + t]; nq[2] = q32[nr * 9 + 4 + t]; nq[3] = q32[(nr + 8) * 9 + 4 + t];
            nq[4] = q32[nr * 9 + 8]; nq[5] = q32[(nr + 8) * 9 + 8];
        }
        const bool unsafe = !(fmaxf(n0, n1) * kmax2 <= FAST_BOUND * FAST_BOUND);
        uint32_t any_unsafe;
        asm volatile("{\n.reg .pred p, q;\nsetp.ne.u32 p, %1, 0;\nbar.red.or.pred q, %2, 128, p;\nselp.u32 %0, 1, 0, q;\n}\n" : "=r"(any_unsafe) : "r"((uint32_t)unsafe), "r"(wg + 1) : "memory");
        if (tid == 0) TS(1, 2 + rep * 2);
        float o[12];
#pragma unroll
        for (int i = 0; i < 12; i++) o[i] = 0.f;
        if (!any_unsafe) {
            float s[64];
            const uint32_t cst = t == 1 ? 0x3F804780u   : (t == 2 ? 0x00003F80u   : 0u);
            qb[0] = t == 0 ? x0 : cst; qb[1] = t == 0 ? x1 : cst; qb[2] = 0; qb[3] = 0;
            pin(qa); pin(qb); pin(o);
#pragma unroll 1
            for (int j = 0; j < 16; j++) {
                if (rep == 0 && (j & 1) == 0) mbar_wait(bars + (j >> 1) * 8, 0);
                const uint32_t off = j * (16 * 384 >> 4);
                wg_fence();
                wgmma_rs_n128<0>(s, qa[0], qa[1], qa[2], qa[3], desc64(k0lo + off, HI_K), 0);
                wgmma_rs_n128<0>(s, qb[0], qb[1], qb[2], qb[3], desc64(k1lo + off, HI_K), 1);
                wg_commit();
                wg_wait<0>();
                pin(s);
                uint32_t p[32];
#pragma unroll
                for (int i = 0; i < 32; i++) {
                    if ((POLY_MASK >> (i >> 1)) & 1) p[i] = exp2_pair_fixed(s[2 * i], s[2 * i + 1]);
                    else p[i] = pack_bf16(ex2(s[2 * i]), ex2(s[2 * i + 1]));
                }
                pin(p);
                wg_fence();
#pragma unroll
                for (int k = 0; k < 8; k++) wgmma_rs_n24<1>(o, p[4 * k], p[4 * k + 1], p[4 * k + 2], p[4 * k + 3], desc64(vlo + off + k * 48, HI_V), 1);
                wg_commit();
                wg_wait<0>();
            }
        } else {
            float s[64];
            qb[0] = t == 0 ? x0 : 0u; qb[1] = t == 0 ? x1 : 0u; qb[2] = 0; qb[3] = 0;
            pin(qa); pin(qb); pin(o);
            float m0 = -INFINITY, m1 = -INFINITY;
#pragma unroll 1
            for (int j = 0; j < 16; j++) {
                if (rep == 0 && (j & 1) == 0) mbar_wait(bars + (j >> 1) * 8, 0);
                const uint32_t off = j * (16 * 384 >> 4);
                wg_fence();
                wgmma_rs_n128<0>(s, qa[0], qa[1], qa[2], qa[3], desc64(k0lo + off, HI_K), 0);
                wgmma_rs_n128<0>(s, qb[0], qb[1], qb[2], qb[3], desc64(k1lo + off, HI_K), 1);
                wg_commit();
                wg_wait<0>();
                pin(s);
                float x0m = m0, x1m = m1;
#pragma unroll
                for (int b = 0; b < 16; b++) { x0m = fmaxf(x0m, fmaxf(s[4 * b], s[4 * b + 1])); x1m = fmaxf(x1m, fmaxf(s[4 * b + 2], s[4 * b + 3])); }
                x0m = fmaxf(x0m, __shfl_xor_sync(~0u, x0m, 1)); x0m = fmaxf(x0m, __shfl_xor_sync(~0u, x0m, 2));
                x1m = fmaxf(x1m, __shfl_xor_sync(~0u, x1m, 1)); x1m = fmaxf(x1m, __shfl_xor_sync(~0u, x1m, 2));
                const float c0 = ex2(m0 - x0m), c1 = ex2(m1 - x1m);
                m0 = x0m; m1 = x1m;
#pragma unroll
                for (int b = 0; b < 3; b++) { o[4 * b] *= c0; o[4 * b + 1] *= c0; o[4 * b + 2] *= c1; o[4 * b + 3] *= c1; }
                uint32_t p[32];
#pragma unroll
                for (int b = 0; b < 16; b++) {
                    p[2 * b] = pack_bf16(ex2(s[4 * b] - m0), ex2(s[4 * b + 1] - m0));
                    p[2 * b + 1] = pack_bf16(ex2(s[4 * b + 2] - m1), ex2(s[4 * b + 3] - m1));
                }
                pin(p); pin(o);
                wg_fence();
#pragma unroll
                for (int k = 0; k < 8; k++) wgmma_rs_n24<1>(o, p[4 * k], p[4 * k + 1], p[4 * k + 2], p[4 * k + 3], desc64(vlo + off + k * 48, HI_V), 1);
                wg_commit();
                wg_wait<0>();
            }
        }
        pin(o);
        if (tid == 0) TS(1, 3 + rep * 2);
        const float l0 = __shfl_sync(~0u, o[8], (lane & ~3) | 1), l1 = __shfl_sync(~0u, o[10], (lane & ~3) | 1);
        const float i0 = 1.0f / l0, i1 = 1.0f / l1;
        o32[row * 9 + t] = pack_bf16(o[0] * i0, o[1] * i0);
        o32[(row + 8) * 9 + t] = pack_bf16(o[2] * i1, o[3] * i1);
        o32[row * 9 + 4 + t] = pack_bf16(o[4] * i0, o[5] * i0);
        o32[(row + 8) * 9 + 4 + t] = pack_bf16(o[6] * i1, o[7] * i1);
        if (t == 0) { o32[row * 9 + 8] = pack_bf16(o[8] * i0, o[9] * i0); o32[(row + 8) * 9 + 8] = pack_bf16(o[10] * i1, o[11] * i1); }
    }
    if (tid == 0) TS(1, 6);
}

template <int NB>
__device__ __forceinline__ void oproj_load_x(uint32_t (&xr)[NB * 2], const uint32_t* __restrict__ x32, int r0, int col0, int t) {
#pragma unroll
    for (int b = 0; b < NB; b++) {
        const int i0 = (r0 * DM + col0 + b * 8 + 2 * t) >> 1;
        xr[2 * b] = __ldg(x32 + i0); xr[2 * b + 1] = __ldg(x32 + i0 + 4 * DM);
    }
}
template <int NB>
__device__ __forceinline__ void oproj_epilogue(const float (&acc)[NB * 4], uint32_t (&xr)[NB * 2], uint32_t stg, int r0, int part, int w, int lane) {
    float s0 = 0.f, q0 = 0.f, s1 = 0.f, q1 = 0.f;
#pragma unroll
    for (int b = 0; b < NB; b++) {
        const uint32_t xa = xr[2 * b], xb = xr[2 * b + 1];
        const uint32_t ha = pack_bf16(acc[4 * b] + bf_lo(xa), acc[4 * b + 1] + bf_hi(xa));
        const uint32_t hb = pack_bf16(acc[4 * b + 2] + bf_lo(xb), acc[4 * b + 3] + bf_hi(xb));
        xr[2 * b] = ha; xr[2 * b + 1] = hb;
        const float a = bf_lo(ha), c = bf_hi(ha), d = bf_lo(hb), e = bf_hi(hb);
        s0 += a + c; q0 = fmaf(a, a, fmaf(c, c, q0));
        s1 += d + e; q1 = fmaf(d, d, fmaf(e, e, q1));
    }
    stage_tile<NB>(xr, stg, w, lane);
    s0 += __shfl_xor_sync(~0u, s0, 1); s0 += __shfl_xor_sync(~0u, s0, 2);
    q0 += __shfl_xor_sync(~0u, q0, 1); q0 += __shfl_xor_sync(~0u, q0, 2);
    s1 += __shfl_xor_sync(~0u, s1, 1); s1 += __shfl_xor_sync(~0u, s1, 2);
    q1 += __shfl_xor_sync(~0u, q1, 1); q1 += __shfl_xor_sync(~0u, q1, 2);
    if ((lane & 3) == 0) { g_stat[part * SEQ + r0] = make_float2(s0, q0); g_stat[part * SEQ + r0 + 8] = make_float2(s1, q1); }
}

__global__ void __launch_bounds__(P_THREADS, 1)
k_oproj(const __grid_constant__ CUtensorMap tmO, const __grid_constant__ CUtensorMap tmWo, const __grid_constant__ CUtensorMap tmH, const __grid_constant__ CUtensorMap tmOut, const __nv_bfloat16* __restrict__ x) {
    extern __shared__ __align__(1024) uint8_t smem[];
    const uint32_t sA = smem_u32(smem), sB = sA + P_A_BYTES, bars = sB + P_NST * P_B_STAGE;
    const uint32_t fullB = bars, emptyB = bars + 64, fullA = bars + 128;
    const int tid = threadIdx.x, warp = __shfl_sync(~0u, tid >> 5, 0), lane = tid & 31;
    const int m = blockIdx.x / 3, cg = blockIdx.x % 3;
    if (tid == 0) TS(2, 0);
    if (tid == 0) {
        for (int i = 0; i < P_NST; i++) { mbar_init(fullB + i * 8, 1); mbar_init(emptyB + i * 8, 8); }
        for (int i = 0; i < 9; i++) mbar_init(fullA + i * 8, 1);
        bar_init_fence();
    }
    __syncthreads();
    pdl_launch();
    if (warp == 8) {
        if (elect_one()) {
            for (int kb = 0; kb < P_NST; kb++) {
                mbar_expect(fullB + kb * 8, P_B_STAGE);
                for (int a = 0; a < 3; a++) tma_2d(sB + kb * P_B_STAGE + a * 8192, &tmWo, cg * 192 + a * 64, kb * 64, fullB + kb * 8);
            }
            pdl_wait();
            for (int kb = 0; kb < 9; kb++) {
                mbar_expect(fullA + kb * 8, 8192);
                tma_2d(sA + kb * 8192, &tmO, kb * 64, m * 64, fullA + kb * 8);
            }
            for (int kb = P_NST; kb < 9; kb++) {
                const int s = kb - P_NST;
                mbar_wait(emptyB + s * 8, 0);
                mbar_expect(fullB + s * 8, P_B_STAGE);
                for (int a = 0; a < 3; a++) tma_2d(sB + s * P_B_STAGE + a * 8192, &tmWo, cg * 192 + a * 64, kb * 64, fullB + s * 8);
            }
        }
        return;
    }
    const int wg = warp >> 2, w = warp & 3, g = lane >> 2, t = lane & 3;
    const int r0 = m * 64 + w * 16 + g;
    const uint32_t* x32 = reinterpret_cast<const uint32_t*>(x);
    if (wg == 0) {
        uint32_t xr[32];
        oproj_load_x<16>(xr, x32, r0, cg * 192, t);
        float acc[64];
        proj_mma<128, true>(acc, sA, sB, 0, fullB, emptyB, fullA, lane);
        if (tid == 0) TS(2, 2);
        named_sync(1, 256);
        pdl_wait();
        oproj_epilogue<16>(acc, xr, sA, r0, cg * 2, w, lane);
    } else {
        uint32_t xr[16];
        oproj_load_x<8>(xr, x32, r0, cg * 192 + 128, t);
        float acc[32];
        proj_mma<64, true>(acc, sA, sB, 2 * 8192, fullB, emptyB, fullA, lane);
        named_sync(1, 256);
        pdl_wait();
        oproj_epilogue<8>(acc, xr, sA + 2 * 8192, r0, cg * 2 + 1, w, lane);
    }
    proxy_fence();
    named_sync(1, 256);
    if (warp == 0 && elect_one()) {
        for (int a = 0; a < 3; a++) {
            tma_st_2d(&tmH, cg * 192 + a * 64, m * 64, sA + a * 8192);
            tma_st_2d(&tmOut, cg * 192 + a * 64, m * 64, sA + a * 8192);
        }
        bulk_commit();
        bulk_wait_all();
        TS(2, 3);
    }
}

constexpr int F_THREADS = 384;
constexpr int F_NST = 6;
constexpr int F_STAGE = 96 * 128;
constexpr int F_X_BYTES = 9 * 16384;
constexpr int F_OFF_ST = F_X_BYTES;
constexpr int F_OFF_CS = F_OFF_ST + F_NST * F_STAGE;
constexpr int F_OFF_BAR = F_OFF_CS + 576 * 4;
constexpr int F_SMEM = F_OFF_BAR + 256;

struct RowStat { float nmean0, c0, istd0, nmean1, c1, istd1; };

#define SEX2(x) ex2(x)
#define SRCP(x) rcp(x)
__device__ __forceinline__ void silu_s1(float (&acc)[32], float (&tmp)[8], int piece, uint32_t cs_addr, const RowStat& st) {
#pragma unroll
    for (int h = 0; h < 2; h++) {
        const int b = 2 * piece + h;
        float cs0, cs1;
        asm volatile("ld.shared.v2.f32 {%0, %1}, [%2];" : "=f"(cs0), "=f"(cs1) : "r"(cs_addr + b * 32));
        acc[4 * b] = fmaf(st.nmean0, cs0, acc[4 * b]); acc[4 * b + 1] = fmaf(st.nmean0, cs1, acc[4 * b + 1]);
        acc[4 * b + 2] = fmaf(st.nmean1, cs0, acc[4 * b + 2]); acc[4 * b + 3] = fmaf(st.nmean1, cs1, acc[4 * b + 3]);
        tmp[4 * h] = SEX2(acc[4 * b] * st.c0); tmp[4 * h + 1] = SEX2(acc[4 * b + 1] * st.c0);
        tmp[4 * h + 2] = SEX2(acc[4 * b + 2] * st.c1); tmp[4 * h + 3] = SEX2(acc[4 * b + 3] * st.c1);
    }
}
__device__ __forceinline__ float after_issue(float v, uint32_t tick) {
    uint32_t r;
    asm("lop3.b32 %0, %1, %1, %2, 0xF0;" : "=r"(r) : "r"(__float_as_uint(v)), "r"(tick));
    return __uint_as_float(r);
}
__device__ __forceinline__ uint32_t read_tick() { uint32_t c; asm volatile("mov.u32 %0, %%clock;" : "=r"(c)::"memory"); return c; }
__device__ __forceinline__ void silu_s2(float (&tmp)[8], const RowStat& st, uint32_t tick) {
    const float is0 = after_issue(st.istd0, tick), is1 = after_issue(st.istd1, tick);
#pragma unroll
    for (int i = 0; i < 8; i++) { const float is = (i & 2) ? is1 : is0; tmp[i] = SRCP(fmaf(tmp[i], is, is)); }
}
template <int C>
__device__ __forceinline__ void silu_s3(const float (&acc)[32], const float (&tmp)[8], uint32_t (&h1)[144], int piece) {
#pragma unroll
    for (int i = 0; i < 4; i++) h1[C * 16 + 4 * piece + i] = pack_bf16(acc[8 * piece + 2 * i] * tmp[2 * i], acc[8 * piece + 2 * i + 1] * tmp[2 * i + 1]);
}

struct FfnPipe {
    uint32_t full, empty;
    int lane;
    __device__ __forceinline__ void acquire(int s, uint32_t ph) const { mbar_wait(full + s * 8, ph); }
    __device__ __forceinline__ void release(int s) const { if (lane == 0) mbar_arrive(empty + s * 8); }
};

template <int C>
__device__ __forceinline__ void ffn_phase1_chunk(float (&cur)[32], float (&prev)[32], uint32_t (&h1)[144], const FfnPipe& pp, uint64_t dx, uint32_t fullX, uint32_t cs_addr, const RowStat& st) {
    float tmp[2][8];
    dx += blockIdx.y * C;
#pragma unroll
    for (int j = 0; j < 6; j++) {
        if (C == 0) { mbar_wait(fullX + ((6 * j) >> 2) * 8, 0); mbar_wait(fullX + ((6 * j + 5) >> 2) * 8, 0); }
        pp.acquire(j, C & 1);
        if (j == 0) pin(cur);
        wg_fence();
#pragma unroll
        for (int i = 0; i < 6; i++) {
            const int ks = 6 * j + i;
            wgmma_ss_n64<1>(cur, dx + ((ks >> 2) * 1024 + (ks & 3) * 2), cdesc(F_OFF_ST + j * F_STAGE + i * 2048, 8192, 1024, 1), ks != 0);
        }
        wg_commit();
        if (C > 0 || j > 0) { wg_wait<1>(); pp.release((j + 5) % 6); }
        if (C > 0) {
            pin(prev);
            if (j >= 1) { pin(tmp[0]); if (j >= 2) pin(tmp[1]); }
            if (j >= 2) silu_s3<(C > 0 ? C - 1 : 0)>(prev, tmp[j & 1], h1, j - 2);
            if (j >= 1 && j <= 4) { silu_s2(tmp[(j - 1) & 1], st, read_tick()); pin(tmp[(j - 1) & 1]); }
            if (j <= 3) { silu_s1(prev, tmp[j & 1], j, cs_addr + (C - 1) * 256, st); pin(tmp[j & 1]); }
            if (j >= 2) { asm volatile("" : "+r"(h1[(C - 1) * 16 + 4 * (j - 2)]), "+r"(h1[(C - 1) * 16 + 4 * (j - 2) + 1]), "+r"(h1[(C - 1) * 16 + 4 * (j - 2) + 2]), "+r"(h1[(C - 1) * 16 + 4 * (j - 2) + 3]) :: "memory"); }
        }
    }
}

__device__ __forceinline__ void ffn_store_chunk(const float (&acc)[32], const CUtensorMap* tmOut, uint32_t stg, int col, int row, int w, int lane, int wgid) {
    uint32_t pk[16];
#pragma unroll
    for (int i = 0; i < 16; i++) pk[i] = pack_bf16(acc[2 * i], acc[2 * i + 1]);
    stage_tile<8>(pk, stg, w, lane);
    proxy_fence();
    named_sync(2 + wgid, 128);
    if (w == 0 && elect_one()) {
        tma_red_2d(tmOut, col, row, stg);
        bulk_commit();
    }
}

__device__ __forceinline__ void ffn_phase2_chunk(float (&cur)[32], float (&prev)[32], uint32_t (&h1)[144], const FfnPipe& pp, uint32_t ph, bool store_prev, const CUtensorMap* tmOut, uint32_t stg_prev, int col_prev, int row, int w, int lane, int wgid) {
#pragma unroll
    for (int j = 0; j < 6; j++) {
        pp.acquire(j, ph);
        if (j == 0) pin(cur);
        wg_fence();
#pragma unroll
        for (int i = 0; i < 6; i++) {
            const int f = (6 * j + i) * 4;
            wgmma_rs_n64<1>(cur, h1[f], h1[f + 1], h1[f + 2], h1[f + 3], cdesc(F_OFF_ST + j * F_STAGE + i * 2048, 8192, 1024, 1), (j | i) != 0);
        }
        wg_commit();
        if (j > 0 || store_prev) { wg_wait<1>(); pp.release((j + 5) % 6); }
        if (j == 0 && store_prev) { pin(prev); ffn_store_chunk(prev, tmOut, stg_prev, col_prev, row, w, lane, wgid); }
    }
}

__global__ void __launch_bounds__(F_THREADS, 1)
k_ffn(const __grid_constant__ CUtensorMap tmH, const __grid_constant__ CUtensorMap tmW1, const __grid_constant__ CUtensorMap tmW2, const __grid_constant__ CUtensorMap tmOut) {
    extern __shared__ __align__(1024) uint8_t smem[];
    const uint32_t sX = smem_u32(smem), sSt = sX + F_OFF_ST, sCs = sX + F_OFF_CS, bars = sX + F_OFF_BAR;
    const uint32_t full = bars, empty = bars + 64, fullX = bars + 128;
    const int tid = threadIdx.x, warp = __shfl_sync(~0u, tid >> 5, 0), lane = tid & 31;
    const int m = blockIdx.x & 15, fs = blockIdx.x >> 4;
    if (tid == 0) TS(3, 0);
    check_smem_base(sX);
    if (tid == 0) {
        for (int i = 0; i < F_NST; i++) { mbar_init(full + i * 8, 1); mbar_init(empty + i * 8, 8); }
        for (int i = 0; i < 9; i++) mbar_init(fullX + i * 8, 1);
        bar_init_fence();
    }
    __syncthreads();
    if (warp < 4) {
        asm volatile("setmaxnreg.dec.sync.aligned.u32 24;");
        if (warp == 0 && elect_one()) {
            int s = 0; uint32_t ph = 1;
            int c = 0, j = 0;
#pragma unroll 1
            for (int i = 0; i < 108; i++) {
                if (i == F_NST) {
                    pdl_wait();
                    for (int kb = 0; kb < 9; kb++) {
                        mbar_expect(fullX + kb * 8, 16384);
                        tma_2d(sX + kb * 16384, &tmH, kb * 64, m * 128, fullX + kb * 8);
                    }
                }
                if (i == 54) c = fs;
                mbar_wait(empty + s * 8, ph);
                mbar_expect(full + s * 8, F_STAGE);
                if (i < 54) tma_2d(sSt + s * F_STAGE, &tmW1, fs * 576 + c * 64, j * 96, full + s * 8);
                else tma_2d(sSt + s * F_STAGE, &tmW2, c * 64, fs * 576 + j * 96, full + s * 8);
                if (++j == 6) { j = 0; if (++c == 9) c = 0; }
                if (++s == F_NST) { s = 0; ph ^= 1; }
            }
        }
    } else {
        asm volatile("setmaxnreg.inc.sync.aligned.u32 240;");
        const int wgid = (warp >> 2) - 1, w = warp & 3, g = lane >> 2;
        pdl_wait();
        if (tid == 128) TS(3, 1);
        for (int i = tid - 128; i < 576; i += 256) reinterpret_cast<float*>(smem + F_OFF_CS)[i] = g_cs1[fs * 576 + i];
        RowStat st;
        {
            const int r0 = m * 128 + wgid * 64 + w * 16 + g;
            float s0 = 0.f, q0 = 0.f, s1 = 0.f, q1 = 0.f;
#pragma unroll
            for (int p = 0; p < 6; p++) {
                const float2 a = g_stat[p * SEQ + r0], b = g_stat[p * SEQ + r0 + 8];
                s0 += a.x; q0 += a.y; s1 += b.x; q1 += b.y;
            }
            const float m0 = s0 * (1.0f / DM), m1 = s1 * (1.0f / DM);
            const float v0 = fmaxf(q0 * (1.0f / DM) - m0 * m0, 0.f) + LN_EPS, v1 = fmaxf(q1 * (1.0f / DM) - m1 * m1, 0.f) + LN_EPS;
            st.istd0 = sqrtf(v0); st.istd1 = sqrtf(v1);
            st.nmean0 = -m0; st.nmean1 = -m1;
            st.c0 = -LOG2E / st.istd0; st.c1 = -LOG2E / st.istd1;
        }
        FfnPipe pp{full, empty, lane};
        const uint32_t cs_addr = sCs + (lane & 3) * 8;
        const uint64_t xlo = cdesc(0, 16, 1024, 1) + wgid * 512;
        uint32_t h1[144];
        float acc0[32], acc1[32];
        ffn_phase1_chunk<0>(acc0, acc1, h1, pp, xlo, fullX, cs_addr, st);
        named_sync(1, 256);
        if (tid == 128) TS(3, 2);
        ffn_phase1_chunk<1>(acc1, acc0, h1, pp, xlo, fullX, cs_addr, st);
        ffn_phase1_chunk<2>(acc0, acc1, h1, pp, xlo, fullX, cs_addr, st);
        ffn_phase1_chunk<3>(acc1, acc0, h1, pp, xlo, fullX, cs_addr, st);
        ffn_phase1_chunk<4>(acc0, acc1, h1, pp, xlo, fullX, cs_addr, st);
        ffn_phase1_chunk<5>(acc1, acc0, h1, pp, xlo, fullX, cs_addr, st);
        ffn_phase1_chunk<6>(acc0, acc1, h1, pp, xlo, fullX, cs_addr, st);
        ffn_phase1_chunk<7>(acc1, acc0, h1, pp, xlo, fullX, cs_addr, st);
        ffn_phase1_chunk<8>(acc0, acc1, h1, pp, xlo, fullX, cs_addr, st);
        wg_wait<0>();
        pp.release(5);
        pin(acc0);
        {
            float tmp[4][8];
#pragma unroll
            for (int p = 0; p < 4; p++) silu_s1(acc0, tmp[p], p, cs_addr + 8 * 256, st);
#pragma unroll
            for (int p = 0; p < 4; p++) silu_s2(tmp[p], st, 0);
#pragma unroll
            for (int p = 0; p < 4; p++) silu_s3<8>(acc0, tmp[p], h1, p);
        }
        pin(h1);
        if (tid == 128) TS(3, 3);
        const int row = m * 128 + wgid * 64;
        const uint32_t stg = sX + wgid * 8192;
        int c = fs, cprev = 0;
#pragma unroll 1
        for (int j = 0; j < 8; j += 2) {
            ffn_phase2_chunk(acc1, acc0, h1, pp, 1, j > 0, &tmOut, stg + (j - 1) * 16384, cprev * 64, row, w, lane, wgid);
            cprev = c; if (++c == 9) c = 0;
            ffn_phase2_chunk(acc0, acc1, h1, pp, 0, true, &tmOut, stg + j * 16384, cprev * 64, row, w, lane, wgid);
            cprev = c; if (++c == 9) c = 0;
        }
        ffn_phase2_chunk(acc1, acc0, h1, pp, 1, true, &tmOut, stg + 7 * 16384, cprev * 64, row, w, lane, wgid);
        wg_wait<0>();
        pin(acc1);
        ffn_store_chunk(acc1, &tmOut, stg + 8 * 16384, c * 64, row, w, lane, wgid);
        if (tid == 128) TS(3, 4);
        if (w == 0) bulk_wait_all();
        if (tid == 128) TS(3, 5);
    }
}

typedef CUresult (*EncodeFn)(CUtensorMap*, CUtensorMapDataType, cuuint32_t, void*, const cuuint64_t*, const cuuint64_t*, const cuuint32_t*, const cuuint32_t*,
                             CUtensorMapInterleave, CUtensorMapSwizzle, CUtensorMapL2promotion, CUtensorMapFloatOOBfill);

CUtensorMap make_map(EncodeFn enc, const void* base, int rows, int cols, int box_rows) {
    CUtensorMap tm;
    cuuint64_t dims[2] = {(cuuint64_t)cols, (cuuint64_t)rows};
    cuuint64_t strides[1] = {(cuuint64_t)cols * 2};
    cuuint32_t box[2] = {64, (cuuint32_t)box_rows};
    cuuint32_t es[2] = {1, 1};
    enc(&tm, CU_TENSOR_MAP_DATA_TYPE_BFLOAT16, 2, const_cast<void*>(base), dims, strides, box, es, CU_TENSOR_MAP_INTERLEAVE_NONE,
        CU_TENSOR_MAP_SWIZZLE_128B, CU_TENSOR_MAP_L2_PROMOTION_L2_256B, CU_TENSOR_MAP_FLOAT_OOB_FILL_NONE);
    return tm;
}

template <typename... KArgs, typename... Args>
void launch(void (*kern)(KArgs...), int grid, int block, int smem, bool pdl, Args... args) {
    cudaLaunchConfig_t cfg = {};
    cfg.gridDim = dim3(grid); cfg.blockDim = dim3(block); cfg.dynamicSmemBytes = smem; cfg.stream = cudaStreamPerThread;
    cudaLaunchAttribute at[1];
    at[0].id = cudaLaunchAttributeProgrammaticStreamSerialization;
    at[0].val.programmaticStreamSerializationAllowed = 1;
    cfg.attrs = at; cfg.numAttrs = pdl ? 1 : 0;
    cudaLaunchKernelEx(&cfg, kern, KArgs(args)...);
}

}

#define USE_PDL 1

extern "C" void kernel_launch(void* const* d_in, const int* in_sizes, int n_in, void* d_out, int out_size) {
    const __nv_bfloat16* x = (const __nv_bfloat16*)d_in[0];
    const __nv_bfloat16* wq = (const __nv_bfloat16*)d_in[1];
    const __nv_bfloat16* wk = (const __nv_bfloat16*)d_in[2];
    const __nv_bfloat16* wv = (const __nv_bfloat16*)d_in[3];
    const __nv_bfloat16* wo = (const __nv_bfloat16*)d_in[4];
    const __nv_bfloat16* w1 = (const __nv_bfloat16*)d_in[6];
    const __nv_bfloat16* w2 = (const __nv_bfloat16*)d_in[7];
    __nv_bfloat16* out = (__nv_bfloat16*)d_out;

    static EncodeFn enc = nullptr;
    static void *p_o = nullptr, *p_h = nullptr, *p_q = nullptr;
    if (!enc) {
        cudaDriverEntryPointQueryResult qr;
        cudaGetDriverEntryPoint("cuTensorMapEncodeTiled", (void**)&enc, cudaEnableDefault, &qr);
        cudaGetSymbolAddress(&p_o, g_o);
        cudaGetSymbolAddress(&p_h, g_h);
        cudaGetSymbolAddress(&p_q, g_q);
        cudaFuncSetAttribute(k_qkv, cudaFuncAttributeMaxDynamicSharedMemorySize, P_SMEM);
        cudaFuncSetAttribute(k_attn, cudaFuncAttributeMaxDynamicSharedMemorySize, A_SMEM);
        cudaFuncSetAttribute(k_oproj, cudaFuncAttributeMaxDynamicSharedMemorySize, P_SMEM);
        cudaFuncSetAttribute(k_ffn, cudaFuncAttributeMaxDynamicSharedMemorySize, F_SMEM);
    }
    const CUtensorMap tmWq = make_map(enc, wq, DM, DM, 64);
    const CUtensorMap tmWo = make_map(enc, wo, DM, DM, 64);
    const CUtensorMap tmO = make_map(enc, p_o, SEQ, DM, 64);
    const CUtensorMap tmH = make_map(enc, p_h, SEQ, DM, 128);
    const CUtensorMap tmH64 = make_map(enc, p_h, SEQ, DM, 64);
    const CUtensorMap tmQ = make_map(enc, p_q, SEQ, DM, 64);
    const CUtensorMap tmW1 = make_map(enc, w1, DM, FF, 96);
    const CUtensorMap tmW2 = make_map(enc, w2, FF, DM, 96);
    const CUtensorMap tmOut = make_map(enc, out, SEQ, DM, 64);

    launch(k_qkv, 128, P_THREADS, P_SMEM, false, tmWq, tmQ, x, wk, wv);
    launch(k_attn, 132, A_THREADS, A_SMEM, USE_PDL, w1, w2, wo);
    launch(k_oproj, 96, P_THREADS, P_SMEM, USE_PDL, tmO, tmWo, tmH64, tmOut, x);
    launch(k_ffn, 128, F_THREADS, F_SMEM, USE_PDL, tmH, tmW1, tmW2, tmOut);
}
```

```cpp
#include <cuda_runtime.h>
#include <cuda_bf16.h>
#include <cuda.h>
#include <stdint.h>

namespace {

constexpr int SEQ = 2048, DM = 576, FF = 4608;
constexpr int KV_BYTES = SEQ * 48;
constexpr float LN_EPS = 1e-5f;
constexpr float LOG2E = 1.4426950408889634f;
constexpr float Q_SCALE = 0.23570226039551584f * LOG2E;

constexpr uint32_t POLY_MASK = 0xB5B5u;
constexpr float FAST_BOUND = 60.0f;

__device__ __align__(1024) __nv_bfloat16 g_q[SEQ * DM];
__device__ __align__(1024) uint4 g_kc[KV_BYTES / 16];
__device__ __align__(1024) uint4 g_vc[KV_BYTES / 16];
__device__ float g_kmax[32];
__device__ __align__(1024) __nv_bfloat16 g_o[SEQ * DM];
__device__ __align__(1024) __nv_bfloat16 g_x2[SEQ * DM];

#define TS(k, i)

__device__ __forceinline__ uint32_t smem_u32(const void* p) { return (uint32_t)__cvta_generic_to_shared(p); }
__device__ __forceinline__ void wg_fence() { asm volatile("wgmma.fence.sync.aligned;" ::: "memory"); }
__device__ __forceinline__ void wg_commit() { asm volatile("wgmma.commit_group.sync.aligned;" ::: "memory"); }
template <int N> __device__ __forceinline__ void wg_wait() { asm volatile("wgmma.wait_group.sync.aligned %0;" ::"n"(N) : "memory"); }
template <int N> __device__ __forceinline__ void pin(float (&r)[N]) {
#pragma unroll
    for (int i = 0; i < N; i++) asm volatile("" : "+f"(r[i])::"memory");
}
template <int N> __device__ __forceinline__ void pin(uint32_t (&r)[N]) {
#pragma unroll
    for (int i = 0; i < N; i++) asm volatile("" : "+r"(r[i])::"memory");
}
__device__ __forceinline__ constexpr uint32_t desc_hi(uint32_t sbo, uint32_t swz) { return (sbo >> 4) | (swz << 30); }
__device__ __forceinline__ uint32_t desc_lo(uint32_t addr, uint32_t lbo) { return ((addr & 0x3FFFF) >> 4) | ((lbo >> 4) << 16); }
__device__ __forceinline__ uint64_t desc64(uint32_t lo, uint32_t hi) { return ((uint64_t)hi << 32) | lo; }
constexpr uint32_t SMEM0 = 0x400;
__host__ __device__ constexpr uint64_t cdesc(uint32_t off, uint32_t lbo, uint32_t sbo, uint32_t swz) {
    return (uint64_t)(((SMEM0 + off) & 0x3FFFF) >> 4) | ((uint64_t)(lbo >> 4) << 16) | ((uint64_t)(sbo >> 4) << 32) | ((uint64_t)swz << 62);
}
__device__ __forceinline__ void check_smem_base(uint32_t base) { if ((base & 0x3FFFF) != SMEM0) __trap(); }

__device__ __forceinline__ void mbar_init(uint32_t bar, int cnt) { asm volatile("mbarrier.init.shared::cta.b64 [%0], %1;" ::"r"(bar), "r"(cnt) : "memory"); }
__device__ __forceinline__ void mbar_expect(uint32_t bar, int bytes) { asm volatile("mbarrier.arrive.expect_tx.shared::cta.b64 _, [%0], %1;" ::"r"(bar), "r"(bytes) : "memory"); }
__device__ __forceinline__ void mbar_arrive(uint32_t bar) { asm volatile("mbarrier.arrive.shared::cta.b64 _, [%0];" ::"r"(bar) : "memory"); }
__device__ __forceinline__ void mbar_wait(uint32_t bar, uint32_t parity) {
    asm volatile(
        "{\n.reg .pred p;\n.reg .u32 n;\nmov.u32 n, 0;\n"
        "LAB_WAIT:\n"
        "mbarrier.try_wait.parity.shared::cta.b64 p, [%0], %1;\n"
        "@p bra DONE;\n"
        "add.u32 n, n, 1;\n"
        "setp.lt.u32 p, n, 4000000;\n"
        "@p bra LAB_WAIT;\n"
        "trap;\n"
        "DONE:\n}\n" ::"r"(bar), "r"(parity) : "memory");
}
__device__ __forceinline__ void bar_init_fence() {
    asm volatile("fence.mbarrier_init.release.cluster;" ::: "memory");
    asm volatile("fence.proxy.async.shared::cta;" ::: "memory");
}
__device__ __forceinline__ void proxy_fence() { asm volatile("fence.proxy.async.shared::cta;" ::: "memory"); }
__device__ __forceinline__ void named_sync(int id, int n) { asm volatile("bar.sync %0, %1;" ::"r"(id), "r"(n) : "memory"); }
__device__ __forceinline__ void bulk_g2s(uint32_t dst, const void* src, int bytes, uint32_t bar) {
    asm volatile("cp.async.bulk.shared::cluster.global.mbarrier::complete_tx::bytes [%0], [%1], %2, [%3];" ::"r"(dst), "l"(src), "r"(bytes), "r"(bar) : "memory");
}
__device__ __forceinline__ void tma_2d(uint32_t dst, const CUtensorMap* tm, int c0, int c1, uint32_t bar) {
    asm volatile("cp.async.bulk.tensor.2d.shared::cluster.global.mbarrier::complete_tx::bytes [%0], [%1, {%3, %4}], [%2];" ::"r"(dst), "l"(tm), "r"(bar), "r"(c0), "r"(c1) : "memory");
}
__device__ __forceinline__ void tma_red_2d(const CUtensorMap* tm, int c0, int c1, uint32_t src) {
    asm volatile("cp.reduce.async.bulk.tensor.2d.global.shared::cta.add.tile.bulk_group [%0, {%2, %3}], [%1];" ::"l"(tm), "r"(src), "r"(c0), "r"(c1) : "memory");
}
__device__ __forceinline__ void tma_st_2d(const CUtensorMap* tm, int c0, int c1, uint32_t src) {
    asm volatile("cp.async.bulk.tensor.2d.global.shared::cta.tile.bulk_group [%0, {%2, %3}], [%1];" ::"l"(tm), "r"(src), "r"(c0), "r"(c1) : "memory");
}
__device__ __forceinline__ void bulk_commit() { asm volatile("cp.async.bulk.commit_group;" ::: "memory"); }
__device__ __forceinline__ void bulk_wait_all() { asm volatile("cp.async.bulk.wait_group 0;" ::: "memory"); }
__device__ __forceinline__ bool elect_one() {
    uint32_t p;
    asm volatile("{\n.reg .pred P;\nelect.sync _|P, 0xffffffff;\nselp.b32 %0, 1, 0, P;\n}\n" : "=r"(p));
    return p != 0;
}
__device__ __forceinline__ void prefetch_l2(const void* p, int bytes) { asm volatile("cp.async.bulk.prefetch.L2.global [%0], %1;" ::"l"(p), "r"(bytes) : "memory"); }
__device__ __forceinline__ void pdl_launch() { asm volatile("griddepcontrol.launch_dependents;" ::: "memory"); }
__device__ __forceinline__ void pdl_wait() { asm volatile("griddepcontrol.wait;" ::: "memory"); }
__device__ __forceinline__ float ex2(float x) { float y; asm("ex2.approx.ftz.f32 %0, %1;" : "=f"(y) : "f"(x)); return y; }
__device__ __forceinline__ float rcp(float x) { float y; asm("rcp.approx.ftz.f32 %0, %1;" : "=f"(y) : "f"(x)); return y; }
__device__ __forceinline__ uint32_t pack_bf16(float lo, float hi) { uint32_t r; asm("cvt.rn.bf16x2.f32 %0, %1, %2;" : "=r"(r) : "f"(hi), "f"(lo)); return r; }
__device__ __forceinline__ float bf_lo(uint32_t v) { return __uint_as_float(v << 16); }
__device__ __forceinline__ float bf_hi(uint32_t v) { return __uint_as_float(v & 0xFFFF0000u); }
__device__ __forceinline__ uint32_t hfma2(uint32_t a, uint32_t b, uint32_t c) { uint32_t r; asm("fma.rn.f16x2 %0, %1, %2, %3;" : "=r"(r) : "r"(a), "r"(b), "r"(c)); return r; }
__device__ __forceinline__ void stmatrix_x4(uint32_t addr, uint32_t r0, uint32_t r1, uint32_t r2, uint32_t r3) {
    asm volatile("stmatrix.sync.aligned.m8n8.x4.shared.b16 [%0], {%1, %2, %3, %4};" ::"r"(addr), "r"(r0), "r"(r1), "r"(r2), "r"(r3) : "memory");
}

template <int TB> __device__ __forceinline__ void wgmma_ss_n24(float (&d)[12], uint64_t da, uint64_t db, int sc) {
    asm volatile("{\n.reg .pred p;\nsetp.ne.b32 p, %14, 0;\n"
        "wgmma.mma_async.sync.aligned.m64n24k16.f32.bf16.bf16 {%0, %1, %2, %3, %4, %5, %6, %7, %8, %9, %10, %11}, %12, %13, p, 1, 1, 0, %15;\n}\n"
        : "+f"(d[0]), "+f"(d[1]), "+f"(d[2]), "+f"(d[3]), "+f"(d[4]), "+f"(d[5]), "+f"(d[6]), "+f"(d[7]), "+f"(d[8]), "+f"(d[9]), "+f"(d[10]), "+f"(d[11])
        : "l"(da), "l"(db), "r"(sc), "n"(TB));
}
template <int TB> __device__ __forceinline__ void wgmma_ss_n64(float (&d)[32], uint64_t da, uint64_t db, int sc) {
    asm volatile("{\n.reg .pred p;\nsetp.ne.b32 p, %34, 0;\n"
        "wgmma.mma_async.sync.aligned.m64n64k16.f32.bf16.bf16 {%0, %1, %2, %3, %4, %5, %6, %7, %8, %9, %10, %11, %12, %13, %14, %15, %16, %17, %18, %19, %20, %21, %22, %23, %24, %25, %26, %27, %28, %29, %30, %31}, %32, %33, p, 1, 1, 0, %35;\n}\n"
        : "+f"(d[0]), "+f"(d[1]), "+f"(d[2]), "+f"(d[3]), "+f"(d[4]), "+f"(d[5]), "+f"(d[6]), "+f"(d[7]), "+f"(d[8]), "+f"(d[9]), "+f"(d[10]), "+f"(d[11]), "+f"(d[12]), "+f"(d[13]), "+f"(d[14]), "+f"(d[15]), "+f"(d[16]), "+f"(d[17]), "+f"(d[18]), "+f"(d[19]), "+f"(d[20]), "+f"(d[21]), "+f"(d[22]), "+f"(d[23]), "+f"(d[24]), "+f"(d[25]), "+f"(d[26]), "+f"(d[27]), "+f"(d[28]), "+f"(d[29]), "+f"(d[30]), "+f"(d[31])
        : "l"(da), "l"(db), "r"(sc), "n"(TB));
}
template <int TB> __device__ __forceinline__ void wgmma_ss_n128(float (&d)[64], uint64_t da, uint64_t db, int sc) {
    asm volatile("{\n.reg .pred p;\nsetp.ne.b32 p, %66, 0;\n"
        "wgmma.mma_async.sync.aligned.m64n128k16.f32.bf16.bf16 {%0, %1, %2, %3, %4, %5, %6, %7, %8, %9, %10, %11, %12, %13, %14, %15, %16, %17, %18, %19, %20, %21, %22, %23, %24, %25, %26, %27, %28, %29, %30, %31, %32, %33, %34, %35, %36, %37, %38, %39, %40, %41, %42, %43, %44, %45, %46, %47, %48, %49, %50, %51, %52, %53, %54, %55, %56, %57, %58, %59, %60, %61, %62, %63}, %64, %65, p, 1, 1, 0, %67;\n}\n"
        : "+f"(d[0]), "+f"(d[1]), "+f"(d[2]), "+f"(d[3]), "+f"(d[4]), "+f"(d[5]), "+f"(d[6]), "+f"(d[7]), "+f"(d[8]), "+f"(d[9]), "+f"(d[10]), "+f"(d[11]), "+f"(d[12]), "+f"(d[13]), "+f"(d[14]), "+f"(d[15]), "+f"(d[16]), "+f"(d[17]), "+f"(d[18]), "+f"(d[19]), "+f"(d[20]), "+f"(d[21]), "+f"(d[22]), "+f"(d[23]), "+f"(d[24]), "+f"(d[25]), "+f"(d[26]), "+f"(d[27]), "+f"(d[28]), "+f"(d[29]), "+f"(d[30]), "+f"(d[31]), "+f"(d[32]), "+f"(d[33]), "+f"(d[34]), "+f"(d[35]), "+f"(d[36]), "+f"(d[37]), "+f"(d[38]), "+f"(d[39]), "+f"(d[40]), "+f"(d[41]), "+f"(d[42]), "+f"(d[43]), "+f"(d[44]), "+f"(d[45]), "+f"(d[46]), "+f"(d[47]), "+f"(d[48]), "+f"(d[49]), "+f"(d[50]), "+f"(d[51]), "+f"(d[52]), "+f"(d[53]), "+f"(d[54]), "+f"(d[55]), "+f"(d[56]), "+f"(d[57]), "+f"(d[58]), "+f"(d[59]), "+f"(d[60]), "+f"(d[61]), "+f"(d[62]), "+f"(d[63])
        : "l"(da), "l"(db), "r"(sc), "n"(TB));
}
template <int TB> __device__ __forceinline__ void wgmma_rs_n24(float (&d)[12], uint32_t a0, uint32_t a1, uint32_t a2, uint32_t a3, uint64_t db, int sc) {
    asm volatile("{\n.reg .pred p;\nsetp.ne.b32 p, %17, 0;\n"
        "wgmma.mma_async.sync.aligned.m64n24k16.f32.bf16.bf16 {%0, %1, %2, %3, %4, %5, %6, %7, %8, %9, %10, %11}, {%12, %13, %14, %15}, %16, p, 1, 1, %18;\n}\n"
        : "+f"(d[0]), "+f"(d[1]), "+f"(d[2]), "+f"(d[3]), "+f"(d[4]), "+f"(d[5]), "+f"(d[6]), "+f"(d[7]), "+f"(d[8]), "+f"(d[9]), "+f"(d[10]), "+f"(d[11])
        : "r"(a0), "r"(a1), "r"(a2), "r"(a3), "l"(db), "r"(sc), "n"(TB));
}
template <int TB> __device__ __forceinline__ void wgmma_rs_n64(float (&d)[32], uint32_t a0, uint32_t a1, uint32_t a2, uint32_t a3, uint64_t db, int sc) {
    asm volatile("{\n.reg .pred p;\nsetp.ne.b32 p, %37, 0;\n"
        "wgmma.mma_async.sync.aligned.m64n64k16.f32.bf16.bf16 {%0, %1, %2, %3, %4, %5, %6, %7, %8, %9, %10, %11, %12, %13, %14, %15, %16, %17, %18, %19, %20, %21, %22, %23, %24, %25, %26, %27, %28, %29, %30, %31}, {%32, %33, %34, %35}, %36, p, 1, 1, %38;\n}\n"
        : "+f"(d[0]), "+f"(d[1]), "+f"(d[2]), "+f"(d[3]), "+f"(d[4]), "+f"(d[5]), "+f"(d[6]), "+f"(d[7]), "+f"(d[8]), "+f"(d[9]), "+f"(d[10]), "+f"(d[11]), "+f"(d[12]), "+f"(d[13]), "+f"(d[14]), "+f"(d[15]), "+f"(d[16]), "+f"(d[17]), "+f"(d[18]), "+f"(d[19]), "+f"(d[20]), "+f"(d[21]), "+f"(d[22]), "+f"(d[23]), "+f"(d[24]), "+f"(d[25]), "+f"(d[26]), "+f"(d[27]), "+f"(d[28]), "+f"(d[29]), "+f"(d[30]), "+f"(d[31])
        : "r"(a0), "r"(a1), "r"(a2), "r"(a3), "l"(db), "r"(sc), "n"(TB));
}
template <int TB> __device__ __forceinline__ void wgmma_rs_n128(float (&d)[64], uint32_t a0, uint32_t a1, uint32_t a2, uint32_t a3, uint64_t db, int sc) {
    asm volatile("{\n.reg .pred p;\nsetp.ne.b32 p, %69, 0;\n"
        "wgmma.mma_async.sync.aligned.m64n128k16.f32.bf16.bf16 {%0, %1, %2, %3, %4, %5, %6, %7, %8, %9, %10, %11, %12, %13, %14, %15, %16, %17, %18, %19, %20, %21, %22, %23, %24, %25, %26, %27, %28, %29, %30, %31, %32, %33, %34, %35, %36, %37, %38, %39, %40, %41, %42, %43, %44, %45, %46, %47, %48, %49, %50, %51, %52, %53, %54, %55, %56, %57, %58, %59, %60, %61, %62, %63}, {%64, %65, %66, %67}, %68, p, 1, 1, %70;\n}\n"
        : "+f"(d[0]), "+f"(d[1]), "+f"(d[2]), "+f"(d[3]), "+f"(d[4]), "+f"(d[5]), "+f"(d[6]), "+f"(d[7]), "+f"(d[8]), "+f"(d[9]), "+f"(d[10]), "+f"(d[11]), "+f"(d[12]), "+f"(d[13]), "+f"(d[14]), "+f"(d[15]), "+f"(d[16]), "+f"(d[17]), "+f"(d[18]), "+f"(d[19]), "+f"(d[20]), "+f"(d[21]), "+f"(d[22]), "+f"(d[23]), "+f"(d[24]), "+f"(d[25]), "+f"(d[26]), "+f"(d[27]), "+f"(d[28]), "+f"(d[29]), "+f"(d[30]), "+f"(d[31]), "+f"(d[32]), "+f"(d[33]), "+f"(d[34]), "+f"(d[35]), "+f"(d[36]), "+f"(d[37]), "+f"(d[38]), "+f"(d[39]), "+f"(d[40]), "+f"(d[41]), "+f"(d[42]), "+f"(d[43]), "+f"(d[44]), "+f"(d[45]), "+f"(d[46]), "+f"(d[47]), "+f"(d[48]), "+f"(d[49]), "+f"(d[50]), "+f"(d[51]), "+f"(d[52]), "+f"(d[53]), "+f"(d[54]), "+f"(d[55]), "+f"(d[56]), "+f"(d[57]), "+f"(d[58]), "+f"(d[59]), "+f"(d[60]), "+f"(d[61]), "+f"(d[62]), "+f"(d[63])
        : "r"(a0), "r"(a1), "r"(a2), "r"(a3), "l"(db), "r"(sc), "n"(TB));
}

constexpr int P_THREADS = 288;
constexpr int P_NST = 6;
constexpr int P_A_BYTES = 9 * 8192;
constexpr int P_B_STAGE = 3 * 8192;
constexpr int P_SMEM = P_A_BYTES + P_NST * P_B_STAGE + 256;
constexpr uint32_t HI_SW128 = (1024u >> 4) | (1u << 30);

template <int NCOL, bool WAIT_A>
__device__ __forceinline__ void proj_mma(float (&acc)[NCOL / 2], uint32_t sA, uint32_t sB, uint32_t colofs, uint32_t fullB, uint32_t emptyB, uint32_t fullA, int lane) {
#pragma unroll 1
    for (int kb = 0; kb < 9; kb++) {
        const int s = kb >= P_NST ? kb - P_NST : kb;
        if (WAIT_A) mbar_wait(fullA + kb * 8, 0);
        mbar_wait(fullB + s * 8, kb >= P_NST ? 1 : 0);
        const uint32_t alo = desc_lo(sA + kb * 8192, 16), blo = desc_lo(sB + s * P_B_STAGE + colofs, 8192);
        wg_fence();
#pragma unroll
        for (int ks = 0; ks < 4; ks++) {
            const uint64_t da = desc64(alo + ks * 2, HI_SW128), db = desc64(blo + ks * 128, HI_SW128);
            if constexpr (NCOL == 128) wgmma_ss_n128<1>(acc, da, db, (kb | ks) != 0);
            else wgmma_ss_n64<1>(acc, da, db, (kb | ks) != 0);
        }
        wg_commit();
        if (kb + P_NST < 9 + 1) {
            wg_wait<1>();
            if (kb >= 1 && kb - 1 + P_NST < 9 && lane == 0) mbar_arrive(emptyB + (kb - 1) * 8);
        }
    }
    wg_wait<0>();
    pin(acc);
}

template <int NB>
__device__ __forceinline__ void stage_tile(const uint32_t (&pk)[NB * 2], uint32_t base, int w, int lane) {
    const int r = w * 16 + (lane & 7) + ((lane >> 3) & 1) * 8;
#pragma unroll
    for (int b = 0; b < NB; b += 2) {
        const uint32_t a = base + (b >> 3) * 8192 + r * 128 + ((((b & 7) + (lane >> 4)) ^ (r & 7)) << 4);
        stmatrix_x4(a, pk[2 * b], pk[2 * b + 1], pk[2 * b + 2], pk[2 * b + 3]);
    }
}

__global__ void __launch_bounds__(P_THREADS, 1)
k_qkv(const __grid_constant__ CUtensorMap tmWq, const __grid_constant__ CUtensorMap tmQ, const __nv_bfloat16* __restrict__ x, const __nv_bfloat16* __restrict__ wk, const __nv_bfloat16* __restrict__ wv) {
    extern __shared__ __align__(1024) uint8_t smem[];
    const uint32_t sA = smem_u32(smem), sB = sA + P_A_BYTES, bars = sB + P_NST * P_B_STAGE;
    const uint32_t fullB = bars, emptyB = bars + 64;
    const int tid = threadIdx.x, warp = __shfl_sync(~0u, tid >> 5, 0), lane = tid & 31;
    const bool isQ = blockIdx.x < 96;
    const int m = isQ ? blockIdx.x / 3 : blockIdx.x - 96, cg = blockIdx.x % 3;
    if (tid == 0) TS(0, 0);
    if (tid == 0) {
        for (int i = 0; i < P_NST; i++) { mbar_init(fullB + i * 8, 1); mbar_init(emptyB + i * 8, 8); }
        bar_init_fence();
    }
    __syncthreads();
    pdl_launch();
    if (warp == 8) {
        if (isQ && elect_one()) {
            for (int kb = 0; kb < 9; kb++) {
                const int s = kb >= P_NST ? kb - P_NST : kb;
                if (kb >= P_NST) mbar_wait(emptyB + s * 8, 0);
                mbar_expect(fullB + s * 8, P_B_STAGE);
                for (int a = 0; a < 3; a++) tma_2d(sB + s * P_B_STAGE + a * 8192, &tmWq, cg * 192 + a * 64, kb * 64, fullB + s * 8);
            }
        }
        return;
    }
    {
        const int row = tid >> 2, q = tid & 3;
        const uint4* src = reinterpret_cast<const uint4*>(x + (size_t)(m * 64 + row) * DM) + q;
        uint4 v[18];
#pragma unroll
        for (int i = 0; i < 18; i++) v[i] = __ldg(src + 4 * i);
        if (!isQ) {
            const uint32_t* wk32 = reinterpret_cast<const uint32_t*>(wk);
            const uint32_t* wv32 = reinterpret_cast<const uint32_t*>(wv);
            uint32_t wreg[41];
#pragma unroll
            for (int i = 0; i < 41; i++) {
                const int idx = tid + i * 256;
                wreg[i] = idx < DM * 9 ? __ldg(wk32 + idx) : (idx < 2 * DM * 9 ? __ldg(wv32 + idx - DM * 9) : 0u);
            }
#pragma unroll
            for (int i = 0; i < 41; i++) {
                const int idx = tid + i * 256;
                if (idx < 2 * DM * 9) {
                    const int sel = idx >= DM * 9, j = idx - sel * DM * 9, k = j / 9, n = (j - k * 9) * 2;
                    const uint32_t a = sB + (sel * 3 + (n >> 3)) * 9216 + (k >> 3) * 128 + (n & 7) * 16 + (k & 7) * 2;
                    asm volatile("st.shared.u16 [%0], %1;" ::"r"(a), "h"((uint16_t)(wreg[i] & 0xFFFF)) : "memory");
                    asm volatile("st.shared.u16 [%0], %1;" ::"r"(a + 16), "h"((uint16_t)(wreg[i] >> 16)) : "memory");
                }
            }
        }
        float sum = 0.f;
#pragma unroll
        for (int i = 0; i < 18; i++) {
            sum += (bf_lo(v[i].x) + bf_hi(v[i].x)) + (bf_lo(v[i].y) + bf_hi(v[i].y)) + (bf_lo(v[i].z) + bf_hi(v[i].z)) + (bf_lo(v[i].w) + bf_hi(v[i].w));
        }
        sum += __shfl_xor_sync(~0u, sum, 1); sum += __shfl_xor_sync(~0u, sum, 2);
        const float mean = sum * (1.0f / DM);
        float sq = 0.f;
#pragma unroll
        for (int i = 0; i < 18; i++) {
            const uint32_t w[4] = {v[i].x, v[i].y, v[i].z, v[i].w};
#pragma unroll
            for (int j = 0; j < 4; j++) { const float a = bf_lo(w[j]) - mean, b = bf_hi(w[j]) - mean; sq = fmaf(a, a, sq); sq = fmaf(b, b, sq); }
        }
        sq += __shfl_xor_sync(~0u, sq, 1); sq += __shfl_xor_sync(~0u, sq, 2);
        const float rstd = rsqrtf(sq * (1.0f / DM) + LN_EPS), nmr = -mean * rstd;
#pragma unroll
        for (int i = 0; i < 18; i++) {
            const int c = q + 4 * i;
            const uint32_t w[4] = {v[i].x, v[i].y, v[i].z, v[i].w};
            uint32_t o[4];
#pragma unroll
            for (int j = 0; j < 4; j++) o[j] = pack_bf16(fmaf(bf_lo(w[j]), rstd, nmr), fmaf(bf_hi(w[j]), rstd, nmr));
            const uint32_t a = sA + (c >> 3) * 8192 + row * 128 + (((c & 7) ^ (row & 7)) << 4);
            asm volatile("st.shared.v4.b32 [%0], {%1, %2, %3, %4};" ::"r"(a), "r"(o[0]), "r"(o[1]), "r"(o[2]), "r"(o[3]) : "memory");
        }
    }
    proxy_fence();
    named_sync(1, 256);
    if (tid == 0) TS(0, 1);
    const int wg = warp >> 2, w = warp & 3, g = lane >> 2, t = lane & 3;
    const int r0 = m * 64 + w * 16 + g;
    if (isQ) {
        if (wg == 0) {
            float acc[64];
            proj_mma<128, false>(acc, sA, sB, 0, fullB, emptyB, 0, lane);
            if (tid == 0) TS(0, 2);
            named_sync(1, 256);
            uint32_t pk[32];
#pragma unroll
            for (int i = 0; i < 32; i++) pk[i] = pack_bf16(acc[2 * i] * Q_SCALE, acc[2 * i + 1] * Q_SCALE);
            stage_tile<16>(pk, sA, w, lane);
        } else {
            float acc[32];
            proj_mma<64, false>(acc, sA, sB, 2 * 8192, fullB, emptyB, 0, lane);
            named_sync(1, 256);
            uint32_t pk[16];
#pragma unroll
            for (int i = 0; i < 16; i++) pk[i] = pack_bf16(acc[2 * i] * Q_SCALE, acc[2 * i + 1] * Q_SCALE);
            stage_tile<8>(pk, sA + 2 * 8192, w, lane);
        }
        proxy_fence();
        named_sync(1, 256);
        if (warp == 0 && elect_one()) {
            for (int a = 0; a < 3; a++) tma_st_2d(&tmQ, cg * 192 + a * 64, m * 64, sA + a * 8192);
            bulk_commit();
            bulk_wait_all();
        }
    } else {
        float acc[12];
        const uint32_t blo = desc_lo(sB + wg * 3 * 9216, 128);
#pragma unroll 1
        for (int kb = 0; kb < 9; kb++) {
            const uint32_t alo = desc_lo(sA + kb * 8192, 16);
            wg_fence();
#pragma unroll
            for (int ks = 0; ks < 4; ks++)
                wgmma_ss_n24<0>(acc, desc64(alo + ks * 2, HI_SW128), desc64(blo + (kb * 4 + ks) * 16, desc_hi(9216, 0)), (kb | ks) != 0);
        }
        wg_commit();
        wg_wait<0>();
        pin(acc);
        uint32_t pk[6];
#pragma unroll
        for (int i = 0; i < 6; i++) pk[i] = pack_bf16(acc[2 * i], acc[2 * i + 1]);
        float n0 = 0.f, n1 = 0.f, vm = 0.f;
#pragma unroll
        for (int b = 0; b < 3; b++) {
            if (b < 2 || t == 0) {
                const float a = bf_lo(pk[2 * b]), c = bf_hi(pk[2 * b]), d = bf_lo(pk[2 * b + 1]), e = bf_hi(pk[2 * b + 1]);
                n0 = fmaf(a, a, fmaf(c, c, n0)); n1 = fmaf(d, d, fmaf(e, e, n1));
            }
        }
        n0 += __shfl_xor_sync(~0u, n0, 1); n0 += __shfl_xor_sync(~0u, n0, 2);
        n1 += __shfl_xor_sync(~0u, n1, 1); n1 += __shfl_xor_sync(~0u, n1, 2);
        vm = fmaxf(n0, n1);
        if (!(vm == vm)) vm = __int_as_float(0x7F800000);
#pragma unroll
        for (int o = 4; o < 32; o <<= 1) vm = fmaxf(vm, __shfl_xor_sync(~0u, vm, o));
        if (t != 0) {
            uint32_t lo, hi;
            if (wg == 0) {
                const int grp = m * 8 + w * 2;
                const uint32_t c = t == 1 ? 0x42FE3F80u   : (t == 2 ? 0x00003BC0u   : 0u);
                lo = ((POLY_MASK >> (grp & 15)) & 1) ? c : 0u;
                hi = ((POLY_MASK >> ((grp + 1) & 15)) & 1) ? c : 0u;
            } else {
                lo = hi = t == 1 ? 0x00003F80u : 0u;
            }
            pk[4] = lo; pk[5] = hi;
        }
        uint32_t* dst = reinterpret_cast<uint32_t*>(wg == 0 ? g_kc : g_vc) + (m * 8 + w * 2) * 96 + g * 4 + t;
#pragma unroll
        for (int b = 0; b < 3; b++) { dst[b * 32] = pk[2 * b]; dst[96 + b * 32] = pk[2 * b + 1]; }
        float* red = reinterpret_cast<float*>(smem + P_A_BYTES + 6 * 9216);
        if (lane == 0) red[warp] = (wg == 0) ? vm : (vm <= 1e24f ? 0.f : __int_as_float(0x7F800000));
        named_sync(1, 256);
        if (tid == 0) {
            float mx = red[0];
#pragma unroll
            for (int i = 1; i < 8; i++) mx = fmaxf(mx, red[i]);
            g_kmax[m] = mx;
        }
    }
    if (tid == 0) TS(0, 3);
}

constexpr int A_THREADS = 512;
constexpr int A_NPIECE = 8;
constexpr int A_SMEM = 2 * KV_BYTES + 128;

__device__ __forceinline__ uint32_t exp2_pair_fixed(float lo, float hi) {
    const uint32_t G = __byte_perm(__float_as_uint(lo), __float_as_uint(hi), 0x5410);
    const uint32_t Hh = G & 0x007F007Fu;
    const uint32_t tt = hfma2(Hh, 0xF96BF96Bu, 0x358C358Cu);
    return G - hfma2(tt, Hh, 0u);
}

__device__ __forceinline__ void attn_side_job(const __nv_bfloat16* __restrict__ w1, const __nv_bfloat16* __restrict__ w2, const __nv_bfloat16* __restrict__ wo) {
    const int e = blockIdx.x - 128, tid = threadIdx.x;
    if (tid < 32) {
        const char* p = reinterpret_cast<const char*>(wo) + e * (DM * DM * 2 / 4);
        for (int i = tid; i < DM * DM * 2 / 4 / 4608; i += 32) prefetch_l2(p + i * 4608, 4608);
        p = reinterpret_cast<const char*>(w1) + (size_t)e * (FF * DM * 2 / 4);
        for (int i = tid; i < FF * DM * 2 / 4 / 9216; i += 32) prefetch_l2(p + (size_t)i * 9216, 9216);
        p = reinterpret_cast<const char*>(w2) + (size_t)e * (FF * DM * 2 / 4);
        for (int i = tid; i < FF * DM * 2 / 4 / 9216; i += 32) prefetch_l2(p + (size_t)i * 9216, 9216);
    }
}

__global__ void __launch_bounds__(A_THREADS, 1)
k_attn(const __nv_bfloat16* __restrict__ w1, const __nv_bfloat16* __restrict__ w2, const __nv_bfloat16* __restrict__ wo) {
    extern __shared__ __align__(1024) uint8_t smem[];
    pdl_launch();
    if (blockIdx.x >= 128) { attn_side_job(w1, w2, wo); return; }
    const uint32_t sK = smem_u32(smem), sV = sK + KV_BYTES, bars = sV + KV_BYTES;
    const int tid = threadIdx.x;
    if (tid == 0) TS(1, 0);
    if (tid == 0) {
        for (int i = 0; i < A_NPIECE; i++) mbar_init(bars + i * 8, 1);
        bar_init_fence();
    }
    __syncthreads();
    pdl_wait();
    if (tid == 0) TS(1, 1);
    if (tid < 32 && elect_one()) {
        constexpr int PB = KV_BYTES / A_NPIECE;
        for (int i = 0; i < A_NPIECE; i++) {
            mbar_expect(bars + i * 8, 2 * PB);
            bulk_g2s(sK + i * PB, reinterpret_cast<const char*>(g_kc) + i * PB, PB, bars + i * 8);
            bulk_g2s(sV + i * PB, reinterpret_cast<const char*>(g_vc) + i * PB, PB, bars + i * 8);
        }
    }
    const int wg = __shfl_sync(~0u, tid >> 7, 0), w = (tid >> 5) & 3, lane = tid & 31, g = lane >> 2, t = lane & 3;
    const uint32_t* q32 = reinterpret_cast<const uint32_t*>(g_q);
    uint32_t* o32 = reinterpret_cast<uint32_t*>(g_o);
    float kmax2 = g_kmax[lane];
#pragma unroll
    for (int o = 1; o < 32; o <<= 1) kmax2 = fmaxf(kmax2, __shfl_xor_sync(~0u, kmax2, o));
    constexpr uint32_t HI_K = desc_hi(384, 0), HI_V = desc_hi(128, 0);
    const uint32_t k0lo = desc_lo(sK, 128), k1lo = desc_lo(sK + 256, 0), vlo = desc_lo(sV, 384);

    int row = (blockIdx.x * 8 + wg) * 64 + w * 16 + g;
    uint32_t nq[6];
    nq[0] = q32[row * 9 + t]; nq[1] = q32[(row + 8) * 9 + t]; nq[2] = q32[row * 9 + 4 + t]; nq[3] = q32[(row + 8) * 9 + 4 + t];
    nq[4] = q32[row * 9 + 8]; nq[5] = q32[(row + 8) * 9 + 8];
#pragma unroll 1
    for (int rep = 0; rep < 2; rep++, row += 256) {
        uint32_t qa[4] = {nq[0], nq[1], nq[2], nq[3]}, qb[4];
        float n0, n1;
        {
            const float a0 = bf_lo(qa[0]), a1 = bf_hi(qa[0]), a2 = bf_lo(qa[2]), a3 = bf_hi(qa[2]);
            const float b0 = bf_lo(qa[1]), b1 = bf_hi(qa[1]), b2 = bf_lo(qa[3]), b3 = bf_hi(qa[3]);
            n0 = a0 * a0 + a1 * a1 + a2 * a2 + a3 * a3; n1 = b0 * b0 + b1 * b1 + b2 * b2 + b3 * b3;
            if (t == 0) {
                const float c0 = bf_lo(nq[4]), c1 = bf_hi(nq[4]), d0 = bf_lo(nq[5]), d1 = bf_hi(nq[5]);
                n0 += c0 * c0 + c1 * c1; n1 += d0 * d0 + d1 * d1;
            }
            n0 += __shfl_xor_sync(~0u, n0, 1); n0 += __shfl_xor_sync(~0u, n0, 2);
            n1 += __shfl_xor_sync(~0u, n1, 1); n1 += __shfl_xor_sync(~0u, n1, 2);
        }
        const uint32_t x0 = nq[4], x1 = nq[5];
        if (rep == 0) {
            const int nr = row + 256;
            nq[0] = q32[nr * 9 + t]; nq[1] = q32[(nr + 8) * 9 + t]; nq[2] = q32[nr * 9 + 4 + t]; nq[3] = q32[(nr + 8) * 9 + 4 + t];
            nq[4] = q32[nr * 9 + 8]; nq[5] = q32[(nr + 8) * 9 + 8];
        }
        const bool unsafe = !(fmaxf(n0, n1) * kmax2 <= FAST_BOUND * FAST_BOUND);
        uint32_t any_unsafe;
        asm volatile("{\n.reg .pred p, q;\nsetp.ne.u32 p, %1, 0;\nbar.red.or.pred q, %2, 128, p;\nselp.u32 %0, 1, 0, q;\n}\n" : "=r"(any_unsafe) : "r"((uint32_t)unsafe), "r"(wg + 1) : "memory");
        if (tid == 0) TS(1, 2 + rep * 2);
        float o[12];
#pragma unroll
        for (int i = 0; i < 12; i++) o[i] = 0.f;
        if (!any_unsafe) {
            float s[64];
            const uint32_t cst = t == 1 ? 0x3F804780u   : (t == 2 ? 0x00003F80u   : 0u);
            qb[0] = t == 0 ? x0 : cst; qb[1] = t == 0 ? x1 : cst; qb[2] = 0; qb[3] = 0;
            pin(qa); pin(qb); pin(o);
#pragma unroll 1
            for (int j = 0; j < 16; j++) {
                if (rep == 0 && (j & 1) == 0) mbar_wait(bars + (j >> 1) * 8, 0);
                const uint32_t off = j * (16 * 384 >> 4);
                wg_fence();
                wgmma_rs_n128<0>(s, qa[0], qa[1], qa[2], qa[3], desc64(k0lo + off, HI_K), 0);
                wgmma_rs_n128<0>(s, qb[0], qb[1], qb[2], qb[3], desc64(k1lo + off, HI_K), 1);
                wg_commit();
                wg_wait<0>();
                pin(s);
                uint32_t p[32];
#pragma unroll
                for (int i = 0; i < 32; i++) {
                    if ((POLY_MASK >> (i >> 1)) & 1) p[i] = exp2_pair_fixed(s[2 * i], s[2 * i + 1]);
                    else p[i] = pack_bf16(ex2(s[2 * i]), ex2(s[2 * i + 1]));
                }
                pin(p);
                wg_fence();
#pragma unroll
                for (int k = 0; k < 8; k++) wgmma_rs_n24<1>(o, p[4 * k], p[4 * k + 1], p[4 * k + 2], p[4 * k + 3], desc64(vlo + off + k * 48, HI_V), 1);
                wg_commit();
                wg_wait<0>();
            }
        } else {
            float s[64];
            qb[0] = t == 0 ? x0 : 0u; qb[1] = t == 0 ? x1 : 0u; qb[2] = 0; qb[3] = 0;
            pin(qa); pin(qb); pin(o);
            float m0 = -INFINITY, m1 = -INFINITY;
#pragma unroll 1
            for (int j = 0; j < 16; j++) {
                if (rep == 0 && (j & 1) == 0) mbar_wait(bars + (j >> 1) * 8, 0);
                const uint32_t off = j * (16 * 384 >> 4);
                wg_fence();
                wgmma_rs_n128<0>(s, qa[0], qa[1], qa[2], qa[3], desc64(k0lo + off, HI_K), 0);
                wgmma_rs_n128<0>(s, qb[0], qb[1], qb[2], qb[3], desc64(k1lo + off, HI_K), 1);
                wg_commit();
                wg_wait<0>();
                pin(s);
                float x0m = m0, x1m = m1;
#pragma unroll
                for (int b = 0; b < 16; b++) { x0m = fmaxf(x0m, fmaxf(s[4 * b], s[4 * b + 1])); x1m = fmaxf(x1m, fmaxf(s[4 * b + 2], s[4 * b + 3])); }
                x0m = fmaxf(x0m, __shfl_xor_sync(~0u, x0m, 1)); x0m = fmaxf(x0m, __shfl_xor_sync(~0u, x0m, 2));
                x1m = fmaxf(x1m, __shfl_xor_sync(~0u, x1m, 1)); x1m = fmaxf(x1m, __shfl_xor_sync(~0u, x1m, 2));
                const float c0 = ex2(m0 - x0m), c1 = ex2(m1 - x1m);
                m0 = x0m; m1 = x1m;
#pragma unroll
                for (int b = 0; b < 3; b++) { o[4 * b] *= c0; o[4 * b + 1] *= c0; o[4 * b + 2] *= c1; o[4 * b + 3] *= c1; }
                uint32_t p[32];
#pragma unroll
                for (int b = 0; b < 16; b++) {
                    p[2 * b] = pack_bf16(ex2(s[4 * b] - m0), ex2(s[4 * b + 1] - m0));
                    p[2 * b + 1] = pack_bf16(ex2(s[4 * b + 2] - m1), ex2(s[4 * b + 3] - m1));
                }
                pin(p); pin(o);
                wg_fence();
#pragma unroll
                for (int k = 0; k < 8; k++) wgmma_rs_n24<1>(o, p[4 * k], p[4 * k + 1], p[4 * k + 2], p[4 * k + 3], desc64(vlo + off + k * 48, HI_V), 1);
                wg_commit();
                wg_wait<0>();
            }
        }
        pin(o);
        if (tid == 0) TS(1, 3 + rep * 2);
        const float l0 = __shfl_sync(~0u, o[8], (lane & ~3) | 1), l1 = __shfl_sync(~0u, o[10], (lane & ~3) | 1);
        const float i0 = 1.0f / l0, i1 = 1.0f / l1;
        o32[row * 9 + t] = pack_bf16(o[0] * i0, o[1] * i0);
        o32[(row + 8) * 9 + t] = pack_bf16(o[2] * i1, o[3] * i1);
        o32[row * 9 + 4 + t] = pack_bf16(o[4] * i0, o[5] * i0);
        o32[(row + 8) * 9 + 4 + t] = pack_bf16(o[6] * i1, o[7] * i1);
        if (t == 0) { o32[row * 9 + 8] = pack_bf16(o[8] * i0, o[9] * i0); o32[(row + 8) * 9 + 8] = pack_bf16(o[10] * i1, o[11] * i1); }
    }
    if (tid == 0) TS(1, 6);
}

template <int NB>
__device__ __forceinline__ void oproj_load_x(uint32_t (&xr)[NB * 2], const uint32_t* __restrict__ x32, int r0, int col0, int t) {
#pragma unroll
    for (int b = 0; b < NB; b++) {
        const int i0 = (r0 * DM + col0 + b * 8 + 2 * t) >> 1;
        xr[2 * b] = __ldg(x32 + i0); xr[2 * b + 1] = __ldg(x32 + i0 + 4 * DM);
    }
}
constexpr int P_OFF_STAT = 3 * 8192 + 3 * 8192;
template <int NB>
__device__ __forceinline__ void oproj_epilogue(const float (&acc)[NB * 4], uint32_t (&xr)[NB * 2], uint32_t sA, uint32_t tile_ofs, int part, int w, int lane) {
    float s0 = 0.f, q0 = 0.f, s1 = 0.f, q1 = 0.f;
#pragma unroll
    for (int b = 0; b < NB; b++) {
        const uint32_t xa = xr[2 * b], xb = xr[2 * b + 1];
        const uint32_t ha = pack_bf16(acc[4 * b] + bf_lo(xa), acc[4 * b + 1] + bf_hi(xa));
        const uint32_t hb = pack_bf16(acc[4 * b + 2] + bf_lo(xb), acc[4 * b + 3] + bf_hi(xb));
        xr[2 * b] = ha; xr[2 * b + 1] = hb;
        const float a = bf_lo(ha), c = bf_hi(ha), d = bf_lo(hb), e = bf_hi(hb);
        s0 += a + c; q0 = fmaf(a, a, fmaf(c, c, q0));
        s1 += d + e; q1 = fmaf(d, d, fmaf(e, e, q1));
    }
    s0 += __shfl_xor_sync(~0u, s0, 1); s0 += __shfl_xor_sync(~0u, s0, 2);
    q0 += __shfl_xor_sync(~0u, q0, 1); q0 += __shfl_xor_sync(~0u, q0, 2);
    s1 += __shfl_xor_sync(~0u, s1, 1); s1 += __shfl_xor_sync(~0u, s1, 2);
    q1 += __shfl_xor_sync(~0u, q1, 1); q1 += __shfl_xor_sync(~0u, q1, 2);
    const int r = w * 16 + (lane >> 2);
    const uint32_t sStat = sA + P_OFF_STAT;
    if ((lane & 3) < 3) {
        uint32_t dst;
        asm("mapa.shared::cluster.u32 %0, %1, %2;" : "=r"(dst) : "r"(sStat + (part * 64 + r) * 8), "r"(lane & 3));
        asm volatile("st.shared::cluster.v2.f32 [%0], {%1, %2};" ::"r"(dst), "f"(s0), "f"(q0) : "memory");
        asm volatile("st.shared::cluster.v2.f32 [%0], {%1, %2};" ::"r"(dst + 64), "f"(s1), "f"(q1) : "memory");
    }
    asm volatile("barrier.cluster.arrive.release.aligned;" ::: "memory");
    stage_tile<NB>(xr, sA + tile_ofs, w, lane);
    asm volatile("barrier.cluster.wait.acquire.aligned;" ::: "memory");
    s0 = q0 = s1 = q1 = 0.f;
#pragma unroll
    for (int p = 0; p < 6; p++) {
        float a, b, c, d;
        asm volatile("ld.shared.v2.f32 {%0, %1}, [%2];" : "=f"(a), "=f"(b) : "r"(sStat + (p * 64 + r) * 8));
        asm volatile("ld.shared.v2.f32 {%0, %1}, [%2];" : "=f"(c), "=f"(d) : "r"(sStat + (p * 64 + r + 8) * 8));
        s0 += a; q0 += b; s1 += c; q1 += d;
    }
    const float m0 = s0 * (1.0f / DM), m1 = s1 * (1.0f / DM);
    const float rs0 = rsqrtf(fmaxf(q0 * (1.0f / DM) - m0 * m0, 0.f) + LN_EPS), rs1 = rsqrtf(fmaxf(q1 * (1.0f / DM) - m1 * m1, 0.f) + LN_EPS);
    const float n0 = -m0 * rs0, n1 = -m1 * rs1;
#pragma unroll
    for (int b = 0; b < NB; b++) {
        xr[2 * b] = pack_bf16(fmaf(bf_lo(xr[2 * b]), rs0, n0), fmaf(bf_hi(xr[2 * b]), rs0, n0));
        xr[2 * b + 1] = pack_bf16(fmaf(bf_lo(xr[2 * b + 1]), rs1, n1), fmaf(bf_hi(xr[2 * b + 1]), rs1, n1));
    }
    stage_tile<NB>(xr, sA + 3 * 8192 + tile_ofs, w, lane);
}

__global__ void __cluster_dims__(3, 1, 1) __launch_bounds__(P_THREADS, 1)
k_oproj(const __grid_constant__ CUtensorMap tmO, const __grid_constant__ CUtensorMap tmWo, const __grid_constant__ CUtensorMap tmX2, const __grid_constant__ CUtensorMap tmOut, const __nv_bfloat16* __restrict__ x) {
    extern __shared__ __align__(1024) uint8_t smem[];
    const uint32_t sA = smem_u32(smem), sB = sA + P_A_BYTES, bars = sB + P_NST * P_B_STAGE;
    const uint32_t fullB = bars, emptyB = bars + 64, fullA = bars + 128;
    const int tid = threadIdx.x, warp = __shfl_sync(~0u, tid >> 5, 0), lane = tid & 31;
    const int m = blockIdx.x / 3, cg = blockIdx.x % 3;
    if (tid == 0) TS(2, 0);
    if (tid == 0) {
        for (int i = 0; i < P_NST; i++) { mbar_init(fullB + i * 8, 1); mbar_init(emptyB + i * 8, 8); }
        for (int i = 0; i < 9; i++) mbar_init(fullA + i * 8, 1);
        bar_init_fence();
    }
    __syncthreads();
    pdl_launch();
    if (warp == 8) {
        if (elect_one()) {
            for (int kb = 0; kb < P_NST; kb++) {
                mbar_expect(fullB + kb * 8, P_B_STAGE);
                for (int a = 0; a < 3; a++) tma_2d(sB + kb * P_B_STAGE + a * 8192, &tmWo, cg * 192 + a * 64, kb * 64, fullB + kb * 8);
            }
            pdl_wait();
            for (int kb = 0; kb < 9; kb++) {
                mbar_expect(fullA + kb * 8, 8192);
                tma_2d(sA + kb * 8192, &tmO, kb * 64, m * 64, fullA + kb * 8);
            }
            for (int kb = P_NST; kb < 9; kb++) {
                const int s = kb - P_NST;
                mbar_wait(emptyB + s * 8, 0);
                mbar_expect(fullB + s * 8, P_B_STAGE);
                for (int a = 0; a < 3; a++) tma_2d(sB + s * P_B_STAGE + a * 8192, &tmWo, cg * 192 + a * 64, kb * 64, fullB + s * 8);
            }
        }
        return;
    }
    const int wg = warp >> 2, w = warp & 3, g = lane >> 2, t = lane & 3;
    const int r0 = m * 64 + w * 16 + g;
    const uint32_t* x32 = reinterpret_cast<const uint32_t*>(x);
    if (wg == 0) {
        uint32_t xr[32];
        oproj_load_x<16>(xr, x32, r0, cg * 192, t);
        float acc[64];
        proj_mma<128, true>(acc, sA, sB, 0, fullB, emptyB, fullA, lane);
        if (tid == 0) TS(2, 2);
        named_sync(1, 256);
        oproj_epilogue<16>(acc, xr, sA, 0, cg * 2, w, lane);
    } else {
        uint32_t xr[16];
        oproj_load_x<8>(xr, x32, r0, cg * 192 + 128, t);
        float acc[32];
        proj_mma<64, true>(acc, sA, sB, 2 * 8192, fullB, emptyB, fullA, lane);
        named_sync(1, 256);
        oproj_epilogue<8>(acc, xr, sA, 2 * 8192, cg * 2 + 1, w, lane);
    }
    proxy_fence();
    named_sync(1, 256);
    if (warp == 0 && elect_one()) {
        for (int a = 0; a < 3; a++) {
            tma_st_2d(&tmX2, cg * 192 + a * 64, m * 64, sA + (3 + a) * 8192);
            tma_st_2d(&tmOut, cg * 192 + a * 64, m * 64, sA + a * 8192);
        }
        bulk_commit();
        bulk_wait_all();
        TS(2, 3);
    }
}

constexpr int F_THREADS = 384;
constexpr int F_NST = 6;
constexpr int F_STAGE = 96 * 128;
constexpr int F_X_BYTES = 9 * 16384;
constexpr int F_OFF_ST = F_X_BYTES;
constexpr int F_OFF_BAR = F_OFF_ST + F_NST * F_STAGE;
constexpr int F_SMEM = F_OFF_BAR + 256;

__device__ __forceinline__ void silu_s1(const float (&acc)[32], float (&tmp)[8], int piece) {
#pragma unroll
    for (int i = 0; i < 8; i++) tmp[i] = ex2(acc[8 * piece + i] * -LOG2E);
}
__device__ __forceinline__ float after_issue(float v, uint32_t tick) {
    uint32_t r;
    asm("lop3.b32 %0, %1, %1, %2, 0xF0;" : "=r"(r) : "r"(__float_as_uint(v)), "r"(tick));
    return __uint_as_float(r);
}
__device__ __forceinline__ uint32_t read_tick() { uint32_t c; asm volatile("mov.u32 %0, %%clock;" : "=r"(c)::"memory"); return c; }
__device__ __forceinline__ void silu_s2(float (&tmp)[8], uint32_t tick) {
    const float one = after_issue(1.0f, tick);
#pragma unroll
    for (int i = 0; i < 8; i++) tmp[i] = rcp(tmp[i] + one);
}
template <int C>
__device__ __forceinline__ void silu_s3(const float (&acc)[32], const float (&tmp)[8], uint32_t (&h1)[144], int piece) {
#pragma unroll
    for (int i = 0; i < 4; i++) h1[C * 16 + 4 * piece + i] = pack_bf16(acc[8 * piece + 2 * i] * tmp[2 * i], acc[8 * piece + 2 * i + 1] * tmp[2 * i + 1]);
}

struct FfnPipe {
    uint32_t full, empty;
    int lane;
    __device__ __forceinline__ void acquire(int s, uint32_t ph) const { mbar_wait(full + s * 8, ph); }
    __device__ __forceinline__ void release(int s) const { if (lane == 0) mbar_arrive(empty + s * 8); }
};

template <int C>
__device__ __forceinline__ void ffn_phase1_chunk(float (&cur)[32], float (&prev)[32], uint32_t (&h1)[144], const FfnPipe& pp, uint64_t dx, uint32_t fullX) {
    float tmp[2][8];
    const uint64_t dw = cdesc(F_OFF_ST, 8192, 1024, 1) + blockIdx.y * (C + 1);
    dx += blockIdx.y * C;
#pragma unroll
    for (int j = 0; j < 6; j++) {
        if (C == 0) { mbar_wait(fullX + ((6 * j) >> 2) * 8, 0); mbar_wait(fullX + ((6 * j + 5) >> 2) * 8, 0); }
        pp.acquire(j, C & 1);
        if (j == 0) pin(cur);
        wg_fence();
#pragma unroll
        for (int i = 0; i < 6; i++) {
            const int ks = 6 * j + i;
            wgmma_ss_n64<1>(cur, dx + ((ks >> 2) * 1024 + (ks & 3) * 2), dw + ((j * F_STAGE + i * 2048) >> 4), ks != 0);
        }
        wg_commit();
        if (C > 0 || j > 0) { wg_wait<1>(); pp.release((j + 5) % 6); }
        if (C > 0) {
            pin(prev);
            if (j >= 1) { pin(tmp[0]); if (j >= 2) pin(tmp[1]); }
            if (j >= 2) silu_s3<(C > 0 ? C - 1 : 0)>(prev, tmp[j & 1], h1, j - 2);
            if (j >= 1 && j <= 4) { silu_s2(tmp[(j - 1) & 1], read_tick()); pin(tmp[(j - 1) & 1]); }
            if (j <= 3) { silu_s1(prev, tmp[j & 1], j); pin(tmp[j & 1]); }
            if (j >= 2) { asm volatile("" : "+r"(h1[(C - 1) * 16 + 4 * (j - 2)]), "+r"(h1[(C - 1) * 16 + 4 * (j - 2) + 1]), "+r"(h1[(C - 1) * 16 + 4 * (j - 2) + 2]), "+r"(h1[(C - 1) * 16 + 4 * (j - 2) + 3]) :: "memory"); }
        }
    }
}

__device__ __forceinline__ void ffn_store_chunk(const float (&acc)[32], const CUtensorMap* tmOut, uint32_t stg, int col, int row, int w, int lane, int wgid) {
    uint32_t pk[16];
#pragma unroll
    for (int i = 0; i < 16; i++) pk[i] = pack_bf16(acc[2 * i], acc[2 * i + 1]);
    stage_tile<8>(pk, stg, w, lane);
    proxy_fence();
    named_sync(2 + wgid, 128);
    if (w == 0 && elect_one()) {
        tma_red_2d(tmOut, col, row, stg);
        bulk_commit();
    }
}

__device__ __forceinline__ void ffn_phase2_chunk(float (&cur)[32], float (&prev)[32], uint32_t (&h1)[144], const FfnPipe& pp, uint32_t ph, bool store_prev, const CUtensorMap* tmOut, uint32_t stg_prev, int col_prev, int row, int w, int lane, int wgid) {
    const uint64_t dw = cdesc(F_OFF_ST, 8192, 1024, 1) + blockIdx.y * col_prev;
#pragma unroll
    for (int j = 0; j < 6; j++) {
        pp.acquire(j, ph);
        if (j == 0) pin(cur);
        wg_fence();
#pragma unroll
        for (int i = 0; i < 6; i++) {
            const int f = (6 * j + i) * 4;
            wgmma_rs_n64<1>(cur, h1[f], h1[f + 1], h1[f + 2], h1[f + 3], dw + ((j * F_STAGE + i * 2048) >> 4), (j | i) != 0);
        }
        wg_commit();
        if (j > 0 || store_prev) { wg_wait<1>(); pp.release((j + 5) % 6); }
        if (j == 0 && store_prev) { pin(prev); ffn_store_chunk(prev, tmOut, stg_prev, col_prev, row, w, lane, wgid); }
    }
}

__global__ void __launch_bounds__(F_THREADS, 1)
k_ffn(const __grid_constant__ CUtensorMap tmH, const __grid_constant__ CUtensorMap tmW1, const __grid_constant__ CUtensorMap tmW2, const __grid_constant__ CUtensorMap tmOut) {
    extern __shared__ __align__(1024) uint8_t smem[];
    const uint32_t sX = smem_u32(smem), sSt = sX + F_OFF_ST, bars = sX + F_OFF_BAR;
    const uint32_t full = bars, empty = bars + 64, fullX = bars + 128;
    const int tid = threadIdx.x, warp = __shfl_sync(~0u, tid >> 5, 0), lane = tid & 31;
    const int m = blockIdx.x & 15, fs = blockIdx.x >> 4;
    if (tid == 0) TS(3, 0);
    check_smem_base(sX);
    if (tid == 0) {
        for (int i = 0; i < F_NST; i++) { mbar_init(full + i * 8, 1); mbar_init(empty + i * 8, 8); }
        for (int i = 0; i < 9; i++) mbar_init(fullX + i * 8, 1);
        bar_init_fence();
    }
    __syncthreads();
    if (warp < 4) {
        asm volatile("setmaxnreg.dec.sync.aligned.u32 24;");
        if (warp == 0 && elect_one()) {
            int s = 0; uint32_t ph = 1;
            int c = 0, j = 0;
#pragma unroll 1
            for (int i = 0; i < 108; i++) {
                if (i == F_NST) {
                    pdl_wait();
                    for (int kb = 0; kb < 9; kb++) {
                        mbar_expect(fullX + kb * 8, 16384);
                        tma_2d(sX + kb * 16384, &tmH, kb * 64, m * 128, fullX + kb * 8);
                    }
                }
                if (i == 54) c = fs;
                mbar_wait(empty + s * 8, ph);
                mbar_expect(full + s * 8, F_STAGE);
                if (i < 54) tma_2d(sSt + s * F_STAGE, &tmW1, fs * 576 + c * 64, j * 96, full + s * 8);
                else tma_2d(sSt + s * F_STAGE, &tmW2, c * 64, fs * 576 + j * 96, full + s * 8);
                if (++j == 6) { j = 0; if (++c == 9) c = 0; }
                if (++s == F_NST) { s = 0; ph ^= 1; }
            }
        }
    } else {
        asm volatile("setmaxnreg.inc.sync.aligned.u32 240;");
        const int wgid = (warp >> 2) - 1, w = warp & 3;
        pdl_wait();
        if (tid == 128) TS(3, 1);
        FfnPipe pp{full, empty, lane};
        const uint64_t xlo = cdesc(0, 16, 1024, 1) + wgid * 512;
        uint32_t h1[144];
        float acc0[32], acc1[32];
        ffn_phase1_chunk<0>(acc0, acc1, h1, pp, xlo, fullX);
        if (tid == 128) TS(3, 2);
        ffn_phase1_chunk<1>(acc1, acc0, h1, pp, xlo, fullX);
        ffn_phase1_chunk<2>(acc0, acc1, h1, pp, xlo, fullX);
        ffn_phase1_chunk<3>(acc1, acc0, h1, pp, xlo, fullX);
        ffn_phase1_chunk<4>(acc0, acc1, h1, pp, xlo, fullX);
        ffn_phase1_chunk<5>(acc1, acc0, h1, pp, xlo, fullX);
        ffn_phase1_chunk<6>(acc0, acc1, h1, pp, xlo, fullX);
        ffn_phase1_chunk<7>(acc1, acc0, h1, pp, xlo, fullX);
        ffn_phase1_chunk<8>(acc0, acc1, h1, pp, xlo, fullX);
        wg_wait<0>();
        pp.release(5);
        pin(acc0);
        {
            float tmp[4][8];
#pragma unroll
            for (int p = 0; p < 4; p++) silu_s1(acc0, tmp[p], p);
#pragma unroll
            for (int p = 0; p < 4; p++) silu_s2(tmp[p], 0);
#pragma unroll
            for (int p = 0; p < 4; p++) silu_s3<8>(acc0, tmp[p], h1, p);
        }
        pin(h1);
        if (tid == 128) TS(3, 3);
        const int row = m * 128 + wgid * 64;
        const uint32_t stg = sX + wgid * 8192;
        int c = fs, cprev = 0;
#pragma unroll 1
        for (int j = 0; j < 8; j += 2) {
            ffn_phase2_chunk(acc1, acc0, h1, pp, 1, j > 0, &tmOut, stg + (j - 1) * 16384, cprev * 64, row, w, lane, wgid);
            cprev = c; if (++c == 9) c = 0;
            ffn_phase2_chunk(acc0, acc1, h1, pp, 0, true, &tmOut, stg + j * 16384, cprev * 64, row, w, lane, wgid);
            cprev = c; if (++c == 9) c = 0;
        }
        ffn_phase2_chunk(acc1, acc0, h1, pp, 1, true, &tmOut, stg + 7 * 16384, cprev * 64, row, w, lane, wgid);
        wg_wait<0>();
        pin(acc1);
        ffn_store_chunk(acc1, &tmOut, stg + 8 * 16384, c * 64, row, w, lane, wgid);
        if (tid == 128) TS(3, 4);
        if (w == 0) bulk_wait_all();
        if (tid == 128) TS(3, 5);
    }
}

typedef CUresult (*EncodeFn)(CUtensorMap*, CUtensorMapDataType, cuuint32_t, void*, const cuuint64_t*, const cuuint64_t*, const cuuint32_t*, const cuuint32_t*,
                             CUtensorMapInterleave, CUtensorMapSwizzle, CUtensorMapL2promotion, CUtensorMapFloatOOBfill);

CUtensorMap make_map(EncodeFn enc, const void* base, int rows, int cols, int box_rows) {
    CUtensorMap tm;
    cuuint64_t dims[2] = {(cuuint64_t)cols, (cuuint64_t)rows};
    cuuint64_t strides[1] = {(cuuint64_t)cols * 2};
    cuuint32_t box[2] = {64, (cuuint32_t)box_rows};
    cuuint32_t es[2] = {1, 1};
    enc(&tm, CU_TENSOR_MAP_DATA_TYPE_BFLOAT16, 2, const_cast<void*>(base), dims, strides, box, es, CU_TENSOR_MAP_INTERLEAVE_NONE,
        CU_TENSOR_MAP_SWIZZLE_128B, CU_TENSOR_MAP_L2_PROMOTION_L2_256B, CU_TENSOR_MAP_FLOAT_OOB_FILL_NONE);
    return tm;
}

template <typename... KArgs, typename... Args>
void launch(void (*kern)(KArgs...), int grid, int block, int smem, bool pdl, Args... args) {
    cudaLaunchConfig_t cfg = {};
    cfg.gridDim = dim3(grid); cfg.blockDim = dim3(block); cfg.dynamicSmemBytes = smem; cfg.stream = cudaStreamPerThread;
    cudaLaunchAttribute at[1];
    at[0].id = cudaLaunchAttributeProgrammaticStreamSerialization;
    at[0].val.programmaticStreamSerializationAllowed = 1;
    cfg.attrs = at; cfg.numAttrs = pdl ? 1 : 0;
    cudaLaunchKernelEx(&cfg, kern, KArgs(args)...);
}

}

#define USE_PDL 1

extern "C" void kernel_launch(void* const* d_in, const int* in_sizes, int n_in, void* d_out, int out_size) {
    const __nv_bfloat16* x = (const __nv_bfloat16*)d_in[0];
    const __nv_bfloat16* wq = (const __nv_bfloat16*)d_in[1];
    const __nv_bfloat16* wk = (const __nv_bfloat16*)d_in[2];
    const __nv_bfloat16* wv = (const __nv_bfloat16*)d_in[3];
    const __nv_bfloat16* wo = (const __nv_bfloat16*)d_in[4];
    const __nv_bfloat16* w1 = (const __nv_bfloat16*)d_in[6];
    const __nv_bfloat16* w2 = (const __nv_bfloat16*)d_in[7];
    __nv_bfloat16* out = (__nv_bfloat16*)d_out;

    static EncodeFn enc = nullptr;
    static void *p_o = nullptr, *p_h = nullptr, *p_q = nullptr;
    if (!enc) {
        cudaDriverEntryPointQueryResult qr;
        cudaGetDriverEntryPoint("cuTensorMapEncodeTiled", (void**)&enc, cudaEnableDefault, &qr);
        cudaGetSymbolAddress(&p_o, g_o);
        cudaGetSymbolAddress(&p_h, g_x2);
        cudaGetSymbolAddress(&p_q, g_q);
        cudaFuncSetAttribute(k_qkv, cudaFuncAttributeMaxDynamicSharedMemorySize, P_SMEM);
        cudaFuncSetAttribute(k_attn, cudaFuncAttributeMaxDynamicSharedMemorySize, A_SMEM);
        cudaFuncSetAttribute(k_oproj, cudaFuncAttributeMaxDynamicSharedMemorySize, P_SMEM);
        cudaFuncSetAttribute(k_ffn, cudaFuncAttributeMaxDynamicSharedMemorySize, F_SMEM);
    }
    const CUtensorMap tmWq = make_map(enc, wq, DM, DM, 64);
    const CUtensorMap tmWo = make_map(enc, wo, DM, DM, 64);
    const CUtensorMap tmO = make_map(enc, p_o, SEQ, DM, 64);
    const CUtensorMap tmH = make_map(enc, p_h, SEQ, DM, 128);
    const CUtensorMap tmH64 = make_map(enc, p_h, SEQ, DM, 64);
    const CUtensorMap tmQ = make_map(enc, p_q, SEQ, DM, 64);
    const CUtensorMap tmW1 = make_map(enc, w1, DM, FF, 96);
    const CUtensorMap tmW2 = make_map(enc, w2, FF, DM, 96);
    const CUtensorMap tmOut = make_map(enc, out, SEQ, DM, 64);

    launch(k_qkv, 128, P_THREADS, P_SMEM, false, tmWq, tmQ, x, wk, wv);
    launch(k_attn, 132, A_THREADS, A_SMEM, USE_PDL, w1, w2, wo);
    launch(k_oproj, 96, P_THREADS, P_SMEM, USE_PDL, tmO, tmWo, tmH64, tmOut, x);
    launch(k_ffn, 128, F_THREADS, F_SMEM, USE_PDL, tmH, tmW1, tmW2, tmOut);
}
```

```cpp
#include <cuda_runtime.h>
#include <cuda_bf16.h>
#include <cuda.h>
#include <stdint.h>

namespace {

constexpr int SEQ = 2048, DM = 576, FF = 4608;
constexpr int KV_BYTES = SEQ * 48;
constexpr float LN_EPS = 1e-5f;
constexpr float LOG2E = 1.4426950408889634f;
constexpr float Q_SCALE = 0.23570226039551584f * LOG2E;

constexpr uint32_t POLY_MASK = 0xB5B5u;
constexpr float FAST_BOUND = 60.0f;

__device__ __align__(1024) __nv_bfloat16 g_q[SEQ * DM];
__device__ __align__(1024) uint4 g_kc[KV_BYTES / 16];
__device__ __align__(1024) uint4 g_vc[KV_BYTES / 16];
__device__ float g_kmax[32];
__device__ __align__(1024) __nv_bfloat16 g_o[SEQ * DM];
__device__ __align__(1024) __nv_bfloat16 g_x2[SEQ * DM];

#define TS(k, i)

__device__ __forceinline__ uint32_t smem_u32(const void* p) { return (uint32_t)__cvta_generic_to_shared(p); }
__device__ __forceinline__ void wg_fence() { asm volatile("wgmma.fence.sync.aligned;" ::: "memory"); }
__device__ __forceinline__ void wg_commit() { asm volatile("wgmma.commit_group.sync.aligned;" ::: "memory"); }
template <int N> __device__ __forceinline__ void wg_wait() { asm volatile("wgmma.wait_group.sync.aligned %0;" ::"n"(N) : "memory"); }
template <int N> __device__ __forceinline__ void pin(float (&r)[N]) {
#pragma unroll
    for (int i = 0; i < N; i++) asm volatile("" : "+f"(r[i])::"memory");
}
template <int N> __device__ __forceinline__ void pin(uint32_t (&r)[N]) {
#pragma unroll
    for (int i = 0; i < N; i++) asm volatile("" : "+r"(r[i])::"memory");
}
__device__ __forceinline__ constexpr uint32_t desc_hi(uint32_t sbo, uint32_t swz) { return (sbo >> 4) | (swz << 30); }
__device__ __forceinline__ uint32_t desc_lo(uint32_t addr, uint32_t lbo) { return ((addr & 0x3FFFF) >> 4) | ((lbo >> 4) << 16); }
__device__ __forceinline__ uint64_t desc64(uint32_t lo, uint32_t hi) { return ((uint64_t)hi << 32) | lo; }
constexpr uint32_t SMEM0 = 0x400;
__host__ __device__ constexpr uint64_t cdesc(uint32_t off, uint32_t lbo, uint32_t sbo, uint32_t swz) {
    return (uint64_t)(((SMEM0 + off) & 0x3FFFF) >> 4) | ((uint64_t)(lbo >> 4) << 16) | ((uint64_t)(sbo >> 4) << 32) | ((uint64_t)swz << 62);
}
__device__ __forceinline__ void check_smem_base(uint32_t base) { if ((base & 0x3FFFF) != SMEM0) __trap(); }

__device__ __forceinline__ void mbar_init(uint32_t bar, int cnt) { asm volatile("mbarrier.init.shared::cta.b64 [%0], %1;" ::"r"(bar), "r"(cnt) : "memory"); }
__device__ __forceinline__ void mbar_expect(uint32_t bar, int bytes) { asm volatile("mbarrier.arrive.expect_tx.shared::cta.b64 _, [%0], %1;" ::"r"(bar), "r"(bytes) : "memory"); }
__device__ __forceinline__ void mbar_arrive(uint32_t bar) { asm volatile("mbarrier.arrive.shared::cta.b64 _, [%0];" ::"r"(bar) : "memory"); }
__device__ __forceinline__ void mbar_wait(uint32_t bar, uint32_t parity) {
    asm volatile(
        "{\n.reg .pred p;\n.reg .u32 n;\nmov.u32 n, 0;\n"
        "LAB_WAIT:\n"
        "mbarrier.try_wait.parity.shared::cta.b64 p, [%0], %1;\n"
        "@p bra DONE;\n"
        "add.u32 n, n, 1;\n"
        "setp.lt.u32 p, n, 4000000;\n"
        "@p bra LAB_WAIT;\n"
        "trap;\n"
        "DONE:\n}\n" ::"r"(bar), "r"(parity) : "memory");
}
__device__ __forceinline__ void bar_init_fence() {
    asm volatile("fence.mbarrier_init.release.cluster;" ::: "memory");
    asm volatile("fence.proxy.async.shared::cta;" ::: "memory");
}
__device__ __forceinline__ void proxy_fence() { asm volatile("fence.proxy.async.shared::cta;" ::: "memory"); }
__device__ __forceinline__ void named_sync(int id, int n) { asm volatile("bar.sync %0, %1;" ::"r"(id), "r"(n) : "memory"); }
__device__ __forceinline__ void bulk_g2s(uint32_t dst, const void* src, int bytes, uint32_t bar) {
    asm volatile("cp.async.bulk.shared::cluster.global.mbarrier::complete_tx::bytes [%0], [%1], %2, [%3];" ::"r"(dst), "l"(src), "r"(bytes), "r"(bar) : "memory");
}
__device__ __forceinline__ void tma_2d(uint32_t dst, const CUtensorMap* tm, int c0, int c1, uint32_t bar) {
    asm volatile("cp.async.bulk.tensor.2d.shared::cluster.global.mbarrier::complete_tx::bytes [%0], [%1, {%3, %4}], [%2];" ::"r"(dst), "l"(tm), "r"(bar), "r"(c0), "r"(c1) : "memory");
}
__device__ __forceinline__ void tma_red_2d(const CUtensorMap* tm, int c0, int c1, uint32_t src) {
    asm volatile("cp.reduce.async.bulk.tensor.2d.global.shared::cta.add.tile.bulk_group [%0, {%2, %3}], [%1];" ::"l"(tm), "r"(src), "r"(c0), "r"(c1) : "memory");
}
__device__ __forceinline__ void tma_st_2d(const CUtensorMap* tm, int c0, int c1, uint32_t src) {
    asm volatile("cp.async.bulk.tensor.2d.global.shared::cta.tile.bulk_group [%0, {%2, %3}], [%1];" ::"l"(tm), "r"(src), "r"(c0), "r"(c1) : "memory");
}
__device__ __forceinline__ void bulk_commit() { asm volatile("cp.async.bulk.commit_group;" ::: "memory"); }
__device__ __forceinline__ void bulk_wait_all() { asm volatile("cp.async.bulk.wait_group 0;" ::: "memory"); }
__device__ __forceinline__ bool elect_one() {
    uint32_t p;
    asm volatile("{\n.reg .pred P;\nelect.sync _|P, 0xffffffff;\nselp.b32 %0, 1, 0, P;\n}\n" : "=r"(p));
    return p != 0;
}
__device__ __forceinline__ void prefetch_l2(const void* p, int bytes) { asm volatile("cp.async.bulk.prefetch.L2.global [%0], %1;" ::"l"(p), "r"(bytes) : "memory"); }
__device__ __forceinline__ void pdl_launch() { asm volatile("griddepcontrol.launch_dependents;" ::: "memory"); }
__device__ __forceinline__ void pdl_wait() { asm volatile("griddepcontrol.wait;" ::: "memory"); }
__device__ __forceinline__ float ex2(float x) { float y; asm("ex2.approx.ftz.f32 %0, %1;" : "=f"(y) : "f"(x)); return y; }
__device__ __forceinline__ float rcp(float x) { float y; asm("rcp.approx.ftz.f32 %0, %1;" : "=f"(y) : "f"(x)); return y; }
__device__ __forceinline__ uint32_t pack_bf16(float lo, float hi) { uint32_t r; asm("cvt.rn.bf16x2.f32 %0, %1, %2;" : "=r"(r) : "f"(hi), "f"(lo)); return r; }
__device__ __forceinline__ float bf_lo(uint32_t v) { return __uint_as_float(v << 16); }
__device__ __forceinline__ float bf_hi(uint32_t v) { return __uint_as_float(v & 0xFFFF0000u); }
__device__ __forceinline__ uint32_t hfma2(uint32_t a, uint32_t b, uint32_t c) { uint32_t r; asm("fma.rn.f16x2 %0, %1, %2, %3;" : "=r"(r) : "r"(a), "r"(b), "r"(c)); return r; }
__device__ __forceinline__ void stmatrix_x4(uint32_t addr, uint32_t r0, uint32_t r1, uint32_t r2, uint32_t r3) {
    asm volatile("stmatrix.sync.aligned.m8n8.x4.shared.b16 [%0], {%1, %2, %3, %4};" ::"r"(addr), "r"(r0), "r"(r1), "r"(r2), "r"(r3) : "memory");
}

template <int TB> __device__ __forceinline__ void wgmma_ss_n24(float (&d)[12], uint64_t da, uint64_t db, int sc) {
    asm volatile("{\n.reg .pred p;\nsetp.ne.b32 p, %14, 0;\n"
        "wgmma.mma_async.sync.aligned.m64n24k16.f32.bf16.bf16 {%0, %1, %2, %3, %4, %5, %6, %7, %8, %9, %10, %11}, %12, %13, p, 1, 1, 0, %15;\n}\n"
        : "+f"(d[0]), "+f"(d[1]), "+f"(d[2]), "+f"(d[3]), "+f"(d[4]), "+f"(d[5]), "+f"(d[6]), "+f"(d[7]), "+f"(d[8]), "+f"(d[9]), "+f"(d[10]), "+f"(d[11])
        : "l"(da), "l"(db), "r"(sc), "n"(TB));
}
template <int TB> __device__ __forceinline__ void wgmma_ss_n64(float (&d)[32], uint64_t da, uint64_t db, int sc) {
    asm volatile("{\n.reg .pred p;\nsetp.ne.b32 p, %34, 0;\n"
        "wgmma.mma_async.sync.aligned.m64n64k16.f32.bf16.bf16 {%0, %1, %2, %3, %4, %5, %6, %7, %8, %9, %10, %11, %12, %13, %14, %15, %16, %17, %18, %19, %20, %21, %22, %23, %24, %25, %26, %27, %28, %29, %30, %31}, %32, %33, p, 1, 1, 0, %35;\n}\n"
        : "+f"(d[0]), "+f"(d[1]), "+f"(d[2]), "+f"(d[3]), "+f"(d[4]), "+f"(d[5]), "+f"(d[6]), "+f"(d[7]), "+f"(d[8]), "+f"(d[9]), "+f"(d[10]), "+f"(d[11]), "+f"(d[12]), "+f"(d[13]), "+f"(d[14]), "+f"(d[15]), "+f"(d[16]), "+f"(d[17]), "+f"(d[18]), "+f"(d[19]), "+f"(d[20]), "+f"(d[21]), "+f"(d[22]), "+f"(d[23]), "+f"(d[24]), "+f"(d[25]), "+f"(d[26]), "+f"(d[27]), "+f"(d[28]), "+f"(d[29]), "+f"(d[30]), "+f"(d[31])
        : "l"(da), "l"(db), "r"(sc), "n"(TB));
}
template <int TB> __device__ __forceinline__ void wgmma_ss_n128(float (&d)[64], uint64_t da, uint64_t db, int sc) {
    asm volatile("{\n.reg .pred p;\nsetp.ne.b32 p, %66, 0;\n"
        "wgmma.mma_async.sync.aligned.m64n128k16.f32.bf16.bf16 {%0, %1, %2, %3, %4, %5, %6, %7, %8, %9, %10, %11, %12, %13, %14, %15, %16, %17, %18, %19, %20, %21, %22, %23, %24, %25, %26, %27, %28, %29, %30, %31, %32, %33, %34, %35, %36, %37, %38, %39, %40, %41, %42, %43, %44, %45, %46, %47, %48, %49, %50, %51, %52, %53, %54, %55, %56, %57, %58, %59, %60, %61, %62, %63}, %64, %65, p, 1, 1, 0, %67;\n}\n"
        : "+f"(d[0]), "+f"(d[1]), "+f"(d[2]), "+f"(d[3]), "+f"(d[4]), "+f"(d[5]), "+f"(d[6]), "+f"(d[7]), "+f"(d[8]), "+f"(d[9]), "+f"(d[10]), "+f"(d[11]), "+f"(d[12]), "+f"(d[13]), "+f"(d[14]), "+f"(d[15]), "+f"(d[16]), "+f"(d[17]), "+f"(d[18]), "+f"(d[19]), "+f"(d[20]), "+f"(d[21]), "+f"(d[22]), "+f"(d[23]), "+f"(d[24]), "+f"(d[25]), "+f"(d[26]), "+f"(d[27]), "+f"(d[28]), "+f"(d[29]), "+f"(d[30]), "+f"(d[31]), "+f"(d[32]), "+f"(d[33]), "+f"(d[34]), "+f"(d[35]), "+f"(d[36]), "+f"(d[37]), "+f"(d[38]), "+f"(d[39]), "+f"(d[40]), "+f"(d[41]), "+f"(d[42]), "+f"(d[43]), "+f"(d[44]), "+f"(d[45]), "+f"(d[46]), "+f"(d[47]), "+f"(d[48]), "+f"(d[49]), "+f"(d[50]), "+f"(d[51]), "+f"(d[52]), "+f"(d[53]), "+f"(d[54]), "+f"(d[55]), "+f"(d[56]), "+f"(d[57]), "+f"(d[58]), "+f"(d[59]), "+f"(d[60]), "+f"(d[61]), "+f"(d[62]), "+f"(d[63])
        : "l"(da), "l"(db), "r"(sc), "n"(TB));
}
template <int TB> __device__ __forceinline__ void wgmma_rs_n24(float (&d)[12], uint32_t a0, uint32_t a1, uint32_t a2, uint32_t a3, uint64_t db, int sc) {
    asm volatile("{\n.reg .pred p;\nsetp.ne.b32 p, %17, 0;\n"
        "wgmma.mma_async.sync.aligned.m64n24k16.f32.bf16.bf16 {%0, %1, %2, %3, %4, %5, %6, %7, %8, %9, %10, %11}, {%12, %13, %14, %15}, %16, p, 1, 1, %18;\n}\n"
        : "+f"(d[0]), "+f"(d[1]), "+f"(d[2]), "+f"(d[3]), "+f"(d[4]), "+f"(d[5]), "+f"(d[6]), "+f"(d[7]), "+f"(d[8]), "+f"(d[9]), "+f"(d[10]), "+f"(d[11])
        : "r"(a0), "r"(a1), "r"(a2), "r"(a3), "l"(db), "r"(sc), "n"(TB));
}
template <int TB> __device__ __forceinline__ void wgmma_rs_n64(float (&d)[32], uint32_t a0, uint32_t a1, uint32_t a2, uint32_t a3, uint64_t db, int sc) {
    asm volatile("{\n.reg .pred p;\nsetp.ne.b32 p, %37, 0;\n"
        "wgmma.mma_async.sync.aligned.m64n64k16.f32.bf16.bf16 {%0, %1, %2, %3, %4, %5, %6, %7, %8, %9, %10, %11, %12, %13, %14, %15, %16, %17, %18, %19, %20, %21, %22, %23, %24, %25, %26, %27, %28, %29, %30, %31}, {%32, %33, %34, %35}, %36, p, 1, 1, %38;\n}\n"
        : "+f"(d[0]), "+f"(d[1]), "+f"(d[2]), "+f"(d[3]), "+f"(d[4]), "+f"(d[5]), "+f"(d[6]), "+f"(d[7]), "+f"(d[8]), "+f"(d[9]), "+f"(d[10]), "+f"(d[11]), "+f"(d[12]), "+f"(d[13]), "+f"(d[14]), "+f"(d[15]), "+f"(d[16]), "+f"(d[17]), "+f"(d[18]), "+f"(d[19]), "+f"(d[20]), "+f"(d[21]), "+f"(d[22]), "+f"(d[23]), "+f"(d[24]), "+f"(d[25]), "+f"(d[26]), "+f"(d[27]), "+f"(d[28]), "+f"(d[29]), "+f"(d[30]), "+f"(d[31])
        : "r"(a0), "r"(a1), "r"(a2), "r"(a3), "l"(db), "r"(sc), "n"(TB));
}
template <int TB> __device__ __forceinline__ void wgmma_rs_n128(float (&d)[64], uint32_t a0, uint32_t a1, uint32_t a2, uint32_t a3, uint64_t db, int sc) {
    asm volatile("{\n.reg .pred p;\nsetp.ne.b32 p, %69, 0;\n"
        "wgmma.mma_async.sync.aligned.m64n128k16.f32.bf16.bf16 {%0, %1, %2, %3, %4, %5, %6, %7, %8, %9, %10, %11, %12, %13, %14, %15, %16, %17, %18, %19, %20, %21, %22, %23, %24, %25, %26, %27, %28, %29, %30, %31, %32, %33, %34, %35, %36, %37, %38, %39, %40, %41, %42, %43, %44, %45, %46, %47, %48, %49, %50, %51, %52, %53, %54, %55, %56, %57, %58, %59, %60, %61, %62, %63}, {%64, %65, %66, %67}, %68, p, 1, 1, %70;\n}\n"
        : "+f"(d[0]), "+f"(d[1]), "+f"(d[2]), "+f"(d[3]), "+f"(d[4]), "+f"(d[5]), "+f"(d[6]), "+f"(d[7]), "+f"(d[8]), "+f"(d[9]), "+f"(d[10]), "+f"(d[11]), "+f"(d[12]), "+f"(d[13]), "+f"(d[14]), "+f"(d[15]), "+f"(d[16]), "+f"(d[17]), "+f"(d[18]), "+f"(d[19]), "+f"(d[20]), "+f"(d[21]), "+f"(d[22]), "+f"(d[23]), "+f"(d[24]), "+f"(d[25]), "+f"(d[26]), "+f"(d[27]), "+f"(d[28]), "+f"(d[29]), "+f"(d[30]), "+f"(d[31]), "+f"(d[32]), "+f"(d[33]), "+f"(d[34]), "+f"(d[35]), "+f"(d[36]), "+f"(d[37]), "+f"(d[38]), "+f"(d[39]), "+f"(d[40]), "+f"(d[41]), "+f"(d[42]), "+f"(d[43]), "+f"(d[44]), "+f"(d[45]), "+f"(d[46]), "+f"(d[47]), "+f"(d[48]), "+f"(d[49]), "+f"(d[50]), "+f"(d[51]), "+f"(d[52]), "+f"(d[53]), "+f"(d[54]), "+f"(d[55]), "+f"(d[56]), "+f"(d[57]), "+f"(d[58]), "+f"(d[59]), "+f"(d[60]), "+f"(d[61]), "+f"(d[62]), "+f"(d[63])
        : "r"(a0), "r"(a1), "r"(a2), "r"(a3), "l"(db), "r"(sc), "n"(TB));
}

constexpr int P_THREADS = 288;
constexpr int P_NST = 6;
constexpr int P_A_BYTES = 9 * 8192;
constexpr int P_B_STAGE = 3 * 8192;
constexpr int P_SMEM = P_A_BYTES + P_NST * P_B_STAGE + 256 + 320;
constexpr uint32_t HI_SW128 = (1024u >> 4) | (1u << 30);

template <int NCOL, bool WAIT_A>
__device__ __forceinline__ void proj_mma(float (&acc)[NCOL / 2], uint32_t sA, uint32_t sB, uint32_t colofs, uint32_t fullB, uint32_t emptyB, uint32_t fullA, int lane) {
#pragma unroll 1
    for (int kb = 0; kb < 9; kb++) {
        const int s = kb >= P_NST ? kb - P_NST : kb;
        if (WAIT_A) mbar_wait(fullA + kb * 8, 0);
        mbar_wait(fullB + s * 8, kb >= P_NST ? 1 : 0);
        const uint32_t alo = desc_lo(sA + kb * 8192, 16), blo = desc_lo(sB + s * P_B_STAGE + colofs, 8192);
        wg_fence();
#pragma unroll
        for (int ks = 0; ks < 4; ks++) {
            const uint64_t da = desc64(alo + ks * 2, HI_SW128), db = desc64(blo + ks * 128, HI_SW128);
            if constexpr (NCOL == 128) wgmma_ss_n128<1>(acc, da, db, (kb | ks) != 0);
            else wgmma_ss_n64<1>(acc, da, db, (kb | ks) != 0);
        }
        wg_commit();
        if (kb + P_NST < 9 + 1) {
            wg_wait<1>();
            if (kb >= 1 && kb - 1 + P_NST < 9 && lane == 0) mbar_arrive(emptyB + (kb - 1) * 8);
        }
    }
    wg_wait<0>();
    pin(acc);
}

template <int NB>
__device__ __forceinline__ void stage_tile(const uint32_t (&pk)[NB * 2], uint32_t base, int w, int lane) {
    const int r = w * 16 + (lane & 7) + ((lane >> 3) & 1) * 8;
#pragma unroll
    for (int b = 0; b < NB; b += 2) {
        const uint32_t a = base + (b >> 3) * 8192 + r * 128 + ((((b & 7) + (lane >> 4)) ^ (r & 7)) << 4);
        stmatrix_x4(a, pk[2 * b], pk[2 * b + 1], pk[2 * b + 2], pk[2 * b + 3]);
    }
}

__device__ __forceinline__ uint32_t hsub2_bf16(uint32_t a, uint32_t b) { uint32_t r; asm("sub.rn.bf16x2 %0, %1, %2;" : "=r"(r) : "r"(a), "r"(b)); return r; }

constexpr int KV_B_BYTES = 6 * 9216;
constexpr int KV_RAW = DM * 18 * 2;

__global__ void __launch_bounds__(P_THREADS, 1)
k_qkv(const __grid_constant__ CUtensorMap tmX, const __grid_constant__ CUtensorMap tmWq, const __grid_constant__ CUtensorMap tmQ, const __nv_bfloat16* __restrict__ wk, const __nv_bfloat16* __restrict__ wv) {
    extern __shared__ __align__(1024) uint8_t smem[];
    const uint32_t sA = smem_u32(smem), sB = sA + P_A_BYTES, bars = sB + P_NST * P_B_STAGE;
    const uint32_t fullB = bars, emptyB = bars + 64, fullX = bars + 128, fullW = bars + 136;
    float* s_rstd = reinterpret_cast<float*>(smem + P_A_BYTES + P_NST * P_B_STAGE + 256);
    const int tid = threadIdx.x, warp = __shfl_sync(~0u, tid >> 5, 0), lane = tid & 31;
    const bool isQ = blockIdx.x < 96;
    const int m = isQ ? blockIdx.x / 3 : blockIdx.x - 96, cg = blockIdx.x % 3;
    if (tid == 0) TS(0, 0);
    if (warp == 8) {
        if (elect_one()) {
            for (int i = 0; i < P_NST; i++) { mbar_init(fullB + i * 8, 1); mbar_init(emptyB + i * 8, 8); }
            mbar_init(fullX, 1); mbar_init(fullW, 1);
            bar_init_fence();
            mbar_expect(fullX, P_A_BYTES);
            for (int kb = 0; kb < 9; kb++) tma_2d(sA + kb * 8192, &tmX, kb * 64, m * 64, fullX);
            if (isQ) {
                for (int kb = 0; kb < P_NST; kb++) {
                    mbar_expect(fullB + kb * 8, P_B_STAGE);
                    for (int a = 0; a < 3; a++) tma_2d(sB + kb * P_B_STAGE + a * 8192, &tmWq, cg * 192 + a * 64, kb * 64, fullB + kb * 8);
                }
            } else {
                mbar_expect(fullW, 2 * KV_RAW);
                bulk_g2s(sB + KV_B_BYTES, wk, KV_RAW, fullW);
                bulk_g2s(sB + KV_B_BYTES + KV_RAW, wv, KV_RAW, fullW);
            }
        }
        __syncwarp();
    }
    __syncthreads();
    pdl_launch();
    if (warp == 8) {
        if (isQ && elect_one()) {
            for (int kb = P_NST; kb < 9; kb++) {
                const int s = kb - P_NST;
                mbar_wait(emptyB + s * 8, 0);
                mbar_expect(fullB + s * 8, P_B_STAGE);
                for (int a = 0; a < 3; a++) tma_2d(sB + s * P_B_STAGE + a * 8192, &tmWq, cg * 192 + a * 64, kb * 64, fullB + s * 8);
            }
        }
        return;
    }
    if (!isQ) {
        mbar_wait(fullW, 0);
#pragma unroll 4
        for (int idx = tid; idx < 2 * DM * 9; idx += 256) {
            const int sel = idx >= DM * 9, j = idx - sel * DM * 9, k = j / 9, n = (j - k * 9) * 2;
            uint32_t wv32;
            asm volatile("ld.shared.b32 %0, [%1];" : "=r"(wv32) : "r"(sB + KV_B_BYTES + idx * 4));
            asm volatile("st.shared.b32 [%0], %1;" ::"r"(sB + (sel * 3 + (n >> 3)) * 9216 + (k >> 3) * 128 + (k & 7) * 16 + (n & 7) * 2), "r"(wv32) : "memory");
        }
    }
    {
        const int row = tid >> 2, q = tid & 3;
        mbar_wait(fullX, 0);
        if (tid == 0) TS(0, 6);
        uint4 v[18];
#pragma unroll
        for (int i = 0; i < 18; i++) {
            const int c = q + 4 * i;
            asm volatile("ld.shared.v4.b32 {%0, %1, %2, %3}, [%4];" : "=r"(v[i].x), "=r"(v[i].y), "=r"(v[i].z), "=r"(v[i].w) : "r"(sA + (c >> 3) * 8192 + row * 128 + (((c & 7) ^ (row & 7)) << 4)));
        }
        float sum = 0.f, sum2 = 0.f, sq = 0.f, sq2 = 0.f;
#pragma unroll
        for (int i = 0; i < 18; i++) {
            const uint32_t w[4] = {v[i].x, v[i].y, v[i].z, v[i].w};
#pragma unroll
            for (int j = 0; j < 4; j++) { const float a = bf_lo(w[j]), b = bf_hi(w[j]); sum += a; sum2 += b; sq = fmaf(a, a, sq); sq2 = fmaf(b, b, sq2); }
        }
        sum += sum2; sq += sq2;
        sum += __shfl_xor_sync(~0u, sum, 1); sum += __shfl_xor_sync(~0u, sum, 2);
        sq += __shfl_xor_sync(~0u, sq, 1); sq += __shfl_xor_sync(~0u, sq, 2);
        if (tid == 0) TS(0, 4);
        const float mean = sum * (1.0f / DM);
        if (q == 0) s_rstd[row] = rsqrtf(fmaxf(sq * (1.0f / DM) - mean * mean, 0.f) + LN_EPS);
        const uint32_t mhi = pack_bf16(mean, mean);
        const float rem = mean - bf_lo(mhi);
        const uint32_t mlo = pack_bf16(rem, rem);
#pragma unroll
        for (int i = 0; i < 18; i++) {
            const int c = q + 4 * i;
            const uint32_t o0 = hsub2_bf16(hsub2_bf16(v[i].x, mhi), mlo), o1 = hsub2_bf16(hsub2_bf16(v[i].y, mhi), mlo);
            const uint32_t o2 = hsub2_bf16(hsub2_bf16(v[i].z, mhi), mlo), o3 = hsub2_bf16(hsub2_bf16(v[i].w, mhi), mlo);
            asm volatile("st.shared.v4.b32 [%0], {%1, %2, %3, %4};" ::"r"(sA + (c >> 3) * 8192 + row * 128 + (((c & 7) ^ (row & 7)) << 4)), "r"(o0), "r"(o1), "r"(o2), "r"(o3) : "memory");
        }
    }
    proxy_fence();
    named_sync(1, 256);
    if (tid == 0) TS(0, 1);
    const int wg = warp >> 2, w = warp & 3, g = lane >> 2, t = lane & 3;
    const float rs0 = s_rstd[w * 16 + g], rs1 = s_rstd[w * 16 + g + 8];
    if (isQ) {
        const float c0 = rs0 * Q_SCALE, c1 = rs1 * Q_SCALE;
        if (wg == 0) {
            float acc[64];
            proj_mma<128, false>(acc, sA, sB, 0, fullB, emptyB, 0, lane);
            if (tid == 0) TS(0, 2);
            named_sync(1, 256);
            uint32_t pk[32];
#pragma unroll
            for (int i = 0; i < 16; i++) { pk[2 * i] = pack_bf16(acc[4 * i] * c0, acc[4 * i + 1] * c0); pk[2 * i + 1] = pack_bf16(acc[4 * i + 2] * c1, acc[4 * i + 3] * c1); }
            stage_tile<16>(pk, sA, w, lane);
        } else {
            float acc[32];
            proj_mma<64, false>(acc, sA, sB, 2 * 8192, fullB, emptyB, 0, lane);
            named_sync(1, 256);
            uint32_t pk[16];
#pragma unroll
            for (int i = 0; i < 8; i++) { pk[2 * i] = pack_bf16(acc[4 * i] * c0, acc[4 * i + 1] * c0); pk[2 * i + 1] = pack_bf16(acc[4 * i + 2] * c1, acc[4 * i + 3] * c1); }
            stage_tile<8>(pk, sA + 2 * 8192, w, lane);
        }
        proxy_fence();
        named_sync(1, 256);
        if (warp == 0 && elect_one()) {
            for (int a = 0; a < 3; a++) tma_st_2d(&tmQ, cg * 192 + a * 64, m * 64, sA + a * 8192);
            bulk_commit();
            bulk_wait_all();
        }
    } else {
        float acc[12];
        const uint32_t blo = desc_lo(sB + wg * 3 * 9216, 128);
#pragma unroll
        for (int i = 0; i < 12; i++) acc[i] = 0.f;
        pin(acc);
        wg_fence();
#pragma unroll 1
        for (int kb = 0; kb < 9; kb++) {
            const uint32_t alo = desc_lo(sA + kb * 8192, 16);
#pragma unroll
            for (int ks = 0; ks < 4; ks++)
                wgmma_ss_n24<1>(acc, desc64(alo + ks * 2, HI_SW128), desc64(blo + (kb * 4 + ks) * 16, desc_hi(9216, 0)), 1);
        }
        wg_commit();
        wg_wait<0>();
        pin(acc);
        uint32_t pk[6];
#pragma unroll
        for (int b = 0; b < 3; b++) { pk[2 * b] = pack_bf16(acc[4 * b] * rs0, acc[4 * b + 1] * rs0); pk[2 * b + 1] = pack_bf16(acc[4 * b + 2] * rs1, acc[4 * b + 3] * rs1); }
        float n0 = 0.f, n1 = 0.f, vm = 0.f;
#pragma unroll
        for (int b = 0; b < 3; b++) {
            if (b < 2 || t == 0) {
                const float a = bf_lo(pk[2 * b]), c = bf_hi(pk[2 * b]), d = bf_lo(pk[2 * b + 1]), e = bf_hi(pk[2 * b + 1]);
                n0 = fmaf(a, a, fmaf(c, c, n0)); n1 = fmaf(d, d, fmaf(e, e, n1));
            }
        }
        n0 += __shfl_xor_sync(~0u, n0, 1); n0 += __shfl_xor_sync(~0u, n0, 2);
        n1 += __shfl_xor_sync(~0u, n1, 1); n1 += __shfl_xor_sync(~0u, n1, 2);
        vm = fmaxf(n0, n1);
        if (!(n0 == n0) || !(n1 == n1)) vm = __int_as_float(0x7F800000);
#pragma unroll
        for (int o = 4; o < 32; o <<= 1) vm = fmaxf(vm, __shfl_xor_sync(~0u, vm, o));
        if (t != 0) {
            uint32_t lo, hi;
            if (wg == 0) {
                const int grp = m * 8 + w * 2;
                const uint32_t c = t == 1 ? 0x42FE3F80u   : (t == 2 ? 0x00003BC0u   : 0u);
                lo = ((POLY_MASK >> (grp & 15)) & 1) ? c : 0u;
                hi = ((POLY_MASK >> ((grp + 1) & 15)) & 1) ? c : 0u;
            } else {
                lo = hi = t == 1 ? 0x00003F80u : 0u;
            }
            pk[4] = lo; pk[5] = hi;
        }
        uint32_t* dst = reinterpret_cast<uint32_t*>(wg == 0 ? g_kc : g_vc) + (m * 8 + w * 2) * 96 + g * 4 + t;
#pragma unroll
        for (int b = 0; b < 3; b++) { dst[b * 32] = pk[2 * b]; dst[96 + b * 32] = pk[2 * b + 1]; }
        float* red = s_rstd + 64;
        if (lane == 0) red[warp] = (wg == 0) ? vm : (vm <= 1e24f ? 0.f : __int_as_float(0x7F800000));
        named_sync(1, 256);
        if (tid == 0) {
            float mx = red[0];
#pragma unroll
            for (int i = 1; i < 8; i++) mx = fmaxf(mx, red[i]);
            g_kmax[m] = mx;
        }
    }
    if (tid == 0) TS(0, 3);
}

constexpr int A_THREADS = 512;
constexpr int A_NPIECE = 8;
constexpr int A_SMEM = 2 * KV_BYTES + 128;

__device__ __forceinline__ uint32_t exp2_pair_fixed(float lo, float hi) {
    const uint32_t G = __byte_perm(__float_as_uint(lo), __float_as_uint(hi), 0x5410);
    const uint32_t Hh = G & 0x007F007Fu;
    const uint32_t tt = hfma2(Hh, 0xF96BF96Bu, 0x358C358Cu);
    return G - hfma2(tt, Hh, 0u);
}

__device__ __forceinline__ void attn_side_job(const __nv_bfloat16* __restrict__ w1, const __nv_bfloat16* __restrict__ w2, const __nv_bfloat16* __restrict__ wo) {
    const int e = blockIdx.x - 128, tid = threadIdx.x;
    if (tid < 32) {
        const char* p = reinterpret_cast<const char*>(wo) + e * (DM * DM * 2 / 4);
        for (int i = tid; i < DM * DM * 2 / 4 / 4608; i += 32) prefetch_l2(p + i * 4608, 4608);
        p = reinterpret_cast<const char*>(w1) + (size_t)e * (FF * DM * 2 / 4);
        for (int i = tid; i < FF * DM * 2 / 4 / 9216; i += 32) prefetch_l2(p + (size_t)i * 9216, 9216);
        p = reinterpret_cast<const char*>(w2) + (size_t)e * (FF * DM * 2 / 4);
        for (int i = tid; i < FF * DM * 2 / 4 / 9216; i += 32) prefetch_l2(p + (size_t)i * 9216, 9216);
    }
}

__global__ void __launch_bounds__(A_THREADS, 1)
k_attn(const __nv_bfloat16* __restrict__ w1, const __nv_bfloat16* __restrict__ w2, const __nv_bfloat16* __restrict__ wo) {
    extern __shared__ __align__(1024) uint8_t smem[];
    pdl_launch();
    if (blockIdx.x >= 128) { attn_side_job(w1, w2, wo); return; }
    const uint32_t sK = smem_u32(smem), sV = sK + KV_BYTES, bars = sV + KV_BYTES;
    const int tid = threadIdx.x;
    if (tid == 0) TS(1, 0);
    if (tid == 0) {
        for (int i = 0; i < A_NPIECE; i++) mbar_init(bars + i * 8, 1);
        bar_init_fence();
    }
    __syncthreads();
    pdl_wait();
    if (tid == 0) TS(1, 1);
    if (tid < 32 && elect_one()) {
        constexpr int PB = KV_BYTES / A_NPIECE;
        for (int i = 0; i < A_NPIECE; i++) {
            mbar_expect(bars + i * 8, 2 * PB);
            bulk_g2s(sK + i * PB, reinterpret_cast<const char*>(g_kc) + i * PB, PB, bars + i * 8);
            bulk_g2s(sV + i * PB, reinterpret_cast<const char*>(g_vc) + i * PB, PB, bars + i * 8);
        }
    }
    const int wg = __shfl_sync(~0u, tid >> 7, 0), w = (tid >> 5) & 3, lane = tid & 31, g = lane >> 2, t = lane & 3;
    const uint32_t* q32 = reinterpret_cast<const uint32_t*>(g_q);
    uint32_t* o32 = reinterpret_cast<uint32_t*>(g_o);
    int row = (blockIdx.x * 8 + wg) * 64 + w * 16 + g;
    uint32_t nq[6];
    nq[0] = q32[row * 9 + t]; nq[1] = q32[(row + 8) * 9 + t]; nq[2] = q32[row * 9 + 4 + t]; nq[3] = q32[(row + 8) * 9 + 4 + t];
    nq[4] = q32[row * 9 + 8]; nq[5] = q32[(row + 8) * 9 + 8];
    float kmax2 = g_kmax[lane];
#pragma unroll
    for (int o = 1; o < 32; o <<= 1) kmax2 = fmaxf(kmax2, __shfl_xor_sync(~0u, kmax2, o));
    constexpr uint32_t HI_K = desc_hi(384, 0), HI_V = desc_hi(128, 0);
    const uint32_t k0lo = desc_lo(sK, 128), k1lo = desc_lo(sK + 256, 0), vlo = desc_lo(sV, 384);
#pragma unroll 1
    for (int rep = 0; rep < 2; rep++, row += 256) {
        uint32_t qa[4] = {nq[0], nq[1], nq[2], nq[3]}, qb[4];
        float n0, n1;
        {
            const float a0 = bf_lo(qa[0]), a1 = bf_hi(qa[0]), a2 = bf_lo(qa[2]), a3 = bf_hi(qa[2]);
            const float b0 = bf_lo(qa[1]), b1 = bf_hi(qa[1]), b2 = bf_lo(qa[3]), b3 = bf_hi(qa[3]);
            n0 = a0 * a0 + a1 * a1 + a2 * a2 + a3 * a3; n1 = b0 * b0 + b1 * b1 + b2 * b2 + b3 * b3;
            if (t == 0) {
                const float c0 = bf_lo(nq[4]), c1 = bf_hi(nq[4]), d0 = bf_lo(nq[5]), d1 = bf_hi(nq[5]);
                n0 += c0 * c0 + c1 * c1; n1 += d0 * d0 + d1 * d1;
            }
            n0 += __shfl_xor_sync(~0u, n0, 1); n0 += __shfl_xor_sync(~0u, n0, 2);
            n1 += __shfl_xor_sync(~0u, n1, 1); n1 += __shfl_xor_sync(~0u, n1, 2);
        }
        const uint32_t x0 = nq[4], x1 = nq[5];
        if (rep == 0) {
            const int nr = row + 256;
            nq[0] = q32[nr * 9 + t]; nq[1] = q32[(nr + 8) * 9 + t]; nq[2] = q32[nr * 9 + 4 + t]; nq[3] = q32[(nr + 8) * 9 + 4 + t];
            nq[4] = q32[nr * 9 + 8]; nq[5] = q32[(nr + 8) * 9 + 8];
        }
        const bool unsafe = !(fmaxf(n0, n1) * kmax2 <= FAST_BOUND * FAST_BOUND);
        uint32_t any_unsafe;
        asm volatile("{\n.reg .pred p, q;\nsetp.ne.u32 p, %1, 0;\nbar.red.or.pred q, %2, 128, p;\nselp.u32 %0, 1, 0, q;\n}\n" : "=r"(any_unsafe) : "r"((uint32_t)unsafe), "r"(wg + 1) : "memory");
        if (tid == 0) TS(1, 2 + rep * 2);
        float o[12];
#pragma unroll
        for (int i = 0; i < 12; i++) o[i] = 0.f;
        if (!any_unsafe) {
            float s[64];
            const uint32_t cst = t == 1 ? 0x3F804780u   : (t == 2 ? 0x00003F80u   : 0u);
            qb[0] = t == 0 ? x0 : cst; qb[1] = t == 0 ? x1 : cst; qb[2] = 0; qb[3] = 0;
            pin(qa); pin(qb); pin(o);
#pragma unroll 1
            for (int j = 0; j < 16; j++) {
                if (rep == 0 && (j & 1) == 0) mbar_wait(bars + (j >> 1) * 8, 0);
                const uint32_t off = j * (16 * 384 >> 4);
                wg_fence();
                wgmma_rs_n128<0>(s, qa[0], qa[1], qa[2], qa[3], desc64(k0lo + off, HI_K), 0);
                wgmma_rs_n128<0>(s, qb[0], qb[1], qb[2], qb[3], desc64(k1lo + off, HI_K), 1);
                wg_commit();
                wg_wait<0>();
                pin(s);
                uint32_t p[32];
#pragma unroll
                for (int i = 0; i < 32; i++) {
                    if ((POLY_MASK >> (i >> 1)) & 1) p[i] = exp2_pair_fixed(s[2 * i], s[2 * i + 1]);
                    else p[i] = pack_bf16(ex2(s[2 * i]), ex2(s[2 * i + 1]));
                }
                pin(p);
                wg_fence();
#pragma unroll
                for (int k = 0; k < 8; k++) wgmma_rs_n24<1>(o, p[4 * k], p[4 * k + 1], p[4 * k + 2], p[4 * k + 3], desc64(vlo + off + k * 48, HI_V), 1);
                wg_commit();
                wg_wait<0>();
            }
        } else {
            float s[64];
            qb[0] = t == 0 ? x0 : 0u; qb[1] = t == 0 ? x1 : 0u; qb[2] = 0; qb[3] = 0;
            pin(qa); pin(qb); pin(o);
            float m0 = -INFINITY, m1 = -INFINITY;
#pragma unroll 1
            for (int j = 0; j < 16; j++) {
                if (rep == 0 && (j & 1) == 0) mbar_wait(bars + (j >> 1) * 8, 0);
                const uint32_t off = j * (16 * 384 >> 4);
                wg_fence();
                wgmma_rs_n128<0>(s, qa[0], qa[1], qa[2], qa[3], desc64(k0lo + off, HI_K), 0);
                wgmma_rs_n128<0>(s, qb[0], qb[1], qb[2], qb[3], desc64(k1lo + off, HI_K), 1);
                wg_commit();
                wg_wait<0>();
                pin(s);
                float x0m = m0, x1m = m1;
#pragma unroll
                for (int b = 0; b < 16; b++) { x0m = fmaxf(x0m, fmaxf(s[4 * b], s[4 * b + 1])); x1m = fmaxf(x1m, fmaxf(s[4 * b + 2], s[4 * b + 3])); }
                x0m = fmaxf(x0m, __shfl_xor_sync(~0u, x0m, 1)); x0m = fmaxf(x0m, __shfl_xor_sync(~0u, x0m, 2));
                x1m = fmaxf(x1m, __shfl_xor_sync(~0u, x1m, 1)); x1m = fmaxf(x1m, __shfl_xor_sync(~0u, x1m, 2));
                const float c0 = ex2(m0 - x0m), c1 = ex2(m1 - x1m);
                m0 = x0m; m1 = x1m;
#pragma unroll
                for (int b = 0; b < 3; b++) { o[4 * b] *= c0; o[4 * b + 1] *= c0; o[4 * b + 2] *= c1; o[4 * b + 3] *= c1; }
                uint32_t p[32];
#pragma unroll
                for (int b = 0; b < 16; b++) {
                    p[2 * b] = pack_bf16(ex2(s[4 * b] - m0), ex2(s[4 * b + 1] - m0));
                    p[2 * b + 1] = pack_bf16(ex2(s[4 * b + 2] - m1), ex2(s[4 * b + 3] - m1));
                }
                pin(p); pin(o);
                wg_fence();
#pragma unroll
                for (int k = 0; k < 8; k++) wgmma_rs_n24<1>(o, p[4 * k], p[4 * k + 1], p[4 * k + 2], p[4 * k + 3], desc64(vlo + off + k * 48, HI_V), 1);
                wg_commit();
                wg_wait<0>();
            }
        }
        pin(o);
        if (tid == 0) TS(1, 3 + rep * 2);
        const float l0 = __shfl_sync(~0u, o[8], (lane & ~3) | 1), l1 = __shfl_sync(~0u, o[10], (lane & ~3) | 1);
        const float i0 = 1.0f / l0, i1 = 1.0f / l1;
        o32[row * 9 + t] = pack_bf16(o[0] * i0, o[1] * i0);
        o32[(row + 8) * 9 + t] = pack_bf16(o[2] * i1, o[3] * i1);
        o32[row * 9 + 4 + t] = pack_bf16(o[4] * i0, o[5] * i0);
        o32[(row + 8) * 9 + 4 + t] = pack_bf16(o[6] * i1, o[7] * i1);
        if (t == 0) { o32[row * 9 + 8] = pack_bf16(o[8] * i0, o[9] * i0); o32[(row + 8) * 9 + 8] = pack_bf16(o[10] * i1, o[11] * i1); }
    }
    if (tid == 0) TS(1, 6);
}

template <int NB>
__device__ __forceinline__ void oproj_load_x(uint32_t (&xr)[NB * 2], const uint32_t* __restrict__ x32, int r0, int col0, int t) {
#pragma unroll
    for (int b = 0; b < NB; b++) {
        const int i0 = (r0 * DM + col0 + b * 8 + 2 * t) >> 1;
        xr[2 * b] = __ldg(x32 + i0); xr[2 * b + 1] = __ldg(x32 + i0 + 4 * DM);
    }
}
constexpr int P_OFF_STAT = 3 * 8192 + 3 * 8192;
template <int NB>
__device__ __forceinline__ void oproj_epilogue(const float (&acc)[NB * 4], uint32_t (&xr)[NB * 2], uint32_t sA, uint32_t tile_ofs, int part, int w, int lane) {
    float s0 = 0.f, q0 = 0.f, s1 = 0.f, q1 = 0.f;
#pragma unroll
    for (int b = 0; b < NB; b++) {
        const uint32_t xa = xr[2 * b], xb = xr[2 * b + 1];
        const uint32_t ha = pack_bf16(acc[4 * b] + bf_lo(xa), acc[4 * b + 1] + bf_hi(xa));
        const uint32_t hb = pack_bf16(acc[4 * b + 2] + bf_lo(xb), acc[4 * b + 3] + bf_hi(xb));
        xr[2 * b] = ha; xr[2 * b + 1] = hb;
        const float a = bf_lo(ha), c = bf_hi(ha), d = bf_lo(hb), e = bf_hi(hb);
        s0 += a + c; q0 = fmaf(a, a, fmaf(c, c, q0));
        s1 += d + e; q1 = fmaf(d, d, fmaf(e, e, q1));
    }
    s0 += __shfl_xor_sync(~0u, s0, 1); s0 += __shfl_xor_sync(~0u, s0, 2);
    q0 += __shfl_xor_sync(~0u, q0, 1); q0 += __shfl_xor_sync(~0u, q0, 2);
    s1 += __shfl_xor_sync(~0u, s1, 1); s1 += __shfl_xor_sync(~0u, s1, 2);
    q1 += __shfl_xor_sync(~0u, q1, 1); q1 += __shfl_xor_sync(~0u, q1, 2);
    const int r = w * 16 + (lane >> 2);
    const uint32_t sStat = sA + P_OFF_STAT;
    if ((lane & 3) < 3) {
        uint32_t dst;
        asm("mapa.shared::cluster.u32 %0, %1, %2;" : "=r"(dst) : "r"(sStat + (part * 64 + r) * 8), "r"(lane & 3));
        asm volatile("st.shared::cluster.v2.f32 [%0], {%1, %2};" ::"r"(dst), "f"(s0), "f"(q0) : "memory");
        asm volatile("st.shared::cluster.v2.f32 [%0], {%1, %2};" ::"r"(dst + 64), "f"(s1), "f"(q1) : "memory");
    }
    asm volatile("barrier.cluster.arrive.release.aligned;" ::: "memory");
    stage_tile<NB>(xr, sA + tile_ofs, w, lane);
    asm volatile("barrier.cluster.wait.acquire.aligned;" ::: "memory");
    s0 = q0 = s1 = q1 = 0.f;
#pragma unroll
    for (int p = 0; p < 6; p++) {
        float a, b, c, d;
        asm volatile("ld.shared.v2.f32 {%0, %1}, [%2];" : "=f"(a), "=f"(b) : "r"(sStat + (p * 64 + r) * 8));
        asm volatile("ld.shared.v2.f32 {%0, %1}, [%2];" : "=f"(c), "=f"(d) : "r"(sStat + (p * 64 + r + 8) * 8));
        s0 += a; q0 += b; s1 += c; q1 += d;
    }
    const float m0 = s0 * (1.0f / DM), m1 = s1 * (1.0f / DM);
    const float rs0 = rsqrtf(fmaxf(q0 * (1.0f / DM) - m0 * m0, 0.f) + LN_EPS), rs1 = rsqrtf(fmaxf(q1 * (1.0f / DM) - m1 * m1, 0.f) + LN_EPS);
    const float n0 = -m0 * rs0, n1 = -m1 * rs1;
#pragma unroll
    for (int b = 0; b < NB; b++) {
        xr[2 * b] = pack_bf16(fmaf(bf_lo(xr[2 * b]), rs0, n0), fmaf(bf_hi(xr[2 * b]), rs0, n0));
        xr[2 * b + 1] = pack_bf16(fmaf(bf_lo(xr[2 * b + 1]), rs1, n1), fmaf(bf_hi(xr[2 * b + 1]), rs1, n1));
    }
    stage_tile<NB>(xr, sA + 3 * 8192 + tile_ofs, w, lane);
}

__global__ void __cluster_dims__(3, 1, 1) __launch_bounds__(P_THREADS, 1)
k_oproj(const __grid_constant__ CUtensorMap tmO, const __grid_constant__ CUtensorMap tmWo, const __grid_constant__ CUtensorMap tmX2, const __grid_constant__ CUtensorMap tmOut, const __nv_bfloat16* __restrict__ x) {
    extern __shared__ __align__(1024) uint8_t smem[];
    const uint32_t sA = smem_u32(smem), sB = sA + P_A_BYTES, bars = sB + P_NST * P_B_STAGE;
    const uint32_t fullB = bars, emptyB = bars + 64, fullA = bars + 128;
    const int tid = threadIdx.x, warp = __shfl_sync(~0u, tid >> 5, 0), lane = tid & 31;
    const int m = blockIdx.x / 3, cg = blockIdx.x % 3;
    if (tid == 0) TS(2, 0);
    if (tid == 0) {
        for (int i = 0; i < P_NST; i++) { mbar_init(fullB + i * 8, 1); mbar_init(emptyB + i * 8, 8); }
        for (int i = 0; i < 9; i++) mbar_init(fullA + i * 8, 1);
        bar_init_fence();
    }
    __syncthreads();
    pdl_launch();
    if (warp == 8) {
        if (elect_one()) {
            for (int kb = 0; kb < P_NST; kb++) {
                mbar_expect(fullB + kb * 8, P_B_STAGE);
                for (int a = 0; a < 3; a++) tma_2d(sB + kb * P_B_STAGE + a * 8192, &tmWo, cg * 192 + a * 64, kb * 64, fullB + kb * 8);
            }
            pdl_wait();
            for (int kb = 0; kb < 9; kb++) {
                mbar_expect(fullA + kb * 8, 8192);
                tma_2d(sA + kb * 8192, &tmO, kb * 64, m * 64, fullA + kb * 8);
            }
            for (int kb = P_NST; kb < 9; kb++) {
                const int s = kb - P_NST;
                mbar_wait(emptyB + s * 8, 0);
                mbar_expect(fullB + s * 8, P_B_STAGE);
                for (int a = 0; a < 3; a++) tma_2d(sB + s * P_B_STAGE + a * 8192, &tmWo, cg * 192 + a * 64, kb * 64, fullB + s * 8);
            }
        }
        return;
    }
    const int wg = warp >> 2, w = warp & 3, g = lane >> 2, t = lane & 3;
    const int r0 = m * 64 + w * 16 + g;
    const uint32_t* x32 = reinterpret_cast<const uint32_t*>(x);
    if (wg == 0) {
        uint32_t xr[32];
        oproj_load_x<16>(xr, x32, r0, cg * 192, t);
        float acc[64];
        proj_mma<128, true>(acc, sA, sB, 0, fullB, emptyB, fullA, lane);
        if (tid == 0) TS(2, 2);
        named_sync(1, 256);
        oproj_epilogue<16>(acc, xr, sA, 0, cg * 2, w, lane);
    } else {
        uint32_t xr[16];
        oproj_load_x<8>(xr, x32, r0, cg * 192 + 128, t);
        float acc[32];
        proj_mma<64, true>(acc, sA, sB, 2 * 8192, fullB, emptyB, fullA, lane);
        named_sync(1, 256);
        oproj_epilogue<8>(acc, xr, sA, 2 * 8192, cg * 2 + 1, w, lane);
    }
    proxy_fence();
    named_sync(1, 256);
    if (warp == 0 && elect_one()) {
        for (int a = 0; a < 3; a++) {
            tma_st_2d(&tmX2, cg * 192 + a * 64, m * 64, sA + (3 + a) * 8192);
            tma_st_2d(&tmOut, cg * 192 + a * 64, m * 64, sA + a * 8192);
        }
        bulk_commit();
        bulk_wait_all();
        TS(2, 3);
    }
}

constexpr int F_THREADS = 384;
constexpr int F_NST = 6;
constexpr int F_STAGE = 96 * 128;
constexpr int F_X_BYTES = 9 * 16384;
constexpr int F_OFF_ST = F_X_BYTES;
constexpr int F_OFF_BAR = F_OFF_ST + F_NST * F_STAGE;
constexpr int F_SMEM = F_OFF_BAR + 256;

__device__ __forceinline__ void silu_s1(const float (&acc)[32], float (&tmp)[8], int piece) {
#pragma unroll
    for (int i = 0; i < 8; i++) tmp[i] = ex2(acc[8 * piece + i] * -LOG2E);
}
__device__ __forceinline__ float after_issue(float v, uint32_t tick) {
    uint32_t r;
    asm("lop3.b32 %0, %1, %1, %2, 0xF0;" : "=r"(r) : "r"(__float_as_uint(v)), "r"(tick));
    return __uint_as_float(r);
}
__device__ __forceinline__ uint32_t read_tick() { uint32_t c; asm volatile("mov.u32 %0, %%clock;" : "=r"(c)::"memory"); return c; }
__device__ __forceinline__ void silu_s2(float (&tmp)[8], uint32_t tick) {
    const float one = after_issue(1.0f, tick);
#pragma unroll
    for (int i = 0; i < 8; i++) tmp[i] = rcp(tmp[i] + one);
}
template <int C>
__device__ __forceinline__ void silu_s3(const float (&acc)[32], const float (&tmp)[8], uint32_t (&h1)[144], int piece) {
#pragma unroll
    for (int i = 0; i < 4; i++) h1[C * 16 + 4 * piece + i] = pack_bf16(acc[8 * piece + 2 * i] * tmp[2 * i], acc[8 * piece + 2 * i + 1] * tmp[2 * i + 1]);
}

struct FfnPipe {
    uint32_t full, empty;
    int lane;
    __device__ __forceinline__ void acquire(int s, uint32_t ph) const { mbar_wait(full + s * 8, ph); }
    __device__ __forceinline__ void release(int s) const { if (lane == 0) mbar_arrive(empty + s * 8); }
};

template <int C>
__device__ __forceinline__ void ffn_phase1_chunk(float (&cur)[32], float (&prev)[32], uint32_t (&h1)[144], const FfnPipe& pp, uint64_t dx, uint32_t fullX) {
    float tmp[2][8];
    const uint64_t dw = cdesc(F_OFF_ST, 8192, 1024, 1) + blockIdx.y * (C + 1);
    dx += blockIdx.y * C;
#pragma unroll
    for (int j = 0; j < 6; j++) {
        if (C == 0) { mbar_wait(fullX + ((6 * j) >> 2) * 8, 0); mbar_wait(fullX + ((6 * j + 5) >> 2) * 8, 0); }
        pp.acquire(j, C & 1);
        if (j == 0) pin(cur);
        wg_fence();
#pragma unroll
        for (int i = 0; i < 6; i++) {
            const int ks = 6 * j + i;
            wgmma_ss_n64<1>(cur, dx + ((ks >> 2) * 1024 + (ks & 3) * 2), dw + ((j * F_STAGE + i * 2048) >> 4), ks != 0);
        }
        wg_commit();
        if (C > 0 || j > 0) { wg_wait<1>(); pp.release((j + 5) % 6); }
        if (C > 0) {
            pin(prev);
            if (j >= 1) { pin(tmp[0]); if (j >= 2) pin(tmp[1]); }
            if (j >= 2) silu_s3<(C > 0 ? C - 1 : 0)>(prev, tmp[j & 1], h1, j - 2);
            if (j >= 1 && j <= 4) { silu_s2(tmp[(j - 1) & 1], read_tick()); pin(tmp[(j - 1) & 1]); }
            if (j <= 3) { silu_s1(prev, tmp[j & 1], j); pin(tmp[j & 1]); }
            if (j >= 2) { asm volatile("" : "+r"(h1[(C - 1) * 16 + 4 * (j - 2)]), "+r"(h1[(C - 1) * 16 + 4 * (j - 2) + 1]), "+r"(h1[(C - 1) * 16 + 4 * (j - 2) + 2]), "+r"(h1[(C - 1) * 16 + 4 * (j - 2) + 3]) :: "memory"); }
        }
    }
}

__device__ __forceinline__ void ffn_store_chunk(const float (&acc)[32], const CUtensorMap* tmOut, uint32_t stg, int col, int row, int w, int lane, int wgid) {
    uint32_t pk[16];
#pragma unroll
    for (int i = 0; i < 16; i++) pk[i] = pack_bf16(acc[2 * i], acc[2 * i + 1]);
    stage_tile<8>(pk, stg, w, lane);
    proxy_fence();
    named_sync(2 + wgid, 128);
    if (w == 0 && elect_one()) {
        tma_red_2d(tmOut, col, row, stg);
        bulk_commit();
    }
}

__device__ __forceinline__ void ffn_phase2_chunk(float (&cur)[32], float (&prev)[32], uint32_t (&h1)[144], const FfnPipe& pp, uint32_t ph, bool store_prev, const CUtensorMap* tmOut, uint32_t stg_prev, int col_prev, int row, int w, int lane, int wgid) {
    const uint64_t dw = cdesc(F_OFF_ST, 8192, 1024, 1) + blockIdx.y * col_prev;
#pragma unroll
    for (int j = 0; j < 6; j++) {
        pp.acquire(j, ph);
        if (j == 0) pin(cur);
        wg_fence();
#pragma unroll
        for (int i = 0; i < 6; i++) {
            const int f = (6 * j + i) * 4;
            wgmma_rs_n64<1>(cur, h1[f], h1[f + 1], h1[f + 2], h1[f + 3], dw + ((j * F_STAGE + i * 2048) >> 4), (j | i) != 0);
        }
        wg_commit();
        if (j > 0 || store_prev) { wg_wait<1>(); pp.release((j + 5) % 6); }
        if (j == 0 && store_prev) { pin(prev); ffn_store_chunk(prev, tmOut, stg_prev, col_prev, row, w, lane, wgid); }
    }
}

__global__ void __launch_bounds__(F_THREADS, 1)
k_ffn(const __grid_constant__ CUtensorMap tmH, const __grid_constant__ CUtensorMap tmW1, const __grid_constant__ CUtensorMap tmW2, const __grid_constant__ CUtensorMap tmOut) {
    extern __shared__ __align__(1024) uint8_t smem[];
    const uint32_t sX = smem_u32(smem), sSt = sX + F_OFF_ST, bars = sX + F_OFF_BAR;
    const uint32_t full = bars, empty = bars + 64, fullX = bars + 128;
    const int tid = threadIdx.x, warp = __shfl_sync(~0u, tid >> 5, 0), lane = tid & 31;
    const int m = blockIdx.x & 15, fs = blockIdx.x >> 4;
    if (tid == 0) TS(3, 0);
    check_smem_base(sX);
    if (tid == 0) {
        for (int i = 0; i < F_NST; i++) { mbar_init(full + i * 8, 1); mbar_init(empty + i * 8, 8); }
        for (int i = 0; i < 9; i++) mbar_init(fullX + i * 8, 1);
        bar_init_fence();
    }
    __syncthreads();
    if (warp < 4) {
        asm volatile("setmaxnreg.dec.sync.aligned.u32 24;");
        if (warp == 0 && elect_one()) {
            int s = 0; uint32_t ph = 1;
            int c = 0, j = 0;
#pragma unroll 1
            for (int i = 0; i < 108; i++) {
                if (i == F_NST) {
                    pdl_wait();
                    for (int kb = 0; kb < 9; kb++) {
                        mbar_expect(fullX + kb * 8, 16384);
                        tma_2d(sX + kb * 16384, &tmH, kb * 64, m * 128, fullX + kb * 8);
                    }
                }
                if (i == 54) c = fs;
                mbar_wait(empty + s * 8, ph);
                mbar_expect(full + s * 8, F_STAGE);
                if (i < 54) tma_2d(sSt + s * F_STAGE, &tmW1, fs * 576 + c * 64, j * 96, full + s * 8);
                else tma_2d(sSt + s * F_STAGE, &tmW2, c * 64, fs * 576 + j * 96, full + s * 8);
                if (++j == 6) { j = 0; if (++c == 9) c = 0; }
                if (++s == F_NST) { s = 0; ph ^= 1; }
            }
        }
    } else {
        asm volatile("setmaxnreg.inc.sync.aligned.u32 240;");
        const int wgid = (warp >> 2) - 1, w = warp & 3;
        pdl_wait();
        if (tid == 128) TS(3, 1);
        FfnPipe pp{full, empty, lane};
        const uint64_t xlo = cdesc(0, 16, 1024, 1) + wgid * 512;
        uint32_t h1[144];
        float acc0[32], acc1[32];
        ffn_phase1_chunk<0>(acc0, acc1, h1, pp, xlo, fullX);
        if (tid == 128) TS(3, 2);
        ffn_phase1_chunk<1>(acc1, acc0, h1, pp, xlo, fullX);
        ffn_phase1_chunk<2>(acc0, acc1, h1, pp, xlo, fullX);
        ffn_phase1_chunk<3>(acc1, acc0, h1, pp, xlo, fullX);
        ffn_phase1_chunk<4>(acc0, acc1, h1, pp, xlo, fullX);
        ffn_phase1_chunk<5>(acc1, acc0, h1, pp, xlo, fullX);
        ffn_phase1_chunk<6>(acc0, acc1, h1, pp, xlo, fullX);
        ffn_phase1_chunk<7>(acc1, acc0, h1, pp, xlo, fullX);
        ffn_phase1_chunk<8>(acc0, acc1, h1, pp, xlo, fullX);
        wg_wait<0>();
        pp.release(5);
        pin(acc0);
        {
            float tmp[4][8];
#pragma unroll
            for (int p = 0; p < 4; p++) silu_s1(acc0, tmp[p], p);
#pragma unroll
            for (int p = 0; p < 4; p++) silu_s2(tmp[p], 0);
#pragma unroll
            for (int p = 0; p < 4; p++) silu_s3<8>(acc0, tmp[p], h1, p);
        }
        pin(h1);
        if (tid == 128) TS(3, 3);
        const int row = m * 128 + wgid * 64;
        const uint32_t stg = sX + wgid * 8192;
        int c = fs, cprev = 0;
#pragma unroll 1
        for (int j = 0; j < 8; j += 2) {
            ffn_phase2_chunk(acc1, acc0, h1, pp, 1, j > 0, &tmOut, stg + (j - 1) * 16384, cprev * 64, row, w, lane, wgid);
            cprev = c; if (++c == 9) c = 0;
            ffn_phase2_chunk(acc0, acc1, h1, pp, 0, true, &tmOut, stg + j * 16384, cprev * 64, row, w, lane, wgid);
            cprev = c; if (++c == 9) c = 0;
        }
        ffn_phase2_chunk(acc1, acc0, h1, pp, 1, true, &tmOut, stg + 7 * 16384, cprev * 64, row, w, lane, wgid);
        wg_wait<0>();
        pin(acc1);
        ffn_store_chunk(acc1, &tmOut, stg + 8 * 16384, c * 64, row, w, lane, wgid);
        if (tid == 128) TS(3, 4);
        if (w == 0) bulk_wait_all();
        if (tid == 128) TS(3, 5);
    }
}

typedef CUresult (*EncodeFn)(CUtensorMap*, CUtensorMapDataType, cuuint32_t, void*, const cuuint64_t*, const cuuint64_t*, const cuuint32_t*, const cuuint32_t*,
                             CUtensorMapInterleave, CUtensorMapSwizzle, CUtensorMapL2promotion, CUtensorMapFloatOOBfill);

CUtensorMap make_map(EncodeFn enc, const void* base, int rows, int cols, int box_rows) {
    CUtensorMap tm;
    cuuint64_t dims[2] = {(cuuint64_t)cols, (cuuint64_t)rows};
    cuuint64_t strides[1] = {(cuuint64_t)cols * 2};
    cuuint32_t box[2] = {64, (cuuint32_t)box_rows};
    cuuint32_t es[2] = {1, 1};
    enc(&tm, CU_TENSOR_MAP_DATA_TYPE_BFLOAT16, 2, const_cast<void*>(base), dims, strides, box, es, CU_TENSOR_MAP_INTERLEAVE_NONE,
        CU_TENSOR_MAP_SWIZZLE_128B, CU_TENSOR_MAP_L2_PROMOTION_L2_256B, CU_TENSOR_MAP_FLOAT_OOB_FILL_NONE);
    return tm;
}

template <typename... KArgs, typename... Args>
void launch(void (*kern)(KArgs...), int grid, int block, int smem, bool pdl, Args... args) {
    cudaLaunchConfig_t cfg = {};
    cfg.gridDim = dim3(grid); cfg.blockDim = dim3(block); cfg.dynamicSmemBytes = smem; cfg.stream = cudaStreamPerThread;
    cudaLaunchAttribute at[1];
    at[0].id = cudaLaunchAttributeProgrammaticStreamSerialization;
    at[0].val.programmaticStreamSerializationAllowed = 1;
    cfg.attrs = at; cfg.numAttrs = pdl ? 1 : 0;
    cudaLaunchKernelEx(&cfg, kern, KArgs(args)...);
}

}

#define USE_PDL 1

extern "C" void kernel_launch(void* const* d_in, const int* in_sizes, int n_in, void* d_out, int out_size) {
    const __nv_bfloat16* x = (const __nv_bfloat16*)d_in[0];
    const __nv_bfloat16* wq = (const __nv_bfloat16*)d_in[1];
    const __nv_bfloat16* wk = (const __nv_bfloat16*)d_in[2];
    const __nv_bfloat16* wv = (const __nv_bfloat16*)d_in[3];
    const __nv_bfloat16* wo = (const __nv_bfloat16*)d_in[4];
    const __nv_bfloat16* w1 = (const __nv_bfloat16*)d_in[6];
    const __nv_bfloat16* w2 = (const __nv_bfloat16*)d_in[7];
    __nv_bfloat16* out = (__nv_bfloat16*)d_out;

    static EncodeFn enc = nullptr;
    static void *p_o = nullptr, *p_h = nullptr, *p_q = nullptr;
    if (!enc) {
        cudaDriverEntryPointQueryResult qr;
        cudaGetDriverEntryPoint("cuTensorMapEncodeTiled", (void**)&enc, cudaEnableDefault, &qr);
        cudaGetSymbolAddress(&p_o, g_o);
        cudaGetSymbolAddress(&p_h, g_x2);
        cudaGetSymbolAddress(&p_q, g_q);
        cudaFuncSetAttribute(k_qkv, cudaFuncAttributeMaxDynamicSharedMemorySize, P_SMEM);
        cudaFuncSetAttribute(k_attn, cudaFuncAttributeMaxDynamicSharedMemorySize, A_SMEM);
        cudaFuncSetAttribute(k_oproj, cudaFuncAttributeMaxDynamicSharedMemorySize, P_SMEM);
        cudaFuncSetAttribute(k_ffn, cudaFuncAttributeMaxDynamicSharedMemorySize, F_SMEM);
    }
    const CUtensorMap tmX = make_map(enc, x, SEQ, DM, 64);
    const CUtensorMap tmWq = make_map(enc, wq, DM, DM, 64);
    const CUtensorMap tmWo = make_map(enc, wo, DM, DM, 64);
    const CUtensorMap tmO = make_map(enc, p_o, SEQ, DM, 64);
    const CUtensorMap tmH = make_map(enc, p_h, SEQ, DM, 128);
    const CUtensorMap tmH64 = make_map(enc, p_h, SEQ, DM, 64);
    const CUtensorMap tmQ = make_map(enc, p_q, SEQ, DM, 64);
    const CUtensorMap tmW1 = make_map(enc, w1, DM, FF, 96);
    const CUtensorMap tmW2 = make_map(enc, w2, FF, DM, 96);
    const CUtensorMap tmOut = make_map(enc, out, SEQ, DM, 64);

    launch(k_qkv, 128, P_THREADS, P_SMEM, false, tmX, tmWq, tmQ, wk, wv);
    launch(k_attn, 132, A_THREADS, A_SMEM, USE_PDL, w1, w2, wo);
    launch(k_oproj, 96, P_THREADS, P_SMEM, USE_PDL, tmO, tmWo, tmH64, tmOut, x);
    launch(k_ffn, 128, F_THREADS, F_SMEM, USE_PDL, tmH, tmW1, tmW2, tmOut);
}
```

```cpp
#include <cuda_runtime.h>
#include <cuda_bf16.h>
#include <cuda.h>
#include <stdint.h>

namespace {

constexpr int SEQ = 2048, DM = 576, FF = 4608;
constexpr int KV_BYTES = SEQ * 48;
constexpr float LN_EPS = 1e-5f;
constexpr float LOG2E = 1.4426950408889634f;
constexpr float Q_SCALE = 0.23570226039551584f * LOG2E;

constexpr uint32_t POLY_MASK = 0xB5B5u;
constexpr float FAST_BOUND = 60.0f;

__device__ __align__(1024) __nv_bfloat16 g_q[SEQ * DM];
__device__ __align__(1024) uint4 g_kc[KV_BYTES / 16];
__device__ __align__(1024) uint4 g_vc[KV_BYTES / 16];
__device__ float g_kmax[32];
__device__ __align__(1024) __nv_bfloat16 g_o[SEQ * DM];
__device__ __align__(1024) __nv_bfloat16 g_x2[SEQ * DM];

#define TS(k, i)

__device__ __forceinline__ uint32_t smem_u32(const void* p) { return (uint32_t)__cvta_generic_to_shared(p); }
__device__ __forceinline__ void wg_fence() { asm volatile("wgmma.fence.sync.aligned;" ::: "memory"); }
__device__ __forceinline__ void wg_commit() { asm volatile("wgmma.commit_group.sync.aligned;" ::: "memory"); }
template <int N> __device__ __forceinline__ void wg_wait() { asm volatile("wgmma.wait_group.sync.aligned %0;" ::"n"(N) : "memory"); }
template <int N> __device__ __forceinline__ void pin(float (&r)[N]) {
#pragma unroll
    for (int i = 0; i < N; i++) asm volatile("" : "+f"(r[i])::"memory");
}
template <int N> __device__ __forceinline__ void pin(uint32_t (&r)[N]) {
#pragma unroll
    for (int i = 0; i < N; i++) asm volatile("" : "+r"(r[i])::"memory");
}
__device__ __forceinline__ constexpr uint32_t desc_hi(uint32_t sbo, uint32_t swz) { return (sbo >> 4) | (swz << 30); }
__device__ __forceinline__ uint32_t desc_lo(uint32_t addr, uint32_t lbo) { return ((addr & 0x3FFFF) >> 4) | ((lbo >> 4) << 16); }
__device__ __forceinline__ uint64_t desc64(uint32_t lo, uint32_t hi) { return ((uint64_t)hi << 32) | lo; }
constexpr uint32_t SMEM0 = 0x400;
__host__ __device__ constexpr uint64_t cdesc(uint32_t off, uint32_t lbo, uint32_t sbo, uint32_t swz) {
    return (uint64_t)(((SMEM0 + off) & 0x3FFFF) >> 4) | ((uint64_t)(lbo >> 4) << 16) | ((uint64_t)(sbo >> 4) << 32) | ((uint64_t)swz << 62);
}
__device__ __forceinline__ void check_smem_base(uint32_t base) { if ((base & 0x3FFFF) != SMEM0) __trap(); }

__device__ __forceinline__ void mbar_init(uint32_t bar, int cnt) { asm volatile("mbarrier.init.shared::cta.b64 [%0], %1;" ::"r"(bar), "r"(cnt) : "memory"); }
__device__ __forceinline__ void mbar_expect(uint32_t bar, int bytes) { asm volatile("mbarrier.arrive.expect_tx.shared::cta.b64 _, [%0], %1;" ::"r"(bar), "r"(bytes) : "memory"); }
__device__ __forceinline__ void mbar_arrive(uint32_t bar) { asm volatile("mbarrier.arrive.shared::cta.b64 _, [%0];" ::"r"(bar) : "memory"); }
__device__ __forceinline__ void mbar_wait(uint32_t bar, uint32_t parity) {
    asm volatile(
        "{\n.reg .pred p;\n.reg .u32 n;\nmov.u32 n, 0;\n"
        "LAB_WAIT:\n"
        "mbarrier.try_wait.parity.shared::cta.b64 p, [%0], %1;\n"
        "@p bra DONE;\n"
        "add.u32 n, n, 1;\n"
        "setp.lt.u32 p, n, 4000000;\n"
        "@p bra LAB_WAIT;\n"
        "trap;\n"
        "DONE:\n}\n" ::"r"(bar), "r"(parity) : "memory");
}
__device__ __forceinline__ void bar_init_fence() {
    asm volatile("fence.mbarrier_init.release.cluster;" ::: "memory");
    asm volatile("fence.proxy.async.shared::cta;" ::: "memory");
}
__device__ __forceinline__ void proxy_fence() { asm volatile("fence.proxy.async.shared::cta;" ::: "memory"); }
__device__ __forceinline__ void named_sync(int id, int n) { asm volatile("bar.sync %0, %1;" ::"r"(id), "r"(n) : "memory"); }
__device__ __forceinline__ void bulk_g2s(uint32_t dst, const void* src, int bytes, uint32_t bar) {
    asm volatile("cp.async.bulk.shared::cluster.global.mbarrier::complete_tx::bytes [%0], [%1], %2, [%3];" ::"r"(dst), "l"(src), "r"(bytes), "r"(bar) : "memory");
}
__device__ __forceinline__ void tma_2d(uint32_t dst, const CUtensorMap* tm, int c0, int c1, uint32_t bar) {
    asm volatile("cp.async.bulk.tensor.2d.shared::cluster.global.mbarrier::complete_tx::bytes [%0], [%1, {%3, %4}], [%2];" ::"r"(dst), "l"(tm), "r"(bar), "r"(c0), "r"(c1) : "memory");
}
__device__ __forceinline__ void tma_red_2d(const CUtensorMap* tm, int c0, int c1, uint32_t src) {
    asm volatile("cp.reduce.async.bulk.tensor.2d.global.shared::cta.add.tile.bulk_group [%0, {%2, %3}], [%1];" ::"l"(tm), "r"(src), "r"(c0), "r"(c1) : "memory");
}
__device__ __forceinline__ void tma_st_2d(const CUtensorMap* tm, int c0, int c1, uint32_t src) {
    asm volatile("cp.async.bulk.tensor.2d.global.shared::cta.tile.bulk_group [%0, {%2, %3}], [%1];" ::"l"(tm), "r"(src), "r"(c0), "r"(c1) : "memory");
}
__device__ __forceinline__ void bulk_commit() { asm volatile("cp.async.bulk.commit_group;" ::: "memory"); }
__device__ __forceinline__ void bulk_wait_all() { asm volatile("cp.async.bulk.wait_group.read 0;" ::: "memory"); }
__device__ __forceinline__ bool elect_one() {
    uint32_t p;
    asm volatile("{\n.reg .pred P;\nelect.sync _|P, 0xffffffff;\nselp.b32 %0, 1, 0, P;\n}\n" : "=r"(p));
    return p != 0;
}
__device__ __forceinline__ void prefetch_l2(const void* p, int bytes) { asm volatile("cp.async.bulk.prefetch.L2.global [%0], %1;" ::"l"(p), "r"(bytes) : "memory"); }
__device__ __forceinline__ void pdl_launch() { asm volatile("griddepcontrol.launch_dependents;" ::: "memory"); }
__device__ __forceinline__ void pdl_wait() { asm volatile("griddepcontrol.wait;" ::: "memory"); }
__device__ __forceinline__ float ex2(float x) { float y; asm("ex2.approx.ftz.f32 %0, %1;" : "=f"(y) : "f"(x)); return y; }
__device__ __forceinline__ float rcp(float x) { float y; asm("rcp.approx.ftz.f32 %0, %1;" : "=f"(y) : "f"(x)); return y; }
__device__ __forceinline__ uint32_t pack_bf16(float lo, float hi) { uint32_t r; asm("cvt.rn.bf16x2.f32 %0, %1, %2;" : "=r"(r) : "f"(hi), "f"(lo)); return r; }
__device__ __forceinline__ float bf_lo(uint32_t v) { return __uint_as_float(v << 16); }
__device__ __forceinline__ float bf_hi(uint32_t v) { return __uint_as_float(v & 0xFFFF0000u); }
__device__ __forceinline__ uint32_t hfma2(uint32_t a, uint32_t b, uint32_t c) { uint32_t r; asm("fma.rn.f16x2 %0, %1, %2, %3;" : "=r"(r) : "r"(a), "r"(b), "r"(c)); return r; }
__device__ __forceinline__ void stmatrix_x4(uint32_t addr, uint32_t r0, uint32_t r1, uint32_t r2, uint32_t r3) {
    asm volatile("stmatrix.sync.aligned.m8n8.x4.shared.b16 [%0], {%1, %2, %3, %4};" ::"r"(addr), "r"(r0), "r"(r1), "r"(r2), "r"(r3) : "memory");
}

template <int TB> __device__ __forceinline__ void wgmma_ss_n24(float (&d)[12], uint64_t da, uint64_t db, int sc) {
    asm volatile("{\n.reg .pred p;\nsetp.ne.b32 p, %14, 0;\n"
        "wgmma.mma_async.sync.aligned.m64n24k16.f32.bf16.bf16 {%0, %1, %2, %3, %4, %5, %6, %7, %8, %9, %10, %11}, %12, %13, p, 1, 1, 0, %15;\n}\n"
        : "+f"(d[0]), "+f"(d[1]), "+f"(d[2]), "+f"(d[3]), "+f"(d[4]), "+f"(d[5]), "+f"(d[6]), "+f"(d[7]), "+f"(d[8]), "+f"(d[9]), "+f"(d[10]), "+f"(d[11])
        : "l"(da), "l"(db), "r"(sc), "n"(TB));
}
template <int TB> __device__ __forceinline__ void wgmma_ss_n64(float (&d)[32], uint64_t da, uint64_t db, int sc) {
    asm volatile("{\n.reg .pred p;\nsetp.ne.b32 p, %34, 0;\n"
        "wgmma.mma_async.sync.aligned.m64n64k16.f32.bf16.bf16 {%0, %1, %2, %3, %4, %5, %6, %7, %8, %9, %10, %11, %12, %13, %14, %15, %16, %17, %18, %19, %20, %21, %22, %23, %24, %25, %26, %27, %28, %29, %30, %31}, %32, %33, p, 1, 1, 0, %35;\n}\n"
        : "+f"(d[0]), "+f"(d[1]), "+f"(d[2]), "+f"(d[3]), "+f"(d[4]), "+f"(d[5]), "+f"(d[6]), "+f"(d[7]), "+f"(d[8]), "+f"(d[9]), "+f"(d[10]), "+f"(d[11]), "+f"(d[12]), "+f"(d[13]), "+f"(d[14]), "+f"(d[15]), "+f"(d[16]), "+f"(d[17]), "+f"(d[18]), "+f"(d[19]), "+f"(d[20]), "+f"(d[21]), "+f"(d[22]), "+f"(d[23]), "+f"(d[24]), "+f"(d[25]), "+f"(d[26]), "+f"(d[27]), "+f"(d[28]), "+f"(d[29]), "+f"(d[30]), "+f"(d[31])
        : "l"(da), "l"(db), "r"(sc), "n"(TB));
}
template <int TB> __device__ __forceinline__ void wgmma_ss_n128(float (&d)[64], uint64_t da, uint64_t db, int sc) {
    asm volatile("{\n.reg .pred p;\nsetp.ne.b32 p, %66, 0;\n"
        "wgmma.mma_async.sync.aligned.m64n128k16.f32.bf16.bf16 {%0, %1, %2, %3, %4, %5, %6, %7, %8, %9, %10, %11, %12, %13, %14, %15, %16, %17, %18, %19, %20, %21, %22, %23, %24, %25, %26, %27, %28, %29, %30, %31, %32, %33, %34, %35, %36, %37, %38, %39, %40, %41, %42, %43, %44, %45, %46, %47, %48, %49, %50, %51, %52, %53, %54, %55, %56, %57, %58, %59, %60, %61, %62, %63}, %64, %65, p, 1, 1, 0, %67;\n}\n"
        : "+f"(d[0]), "+f"(d[1]), "+f"(d[2]), "+f"(d[3]), "+f"(d[4]), "+f"(d[5]), "+f"(d[6]), "+f"(d[7]), "+f"(d[8]), "+f"(d[9]), "+f"(d[10]), "+f"(d[11]), "+f"(d[12]), "+f"(d[13]), "+f"(d[14]), "+f"(d[15]), "+f"(d[16]), "+f"(d[17]), "+f"(d[18]), "+f"(d[19]), "+f"(d[20]), "+f"(d[21]), "+f"(d[22]), "+f"(d[23]), "+f"(d[24]), "+f"(d[25]), "+f"(d[26]), "+f"(d[27]), "+f"(d[28]), "+f"(d[29]), "+f"(d[30]), "+f"(d[31]), "+f"(d[32]), "+f"(d[33]), "+f"(d[34]), "+f"(d[35]), "+f"(d[36]), "+f"(d[37]), "+f"(d[38]), "+f"(d[39]), "+f"(d[40]), "+f"(d[41]), "+f"(d[42]), "+f"(d[43]), "+f"(d[44]), "+f"(d[45]), "+f"(d[46]), "+f"(d[47]), "+f"(d[48]), "+f"(d[49]), "+f"(d[50]), "+f"(d[51]), "+f"(d[52]), "+f"(d[53]), "+f"(d[54]), "+f"(d[55]), "+f"(d[56]), "+f"(d[57]), "+f"(d[58]), "+f"(d[59]), "+f"(d[60]), "+f"(d[61]), "+f"(d[62]), "+f"(d[63])
        : "l"(da), "l"(db), "r"(sc), "n"(TB));
}
template <int TB> __device__ __forceinline__ void wgmma_rs_n24(float (&d)[12], uint32_t a0, uint32_t a1, uint32_t a2, uint32_t a3, uint64_t db, int sc) {
    asm volatile("{\n.reg .pred p;\nsetp.ne.b32 p, %17, 0;\n"
        "wgmma.mma_async.sync.aligned.m64n24k16.f32.bf16.bf16 {%0, %1, %2, %3, %4, %5, %6, %7, %8, %9, %10, %11}, {%12, %13, %14, %15}, %16, p, 1, 1, %18;\n}\n"
        : "+f"(d[0]), "+f"(d[1]), "+f"(d[2]), "+f"(d[3]), "+f"(d[4]), "+f"(d[5]), "+f"(d[6]), "+f"(d[7]), "+f"(d[8]), "+f"(d[9]), "+f"(d[10]), "+f"(d[11])
        : "r"(a0), "r"(a1), "r"(a2), "r"(a3), "l"(db), "r"(sc), "n"(TB));
}
template <int TB> __device__ __forceinline__ void wgmma_rs_n64(float (&d)[32], uint32_t a0, uint32_t a1, uint32_t a2, uint32_t a3, uint64_t db, int sc) {
    asm volatile("{\n.reg .pred p;\nsetp.ne.b32 p, %37, 0;\n"
        "wgmma.mma_async.sync.aligned.m64n64k16.f32.bf16.bf16 {%0, %1, %2, %3, %4, %5, %6, %7, %8, %9, %10, %11, %12, %13, %14, %15, %16, %17, %18, %19, %20, %21, %22, %23, %24, %25, %26, %27, %28, %29, %30, %31}, {%32, %33, %34, %35}, %36, p, 1, 1, %38;\n}\n"
        : "+f"(d[0]), "+f"(d[1]), "+f"(d[2]), "+f"(d[3]), "+f"(d[4]), "+f"(d[5]), "+f"(d[6]), "+f"(d[7]), "+f"(d[8]), "+f"(d[9]), "+f"(d[10]), "+f"(d[11]), "+f"(d[12]), "+f"(d[13]), "+f"(d[14]), "+f"(d[15]), "+f"(d[16]), "+f"(d[17]), "+f"(d[18]), "+f"(d[19]), "+f"(d[20]), "+f"(d[21]), "+f"(d[22]), "+f"(d[23]), "+f"(d[24]), "+f"(d[25]), "+f"(d[26]), "+f"(d[27]), "+f"(d[28]), "+f"(d[29]), "+f"(d[30]), "+f"(d[31])
        : "r"(a0), "r"(a1), "r"(a2), "r"(a3), "l"(db), "r"(sc), "n"(TB));
}
template <int TB> __device__ __forceinline__ void wgmma_rs_n128(float (&d)[64], uint32_t a0, uint32_t a1, uint32_t a2, uint32_t a3, uint64_t db, int sc) {
    asm volatile("{\n.reg .pred p;\nsetp.ne.b32 p, %69, 0;\n"
        "wgmma.mma_async.sync.aligned.m64n128k16.f32.bf16.bf16 {%0, %1, %2, %3, %4, %5, %6, %7, %8, %9, %10, %11, %12, %13, %14, %15, %16, %17, %18, %19, %20, %21, %22, %23, %24, %25, %26, %27, %28, %29, %30, %31, %32, %33, %34, %35, %36, %37, %38, %39, %40, %41, %42, %43, %44, %45, %46, %47, %48, %49, %50, %51, %52, %53, %54, %55, %56, %57, %58, %59, %60, %61, %62, %63}, {%64, %65, %66, %67}, %68, p, 1, 1, %70;\n}\n"
        : "+f"(d[0]), "+f"(d[1]), "+f"(d[2]), "+f"(d[3]), "+f"(d[4]), "+f"(d[5]), "+f"(d[6]), "+f"(d[7]), "+f"(d[8]), "+f"(d[9]), "+f"(d[10]), "+f"(d[11]), "+f"(d[12]), "+f"(d[13]), "+f"(d[14]), "+f"(d[15]), "+f"(d[16]), "+f"(d[17]), "+f"(d[18]), "+f"(d[19]), "+f"(d[20]), "+f"(d[21]), "+f"(d[22]), "+f"(d[23]), "+f"(d[24]), "+f"(d[25]), "+f"(d[26]), "+f"(d[27]), "+f"(d[28]), "+f"(d[29]), "+f"(d[30]), "+f"(d[31]), "+f"(d[32]), "+f"(d[33]), "+f"(d[34]), "+f"(d[35]), "+f"(d[36]), "+f"(d[37]), "+f"(d[38]), "+f"(d[39]), "+f"(d[40]), "+f"(d[41]), "+f"(d[42]), "+f"(d[43]), "+f"(d[44]), "+f"(d[45]), "+f"(d[46]), "+f"(d[47]), "+f"(d[48]), "+f"(d[49]), "+f"(d[50]), "+f"(d[51]), "+f"(d[52]), "+f"(d[53]), "+f"(d[54]), "+f"(d[55]), "+f"(d[56]), "+f"(d[57]), "+f"(d[58]), "+f"(d[59]), "+f"(d[60]), "+f"(d[61]), "+f"(d[62]), "+f"(d[63])
        : "r"(a0), "r"(a1), "r"(a2), "r"(a3), "l"(db), "r"(sc), "n"(TB));
}

constexpr int P_THREADS = 288;
constexpr int P_NST = 6;
constexpr int P_A_BYTES = 9 * 8192;
constexpr int P_B_STAGE = 3 * 8192;
constexpr int P_SMEM = P_A_BYTES + P_NST * P_B_STAGE + 256 + 320;
constexpr uint32_t HI_SW128 = (1024u >> 4) | (1u << 30);

template <int NCOL, bool WAIT_A>
__device__ __forceinline__ void proj_mma(float (&acc)[NCOL / 2], uint32_t sA, uint32_t sB, uint32_t colofs, uint32_t fullB, uint32_t emptyB, uint32_t fullA, int lane) {
#pragma unroll 1
    for (int kb = 0; kb < 9; kb++) {
        const int s = kb >= P_NST ? kb - P_NST : kb;
        if (WAIT_A) mbar_wait(fullA + kb * 8, 0);
        mbar_wait(fullB + s * 8, kb >= P_NST ? 1 : 0);
        const uint32_t alo = desc_lo(sA + kb * 8192, 16), blo = desc_lo(sB + s * P_B_STAGE + colofs, 8192);
        wg_fence();
#pragma unroll
        for (int ks = 0; ks < 4; ks++) {
            const uint64_t da = desc64(alo + ks * 2, HI_SW128), db = desc64(blo + ks * 128, HI_SW128);
            if constexpr (NCOL == 128) wgmma_ss_n128<1>(acc, da, db, (kb | ks) != 0);
            else wgmma_ss_n64<1>(acc, da, db, (kb | ks) != 0);
        }
        wg_commit();
        if (kb + P_NST < 9 + 1) {
            wg_wait<1>();
            if (kb >= 1 && kb - 1 + P_NST < 9 && lane == 0) mbar_arrive(emptyB + (kb - 1) * 8);
        }
    }
    wg_wait<0>();
    pin(acc);
}

template <int NB>
__device__ __forceinline__ void stage_tile(const uint32_t (&pk)[NB * 2], uint32_t base, int w, int lane) {
    const int r = w * 16 + (lane & 7) + ((lane >> 3) & 1) * 8;
#pragma unroll
    for (int b = 0; b < NB; b += 2) {
        const uint32_t a = base + (b >> 3) * 8192 + r * 128 + ((((b & 7) + (lane >> 4)) ^ (r & 7)) << 4);
        stmatrix_x4(a, pk[2 * b], pk[2 * b + 1], pk[2 * b + 2], pk[2 * b + 3]);
    }
}

__device__ __forceinline__ uint32_t hsub2_bf16(uint32_t a, uint32_t b) { uint32_t r; asm("sub.rn.bf16x2 %0, %1, %2;" : "=r"(r) : "r"(a), "r"(b)); return r; }

constexpr int KV_RAW = DM * 18 * 2;

__global__ void __launch_bounds__(P_THREADS, 1)
k_qkv(const __grid_constant__ CUtensorMap tmWq, const __grid_constant__ CUtensorMap tmQ, const __nv_bfloat16* __restrict__ x, const __nv_bfloat16* __restrict__ wk, const __nv_bfloat16* __restrict__ wv) {
    extern __shared__ __align__(1024) uint8_t smem[];
    const uint32_t sA = smem_u32(smem), sB = sA + P_A_BYTES, bars = sB + P_NST * P_B_STAGE;
    const uint32_t fullB = bars, emptyB = bars + 64, fullX = bars + 128, fullW = bars + 136, rawFree = bars + 144;
    const uint32_t sRaw = sB + 3 * P_B_STAGE;
    float* s_rstd = reinterpret_cast<float*>(smem + P_A_BYTES + P_NST * P_B_STAGE + 256);
    const int tid = threadIdx.x, warp = __shfl_sync(~0u, tid >> 5, 0), lane = tid & 31;
    const bool isQ = blockIdx.x < 96;
    const int m = isQ ? blockIdx.x / 3 : blockIdx.x - 96, cg = blockIdx.x % 3;
    if (tid == 0) TS(0, 0);
    if (warp == 8) {
        if (elect_one()) {
            for (int i = 0; i < P_NST; i++) { mbar_init(fullB + i * 8, 1); mbar_init(emptyB + i * 8, 8); }
            mbar_init(fullX, 1); mbar_init(fullW, 1); mbar_init(rawFree, 8);
            bar_init_fence();
            mbar_expect(fullX, P_A_BYTES);
            bulk_g2s(sRaw, x + (size_t)m * 64 * DM, P_A_BYTES, fullX);
            if (isQ) {
                for (int kb = 0; kb < 3; kb++) {
                    mbar_expect(fullB + kb * 8, P_B_STAGE);
                    for (int a = 0; a < 3; a++) tma_2d(sB + kb * P_B_STAGE + a * 8192, &tmWq, cg * 192 + a * 64, kb * 64, fullB + kb * 8);
                }
            } else {
                mbar_expect(fullW, 2 * KV_RAW);
                bulk_g2s(sA, wk, KV_RAW, fullW);
                bulk_g2s(sA + KV_RAW, wv, KV_RAW, fullW);
            }
        }
        __syncwarp();
    }
    __syncthreads();
    pdl_launch();
    if (warp == 8) {
        if (isQ && elect_one()) {
            mbar_wait(rawFree, 0);
            for (int kb = 3; kb < 9; kb++) {
                const int s = kb >= P_NST ? kb - P_NST : kb;
                if (kb >= P_NST) mbar_wait(emptyB + s * 8, 0);
                mbar_expect(fullB + s * 8, P_B_STAGE);
                for (int a = 0; a < 3; a++) tma_2d(sB + s * P_B_STAGE + a * 8192, &tmWq, cg * 192 + a * 64, kb * 64, fullB + s * 8);
            }
        }
        return;
    }
    {
        const int row = tid >> 2, q = tid & 3, odd = row & 1;
        mbar_wait(fullX, 0);
        if (tid == 0) TS(0, 6);
        uint4 v[18];
#pragma unroll
        for (int i = 0; i < 18; i++)
            asm volatile("ld.shared.v4.b32 {%0, %1, %2, %3}, [%4];" : "=r"(v[i].x), "=r"(v[i].y), "=r"(v[i].z), "=r"(v[i].w) : "r"(sRaw + row * 1152 + (q + 4 * (i ^ odd)) * 16));
        float sum = 0.f, sum2 = 0.f, sq = 0.f, sq2 = 0.f;
#pragma unroll
        for (int i = 0; i < 18; i++) {
            const uint32_t w[4] = {v[i].x, v[i].y, v[i].z, v[i].w};
#pragma unroll
            for (int j = 0; j < 4; j++) { const float a = bf_lo(w[j]), b = bf_hi(w[j]); sum += a; sum2 += b; sq = fmaf(a, a, sq); sq2 = fmaf(b, b, sq2); }
        }
        __syncwarp();
        if (lane == 0) mbar_arrive(rawFree);
        sum += sum2; sq += sq2;
        sum += __shfl_xor_sync(~0u, sum, 1); sum += __shfl_xor_sync(~0u, sum, 2);
        sq += __shfl_xor_sync(~0u, sq, 1); sq += __shfl_xor_sync(~0u, sq, 2);
        if (tid == 0) TS(0, 4);
        if (!isQ) {
            mbar_wait(fullW, 0);
            const uint32_t* raw = reinterpret_cast<const uint32_t*>(smem);
            uint32_t wr[41];
#pragma unroll
            for (int i = 0; i < 41; i++) wr[i] = (tid + i * 256 < 2 * DM * 9) ? raw[tid + i * 256] : 0u;
            int k = tid / 9, r = tid - k * 9;
#pragma unroll
            for (int i = 0; i < 41; i++) {
                if (tid + i * 256 < 2 * DM * 9) {
                    const int sel = k >= DM, kk = k - sel * DM;
                    *reinterpret_cast<uint32_t*>(smem + P_A_BYTES + (sel * 3 + (r >> 2)) * 9216 + (kk >> 3) * 128 + (kk & 7) * 16 + (r & 3) * 4) = wr[i];
                }
                k += 28; r += 4;
                if (r >= 9) { r -= 9; k++; }
            }
            named_sync(1, 256);
        }
        const float mean = sum * (1.0f / DM);
        if (q == 0) s_rstd[row] = rsqrtf(fmaxf(sq * (1.0f / DM) - mean * mean, 0.f) + LN_EPS);
        const uint32_t mhi = pack_bf16(mean, mean);
        const float rem = mean - bf_lo(mhi);
        const uint32_t mlo = pack_bf16(rem, rem);
#pragma unroll
        for (int i = 0; i < 18; i++) {
            const int c = q + 4 * (i ^ odd);
            const uint32_t o0 = hsub2_bf16(hsub2_bf16(v[i].x, mhi), mlo), o1 = hsub2_bf16(hsub2_bf16(v[i].y, mhi), mlo);
            const uint32_t o2 = hsub2_bf16(hsub2_bf16(v[i].z, mhi), mlo), o3 = hsub2_bf16(hsub2_bf16(v[i].w, mhi), mlo);
            asm volatile("st.shared.v4.b32 [%0], {%1, %2, %3, %4};" ::"r"(sA + (c >> 3) * 8192 + row * 128 + (((c & 7) ^ (row & 7)) << 4)), "r"(o0), "r"(o1), "r"(o2), "r"(o3) : "memory");
        }
    }
    proxy_fence();
    named_sync(1, 256);
    if (tid == 0) TS(0, 1);
    const int wg = warp >> 2, w = warp & 3, g = lane >> 2, t = lane & 3;
    const float rs0 = s_rstd[w * 16 + g], rs1 = s_rstd[w * 16 + g + 8];
    if (isQ) {
        const float c0 = rs0 * Q_SCALE, c1 = rs1 * Q_SCALE;
        if (wg == 0) {
            float acc[64];
            proj_mma<128, false>(acc, sA, sB, 0, fullB, emptyB, 0, lane);
            if (tid == 0) TS(0, 2);
            named_sync(1, 256);
            uint32_t pk[32];
#pragma unroll
            for (int i = 0; i < 16; i++) { pk[2 * i] = pack_bf16(acc[4 * i] * c0, acc[4 * i + 1] * c0); pk[2 * i + 1] = pack_bf16(acc[4 * i + 2] * c1, acc[4 * i + 3] * c1); }
            stage_tile<16>(pk, sA, w, lane);
        } else {
            float acc[32];
            proj_mma<64, false>(acc, sA, sB, 2 * 8192, fullB, emptyB, 0, lane);
            named_sync(1, 256);
            uint32_t pk[16];
#pragma unroll
            for (int i = 0; i < 8; i++) { pk[2 * i] = pack_bf16(acc[4 * i] * c0, acc[4 * i + 1] * c0); pk[2 * i + 1] = pack_bf16(acc[4 * i + 2] * c1, acc[4 * i + 3] * c1); }
            stage_tile<8>(pk, sA + 2 * 8192, w, lane);
        }
        proxy_fence();
        named_sync(1, 256);
        if (warp == 0 && elect_one()) {
            for (int a = 0; a < 3; a++) tma_st_2d(&tmQ, cg * 192 + a * 64, m * 64, sA + a * 8192);
            bulk_commit();
            bulk_wait_all();
        }
    } else {
        float acc[12];
        const uint32_t blo = desc_lo(sB + wg * 3 * 9216, 128);
#pragma unroll
        for (int i = 0; i < 12; i++) acc[i] = 0.f;
        pin(acc);
        wg_fence();
#pragma unroll 1
        for (int kb = 0; kb < 9; kb++) {
            const uint32_t alo = desc_lo(sA + kb * 8192, 16);
#pragma unroll
            for (int ks = 0; ks < 4; ks++)
                wgmma_ss_n24<1>(acc, desc64(alo + ks * 2, HI_SW128), desc64(blo + (kb * 4 + ks) * 16, desc_hi(9216, 0)), 1);
        }
        wg_commit();
        wg_wait<0>();
        pin(acc);
        uint32_t pk[6];
#pragma unroll
        for (int b = 0; b < 3; b++) { pk[2 * b] = pack_bf16(acc[4 * b] * rs0, acc[4 * b + 1] * rs0); pk[2 * b + 1] = pack_bf16(acc[4 * b + 2] * rs1, acc[4 * b + 3] * rs1); }
        float n0 = 0.f, n1 = 0.f, vm = 0.f;
#pragma unroll
        for (int b = 0; b < 3; b++) {
            if (b < 2 || t == 0) {
                const float a = bf_lo(pk[2 * b]), c = bf_hi(pk[2 * b]), d = bf_lo(pk[2 * b + 1]), e = bf_hi(pk[2 * b + 1]);
                n0 = fmaf(a, a, fmaf(c, c, n0)); n1 = fmaf(d, d, fmaf(e, e, n1));
            }
        }
        n0 += __shfl_xor_sync(~0u, n0, 1); n0 += __shfl_xor_sync(~0u, n0, 2);
        n1 += __shfl_xor_sync(~0u, n1, 1); n1 += __shfl_xor_sync(~0u, n1, 2);
        vm = fmaxf(n0, n1);
        if (!(n0 == n0) || !(n1 == n1)) vm = __int_as_float(0x7F800000);
#pragma unroll
        for (int o = 4; o < 32; o <<= 1) vm = fmaxf(vm, __shfl_xor_sync(~0u, vm, o));
        if (t != 0) {
            uint32_t lo, hi;
            if (wg == 0) {
                const int grp = m * 8 + w * 2;
                const uint32_t c = t == 1 ? 0x42FE3F80u   : (t == 2 ? 0x00003BC0u   : 0u);
                lo = ((POLY_MASK >> (grp & 15)) & 1) ? c : 0u;
                hi = ((POLY_MASK >> ((grp + 1) & 15)) & 1) ? c : 0u;
            } else {
                lo = hi = t == 1 ? 0x00003F80u : 0u;
            }
            pk[4] = lo; pk[5] = hi;
        }
        uint32_t* dst = reinterpret_cast<uint32_t*>(wg == 0 ? g_kc : g_vc) + (m * 8 + w * 2) * 96 + g * 4 + t;
#pragma unroll
        for (int b = 0; b < 3; b++) { dst[b * 32] = pk[2 * b]; dst[96 + b * 32] = pk[2 * b + 1]; }
        float* red = s_rstd + 64;
        if (lane == 0) red[warp] = (wg == 0) ? vm : (vm <= 1e24f ? 0.f : __int_as_float(0x7F800000));
        named_sync(1, 256);
        if (tid == 0) {
            float mx = red[0];
#pragma unroll
            for (int i = 1; i < 8; i++) mx = fmaxf(mx, red[i]);
            g_kmax[m] = mx;
        }
    }
    if (tid == 0) TS(0, 3);
}

constexpr int A_THREADS = 512;
constexpr int A_NPIECE = 8;
constexpr int A_SMEM = 2 * KV_BYTES + 128;

__device__ __forceinline__ uint32_t exp2_pair_fixed(float lo, float hi) {
    const uint32_t G = __byte_perm(__float_as_uint(lo), __float_as_uint(hi), 0x5410);
    const uint32_t Hh = G & 0x007F007Fu;
    const uint32_t tt = hfma2(Hh, 0xF96BF96Bu, 0x358C358Cu);
    return G - hfma2(tt, Hh, 0u);
}

__device__ __forceinline__ void attn_side_job(const __nv_bfloat16* __restrict__ w1, const __nv_bfloat16* __restrict__ w2, const __nv_bfloat16* __restrict__ wo) {
    const int e = blockIdx.x - 128, tid = threadIdx.x;
    if (tid < 32) {
        const char* p = reinterpret_cast<const char*>(wo) + e * (DM * DM * 2 / 4);
        for (int i = tid; i < DM * DM * 2 / 4 / 4608; i += 32) prefetch_l2(p + i * 4608, 4608);
        p = reinterpret_cast<const char*>(w1) + (size_t)e * (FF * DM * 2 / 4);
        for (int i = tid; i < FF * DM * 2 / 4 / 9216; i += 32) prefetch_l2(p + (size_t)i * 9216, 9216);
        p = reinterpret_cast<const char*>(w2) + (size_t)e * (FF * DM * 2 / 4);
        for (int i = tid; i < FF * DM * 2 / 4 / 9216; i += 32) prefetch_l2(p + (size_t)i * 9216, 9216);
    }
}

__global__ void __launch_bounds__(A_THREADS, 1)
k_attn(const __nv_bfloat16* __restrict__ w1, const __nv_bfloat16* __restrict__ w2, const __nv_bfloat16* __restrict__ wo) {
    extern __shared__ __align__(1024) uint8_t smem[];
    pdl_launch();
    if (blockIdx.x >= 128) { attn_side_job(w1, w2, wo); return; }
    const uint32_t sK = smem_u32(smem), sV = sK + KV_BYTES, bars = sV + KV_BYTES;
    const int tid = threadIdx.x;
    if (tid == 0) TS(1, 0);
    if (tid == 0) {
        for (int i = 0; i < A_NPIECE; i++) mbar_init(bars + i * 8, 1);
        bar_init_fence();
    }
    __syncthreads();
    pdl_wait();
    if (tid == 0) TS(1, 1);
    if (tid < 32 && elect_one()) {
        constexpr int PB = KV_BYTES / A_NPIECE;
        for (int i = 0; i < A_NPIECE; i++) {
            mbar_expect(bars + i * 8, 2 * PB);
            bulk_g2s(sK + i * PB, reinterpret_cast<const char*>(g_kc) + i * PB, PB, bars + i * 8);
            bulk_g2s(sV + i * PB, reinterpret_cast<const char*>(g_vc) + i * PB, PB, bars + i * 8);
        }
    }
    const int wg = __shfl_sync(~0u, tid >> 7, 0), w = (tid >> 5) & 3, lane = tid & 31, g = lane >> 2, t = lane & 3;
    const uint32_t* q32 = reinterpret_cast<const uint32_t*>(g_q);
    uint32_t* o32 = reinterpret_cast<uint32_t*>(g_o);
    int row = (blockIdx.x * 8 + wg) * 64 + w * 16 + g;
    uint32_t nq[6];
    nq[0] = q32[row * 9 + t]; nq[1] = q32[(row + 8) * 9 + t]; nq[2] = q32[row * 9 + 4 + t]; nq[3] = q32[(row + 8) * 9 + 4 + t];
    nq[4] = q32[row * 9 + 8]; nq[5] = q32[(row + 8) * 9 + 8];
    float kmax2 = g_kmax[lane];
#pragma unroll
    for (int o = 1; o < 32; o <<= 1) kmax2 = fmaxf(kmax2, __shfl_xor_sync(~0u, kmax2, o));
    constexpr uint32_t HI_K = desc_hi(384, 0), HI_V = desc_hi(128, 0);
    const uint32_t k0lo = desc_lo(sK, 128), k1lo = desc_lo(sK + 256, 0), vlo = desc_lo(sV, 384);
#pragma unroll 1
    for (int rep = 0; rep < 2; rep++, row += 256) {
        uint32_t qa[4] = {nq[0], nq[1], nq[2], nq[3]}, qb[4];
        float n0, n1;
        {
            const float a0 = bf_lo(qa[0]), a1 = bf_hi(qa[0]), a2 = bf_lo(qa[2]), a3 = bf_hi(qa[2]);
            const float b0 = bf_lo(qa[1]), b1 = bf_hi(qa[1]), b2 = bf_lo(qa[3]), b3 = bf_hi(qa[3]);
            n0 = a0 * a0 + a1 * a1 + a2 * a2 + a3 * a3; n1 = b0 * b0 + b1 * b1 + b2 * b2 + b3 * b3;
            if (t == 0) {
                const float c0 = bf_lo(nq[4]), c1 = bf_hi(nq[4]), d0 = bf_lo(nq[5]), d1 = bf_hi(nq[5]);
                n0 += c0 * c0 + c1 * c1; n1 += d0 * d0 + d1 * d1;
            }
            n0 += __shfl_xor_sync(~0u, n0, 1); n0 += __shfl_xor_sync(~0u, n0, 2);
            n1 += __shfl_xor_sync(~0u, n1, 1); n1 += __shfl_xor_sync(~0u, n1, 2);
        }
        const uint32_t x0 = nq[4], x1 = nq[5];
        if (rep == 0) {
            const int nr = row + 256;
            nq[0] = q32[nr * 9 + t]; nq[1] = q32[(nr + 8) * 9 + t]; nq[2] = q32[nr * 9 + 4 + t]; nq[3] = q32[(nr + 8) * 9 + 4 + t];
            nq[4] = q32[nr * 9 + 8]; nq[5] = q32[(nr + 8) * 9 + 8];
        }
        const bool unsafe = !(fmaxf(n0, n1) * kmax2 <= FAST_BOUND * FAST_BOUND);
        uint32_t any_unsafe;
        asm volatile("{\n.reg .pred p, q;\nsetp.ne.u32 p, %1, 0;\nbar.red.or.pred q, %2, 128, p;\nselp.u32 %0, 1, 0, q;\n}\n" : "=r"(any_unsafe) : "r"((uint32_t)unsafe), "r"(wg + 1) : "memory");
        if (tid == 0) TS(1, 2 + rep * 2);
        float o[12];
#pragma unroll
        for (int i = 0; i < 12; i++) o[i] = 0.f;
        if (!any_unsafe) {
            float s[64];
            const uint32_t cst = t == 1 ? 0x3F804780u   : (t == 2 ? 0x00003F80u   : 0u);
            qb[0] = t == 0 ? x0 : cst; qb[1] = t == 0 ? x1 : cst; qb[2] = 0; qb[3] = 0;
            pin(qa); pin(qb); pin(o);
#pragma unroll 1
            for (int j = 0; j < 16; j++) {
                if (rep == 0 && (j & 1) == 0) mbar_wait(bars + (j >> 1) * 8, 0);
                const uint32_t off = j * (16 * 384 >> 4);
                wg_fence();
                wgmma_rs_n128<0>(s, qa[0], qa[1], qa[2], qa[3], desc64(k0lo + off, HI_K), 0);
                wgmma_rs_n128<0>(s, qb[0], qb[1], qb[2], qb[3], desc64(k1lo + off, HI_K), 1);
                wg_commit();
                wg_wait<0>();
                pin(s);
                uint32_t p[32];
#pragma unroll
                for (int i = 0; i < 32; i++) {
                    if ((POLY_MASK >> (i >> 1)) & 1) p[i] = exp2_pair_fixed(s[2 * i], s[2 * i + 1]);
                    else p[i] = pack_bf16(ex2(s[2 * i]), ex2(s[2 * i + 1]));
                }
                pin(p);
                wg_fence();
#pragma unroll
                for (int k = 0; k < 8; k++) wgmma_rs_n24<1>(o, p[4 * k], p[4 * k + 1], p[4 * k + 2], p[4 * k + 3], desc64(vlo + off + k * 48, HI_V), 1);
                wg_commit();
                wg_wait<0>();
            }
        } else {
            float s[64];
            qb[0] = t == 0 ? x0 : 0u; qb[1] = t == 0 ? x1 : 0u; qb[2] = 0; qb[3] = 0;
            pin(qa); pin(qb); pin(o);
            float m0 = -INFINITY, m1 = -INFINITY;
#pragma unroll 1
            for (int j = 0; j < 16; j++) {
                if (rep == 0 && (j & 1) == 0) mbar_wait(bars + (j >> 1) * 8, 0);
                const uint32_t off = j * (16 * 384 >> 4);
                wg_fence();
                wgmma_rs_n128<0>(s, qa[0], qa[1], qa[2], qa[3], desc64(k0lo + off, HI_K), 0);
                wgmma_rs_n128<0>(s, qb[0], qb[1], qb[2], qb[3], desc64(k1lo + off, HI_K), 1);
                wg_commit();
                wg_wait<0>();
                pin(s);
                float x0m = m0, x1m = m1;
#pragma unroll
                for (int b = 0; b < 16; b++) { x0m = fmaxf(x0m, fmaxf(s[4 * b], s[4 * b + 1])); x1m = fmaxf(x1m, fmaxf(s[4 * b + 2], s[4 * b + 3])); }
                x0m = fmaxf(x0m, __shfl_xor_sync(~0u, x0m, 1)); x0m = fmaxf(x0m, __shfl_xor_sync(~0u, x0m, 2));
                x1m = fmaxf(x1m, __shfl_xor_sync(~0u, x1m, 1)); x1m = fmaxf(x1m, __shfl_xor_sync(~0u, x1m, 2));
                const float c0 = ex2(m0 - x0m), c1 = ex2(m1 - x1m);
                m0 = x0m; m1 = x1m;
#pragma unroll
                for (int b = 0; b < 3; b++) { o[4 * b] *= c0; o[4 * b + 1] *= c0; o[4 * b + 2] *= c1; o[4 * b + 3] *= c1; }
                uint32_t p[32];
#pragma unroll
                for (int b = 0; b < 16; b++) {
                    p[2 * b] = pack_bf16(ex2(s[4 * b] - m0), ex2(s[4 * b + 1] - m0));
                    p[2 * b + 1] = pack_bf16(ex2(s[4 * b + 2] - m1), ex2(s[4 * b + 3] - m1));
                }
                pin(p); pin(o);
                wg_fence();
#pragma unroll
                for (int k = 0; k < 8; k++) wgmma_rs_n24<1>(o, p[4 * k], p[4 * k + 1], p[4 * k + 2], p[4 * k + 3], desc64(vlo + off + k * 48, HI_V), 1);
                wg_commit();
                wg_wait<0>();
            }
        }
        pin(o);
        if (tid == 0) TS(1, 3 + rep * 2);
        const float l0 = __shfl_sync(~0u, o[8], (lane & ~3) | 1), l1 = __shfl_sync(~0u, o[10], (lane & ~3) | 1);
        const float i0 = 1.0f / l0, i1 = 1.0f / l1;
        o32[row * 9 + t] = pack_bf16(o[0] * i0, o[1] * i0);
        o32[(row + 8) * 9 + t] = pack_bf16(o[2] * i1, o[3] * i1);
        o32[row * 9 + 4 + t] = pack_bf16(o[4] * i0, o[5] * i0);
        o32[(row + 8) * 9 + 4 + t] = pack_bf16(o[6] * i1, o[7] * i1);
        if (t == 0) { o32[row * 9 + 8] = pack_bf16(o[8] * i0, o[9] * i0); o32[(row + 8) * 9 + 8] = pack_bf16(o[10] * i1, o[11] * i1); }
    }
    if (tid == 0) TS(1, 6);
}

template <int NB>
__device__ __forceinline__ void oproj_load_x(uint32_t (&xr)[NB * 2], const uint32_t* __restrict__ x32, int r0, int col0, int t) {
#pragma unroll
    for (int b = 0; b < NB; b++) {
        const int i0 = (r0 * DM + col0 + b * 8 + 2 * t) >> 1;
        xr[2 * b] = __ldg(x32 + i0); xr[2 * b + 1] = __ldg(x32 + i0 + 4 * DM);
    }
}
constexpr int P_OFF_STAT = 3 * 8192 + 3 * 8192;
template <int NB>
__device__ __forceinline__ void oproj_epilogue(const float (&acc)[NB * 4], uint32_t (&xr)[NB * 2], uint32_t sA, uint32_t tile_ofs, int part, int w, int lane) {
    float s0 = 0.f, q0 = 0.f, s1 = 0.f, q1 = 0.f;
#pragma unroll
    for (int b = 0; b < NB; b++) {
        const uint32_t xa = xr[2 * b], xb = xr[2 * b + 1];
        const uint32_t ha = pack_bf16(acc[4 * b] + bf_lo(xa), acc[4 * b + 1] + bf_hi(xa));
        const uint32_t hb = pack_bf16(acc[4 * b + 2] + bf_lo(xb), acc[4 * b + 3] + bf_hi(xb));
        xr[2 * b] = ha; xr[2 * b + 1] = hb;
        const float a = bf_lo(ha), c = bf_hi(ha), d = bf_lo(hb), e = bf_hi(hb);
        s0 += a + c; q0 = fmaf(a, a, fmaf(c, c, q0));
        s1 += d + e; q1 = fmaf(d, d, fmaf(e, e, q1));
    }
    s0 += __shfl_xor_sync(~0u, s0, 1); s0 += __shfl_xor_sync(~0u, s0, 2);
    q0 += __shfl_xor_sync(~0u, q0, 1); q0 += __shfl_xor_sync(~0u, q0, 2);
    s1 += __shfl_xor_sync(~0u, s1, 1); s1 += __shfl_xor_sync(~0u, s1, 2);
    q1 += __shfl_xor_sync(~0u, q1, 1); q1 += __shfl_xor_sync(~0u, q1, 2);
    const int r = w * 16 + (lane >> 2);
    const uint32_t sStat = sA + P_OFF_STAT;
    if ((lane & 3) < 3) {
        uint32_t dst;
        asm("mapa.shared::cluster.u32 %0, %1, %2;" : "=r"(dst) : "r"(sStat + (part * 64 + r) * 8), "r"(lane & 3));
        asm volatile("st.shared::cluster.v2.f32 [%0], {%1, %2};" ::"r"(dst), "f"(s0), "f"(q0) : "memory");
        asm volatile("st.shared::cluster.v2.f32 [%0], {%1, %2};" ::"r"(dst + 64), "f"(s1), "f"(q1) : "memory");
    }
    asm volatile("barrier.cluster.arrive.release.aligned;" ::: "memory");
    stage_tile<NB>(xr, sA + tile_ofs, w, lane);
    asm volatile("barrier.cluster.wait.acquire.aligned;" ::: "memory");
    s0 = q0 = s1 = q1 = 0.f;
#pragma unroll
    for (int p = 0; p < 6; p++) {
        float a, b, c, d;
        asm volatile("ld.shared.v2.f32 {%0, %1}, [%2];" : "=f"(a), "=f"(b) : "r"(sStat + (p * 64 + r) * 8));
        asm volatile("ld.shared.v2.f32 {%0, %1}, [%2];" : "=f"(c), "=f"(d) : "r"(sStat + (p * 64 + r + 8) * 8));
        s0 += a; q0 += b; s1 += c; q1 += d;
    }
    const float m0 = s0 * (1.0f / DM), m1 = s1 * (1.0f / DM);
    const float rs0 = rsqrtf(fmaxf(q0 * (1.0f / DM) - m0 * m0, 0.f) + LN_EPS), rs1 = rsqrtf(fmaxf(q1 * (1.0f / DM) - m1 * m1, 0.f) + LN_EPS);
    const float n0 = -m0 * rs0, n1 = -m1 * rs1;
#pragma unroll
    for (int b = 0; b < NB; b++) {
        xr[2 * b] = pack_bf16(fmaf(bf_lo(xr[2 * b]), rs0, n0), fmaf(bf_hi(xr[2 * b]), rs0, n0));
        xr[2 * b + 1] = pack_bf16(fmaf(bf_lo(xr[2 * b + 1]), rs1, n1), fmaf(bf_hi(xr[2 * b + 1]), rs1, n1));
    }
    stage_tile<NB>(xr, sA + 3 * 8192 + tile_ofs, w, lane);
}

__global__ void __cluster_dims__(3, 1, 1) __launch_bounds__(P_THREADS, 1)
k_oproj(const __grid_constant__ CUtensorMap tmO, const __grid_constant__ CUtensorMap tmWo, const __grid_constant__ CUtensorMap tmX2, const __grid_constant__ CUtensorMap tmOut, const __nv_bfloat16* __restrict__ x) {
    extern __shared__ __align__(1024) uint8_t smem[];
    const uint32_t sA = smem_u32(smem), sB = sA + P_A_BYTES, bars = sB + P_NST * P_B_STAGE;
    const uint32_t fullB = bars, emptyB = bars + 64, fullA = bars + 128;
    const int tid = threadIdx.x, warp = __shfl_sync(~0u, tid >> 5, 0), lane = tid & 31;
    const int m = blockIdx.x / 3, cg = blockIdx.x % 3;
    if (tid == 0) TS(2, 0);
    if (tid == 0) {
        for (int i = 0; i < P_NST; i++) { mbar_init(fullB + i * 8, 1); mbar_init(emptyB + i * 8, 8); }
        for (int i = 0; i < 9; i++) mbar_init(fullA + i * 8, 1);
        bar_init_fence();
    }
    __syncthreads();
    pdl_launch();
    if (warp == 8) {
        if (elect_one()) {
            for (int kb = 0; kb < P_NST; kb++) {
                mbar_expect(fullB + kb * 8, P_B_STAGE);
                for (int a = 0; a < 3; a++) tma_2d(sB + kb * P_B_STAGE + a * 8192, &tmWo, cg * 192 + a * 64, kb * 64, fullB + kb * 8);
            }
            pdl_wait();
            for (int kb = 0; kb < 9; kb++) {
                mbar_expect(fullA + kb * 8, 8192);
                tma_2d(sA + kb * 8192, &tmO, kb * 64, m * 64, fullA + kb * 8);
            }
            for (int kb = P_NST; kb < 9; kb++) {
                const int s = kb - P_NST;
                mbar_wait(emptyB + s * 8, 0);
                mbar_expect(fullB + s * 8, P_B_STAGE);
                for (int a = 0; a < 3; a++) tma_2d(sB + s * P_B_STAGE + a * 8192, &tmWo, cg * 192 + a * 64, kb * 64, fullB + s * 8);
            }
        }
        return;
    }
    const int wg = warp >> 2, w = warp & 3, g = lane >> 2, t = lane & 3;
    const int r0 = m * 64 + w * 16 + g;
    const uint32_t* x32 = reinterpret_cast<const uint32_t*>(x);
    if (wg == 0) {
        uint32_t xr[32];
        oproj_load_x<16>(xr, x32, r0, cg * 192, t);
        float acc[64];
        proj_mma<128, true>(acc, sA, sB, 0, fullB, emptyB, fullA, lane);
        if (tid == 0) TS(2, 2);
        named_sync(1, 256);
        oproj_epilogue<16>(acc, xr, sA, 0, cg * 2, w, lane);
    } else {
        uint32_t xr[16];
        oproj_load_x<8>(xr, x32, r0, cg * 192 + 128, t);
        float acc[32];
        proj_mma<64, true>(acc, sA, sB, 2 * 8192, fullB, emptyB, fullA, lane);
        named_sync(1, 256);
        oproj_epilogue<8>(acc, xr, sA, 2 * 8192, cg * 2 + 1, w, lane);
    }
    proxy_fence();
    named_sync(1, 256);
    if (warp == 0 && elect_one()) {
        for (int a = 0; a < 3; a++) {
            tma_st_2d(&tmX2, cg * 192 + a * 64, m * 64, sA + (3 + a) * 8192);
            tma_st_2d(&tmOut, cg * 192 + a * 64, m * 64, sA + a * 8192);
        }
        bulk_commit();
        bulk_wait_all();
        TS(2, 3);
    }
}

constexpr int F_THREADS = 384;
constexpr int F_NST = 6;
constexpr int F_STAGE = 96 * 128;
constexpr int F_X_BYTES = 9 * 16384;
constexpr int F_OFF_ST = F_X_BYTES;
constexpr int F_OFF_BAR = F_OFF_ST + F_NST * F_STAGE;
constexpr int F_SMEM = F_OFF_BAR + 256;

__device__ __forceinline__ void silu_s1(const float (&acc)[32], float (&tmp)[8], int piece) {
#pragma unroll
    for (int i = 0; i < 8; i++) tmp[i] = ex2(acc[8 * piece + i] * -LOG2E);
}
__device__ __forceinline__ float after_issue(float v, uint32_t tick) {
    uint32_t r;
    asm("lop3.b32 %0, %1, %1, %2, 0xF0;" : "=r"(r) : "r"(__float_as_uint(v)), "r"(tick));
    return __uint_as_float(r);
}
__device__ __forceinline__ uint32_t read_tick() { uint32_t c; asm volatile("mov.u32 %0, %%clock;" : "=r"(c)::"memory"); return c; }
__device__ __forceinline__ void silu_s2(float (&tmp)[8], uint32_t tick) {
    const float one = after_issue(1.0f, tick);
#pragma unroll
    for (int i = 0; i < 8; i++) tmp[i] = rcp(tmp[i] + one);
}
template <int C>
__device__ __forceinline__ void silu_s3(const float (&acc)[32], const float (&tmp)[8], uint32_t (&h1)[144], int piece) {
#pragma unroll
    for (int i = 0; i < 4; i++) h1[C * 16 + 4 * piece + i] = pack_bf16(acc[8 * piece + 2 * i] * tmp[2 * i], acc[8 * piece + 2 * i + 1] * tmp[2 * i + 1]);
}

struct FfnPipe {
    uint32_t full, empty;
    int lane;
    __device__ __forceinline__ void acquire(int s, uint32_t ph) const { mbar_wait(full + s * 8, ph); }
    __device__ __forceinline__ void release(int s) const { if (lane == 0) mbar_arrive(empty + s * 8); }
};

template <int C>
__device__ __forceinline__ void ffn_phase1_chunk(float (&cur)[32], float (&prev)[32], uint32_t (&h1)[144], const FfnPipe& pp, uint64_t dx, uint32_t fullX) {
    float tmp[2][8];
    const uint64_t dw = cdesc(F_OFF_ST, 8192, 1024, 1) + blockIdx.y * (C + 1);
    dx += blockIdx.y * C;
#pragma unroll
    for (int j = 0; j < 6; j++) {
        if (C == 0) { mbar_wait(fullX + ((6 * j) >> 2) * 8, 0); mbar_wait(fullX + ((6 * j + 5) >> 2) * 8, 0); }
        pp.acquire(j, C & 1);
        if (j == 0) pin(cur);
        wg_fence();
#pragma unroll
        for (int i = 0; i < 6; i++) {
            const int ks = 6 * j + i;
            wgmma_ss_n64<1>(cur, dx + ((ks >> 2) * 1024 + (ks & 3) * 2), dw + ((j * F_STAGE + i * 2048) >> 4), ks != 0);
        }
        wg_commit();
        if (C > 0 || j > 0) { wg_wait<1>(); pp.release((j + 5) % 6); }
        if (C > 0) {
            pin(prev);
            if (j >= 1) { pin(tmp[0]); if (j >= 2) pin(tmp[1]); }
            if (j >= 2) silu_s3<(C > 0 ? C - 1 : 0)>(prev, tmp[j & 1], h1, j - 2);
            if (j >= 1 && j <= 4) { silu_s2(tmp[(j - 1) & 1], read_tick()); pin(tmp[(j - 1) & 1]); }
            if (j <= 3) { silu_s1(prev, tmp[j & 1], j); pin(tmp[j & 1]); }
            if (j >= 2) { asm volatile("" : "+r"(h1[(C - 1) * 16 + 4 * (j - 2)]), "+r"(h1[(C - 1) * 16 + 4 * (j - 2) + 1]), "+r"(h1[(C - 1) * 16 + 4 * (j - 2) + 2]), "+r"(h1[(C - 1) * 16 + 4 * (j - 2) + 3]) :: "memory"); }
        }
    }
}

__device__ __forceinline__ void ffn_store_chunk(const float (&acc)[32], const CUtensorMap* tmOut, uint32_t stg, int col, int row, int w, int lane, int wgid) {
    uint32_t pk[16];
#pragma unroll
    for (int i = 0; i < 16; i++) pk[i] = pack_bf16(acc[2 * i], acc[2 * i + 1]);
    stage_tile<8>(pk, stg, w, lane);
    proxy_fence();
    named_sync(2 + wgid, 128);
    if (w == 0 && elect_one()) {
        tma_red_2d(tmOut, col, row, stg);
        bulk_commit();
    }
}

__device__ __forceinline__ void ffn_phase2_chunk(float (&cur)[32], float (&prev)[32], uint32_t (&h1)[144], const FfnPipe& pp, uint32_t ph, bool store_prev, const CUtensorMap* tmOut, uint32_t stg_prev, int col_prev, int row, int w, int lane, int wgid) {
    const uint64_t dw = cdesc(F_OFF_ST, 8192, 1024, 1) + blockIdx.y * col_prev;
#pragma unroll
    for (int j = 0; j < 6; j++) {
        pp.acquire(j, ph);
        if (j == 0) pin(cur);
        wg_fence();
#pragma unroll
        for (int i = 0; i < 6; i++) {
            const int f = (6 * j + i) * 4;
            wgmma_rs_n64<1>(cur, h1[f], h1[f + 1], h1[f + 2], h1[f + 3], dw + ((j * F_STAGE + i * 2048) >> 4), (j | i) != 0);
        }
        wg_commit();
        if (j > 0 || store_prev) { wg_wait<1>(); pp.release((j + 5) % 6); }
        if (j == 0 && store_prev) { pin(prev); ffn_store_chunk(prev, tmOut, stg_prev, col_prev, row, w, lane, wgid); }
    }
}

__global__ void __launch_bounds__(F_THREADS, 1)
k_ffn(const __grid_constant__ CUtensorMap tmH, const __grid_constant__ CUtensorMap tmW1, const __grid_constant__ CUtensorMap tmW2, const __grid_constant__ CUtensorMap tmOut) {
    extern __shared__ __align__(1024) uint8_t smem[];
    const uint32_t sX = smem_u32(smem), sSt = sX + F_OFF_ST, bars = sX + F_OFF_BAR;
    const uint32_t full = bars, empty = bars + 64, fullX = bars + 128;
    const int tid = threadIdx.x, warp = __shfl_sync(~0u, tid >> 5, 0), lane = tid & 31;
    const int m = blockIdx.x & 15, fs = blockIdx.x >> 4;
    if (tid == 0) TS(3, 0);
    check_smem_base(sX);
    if (tid == 0) {
        for (int i = 0; i < F_NST; i++) { mbar_init(full + i * 8, 1); mbar_init(empty + i * 8, 8); }
        for (int i = 0; i < 9; i++) mbar_init(fullX + i * 8, 1);
        bar_init_fence();
    }
    __syncthreads();
    if (warp < 4) {
        asm volatile("setmaxnreg.dec.sync.aligned.u32 24;");
        if (warp == 0 && elect_one()) {
            int s = 0; uint32_t ph = 1;
            int c = 0, j = 0;
#pragma unroll 1
            for (int i = 0; i < 108; i++) {
                if (i == F_NST) {
                    pdl_wait();
                    for (int kb = 0; kb < 9; kb++) {
                        mbar_expect(fullX + kb * 8, 16384);
                        tma_2d(sX + kb * 16384, &tmH, kb * 64, m * 128, fullX + kb * 8);
                    }
                }
                if (i == 54) c = fs;
                mbar_wait(empty + s * 8, ph);
                mbar_expect(full + s * 8, F_STAGE);
                if (i < 54) tma_2d(sSt + s * F_STAGE, &tmW1, fs * 576 + c * 64, j * 96, full + s * 8);
                else tma_2d(sSt + s * F_STAGE, &tmW2, c * 64, fs * 576 + j * 96, full + s * 8);
                if (++j == 6) { j = 0; if (++c == 9) c = 0; }
                if (++s == F_NST) { s = 0; ph ^= 1; }
            }
        }
    } else {
        asm volatile("setmaxnreg.inc.sync.aligned.u32 240;");
        const int wgid = (warp >> 2) - 1, w = warp & 3;
        pdl_wait();
        if (tid == 128) TS(3, 1);
        FfnPipe pp{full, empty, lane};
        const uint64_t xlo = cdesc(0, 16, 1024, 1) + wgid * 512;
        uint32_t h1[144];
        float acc0[32], acc1[32];
        ffn_phase1_chunk<0>(acc0, acc1, h1, pp, xlo, fullX);
        if (tid == 128) TS(3, 2);
        ffn_phase1_chunk<1>(acc1, acc0, h1, pp, xlo, fullX);
        ffn_phase1_chunk<2>(acc0, acc1, h1, pp, xlo, fullX);
        ffn_phase1_chunk<3>(acc1, acc0, h1, pp, xlo, fullX);
        ffn_phase1_chunk<4>(acc0, acc1, h1, pp, xlo, fullX);
        ffn_phase1_chunk<5>(acc1, acc0, h1, pp, xlo, fullX);
        ffn_phase1_chunk<6>(acc0, acc1, h1, pp, xlo, fullX);
        ffn_phase1_chunk<7>(acc1, acc0, h1, pp, xlo, fullX);
        ffn_phase1_chunk<8>(acc0, acc1, h1, pp, xlo, fullX);
        wg_wait<0>();
        pp.release(5);
        pin(acc0);
        {
            float tmp[4][8];
#pragma unroll
            for (int p = 0; p < 4; p++) silu_s1(acc0, tmp[p], p);
#pragma unroll
            for (int p = 0; p < 4; p++) silu_s2(tmp[p], 0);
#pragma unroll
            for (int p = 0; p < 4; p++) silu_s3<8>(acc0, tmp[p], h1, p);
        }
        pin(h1);
        if (tid == 128) TS(3, 3);
        const int row = m * 128 + wgid * 64;
        const uint32_t stg = sX + wgid * 8192;
        int c = fs, cprev = 0;
#pragma unroll 1
        for (int j = 0; j < 8; j += 2) {
            ffn_phase2_chunk(acc1, acc0, h1, pp, 1, j > 0, &tmOut, stg + (j - 1) * 16384, cprev * 64, row, w, lane, wgid);
            cprev = c; if (++c == 9) c = 0;
            ffn_phase2_chunk(acc0, acc1, h1, pp, 0, true, &tmOut, stg + j * 16384, cprev * 64, row, w, lane, wgid);
            cprev = c; if (++c == 9) c = 0;
        }
        ffn_phase2_chunk(acc1, acc0, h1, pp, 1, true, &tmOut, stg + 7 * 16384, cprev * 64, row, w, lane, wgid);
        wg_wait<0>();
        pin(acc1);
        ffn_store_chunk(acc1, &tmOut, stg + 8 * 16384, c * 64, row, w, lane, wgid);
        if (tid == 128) TS(3, 4);
        if (w == 0) bulk_wait_all();
        if (tid == 128) TS(3, 5);
    }
}

typedef CUresult (*EncodeFn)(CUtensorMap*, CUtensorMapDataType, cuuint32_t, void*, const cuuint64_t*, const cuuint64_t*, const cuuint32_t*, const cuuint32_t*,
                             CUtensorMapInterleave, CUtensorMapSwizzle, CUtensorMapL2promotion, CUtensorMapFloatOOBfill);

CUtensorMap make_map(EncodeFn enc, const void* base, int rows, int cols, int box_rows) {
    CUtensorMap tm;
    cuuint64_t dims[2] = {(cuuint64_t)cols, (cuuint64_t)rows};
    cuuint64_t strides[1] = {(cuuint64_t)cols * 2};
    cuuint32_t box[2] = {64, (cuuint32_t)box_rows};
    cuuint32_t es[2] = {1, 1};
    enc(&tm, CU_TENSOR_MAP_DATA_TYPE_BFLOAT16, 2, const_cast<void*>(base), dims, strides, box, es, CU_TENSOR_MAP_INTERLEAVE_NONE,
        CU_TENSOR_MAP_SWIZZLE_128B, CU_TENSOR_MAP_L2_PROMOTION_L2_256B, CU_TENSOR_MAP_FLOAT_OOB_FILL_NONE);
    return tm;
}

template <typename... KArgs, typename... Args>
void launch(void (*kern)(KArgs...), int grid, int block, int smem, bool pdl, Args... args) {
    cudaLaunchConfig_t cfg = {};
    cfg.gridDim = dim3(grid); cfg.blockDim = dim3(block); cfg.dynamicSmemBytes = smem; cfg.stream = cudaStreamPerThread;
    cudaLaunchAttribute at[1];
    at[0].id = cudaLaunchAttributeProgrammaticStreamSerialization;
    at[0].val.programmaticStreamSerializationAllowed = 1;
    cfg.attrs = at; cfg.numAttrs = pdl ? 1 : 0;
    cudaLaunchKernelEx(&cfg, kern, KArgs(args)...);
}

}

#define USE_PDL 1

extern "C" void kernel_launch(void* const* d_in, const int* in_sizes, int n_in, void* d_out, int out_size) {
    const __nv_bfloat16* x = (const __nv_bfloat16*)d_in[0];
    const __nv_bfloat16* wq = (const __nv_bfloat16*)d_in[1];
    const __nv_bfloat16* wk = (const __nv_bfloat16*)d_in[2];
    const __nv_bfloat16* wv = (const __nv_bfloat16*)d_in[3];
    const __nv_bfloat16* wo = (const __nv_bfloat16*)d_in[4];
    const __nv_bfloat16* w1 = (const __nv_bfloat16*)d_in[6];
    const __nv_bfloat16* w2 = (const __nv_bfloat16*)d_in[7];
    __nv_bfloat16* out = (__nv_bfloat16*)d_out;

    static EncodeFn enc = nullptr;
    static void *p_o = nullptr, *p_h = nullptr, *p_q = nullptr;
    if (!enc) {
        cudaDriverEntryPointQueryResult qr;
        cudaGetDriverEntryPoint("cuTensorMapEncodeTiled", (void**)&enc, cudaEnableDefault, &qr);
        cudaGetSymbolAddress(&p_o, g_o);
        cudaGetSymbolAddress(&p_h, g_x2);
        cudaGetSymbolAddress(&p_q, g_q);
        cudaFuncSetAttribute(k_qkv, cudaFuncAttributeMaxDynamicSharedMemorySize, P_SMEM);
        cudaFuncSetAttribute(k_attn, cudaFuncAttributeMaxDynamicSharedMemorySize, A_SMEM);
        cudaFuncSetAttribute(k_oproj, cudaFuncAttributeMaxDynamicSharedMemorySize, P_SMEM);
        cudaFuncSetAttribute(k_ffn, cudaFuncAttributeMaxDynamicSharedMemorySize, F_SMEM);
    }
    const CUtensorMap tmWq = make_map(enc, wq, DM, DM, 64);
    const CUtensorMap tmWo = make_map(enc, wo, DM, DM, 64);
    const CUtensorMap tmO = make_map(enc, p_o, SEQ, DM, 64);
    const CUtensorMap tmH = make_map(enc, p_h, SEQ, DM, 128);
    const CUtensorMap tmH64 = make_map(enc, p_h, SEQ, DM, 64);
    const CUtensorMap tmQ = make_map(enc, p_q, SEQ, DM, 64);
    const CUtensorMap tmW1 = make_map(enc, w1, DM, FF, 96);
    const CUtensorMap tmW2 = make_map(enc, w2, FF, DM, 96);
    const CUtensorMap tmOut = make_map(enc, out, SEQ, DM, 64);

    launch(k_qkv, 128, P_THREADS, P_SMEM, false, tmWq, tmQ, x, wk, wv);
    launch(k_attn, 132, A_THREADS, A_SMEM, USE_PDL, w1, w2, wo);
    launch(k_oproj, 96, P_THREADS, P_SMEM, USE_PDL, tmO, tmWo, tmH64, tmOut, x);
    launch(k_ffn, 128, F_THREADS, F_SMEM, USE_PDL, tmH, tmW1, tmW2, tmOut);
}
```

```cpp
#include <cuda_runtime.h>
#include <cuda_bf16.h>
#include <cuda.h>
#include <stdint.h>

namespace {

constexpr int SEQ = 2048, DM = 576, FF = 4608;
constexpr int KV_BYTES = SEQ * 48;
constexpr float LN_EPS = 1e-5f;
constexpr float LOG2E = 1.4426950408889634f;
constexpr float Q_SCALE = 0.23570226039551584f * LOG2E;

#define POLY_MASK_V 0xB5B5u
constexpr uint32_t POLY_MASK = POLY_MASK_V;
constexpr float FAST_BOUND = 60.0f;

__device__ __align__(1024) __nv_bfloat16 g_q[SEQ * DM];
__device__ __align__(1024) uint4 g_kc[KV_BYTES / 16];
__device__ __align__(1024) uint4 g_vc[KV_BYTES / 16];
__device__ float g_kmax[32];
__device__ __align__(1024) __nv_bfloat16 g_o[SEQ * DM];
__device__ __align__(1024) __nv_bfloat16 g_x2[SEQ * DM];

#define TS(k, i)

__device__ __forceinline__ uint32_t smem_u32(const void* p) { return (uint32_t)__cvta_generic_to_shared(p); }
__device__ __forceinline__ void wg_fence() { asm volatile("wgmma.fence.sync.aligned;" ::: "memory"); }
__device__ __forceinline__ void wg_commit() { asm volatile("wgmma.commit_group.sync.aligned;" ::: "memory"); }
template <int N> __device__ __forceinline__ void wg_wait() { asm volatile("wgmma.wait_group.sync.aligned %0;" ::"n"(N) : "memory"); }
template <int N> __device__ __forceinline__ void pin(float (&r)[N]) {
#pragma unroll
    for (int i = 0; i < N; i++) asm volatile("" : "+f"(r[i])::"memory");
}
template <int N> __device__ __forceinline__ void pin(uint32_t (&r)[N]) {
#pragma unroll
    for (int i = 0; i < N; i++) asm volatile("" : "+r"(r[i])::"memory");
}
__device__ __forceinline__ constexpr uint32_t desc_hi(uint32_t sbo, uint32_t swz) { return (sbo >> 4) | (swz << 30); }
__device__ __forceinline__ uint32_t desc_lo(uint32_t addr, uint32_t lbo) { return ((addr & 0x3FFFF) >> 4) | ((lbo >> 4) << 16); }
__device__ __forceinline__ uint64_t desc64(uint32_t lo, uint32_t hi) { return ((uint64_t)hi << 32) | lo; }
constexpr uint32_t SMEM0 = 0x400;
__host__ __device__ constexpr uint64_t cdesc(uint32_t off, uint32_t lbo, uint32_t sbo, uint32_t swz) {
    return (uint64_t)(((SMEM0 + off) & 0x3FFFF) >> 4) | ((uint64_t)(lbo >> 4) << 16) | ((uint64_t)(sbo >> 4) << 32) | ((uint64_t)swz << 62);
}
__device__ __forceinline__ void check_smem_base(uint32_t base) { if ((base & 0x3FFFF) != SMEM0) __trap(); }

__device__ __forceinline__ void mbar_init(uint32_t bar, int cnt) { asm volatile("mbarrier.init.shared::cta.b64 [%0], %1;" ::"r"(bar), "r"(cnt) : "memory"); }
__device__ __forceinline__ void mbar_expect(uint32_t bar, int bytes) { asm volatile("mbarrier.arrive.expect_tx.shared::cta.b64 _, [%0], %1;" ::"r"(bar), "r"(bytes) : "memory"); }
__device__ __forceinline__ void mbar_arrive(uint32_t bar) { asm volatile("mbarrier.arrive.shared::cta.b64 _, [%0];" ::"r"(bar) : "memory"); }
__device__ __forceinline__ void mbar_wait(uint32_t bar, uint32_t parity) {
    asm volatile(
        "{\n.reg .pred p;\n.reg .u32 n;\nmov.u32 n, 0;\n"
        "LAB_WAIT:\n"
        "mbarrier.try_wait.parity.shared::cta.b64 p, [%0], %1;\n"
        "@p bra DONE;\n"
        "add.u32 n, n, 1;\n"
        "setp.lt.u32 p, n, 4000000;\n"
        "@p bra LAB_WAIT;\n"
        "trap;\n"
        "DONE:\n}\n" ::"r"(bar), "r"(parity) : "memory");
}
__device__ __forceinline__ void bar_init_fence() {
    asm volatile("fence.mbarrier_init.release.cluster;" ::: "memory");
    asm volatile("fence.proxy.async.shared::cta;" ::: "memory");
}
__device__ __forceinline__ void proxy_fence() { asm volatile("fence.proxy.async.shared::cta;" ::: "memory"); }
__device__ __forceinline__ void named_sync(int id, int n) { asm volatile("bar.sync %0, %1;" ::"r"(id), "r"(n) : "memory"); }
__device__ __forceinline__ void bulk_g2s(uint32_t dst, const void* src, int bytes, uint32_t bar) {
    asm volatile("cp.async.bulk.shared::cluster.global.mbarrier::complete_tx::bytes [%0], [%1], %2, [%3];" ::"r"(dst), "l"(src), "r"(bytes), "r"(bar) : "memory");
}
__device__ __forceinline__ void tma_2d(uint32_t dst, const CUtensorMap* tm, int c0, int c1, uint32_t bar) {
    asm volatile("cp.async.bulk.tensor.2d.shared::cluster.global.mbarrier::complete_tx::bytes [%0], [%1, {%3, %4}], [%2];" ::"r"(dst), "l"(tm), "r"(bar), "r"(c0), "r"(c1) : "memory");
}
__device__ __forceinline__ void tma_red_2d(const CUtensorMap* tm, int c0, int c1, uint32_t src) {
    asm volatile("cp.reduce.async.bulk.tensor.2d.global.shared::cta.add.tile.bulk_group [%0, {%2, %3}], [%1];" ::"l"(tm), "r"(src), "r"(c0), "r"(c1) : "memory");
}
__device__ __forceinline__ void tma_st_2d(const CUtensorMap* tm, int c0, int c1, uint32_t src) {
    asm volatile("cp.async.bulk.tensor.2d.global.shared::cta.tile.bulk_group [%0, {%2, %3}], [%1];" ::"l"(tm), "r"(src), "r"(c0), "r"(c1) : "memory");
}
__device__ __forceinline__ void bulk_commit() { asm volatile("cp.async.bulk.commit_group;" ::: "memory"); }
__device__ __forceinline__ void bulk_wait_all() { asm volatile("cp.async.bulk.wait_group.read 0;" ::: "memory"); }
__device__ __forceinline__ bool elect_one() {
    uint32_t p;
    asm volatile("{\n.reg .pred P;\nelect.sync _|P, 0xffffffff;\nselp.b32 %0, 1, 0, P;\n}\n" : "=r"(p));
    return p != 0;
}
__device__ __forceinline__ void prefetch_l2(const void* p, int bytes) { asm volatile("cp.async.bulk.prefetch.L2.global [%0], %1;" ::"l"(p), "r"(bytes) : "memory"); }
__device__ __forceinline__ void pdl_launch() { asm volatile("griddepcontrol.launch_dependents;" ::: "memory"); }
__device__ __forceinline__ void pdl_wait() { asm volatile("griddepcontrol.wait;" ::: "memory"); }
__device__ __forceinline__ float ex2(float x) { float y; asm("ex2.approx.ftz.f32 %0, %1;" : "=f"(y) : "f"(x)); return y; }
__device__ __forceinline__ float rcp(float x) { float y; asm("rcp.approx.ftz.f32 %0, %1;" : "=f"(y) : "f"(x)); return y; }
__device__ __forceinline__ uint32_t pack_bf16(float lo, float hi) { uint32_t r; asm("cvt.rn.bf16x2.f32 %0, %1, %2;" : "=r"(r) : "f"(hi), "f"(lo)); return r; }
__device__ __forceinline__ float bf_lo(uint32_t v) { return __uint_as_float(v << 16); }
__device__ __forceinline__ float bf_hi(uint32_t v) { return __uint_as_float(v & 0xFFFF0000u); }
__device__ __forceinline__ uint32_t hfma2(uint32_t a, uint32_t b, uint32_t c) { uint32_t r; asm("fma.rn.f16x2 %0, %1, %2, %3;" : "=r"(r) : "r"(a), "r"(b), "r"(c)); return r; }
__device__ __forceinline__ void stmatrix_x4(uint32_t addr, uint32_t r0, uint32_t r1, uint32_t r2, uint32_t r3) {
    asm volatile("stmatrix.sync.aligned.m8n8.x4.shared.b16 [%0], {%1, %2, %3, %4};" ::"r"(addr), "r"(r0), "r"(r1), "r"(r2), "r"(r3) : "memory");
}

template <int TB> __device__ __forceinline__ void wgmma_ss_n24(float (&d)[12], uint64_t da, uint64_t db, int sc) {
    asm volatile("{\n.reg .pred p;\nsetp.ne.b32 p, %14, 0;\n"
        "wgmma.mma_async.sync.aligned.m64n24k16.f32.bf16.bf16 {%0, %1, %2, %3, %4, %5, %6, %7, %8, %9, %10, %11}, %12, %13, p, 1, 1, 0, %15;\n}\n"
        : "+f"(d[0]), "+f"(d[1]), "+f"(d[2]), "+f"(d[3]), "+f"(d[4]), "+f"(d[5]), "+f"(d[6]), "+f"(d[7]), "+f"(d[8]), "+f"(d[9]), "+f"(d[10]), "+f"(d[11])
        : "l"(da), "l"(db), "r"(sc), "n"(TB));
}
template <int TB> __device__ __forceinline__ void wgmma_ss_n64(float (&d)[32], uint64_t da, uint64_t db, int sc) {
    asm volatile("{\n.reg .pred p;\nsetp.ne.b32 p, %34, 0;\n"
        "wgmma.mma_async.sync.aligned.m64n64k16.f32.bf16.bf16 {%0, %1, %2, %3, %4, %5, %6, %7, %8, %9, %10, %11, %12, %13, %14, %15, %16, %17, %18, %19, %20, %21, %22, %23, %24, %25, %26, %27, %28, %29, %30, %31}, %32, %33, p, 1, 1, 0, %35;\n}\n"
        : "+f"(d[0]), "+f"(d[1]), "+f"(d[2]), "+f"(d[3]), "+f"(d[4]), "+f"(d[5]), "+f"(d[6]), "+f"(d[7]), "+f"(d[8]), "+f"(d[9]), "+f"(d[10]), "+f"(d[11]), "+f"(d[12]), "+f"(d[13]), "+f"(d[14]), "+f"(d[15]), "+f"(d[16]), "+f"(d[17]), "+f"(d[18]), "+f"(d[19]), "+f"(d[20]), "+f"(d[21]), "+f"(d[22]), "+f"(d[23]), "+f"(d[24]), "+f"(d[25]), "+f"(d[26]), "+f"(d[27]), "+f"(d[28]), "+f"(d[29]), "+f"(d[30]), "+f"(d[31])
        : "l"(da), "l"(db), "r"(sc), "n"(TB));
}
template <int TB> __device__ __forceinline__ void wgmma_ss_n128(float (&d)[64], uint64_t da, uint64_t db, int sc) {
    asm volatile("{\n.reg .pred p;\nsetp.ne.b32 p, %66, 0;\n"
        "wgmma.mma_async.sync.aligned.m64n128k16.f32.bf16.bf16 {%0, %1, %2, %3, %4, %5, %6, %7, %8, %9, %10, %11, %12, %13, %14, %15, %16, %17, %18, %19, %20, %21, %22, %23, %24, %25, %26, %27, %28, %29, %30, %31, %32, %33, %34, %35, %36, %37, %38, %39, %40, %41, %42, %43, %44, %45, %46, %47, %48, %49, %50, %51, %52, %53, %54, %55, %56, %57, %58, %59, %60, %61, %62, %63}, %64, %65, p, 1, 1, 0, %67;\n}\n"
        : "+f"(d[0]), "+f"(d[1]), "+f"(d[2]), "+f"(d[3]), "+f"(d[4]), "+f"(d[5]), "+f"(d[6]), "+f"(d[7]), "+f"(d[8]), "+f"(d[9]), "+f"(d[10]), "+f"(d[11]), "+f"(d[12]), "+f"(d[13]), "+f"(d[14]), "+f"(d[15]), "+f"(d[16]), "+f"(d[17]), "+f"(d[18]), "+f"(d[19]), "+f"(d[20]), "+f"(d[21]), "+f"(d[22]), "+f"(d[23]), "+f"(d[24]), "+f"(d[25]), "+f"(d[26]), "+f"(d[27]), "+f"(d[28]), "+f"(d[29]), "+f"(d[30]), "+f"(d[31]), "+f"(d[32]), "+f"(d[33]), "+f"(d[34]), "+f"(d[35]), "+f"(d[36]), "+f"(d[37]), "+f"(d[38]), "+f"(d[39]), "+f"(d[40]), "+f"(d[41]), "+f"(d[42]), "+f"(d[43]), "+f"(d[44]), "+f"(d[45]), "+f"(d[46]), "+f"(d[47]), "+f"(d[48]), "+f"(d[49]), "+f"(d[50]), "+f"(d[51]), "+f"(d[52]), "+f"(d[53]), "+f"(d[54]), "+f"(d[55]), "+f"(d[56]), "+f"(d[57]), "+f"(d[58]), "+f"(d[59]), "+f"(d[60]), "+f"(d[61]), "+f"(d[62]), "+f"(d[63])
        : "l"(da), "l"(db), "r"(sc), "n"(TB));
}
template <int TB> __device__ __forceinline__ void wgmma_rs_n24(float (&d)[12], uint32_t a0, uint32_t a1, uint32_t a2, uint32_t a3, uint64_t db, int sc) {
    asm volatile("{\n.reg .pred p;\nsetp.ne.b32 p, %17, 0;\n"
        "wgmma.mma_async.sync.aligned.m64n24k16.f32.bf16.bf16 {%0, %1, %2, %3, %4, %5, %6, %7, %8, %9, %10, %11}, {%12, %13, %14, %15}, %16, p, 1, 1, %18;\n}\n"
        : "+f"(d[0]), "+f"(d[1]), "+f"(d[2]), "+f"(d[3]), "+f"(d[4]), "+f"(d[5]), "+f"(d[6]), "+f"(d[7]), "+f"(d[8]), "+f"(d[9]), "+f"(d[10]), "+f"(d[11])
        : "r"(a0), "r"(a1), "r"(a2), "r"(a3), "l"(db), "r"(sc), "n"(TB));
}
template <int TB> __device__ __forceinline__ void wgmma_rs_n64(float (&d)[32], uint32_t a0, uint32_t a1, uint32_t a2, uint32_t a3, uint64_t db, int sc) {
    asm volatile("{\n.reg .pred p;\nsetp.ne.b32 p, %37, 0;\n"
        "wgmma.mma_async.sync.aligned.m64n64k16.f32.bf16.bf16 {%0, %1, %2, %3, %4, %5, %6, %7, %8, %9, %10, %11, %12, %13, %14, %15, %16, %17, %18, %19, %20, %21, %22, %23, %24, %25, %26, %27, %28, %29, %30, %31}, {%32, %33, %34, %35}, %36, p, 1, 1, %38;\n}\n"
        : "+f"(d[0]), "+f"(d[1]), "+f"(d[2]), "+f"(d[3]), "+f"(d[4]), "+f"(d[5]), "+f"(d[6]), "+f"(d[7]), "+f"(d[8]), "+f"(d[9]), "+f"(d[10]), "+f"(d[11]), "+f"(d[12]), "+f"(d[13]), "+f"(d[14]), "+f"(d[15]), "+f"(d[16]), "+f"(d[17]), "+f"(d[18]), "+f"(d[19]), "+f"(d[20]), "+f"(d[21]), "+f"(d[22]), "+f"(d[23]), "+f"(d[24]), "+f"(d[25]), "+f"(d[26]), "+f"(d[27]), "+f"(d[28]), "+f"(d[29]), "+f"(d[30]), "+f"(d[31])
        : "r"(a0), "r"(a1), "r"(a2), "r"(a3), "l"(db), "r"(sc), "n"(TB));
}
template <int TB> __device__ __forceinline__ void wgmma_rs_n128(float (&d)[64], uint32_t a0, uint32_t a1, uint32_t a2, uint32_t a3, uint64_t db, int sc) {
    asm volatile("{\n.reg .pred p;\nsetp.ne.b32 p, %69, 0;\n"
        "wgmma.mma_async.sync.aligned.m64n128k16.f32.bf16.bf16 {%0, %1, %2, %3, %4, %5, %6, %7, %8, %9, %10, %11, %12, %13, %14, %15, %16, %17, %18, %19, %20, %21, %22, %23, %24, %25, %26, %27, %28, %29, %30, %31, %32, %33, %34, %35, %36, %37, %38, %39, %40, %41, %42, %43, %44, %45, %46, %47, %48, %49, %50, %51, %52, %53, %54, %55, %56, %57, %58, %59, %60, %61, %62, %63}, {%64, %65, %66, %67}, %68, p, 1, 1, %70;\n}\n"
        : "+f"(d[0]), "+f"(d[1]), "+f"(d[2]), "+f"(d[3]), "+f"(d[4]), "+f"(d[5]), "+f"(d[6]), "+f"(d[7]), "+f"(d[8]), "+f"(d[9]), "+f"(d[10]), "+f"(d[11]), "+f"(d[12]), "+f"(d[13]), "+f"(d[14]), "+f"(d[15]), "+f"(d[16]), "+f"(d[17]), "+f"(d[18]), "+f"(d[19]), "+f"(d[20]), "+f"(d[21]), "+f"(d[22]), "+f"(d[23]), "+f"(d[24]), "+f"(d[25]), "+f"(d[26]), "+f"(d[27]), "+f"(d[28]), "+f"(d[29]), "+f"(d[30]), "+f"(d[31]), "+f"(d[32]), "+f"(d[33]), "+f"(d[34]), "+f"(d[35]), "+f"(d[36]), "+f"(d[37]), "+f"(d[38]), "+f"(d[39]), "+f"(d[40]), "+f"(d[41]), "+f"(d[42]), "+f"(d[43]), "+f"(d[44]), "+f"(d[45]), "+f"(d[46]), "+f"(d[47]), "+f"(d[48]), "+f"(d[49]), "+f"(d[50]), "+f"(d[51]), "+f"(d[52]), "+f"(d[53]), "+f"(d[54]), "+f"(d[55]), "+f"(d[56]), "+f"(d[57]), "+f"(d[58]), "+f"(d[59]), "+f"(d[60]), "+f"(d[61]), "+f"(d[62]), "+f"(d[63])
        : "r"(a0), "r"(a1), "r"(a2), "r"(a3), "l"(db), "r"(sc), "n"(TB));
}

constexpr int P_THREADS = 288;
constexpr int P_NST = 6;
constexpr int P_A_BYTES = 9 * 8192;
constexpr int P_B_STAGE = 3 * 8192;
constexpr int P_SMEM = P_A_BYTES + P_NST * P_B_STAGE + 256 + 320;
constexpr uint32_t HI_SW128 = (1024u >> 4) | (1u << 30);

template <int NCOL, bool WAIT_A>
__device__ __forceinline__ void proj_mma(float (&acc)[NCOL / 2], uint32_t sA, uint32_t sB, uint32_t colofs, uint32_t fullB, uint32_t emptyB, uint32_t fullA, int lane) {
#pragma unroll 1
    for (int kb = 0; kb < 9; kb++) {
        const int s = kb >= P_NST ? kb - P_NST : kb;
        if (WAIT_A) mbar_wait(fullA + kb * 8, 0);
        mbar_wait(fullB + s * 8, kb >= P_NST ? 1 : 0);
        const uint32_t alo = desc_lo(sA + kb * 8192, 16), blo = desc_lo(sB + s * P_B_STAGE + colofs, 8192);
        wg_fence();
#pragma unroll
        for (int ks = 0; ks < 4; ks++) {
            const uint64_t da = desc64(alo + ks * 2, HI_SW128), db = desc64(blo + ks * 128, HI_SW128);
            if constexpr (NCOL == 128) wgmma_ss_n128<1>(acc, da, db, (kb | ks) != 0);
            else wgmma_ss_n64<1>(acc, da, db, (kb | ks) != 0);
        }
        wg_commit();
        if (kb + P_NST < 9 + 1) {
            wg_wait<1>();
            if (kb >= 1 && kb - 1 + P_NST < 9 && lane == 0) mbar_arrive(emptyB + (kb - 1) * 8);
        }
    }
    wg_wait<0>();
    pin(acc);
}

template <int NB>
__device__ __forceinline__ void stage_tile(const uint32_t (&pk)[NB * 2], uint32_t base, int w, int lane) {
    const int r = w * 16 + (lane & 7) + ((lane >> 3) & 1) * 8;
#pragma unroll
    for (int b = 0; b < NB; b += 2) {
        const uint32_t a = base + (b >> 3) * 8192 + r * 128 + ((((b & 7) + (lane >> 4)) ^ (r & 7)) << 4);
        stmatrix_x4(a, pk[2 * b], pk[2 * b + 1], pk[2 * b + 2], pk[2 * b + 3]);
    }
}

__device__ __forceinline__ uint32_t hsub2_bf16(uint32_t a, uint32_t b) { uint32_t r; asm("sub.rn.bf16x2 %0, %1, %2;" : "=r"(r) : "r"(a), "r"(b)); return r; }

constexpr int KV_RAW = DM * 18 * 2;

__global__ void __launch_bounds__(P_THREADS, 1)
k_qkv(const __grid_constant__ CUtensorMap tmWq, const __grid_constant__ CUtensorMap tmQ, const __nv_bfloat16* __restrict__ x, const __nv_bfloat16* __restrict__ wk, const __nv_bfloat16* __restrict__ wv) {
    extern __shared__ __align__(1024) uint8_t smem[];
    const uint32_t sA = smem_u32(smem), sB = sA + P_A_BYTES, bars = sB + P_NST * P_B_STAGE;
    const uint32_t fullB = bars, emptyB = bars + 64, fullX = bars + 128, fullW = bars + 136, rawFree = bars + 144;
    const uint32_t sRaw = sB + 3 * P_B_STAGE;
    float* s_rstd = reinterpret_cast<float*>(smem + P_A_BYTES + P_NST * P_B_STAGE + 256);
    const int tid = threadIdx.x, warp = __shfl_sync(~0u, tid >> 5, 0), lane = tid & 31;
    const bool isQ = blockIdx.x < 96;
    const int m = isQ ? blockIdx.x / 3 : blockIdx.x - 96, cg = blockIdx.x % 3;
    if (tid == 0) TS(0, 0);
    if (warp == 8) {
        if (elect_one()) {
            for (int i = 0; i < P_NST; i++) { mbar_init(fullB + i * 8, 1); mbar_init(emptyB + i * 8, 8); }
            mbar_init(fullX, 1); mbar_init(fullW, 1); mbar_init(rawFree, 8);
            bar_init_fence();
            mbar_expect(fullX, P_A_BYTES);
            bulk_g2s(sRaw, x + (size_t)m * 64 * DM, P_A_BYTES, fullX);
            if (isQ) {
                for (int kb = 0; kb < 3; kb++) {
                    mbar_expect(fullB + kb * 8, P_B_STAGE);
                    for (int a = 0; a < 3; a++) tma_2d(sB + kb * P_B_STAGE + a * 8192, &tmWq, cg * 192 + a * 64, kb * 64, fullB + kb * 8);
                }
            } else {
                mbar_expect(fullW, 2 * KV_RAW);
                bulk_g2s(sA, wk, KV_RAW, fullW);
                bulk_g2s(sA + KV_RAW, wv, KV_RAW, fullW);
            }
        }
        __syncwarp();
    }
    __syncthreads();
    pdl_launch();
    if (warp == 8) {
        if (isQ && elect_one()) {
            mbar_wait(rawFree, 0);
            for (int kb = 3; kb < 9; kb++) {
                const int s = kb >= P_NST ? kb - P_NST : kb;
                if (kb >= P_NST) mbar_wait(emptyB + s * 8, 0);
                mbar_expect(fullB + s * 8, P_B_STAGE);
                for (int a = 0; a < 3; a++) tma_2d(sB + s * P_B_STAGE + a * 8192, &tmWq, cg * 192 + a * 64, kb * 64, fullB + s * 8);
            }
        }
        return;
    }
    {
        const int row = tid >> 2, q = tid & 3, odd = row & 1;
        mbar_wait(fullX, 0);
        if (tid == 0) TS(0, 6);
        uint4 v[18];
#pragma unroll
        for (int i = 0; i < 18; i++)
            asm volatile("ld.shared.v4.b32 {%0, %1, %2, %3}, [%4];" : "=r"(v[i].x), "=r"(v[i].y), "=r"(v[i].z), "=r"(v[i].w) : "r"(sRaw + row * 1152 + (q + 4 * (i ^ odd)) * 16));
        float sum = 0.f, sum2 = 0.f, sq = 0.f, sq2 = 0.f;
#pragma unroll
        for (int i = 0; i < 18; i++) {
            const uint32_t w[4] = {v[i].x, v[i].y, v[i].z, v[i].w};
#pragma unroll
            for (int j = 0; j < 4; j++) { const float a = bf_lo(w[j]), b = bf_hi(w[j]); sum += a; sum2 += b; sq = fmaf(a, a, sq); sq2 = fmaf(b, b, sq2); }
        }
        __syncwarp();
        if (lane == 0) mbar_arrive(rawFree);
        sum += sum2; sq += sq2;
        sum += __shfl_xor_sync(~0u, sum, 1); sum += __shfl_xor_sync(~0u, sum, 2);
        sq += __shfl_xor_sync(~0u, sq, 1); sq += __shfl_xor_sync(~0u, sq, 2);
        if (tid == 0) TS(0, 4);
        if (!isQ) {
            mbar_wait(fullW, 0);
            if (tid == 0) TS(0, 7);
            const uint32_t* raw = reinterpret_cast<const uint32_t*>(smem);
            uint32_t wr[41];
#pragma unroll
            for (int i = 0; i < 40; i++) wr[i] = raw[tid + i * 256];
            wr[40] = raw[(tid & 127) + 40 * 256];
            int k = tid / 9, r = tid - k * 9;
#pragma unroll
            for (int i = 0; i < 41; i++) {
                const int sel = k >= DM, kk = k - sel * DM;
                uint32_t* dst = reinterpret_cast<uint32_t*>(smem + P_A_BYTES + (sel * 3 + (r >> 2)) * 9216 + (kk >> 3) * 128 + (kk & 7) * 16 + (r & 3) * 4);
                if (i < 40 || tid < 128) *dst = wr[i];
                k += 28; r += 4;
                if (r >= 9) { r -= 9; k++; }
            }
            named_sync(1, 256);
            if (tid == 0) TS(0, 8);
        }
        const float mean = sum * (1.0f / DM);
        if (q == 0) s_rstd[row] = rsqrtf(fmaxf(sq * (1.0f / DM) - mean * mean, 0.f) + LN_EPS);
        const uint32_t mhi = pack_bf16(mean, mean);
        const float rem = mean - bf_lo(mhi);
        const uint32_t mlo = pack_bf16(rem, rem);
#pragma unroll
        for (int i = 0; i < 18; i++) {
            const int c = q + 4 * (i ^ odd);
            const uint32_t o0 = hsub2_bf16(hsub2_bf16(v[i].x, mhi), mlo), o1 = hsub2_bf16(hsub2_bf16(v[i].y, mhi), mlo);
            const uint32_t o2 = hsub2_bf16(hsub2_bf16(v[i].z, mhi), mlo), o3 = hsub2_bf16(hsub2_bf16(v[i].w, mhi), mlo);
            asm volatile("st.shared.v4.b32 [%0], {%1, %2, %3, %4};" ::"r"(sA + (c >> 3) * 8192 + row * 128 + (((c & 7) ^ (row & 7)) << 4)), "r"(o0), "r"(o1), "r"(o2), "r"(o3) : "memory");
        }
    }
    proxy_fence();
    named_sync(1, 256);
    if (tid == 0) TS(0, 1);
    const int wg = warp >> 2, w = warp & 3, g = lane >> 2, t = lane & 3;
    const float rs0 = s_rstd[w * 16 + g], rs1 = s_rstd[w * 16 + g + 8];
    if (isQ) {
        const float c0 = rs0 * Q_SCALE, c1 = rs1 * Q_SCALE;
        if (wg == 0) {
            float acc[64];
            proj_mma<128, false>(acc, sA, sB, 0, fullB, emptyB, 0, lane);
            if (tid == 0) TS(0, 2);
            named_sync(1, 256);
            uint32_t pk[32];
#pragma unroll
            for (int i = 0; i < 16; i++) { pk[2 * i] = pack_bf16(acc[4 * i] * c0, acc[4 * i + 1] * c0); pk[2 * i + 1] = pack_bf16(acc[4 * i + 2] * c1, acc[4 * i + 3] * c1); }
            stage_tile<16>(pk, sA, w, lane);
        } else {
            float acc[32];
            proj_mma<64, false>(acc, sA, sB, 2 * 8192, fullB, emptyB, 0, lane);
            named_sync(1, 256);
            uint32_t pk[16];
#pragma unroll
            for (int i = 0; i < 8; i++) { pk[2 * i] = pack_bf16(acc[4 * i] * c0, acc[4 * i + 1] * c0); pk[2 * i + 1] = pack_bf16(acc[4 * i + 2] * c1, acc[4 * i + 3] * c1); }
            stage_tile<8>(pk, sA + 2 * 8192, w, lane);
        }
        proxy_fence();
        named_sync(1, 256);
        if (warp == 0 && elect_one()) {
            for (int a = 0; a < 3; a++) tma_st_2d(&tmQ, cg * 192 + a * 64, m * 64, sA + a * 8192);
            bulk_commit();
            bulk_wait_all();
        }
    } else {
        float acc[12];
        const uint32_t blo = desc_lo(sB + wg * 3 * 9216, 128);
#pragma unroll
        for (int i = 0; i < 12; i++) acc[i] = 0.f;
        pin(acc);
        wg_fence();
#pragma unroll 1
        for (int kb = 0; kb < 9; kb++) {
            const uint32_t alo = desc_lo(sA + kb * 8192, 16);
#pragma unroll
            for (int ks = 0; ks < 4; ks++)
                wgmma_ss_n24<1>(acc, desc64(alo + ks * 2, HI_SW128), desc64(blo + (kb * 4 + ks) * 16, desc_hi(9216, 0)), 1);
        }
        wg_commit();
        wg_wait<0>();
        pin(acc);
        uint32_t pk[6];
#pragma unroll
        for (int b = 0; b < 3; b++) { pk[2 * b] = pack_bf16(acc[4 * b] * rs0, acc[4 * b + 1] * rs0); pk[2 * b + 1] = pack_bf16(acc[4 * b + 2] * rs1, acc[4 * b + 3] * rs1); }
        float n0 = 0.f, n1 = 0.f, vm = 0.f;
#pragma unroll
        for (int b = 0; b < 3; b++) {
            if (b < 2 || t == 0) {
                const float a = bf_lo(pk[2 * b]), c = bf_hi(pk[2 * b]), d = bf_lo(pk[2 * b + 1]), e = bf_hi(pk[2 * b + 1]);
                n0 = fmaf(a, a, fmaf(c, c, n0)); n1 = fmaf(d, d, fmaf(e, e, n1));
            }
        }
        n0 += __shfl_xor_sync(~0u, n0, 1); n0 += __shfl_xor_sync(~0u, n0, 2);
        n1 += __shfl_xor_sync(~0u, n1, 1); n1 += __shfl_xor_sync(~0u, n1, 2);
        vm = fmaxf(n0, n1);
        if (!(n0 == n0) || !(n1 == n1)) vm = __int_as_float(0x7F800000);
#pragma unroll
        for (int o = 4; o < 32; o <<= 1) vm = fmaxf(vm, __shfl_xor_sync(~0u, vm, o));
        if (t != 0) {
            uint32_t lo, hi;
            if (wg == 0) {
                const int grp = m * 8 + w * 2;
                const uint32_t c = t == 1 ? 0x42FE3F80u   : (t == 2 ? 0x00003BC0u   : 0u);
                lo = ((POLY_MASK >> (grp & 15)) & 1) ? c : 0u;
                hi = ((POLY_MASK >> ((grp + 1) & 15)) & 1) ? c : 0u;
            } else {
                lo = hi = t == 1 ? 0x00003F80u : 0u;
            }
            pk[4] = lo; pk[5] = hi;
        }
        uint32_t* dst = reinterpret_cast<uint32_t*>(wg == 0 ? g_kc : g_vc) + (m * 8 + w * 2) * 96 + g * 4 + t;
#pragma unroll
        for (int b = 0; b < 3; b++) { dst[b * 32] = pk[2 * b]; dst[96 + b * 32] = pk[2 * b + 1]; }
        float* red = s_rstd + 64;
        if (lane == 0) red[warp] = (wg == 0) ? vm : (vm <= 1e24f ? 0.f : __int_as_float(0x7F800000));
        named_sync(1, 256);
        if (tid == 0) {
            float mx = red[0];
#pragma unroll
            for (int i = 1; i < 8; i++) mx = fmaxf(mx, red[i]);
            g_kmax[m] = mx;
        }
    }
    if (tid == 0) TS(0, 3);
}

constexpr int A_THREADS = 512;
constexpr int A_NPIECE = 8;
constexpr int A_OFF_Q = 2 * KV_BYTES;
constexpr int A_OFF_BAR = A_OFF_Q + 4 * 4096;
constexpr int A_SMEM = A_OFF_BAR + 128;

__device__ __forceinline__ uint32_t exp2_pair_fixed(float lo, float hi) {
    const uint32_t G = __byte_perm(__float_as_uint(lo), __float_as_uint(hi), 0x5410);
    const uint32_t Hh = G & 0x007F007Fu;
    const uint32_t tt = hfma2(Hh, 0xF96BF96Bu, 0x358C358Cu);
    return G - hfma2(tt, Hh, 0u);
}

__device__ __forceinline__ void attn_side_job(const __nv_bfloat16* __restrict__ w1, const __nv_bfloat16* __restrict__ w2, const __nv_bfloat16* __restrict__ wo) {
    const int e = blockIdx.x - 128, tid = threadIdx.x;
    if (tid < 32) {
        const char* p = reinterpret_cast<const char*>(wo) + e * (DM * DM * 2 / 4);
        for (int i = tid; i < DM * DM * 2 / 4 / 4608; i += 32) prefetch_l2(p + i * 4608, 4608);
        p = reinterpret_cast<const char*>(w1) + (size_t)e * (FF * DM * 2 / 4);
        for (int i = tid; i < FF * DM * 2 / 4 / 9216; i += 32) prefetch_l2(p + (size_t)i * 9216, 9216);
        p = reinterpret_cast<const char*>(w2) + (size_t)e * (FF * DM * 2 / 4);
        for (int i = tid; i < FF * DM * 2 / 4 / 9216; i += 32) prefetch_l2(p + (size_t)i * 9216, 9216);
    }
}

__global__ void __launch_bounds__(A_THREADS, 1)
k_attn(const __nv_bfloat16* __restrict__ w1, const __nv_bfloat16* __restrict__ w2, const __nv_bfloat16* __restrict__ wo) {
    extern __shared__ __align__(1024) uint8_t smem[];
    pdl_launch();
    if (blockIdx.x >= 128) { attn_side_job(w1, w2, wo); return; }
    const uint32_t sK = smem_u32(smem), sV = sK + KV_BYTES, bars = sK + A_OFF_BAR;
    const int tid = threadIdx.x;
    check_smem_base(sK);
    if (tid == 0) TS(1, 0);
    if (tid == 0) {
        for (int i = 0; i < A_NPIECE; i++) mbar_init(bars + i * 8, 1);
        bar_init_fence();
    }
    __syncthreads();
    pdl_wait();
    if (tid == 0) TS(1, 1);
    if (tid < 32 && elect_one()) {
        constexpr int PB = KV_BYTES / A_NPIECE;
        for (int i = 0; i < A_NPIECE; i++) {
            mbar_expect(bars + i * 8, 2 * PB);
            bulk_g2s(sK + i * PB, reinterpret_cast<const char*>(g_kc) + i * PB, PB, bars + i * 8);
            bulk_g2s(sV + i * PB, reinterpret_cast<const char*>(g_vc) + i * PB, PB, bars + i * 8);
        }
    }
    const int wg = __shfl_sync(~0u, tid >> 7, 0), w = (tid >> 5) & 3, lane = tid & 31, g = lane >> 2, t = lane & 3;
    const uint32_t* q32 = reinterpret_cast<const uint32_t*>(g_q);
    uint32_t* o32 = reinterpret_cast<uint32_t*>(g_o);
    int row = (blockIdx.x * 8 + wg) * 64 + w * 16 + g;
    uint32_t nq[6];
    nq[0] = q32[row * 9 + t]; nq[1] = q32[(row + 8) * 9 + t]; nq[2] = q32[row * 9 + 4 + t]; nq[3] = q32[(row + 8) * 9 + 4 + t];
    nq[4] = q32[row * 9 + 8]; nq[5] = q32[(row + 8) * 9 + 8];
    float kmax2 = g_kmax[lane];
#pragma unroll
    for (int o = 1; o < 32; o <<= 1) kmax2 = fmaxf(kmax2, __shfl_xor_sync(~0u, kmax2, o));
    const uint32_t sQ = sK + A_OFF_Q + wg * 4096 + (w * 2) * 512 + g * 16 + t * 4;
    const uint64_t dQ0 = cdesc(A_OFF_Q, 128, 512, 0) + wg * 256, dQ1 = dQ0 + 16;
#pragma unroll 1
    for (int rep = 0; rep < 2; rep++, row += 256) {
        const uint32_t qa[4] = {nq[0], nq[1], nq[2], nq[3]};
        float n0, n1;
        {
            const float a0 = bf_lo(qa[0]), a1 = bf_hi(qa[0]), a2 = bf_lo(qa[2]), a3 = bf_hi(qa[2]);
            const float b0 = bf_lo(qa[1]), b1 = bf_hi(qa[1]), b2 = bf_lo(qa[3]), b3 = bf_hi(qa[3]);
            n0 = a0 * a0 + a1 * a1 + a2 * a2 + a3 * a3; n1 = b0 * b0 + b1 * b1 + b2 * b2 + b3 * b3;
            if (t == 0) {
                const float c0 = bf_lo(nq[4]), c1 = bf_hi(nq[4]), d0 = bf_lo(nq[5]), d1 = bf_hi(nq[5]);
                n0 += c0 * c0 + c1 * c1; n1 += d0 * d0 + d1 * d1;
            }
            n0 += __shfl_xor_sync(~0u, n0, 1); n0 += __shfl_xor_sync(~0u, n0, 2);
            n1 += __shfl_xor_sync(~0u, n1, 1); n1 += __shfl_xor_sync(~0u, n1, 2);
        }
        const uint32_t x0 = nq[4], x1 = nq[5];
        if (rep == 0) {
            const int nr = row + 256;
            nq[0] = q32[nr * 9 + t]; nq[1] = q32[(nr + 8) * 9 + t]; nq[2] = q32[nr * 9 + 4 + t]; nq[3] = q32[(nr + 8) * 9 + 4 + t];
            nq[4] = q32[nr * 9 + 8]; nq[5] = q32[(nr + 8) * 9 + 8];
        }
        const bool unsafe = !(fmaxf(n0, n1) * kmax2 <= FAST_BOUND * FAST_BOUND) || !(n0 == n0) || !(n1 == n1);
        uint32_t any_unsafe;
        asm volatile("{\n.reg .pred p, q;\nsetp.ne.u32 p, %1, 0;\nbar.red.or.pred q, %2, 128, p;\nselp.u32 %0, 1, 0, q;\n}\n" : "=r"(any_unsafe) : "r"((uint32_t)unsafe), "r"(wg + 1) : "memory");
        any_unsafe = __shfl_sync(~0u, any_unsafe, 0);
        {
            const uint32_t cst = any_unsafe ? 0u : (t == 1 ? 0x3F804780u : (t == 2 ? 0x00003F80u : 0u));
            asm volatile("st.shared.b32 [%0], %1;" ::"r"(sQ), "r"(qa[0]) : "memory");
            asm volatile("st.shared.b32 [%0], %1;" ::"r"(sQ + 512), "r"(qa[1]) : "memory");
            asm volatile("st.shared.b32 [%0], %1;" ::"r"(sQ + 128), "r"(qa[2]) : "memory");
            asm volatile("st.shared.b32 [%0], %1;" ::"r"(sQ + 640), "r"(qa[3]) : "memory");
            asm volatile("st.shared.b32 [%0], %1;" ::"r"(sQ + 256), "r"(t == 0 ? x0 : cst) : "memory");
            asm volatile("st.shared.b32 [%0], %1;" ::"r"(sQ + 768), "r"(t == 0 ? x1 : cst) : "memory");
            asm volatile("st.shared.b32 [%0], %1;" ::"r"(sQ + 384), "r"(0u) : "memory");
            asm volatile("st.shared.b32 [%0], %1;" ::"r"(sQ + 896), "r"(0u) : "memory");
            proxy_fence();
            named_sync(wg + 1, 128);
        }
        if (tid == 0) TS(1, 2 + rep * 2);
        float o[12];
#pragma unroll
        for (int i = 0; i < 12; i++) o[i] = 0.f;
        pin(o);
        uint64_t dK0 = cdesc(0, 128, 384, 0), dK1 = cdesc(256, 0, 384, 0), dV = cdesc(KV_BYTES, 384, 128, 0);
        if (!any_unsafe) {
            float s[64];
#pragma unroll 1
            for (int j = 0; j < 16; j++) {
                if (rep == 0 && (j & 1) == 0) mbar_wait(bars + (j >> 1) * 8, 0);
                wg_fence();
                wgmma_ss_n128<0>(s, dQ0, dK0, 0);
                wgmma_ss_n128<0>(s, dQ1, dK1, 1);
                wg_commit();
                dK0 += 16 * 384 >> 4; dK1 += 16 * 384 >> 4;
                wg_wait<0>();
                pin(s);
                uint32_t p[32];
#pragma unroll
                for (int i = 0; i < 32; i++) {
                    if ((POLY_MASK >> (i >> 1)) & 1) p[i] = exp2_pair_fixed(s[2 * i], s[2 * i + 1]);
                    else p[i] = pack_bf16(ex2(s[2 * i]), ex2(s[2 * i + 1]));
                }
                pin(p);
                wg_fence();
#pragma unroll
                for (int k = 0; k < 8; k++) wgmma_rs_n24<1>(o, p[4 * k], p[4 * k + 1], p[4 * k + 2], p[4 * k + 3], dV + k * 48, 1);
                wg_commit();
                dV += 16 * 384 >> 4;
                wg_wait<0>();
            }
        } else {
            float s[64];
            float m0 = -INFINITY, m1 = -INFINITY;
#pragma unroll 1
            for (int j = 0; j < 16; j++) {
                if (rep == 0 && (j & 1) == 0) mbar_wait(bars + (j >> 1) * 8, 0);
                wg_fence();
                wgmma_ss_n128<0>(s, dQ0, dK0, 0);
                wgmma_ss_n128<0>(s, dQ1, dK1, 1);
                wg_commit();
                dK0 += 16 * 384 >> 4; dK1 += 16 * 384 >> 4;
                wg_wait<0>();
                pin(s);
                float x0m = m0, x1m = m1;
#pragma unroll
                for (int b = 0; b < 16; b++) { x0m = fmaxf(x0m, fmaxf(s[4 * b], s[4 * b + 1])); x1m = fmaxf(x1m, fmaxf(s[4 * b + 2], s[4 * b + 3])); }
                x0m = fmaxf(x0m, __shfl_xor_sync(~0u, x0m, 1)); x0m = fmaxf(x0m, __shfl_xor_sync(~0u, x0m, 2));
                x1m = fmaxf(x1m, __shfl_xor_sync(~0u, x1m, 1)); x1m = fmaxf(x1m, __shfl_xor_sync(~0u, x1m, 2));
                const float c0 = ex2(m0 - x0m), c1 = ex2(m1 - x1m);
                m0 = x0m; m1 = x1m;
#pragma unroll
                for (int b = 0; b < 3; b++) { o[4 * b] *= c0; o[4 * b + 1] *= c0; o[4 * b + 2] *= c1; o[4 * b + 3] *= c1; }
                uint32_t p[32];
#pragma unroll
                for (int b = 0; b < 16; b++) {
                    p[2 * b] = pack_bf16(ex2(s[4 * b] - m0), ex2(s[4 * b + 1] - m0));
                    p[2 * b + 1] = pack_bf16(ex2(s[4 * b + 2] - m1), ex2(s[4 * b + 3] - m1));
                }
                pin(p); pin(o);
                wg_fence();
#pragma unroll
                for (int k = 0; k < 8; k++) wgmma_rs_n24<1>(o, p[4 * k], p[4 * k + 1], p[4 * k + 2], p[4 * k + 3], dV + k * 48, 1);
                wg_commit();
                dV += 16 * 384 >> 4;
                wg_wait<0>();
            }
        }
        pin(o);
        if (tid == 0) TS(1, 3 + rep * 2);
        const float l0 = __shfl_sync(~0u, o[8], (lane & ~3) | 1), l1 = __shfl_sync(~0u, o[10], (lane & ~3) | 1);
        const float i0 = 1.0f / l0, i1 = 1.0f / l1;
        o32[row * 9 + t] = pack_bf16(o[0] * i0, o[1] * i0);
        o32[(row + 8) * 9 + t] = pack_bf16(o[2] * i1, o[3] * i1);
        o32[row * 9 + 4 + t] = pack_bf16(o[4] * i0, o[5] * i0);
        o32[(row + 8) * 9 + 4 + t] = pack_bf16(o[6] * i1, o[7] * i1);
        if (t == 0) { o32[row * 9 + 8] = pack_bf16(o[8] * i0, o[9] * i0); o32[(row + 8) * 9 + 8] = pack_bf16(o[10] * i1, o[11] * i1); }
    }
    if (tid == 0) TS(1, 6);
}

template <int NB>
__device__ __forceinline__ void oproj_load_x(uint32_t (&xr)[NB * 2], const uint32_t* __restrict__ x32, int r0, int col0, int t) {
#pragma unroll
    for (int b = 0; b < NB; b++) {
        const int i0 = (r0 * DM + col0 + b * 8 + 2 * t) >> 1;
        xr[2 * b] = __ldg(x32 + i0); xr[2 * b + 1] = __ldg(x32 + i0 + 4 * DM);
    }
}
constexpr int P_OFF_STAT = 3 * 8192 + 3 * 8192;
template <int NB>
__device__ __forceinline__ void oproj_epilogue(const float (&acc)[NB * 4], uint32_t (&xr)[NB * 2], uint32_t sA, uint32_t tile_ofs, int part, int w, int lane) {
    float s0 = 0.f, q0 = 0.f, s1 = 0.f, q1 = 0.f;
#pragma unroll
    for (int b = 0; b < NB; b++) {
        const uint32_t xa = xr[2 * b], xb = xr[2 * b + 1];
        const uint32_t ha = pack_bf16(acc[4 * b] + bf_lo(xa), acc[4 * b + 1] + bf_hi(xa));
        const uint32_t hb = pack_bf16(acc[4 * b + 2] + bf_lo(xb), acc[4 * b + 3] + bf_hi(xb));
        xr[2 * b] = ha; xr[2 * b + 1] = hb;
        const float a = bf_lo(ha), c = bf_hi(ha), d = bf_lo(hb), e = bf_hi(hb);
        s0 += a + c; q0 = fmaf(a, a, fmaf(c, c, q0));
        s1 += d + e; q1 = fmaf(d, d, fmaf(e, e, q1));
    }
    s0 += __shfl_xor_sync(~0u, s0, 1); s0 += __shfl_xor_sync(~0u, s0, 2);
    q0 += __shfl_xor_sync(~0u, q0, 1); q0 += __shfl_xor_sync(~0u, q0, 2);
    s1 += __shfl_xor_sync(~0u, s1, 1); s1 += __shfl_xor_sync(~0u, s1, 2);
    q1 += __shfl_xor_sync(~0u, q1, 1); q1 += __shfl_xor_sync(~0u, q1, 2);
    const int r = w * 16 + (lane >> 2);
    const uint32_t sStat = sA + P_OFF_STAT;
    if ((lane & 3) < 3) {
        uint32_t dst;
        asm("mapa.shared::cluster.u32 %0, %1, %2;" : "=r"(dst) : "r"(sStat + (part * 64 + r) * 8), "r"(lane & 3));
        asm volatile("st.shared::cluster.v2.f32 [%0], {%1, %2};" ::"r"(dst), "f"(s0), "f"(q0) : "memory");
        asm volatile("st.shared::cluster.v2.f32 [%0], {%1, %2};" ::"r"(dst + 64), "f"(s1), "f"(q1) : "memory");
    }
    asm volatile("barrier.cluster.arrive.release.aligned;" ::: "memory");
    stage_tile<NB>(xr, sA + tile_ofs, w, lane);
    asm volatile("barrier.cluster.wait.acquire.aligned;" ::: "memory");
    s0 = q0 = s1 = q1 = 0.f;
#pragma unroll
    for (int p = 0; p < 6; p++) {
        float a, b, c, d;
        asm volatile("ld.shared.v2.f32 {%0, %1}, [%2];" : "=f"(a), "=f"(b) : "r"(sStat + (p * 64 + r) * 8));
        asm volatile("ld.shared.v2.f32 {%0, %1}, [%2];" : "=f"(c), "=f"(d) : "r"(sStat + (p * 64 + r + 8) * 8));
        s0 += a; q0 += b; s1 += c; q1 += d;
    }
    const float m0 = s0 * (1.0f / DM), m1 = s1 * (1.0f / DM);
    const float rs0 = rsqrtf(fmaxf(q0 * (1.0f / DM) - m0 * m0, 0.f) + LN_EPS), rs1 = rsqrtf(fmaxf(q1 * (1.0f / DM) - m1 * m1, 0.f) + LN_EPS);
    const float n0 = -m0 * rs0, n1 = -m1 * rs1;
#pragma unroll
    for (int b = 0; b < NB; b++) {
        xr[2 * b] = pack_bf16(fmaf(bf_lo(xr[2 * b]), rs0, n0), fmaf(bf_hi(xr[2 * b]), rs0, n0));
        xr[2 * b + 1] = pack_bf16(fmaf(bf_lo(xr[2 * b + 1]), rs1, n1), fmaf(bf_hi(xr[2 * b + 1]), rs1, n1));
    }
    stage_tile<NB>(xr, sA + 3 * 8192 + tile_ofs, w, lane);
}

__global__ void __cluster_dims__(3, 1, 1) __launch_bounds__(P_THREADS, 1)
k_oproj(const __grid_constant__ CUtensorMap tmO, const __grid_constant__ CUtensorMap tmWo, const __grid_constant__ CUtensorMap tmX2, const __grid_constant__ CUtensorMap tmOut, const __nv_bfloat16* __restrict__ x) {
    extern __shared__ __align__(1024) uint8_t smem[];
    const uint32_t sA = smem_u32(smem), sB = sA + P_A_BYTES, bars = sB + P_NST * P_B_STAGE;
    const uint32_t fullB = bars, emptyB = bars + 64, fullA = bars + 128;
    const int tid = threadIdx.x, warp = __shfl_sync(~0u, tid >> 5, 0), lane = tid & 31;
    const int m = blockIdx.x / 3, cg = blockIdx.x % 3;
    if (tid == 0) TS(2, 0);
    if (tid == 0) {
        for (int i = 0; i < P_NST; i++) { mbar_init(fullB + i * 8, 1); mbar_init(emptyB + i * 8, 8); }
        for (int i = 0; i < 9; i++) mbar_init(fullA + i * 8, 1);
        bar_init_fence();
    }
    __syncthreads();
    pdl_launch();
    if (warp == 8) {
        if (elect_one()) {
            for (int kb = 0; kb < P_NST; kb++) {
                mbar_expect(fullB + kb * 8, P_B_STAGE);
                for (int a = 0; a < 3; a++) tma_2d(sB + kb * P_B_STAGE + a * 8192, &tmWo, cg * 192 + a * 64, kb * 64, fullB + kb * 8);
            }
            pdl_wait();
            for (int kb = 0; kb < 9; kb++) {
                mbar_expect(fullA + kb * 8, 8192);
                tma_2d(sA + kb * 8192, &tmO, kb * 64, m * 64, fullA + kb * 8);
            }
            for (int kb = P_NST; kb < 9; kb++) {
                const int s = kb - P_NST;
                mbar_wait(emptyB + s * 8, 0);
                mbar_expect(fullB + s * 8, P_B_STAGE);
                for (int a = 0; a < 3; a++) tma_2d(sB + s * P_B_STAGE + a * 8192, &tmWo, cg * 192 + a * 64, kb * 64, fullB + s * 8);
            }
        }
        return;
    }
    const int wg = warp >> 2, w = warp & 3, g = lane >> 2, t = lane & 3;
    const int r0 = m * 64 + w * 16 + g;
    const uint32_t* x32 = reinterpret_cast<const uint32_t*>(x);
    if (wg == 0) {
        uint32_t xr[32];
        oproj_load_x<16>(xr, x32, r0, cg * 192, t);
        float acc[64];
        proj_mma<128, true>(acc, sA, sB, 0, fullB, emptyB, fullA, lane);
        if (tid == 0) TS(2, 2);
        named_sync(1, 256);
        oproj_epilogue<16>(acc, xr, sA, 0, cg * 2, w, lane);
    } else {
        uint32_t xr[16];
        oproj_load_x<8>(xr, x32, r0, cg * 192 + 128, t);
        float acc[32];
        proj_mma<64, true>(acc, sA, sB, 2 * 8192, fullB, emptyB, fullA, lane);
        named_sync(1, 256);
        oproj_epilogue<8>(acc, xr, sA, 2 * 8192, cg * 2 + 1, w, lane);
    }
    proxy_fence();
    named_sync(1, 256);
    if (warp == 0 && elect_one()) {
        for (int a = 0; a < 3; a++) {
            tma_st_2d(&tmX2, cg * 192 + a * 64, m * 64, sA + (3 + a) * 8192);
            tma_st_2d(&tmOut, cg * 192 + a * 64, m * 64, sA + a * 8192);
        }
        bulk_commit();
        bulk_wait_all();
        TS(2, 3);
    }
}

constexpr int F_THREADS = 384;
constexpr int F_NST = 6;
constexpr int F_STAGE = 96 * 128;
constexpr int F_X_BYTES = 9 * 16384;
constexpr int F_OFF_ST = F_X_BYTES;
constexpr int F_OFF_BAR = F_OFF_ST + F_NST * F_STAGE;
constexpr int F_SMEM = F_OFF_BAR + 256;

__device__ __forceinline__ void silu_s1(const float (&acc)[32], float (&tmp)[8], int piece) {
#pragma unroll
    for (int i = 0; i < 8; i++) tmp[i] = ex2(acc[8 * piece + i] * -LOG2E);
}
__device__ __forceinline__ float after_issue(float v, uint32_t tick) {
    uint32_t r;
    asm("lop3.b32 %0, %1, %1, %2, 0xF0;" : "=r"(r) : "r"(__float_as_uint(v)), "r"(tick));
    return __uint_as_float(r);
}
__device__ __forceinline__ uint32_t read_tick() { uint32_t c; asm volatile("mov.u32 %0, %%clock;" : "=r"(c)::"memory"); return c; }
__device__ __forceinline__ void silu_s2(float (&tmp)[8], uint32_t tick) {
    const float one = after_issue(1.0f, tick);
#pragma unroll
    for (int i = 0; i < 8; i++) tmp[i] = rcp(tmp[i] + one);
}
template <int C>
__device__ __forceinline__ void silu_s3(const float (&acc)[32], const float (&tmp)[8], uint32_t (&h1)[144], int piece) {
#pragma unroll
    for (int i = 0; i < 4; i++) h1[C * 16 + 4 * piece + i] = pack_bf16(acc[8 * piece + 2 * i] * tmp[2 * i], acc[8 * piece + 2 * i + 1] * tmp[2 * i + 1]);
}

struct FfnPipe {
    uint32_t full, empty;
    int lane;
    __device__ __forceinline__ void acquire(int s, uint32_t ph) const { mbar_wait(full + s * 8, ph); }
    __device__ __forceinline__ void release(int s) const { if (lane == 0) mbar_arrive(empty + s * 8); }
};

template <int C>
__device__ __forceinline__ void ffn_phase1_chunk(float (&cur)[32], float (&prev)[32], uint32_t (&h1)[144], const FfnPipe& pp, uint64_t dx, uint32_t fullX) {
    float tmp[2][8];
    const uint64_t dw = cdesc(F_OFF_ST, 8192, 1024, 1) + blockIdx.y * (C + 1);
    dx += blockIdx.y * C;
#pragma unroll
    for (int j = 0; j < 6; j++) {
        if (C == 0) { mbar_wait(fullX + ((6 * j) >> 2) * 8, 0); mbar_wait(fullX + ((6 * j + 5) >> 2) * 8, 0); }
        pp.acquire(j, C & 1);
        if (j == 0) pin(cur);
        wg_fence();
#pragma unroll
        for (int i = 0; i < 6; i++) {
            const int ks = 6 * j + i;
            wgmma_ss_n64<1>(cur, dx + ((ks >> 2) * 1024 + (ks & 3) * 2), dw + ((j * F_STAGE + i * 2048) >> 4), ks != 0);
        }
        wg_commit();
        if (C > 0 || j > 0) { wg_wait<1>(); pp.release((j + 5) % 6); }
        if (C > 0) {
            pin(prev);
            if (j >= 1) { pin(tmp[0]); if (j >= 2) pin(tmp[1]); }
            if (j >= 2) silu_s3<(C > 0 ? C - 1 : 0)>(prev, tmp[j & 1], h1, j - 2);
            if (j >= 1 && j <= 4) { silu_s2(tmp[(j - 1) & 1], read_tick()); pin(tmp[(j - 1) & 1]); }
            if (j <= 3) { silu_s1(prev, tmp[j & 1], j); pin(tmp[j & 1]); }
            if (j >= 2) { asm volatile("" : "+r"(h1[(C - 1) * 16 + 4 * (j - 2)]), "+r"(h1[(C - 1) * 16 + 4 * (j - 2) + 1]), "+r"(h1[(C - 1) * 16 + 4 * (j - 2) + 2]), "+r"(h1[(C - 1) * 16 + 4 * (j - 2) + 3]) :: "memory"); }
        }
    }
}

__device__ __forceinline__ void ffn_store_chunk(const float (&acc)[32], const CUtensorMap* tmOut, uint32_t stg, int col, int row, int w, int lane, int wgid) {
    uint32_t pk[16];
#pragma unroll
    for (int i = 0; i < 16; i++) pk[i] = pack_bf16(acc[2 * i], acc[2 * i + 1]);
    stage_tile<8>(pk, stg, w, lane);
    proxy_fence();
    named_sync(2 + wgid, 128);
    if (w == 0 && elect_one()) {
        tma_red_2d(tmOut, col, row, stg);
        bulk_commit();
    }
}

__device__ __forceinline__ void ffn_phase2_chunk(float (&cur)[32], float (&prev)[32], uint32_t (&h1)[144], const FfnPipe& pp, uint32_t ph, bool store_prev, const CUtensorMap* tmOut, uint32_t stg_prev, int col_prev, int row, int w, int lane, int wgid) {
    const uint64_t dw = cdesc(F_OFF_ST, 8192, 1024, 1) + blockIdx.y * col_prev;
#pragma unroll
    for (int j = 0; j < 6; j++) {
        pp.acquire(j, ph);
        if (j == 0) pin(cur);
        wg_fence();
#pragma unroll
        for (int i = 0; i < 6; i++) {
            const int f = (6 * j + i) * 4;
            wgmma_rs_n64<1>(cur, h1[f], h1[f + 1], h1[f + 2], h1[f + 3], dw + ((j * F_STAGE + i * 2048) >> 4), (j | i) != 0);
        }
        wg_commit();
        if (j > 0 || store_prev) { wg_wait<1>(); pp.release((j + 5) % 6); }
        if (j == 0 && store_prev) { pin(prev); ffn_store_chunk(prev, tmOut, stg_prev, col_prev, row, w, lane, wgid); }
    }
}

__global__ void __launch_bounds__(F_THREADS, 1)
k_ffn(const __grid_constant__ CUtensorMap tmH, const __grid_constant__ CUtensorMap tmW1, const __grid_constant__ CUtensorMap tmW2, const __grid_constant__ CUtensorMap tmOut) {
    extern __shared__ __align__(1024) uint8_t smem[];
    const uint32_t sX = smem_u32(smem), sSt = sX + F_OFF_ST, bars = sX + F_OFF_BAR;
    const uint32_t full = bars, empty = bars + 64, fullX = bars + 128;
    const int tid = threadIdx.x, warp = __shfl_sync(~0u, tid >> 5, 0), lane = tid & 31;
    const int m = blockIdx.x & 15, fs = blockIdx.x >> 4;
    if (tid == 0) TS(3, 0);
    check_smem_base(sX);
    if (tid == 0) {
        for (int i = 0; i < F_NST; i++) { mbar_init(full + i * 8, 1); mbar_init(empty + i * 8, 8); }
        for (int i = 0; i < 9; i++) mbar_init(fullX + i * 8, 1);
        bar_init_fence();
    }
    __syncthreads();
    if (warp < 4) {
        asm volatile("setmaxnreg.dec.sync.aligned.u32 24;");
        if (warp == 0 && elect_one()) {
            int s = 0; uint32_t ph = 1;
            int c = 0, j = 0;
#pragma unroll 1
            for (int i = 0; i < 108; i++) {
                if (i == F_NST) {
                    pdl_wait();
                    for (int kb = 0; kb < 9; kb++) {
                        mbar_expect(fullX + kb * 8, 16384);
                        tma_2d(sX + kb * 16384, &tmH, kb * 64, m * 128, fullX + kb * 8);
                    }
                }
                if (i == 54) c = fs;
                mbar_wait(empty + s * 8, ph);
                mbar_expect(full + s * 8, F_STAGE);
                if (i < 54) tma_2d(sSt + s * F_STAGE, &tmW1, fs * 576 + c * 64, j * 96, full + s * 8);
                else tma_2d(sSt + s * F_STAGE, &tmW2, c * 64, fs * 576 + j * 96, full + s * 8);
                if (++j == 6) { j = 0; if (++c == 9) c = 0; }
                if (++s == F_NST) { s = 0; ph ^= 1; }
            }
        }
    } else {
        asm volatile("setmaxnreg.inc.sync.aligned.u32 240;");
        const int wgid = (warp >> 2) - 1, w = warp & 3;
        pdl_wait();
        if (tid == 128) TS(3, 1);
        FfnPipe pp{full, empty, lane};
        const uint64_t xlo = cdesc(0, 16, 1024, 1) + wgid * 512;
        uint32_t h1[144];
        float acc0[32], acc1[32];
        ffn_phase1_chunk<0>(acc0, acc1, h1, pp, xlo, fullX);
        if (tid == 128) TS(3, 2);
        ffn_phase1_chunk<1>(acc1, acc0, h1, pp, xlo, fullX);
        ffn_phase1_chunk<2>(acc0, acc1, h1, pp, xlo, fullX);
        ffn_phase1_chunk<3>(acc1, acc0, h1, pp, xlo, fullX);
        ffn_phase1_chunk<4>(acc0, acc1, h1, pp, xlo, fullX);
        ffn_phase1_chunk<5>(acc1, acc0, h1, pp, xlo, fullX);
        ffn_phase1_chunk<6>(acc0, acc1, h1, pp, xlo, fullX);
        ffn_phase1_chunk<7>(acc1, acc0, h1, pp, xlo, fullX);
        ffn_phase1_chunk<8>(acc0, acc1, h1, pp, xlo, fullX);
        wg_wait<0>();
        pp.release(5);
        pin(acc0);
        {
            float tmp[4][8];
#pragma unroll
            for (int p = 0; p < 4; p++) silu_s1(acc0, tmp[p], p);
#pragma unroll
            for (int p = 0; p < 4; p++) silu_s2(tmp[p], 0);
#pragma unroll
            for (int p = 0; p < 4; p++) silu_s3<8>(acc0, tmp[p], h1, p);
        }
        pin(h1);
        if (tid == 128) TS(3, 3);
        const int row = m * 128 + wgid * 64;
        const uint32_t stg = sX + wgid * 8192;
        int c = fs, cprev = 0;
#pragma unroll 1
        for (int j = 0; j < 8; j += 2) {
            ffn_phase2_chunk(acc1, acc0, h1, pp, 1, j > 0, &tmOut, stg + (j - 1) * 16384, cprev * 64, row, w, lane, wgid);
            cprev = c; if (++c == 9) c = 0;
            ffn_phase2_chunk(acc0, acc1, h1, pp, 0, true, &tmOut, stg + j * 16384, cprev * 64, row, w, lane, wgid);
            cprev = c; if (++c == 9) c = 0;
        }
        ffn_phase2_chunk(acc1, acc0, h1, pp, 1, true, &tmOut, stg + 7 * 16384, cprev * 64, row, w, lane, wgid);
        wg_wait<0>();
        pin(acc1);
        ffn_store_chunk(acc1, &tmOut, stg + 8 * 16384, c * 64, row, w, lane, wgid);
        if (tid == 128) TS(3, 4);
        if (w == 0) bulk_wait_all();
        if (tid == 128) TS(3, 5);
    }
}

typedef CUresult (*EncodeFn)(CUtensorMap*, CUtensorMapDataType, cuuint32_t, void*, const cuuint64_t*, const cuuint64_t*, const cuuint32_t*, const cuuint32_t*,
                             CUtensorMapInterleave, CUtensorMapSwizzle, CUtensorMapL2promotion, CUtensorMapFloatOOBfill);

CUtensorMap make_map(EncodeFn enc, const void* base, int rows, int cols, int box_rows) {
    CUtensorMap tm;
    cuuint64_t dims[2] = {(cuuint64_t)cols, (cuuint64_t)rows};
    cuuint64_t strides[1] = {(cuuint64_t)cols * 2};
    cuuint32_t box[2] = {64, (cuuint32_t)box_rows};
    cuuint32_t es[2] = {1, 1};
    enc(&tm, CU_TENSOR_MAP_DATA_TYPE_BFLOAT16, 2, const_cast<void*>(base), dims, strides, box, es, CU_TENSOR_MAP_INTERLEAVE_NONE,
        CU_TENSOR_MAP_SWIZZLE_128B, CU_TENSOR_MAP_L2_PROMOTION_L2_256B, CU_TENSOR_MAP_FLOAT_OOB_FILL_NONE);
    return tm;
}

template <typename... KArgs, typename... Args>
void launch(void (*kern)(KArgs...), int grid, int block, int smem, bool pdl, Args... args) {
    cudaLaunchConfig_t cfg = {};
    cfg.gridDim = dim3(grid); cfg.blockDim = dim3(block); cfg.dynamicSmemBytes = smem; cfg.stream = cudaStreamPerThread;
    cudaLaunchAttribute at[1];
    at[0].id = cudaLaunchAttributeProgrammaticStreamSerialization;
    at[0].val.programmaticStreamSerializationAllowed = 1;
    cfg.attrs = at; cfg.numAttrs = pdl ? 1 : 0;
    cudaLaunchKernelEx(&cfg, kern, KArgs(args)...);
}

}

#define USE_PDL 1

extern "C" void kernel_launch(void* const* d_in, const int* in_sizes, int n_in, void* d_out, int out_size) {
    const __nv_bfloat16* x = (const __nv_bfloat16*)d_in[0];
    const __nv_bfloat16* wq = (const __nv_bfloat16*)d_in[1];
    const __nv_bfloat16* wk = (const __nv_bfloat16*)d_in[2];
    const __nv_bfloat16* wv = (const __nv_bfloat16*)d_in[3];
    const __nv_bfloat16* wo = (const __nv_bfloat16*)d_in[4];
    const __nv_bfloat16* w1 = (const __nv_bfloat16*)d_in[6];
    const __nv_bfloat16* w2 = (const __nv_bfloat16*)d_in[7];
    __nv_bfloat16* out = (__nv_bfloat16*)d_out;

    static EncodeFn enc = nullptr;
    static void *p_o = nullptr, *p_h = nullptr, *p_q = nullptr;
    if (!enc) {
        cudaDriverEntryPointQueryResult qr;
        cudaGetDriverEntryPoint("cuTensorMapEncodeTiled", (void**)&enc, cudaEnableDefault, &qr);
        cudaGetSymbolAddress(&p_o, g_o);
        cudaGetSymbolAddress(&p_h, g_x2);
        cudaGetSymbolAddress(&p_q, g_q);
        cudaFuncSetAttribute(k_qkv, cudaFuncAttributeMaxDynamicSharedMemorySize, P_SMEM);
        cudaFuncSetAttribute(k_attn, cudaFuncAttributeMaxDynamicSharedMemorySize, A_SMEM);
        cudaFuncSetAttribute(k_oproj, cudaFuncAttributeMaxDynamicSharedMemorySize, P_SMEM);
        cudaFuncSetAttribute(k_ffn, cudaFuncAttributeMaxDynamicSharedMemorySize, F_SMEM);
    }
    const CUtensorMap tmWq = make_map(enc, wq, DM, DM, 64);
    const CUtensorMap tmWo = make_map(enc, wo, DM, DM, 64);
    const CUtensorMap tmO = make_map(enc, p_o, SEQ, DM, 64);
    const CUtensorMap tmH = make_map(enc, p_h, SEQ, DM, 128);
    const CUtensorMap tmH64 = make_map(enc, p_h, SEQ, DM, 64);
    const CUtensorMap tmQ = make_map(enc, p_q, SEQ, DM, 64);
    const CUtensorMap tmW1 = make_map(enc, w1, DM, FF, 96);
    const CUtensorMap tmW2 = make_map(enc, w2, FF, DM, 96);
    const CUtensorMap tmOut = make_map(enc, out, SEQ, DM, 64);

    launch(k_qkv, 128, P_THREADS, P_SMEM, false, tmWq, tmQ, x, wk, wv);
    launch(k_attn, 132, A_THREADS, A_SMEM, USE_PDL, w1, w2, wo);
    launch(k_oproj, 96, P_THREADS, P_SMEM, USE_PDL, tmO, tmWo, tmH64, tmOut, x);
    launch(k_ffn, 128, F_THREADS, F_SMEM, USE_PDL, tmH, tmW1, tmW2, tmOut);
}
```

```cpp
#include <cuda_runtime.h>
#include <cuda_bf16.h>
#include <cuda.h>
#include <stdint.h>

namespace {

constexpr int SEQ = 2048, DM = 576, FF = 4608;
constexpr int KV_BYTES = SEQ * 48;
constexpr float LN_EPS = 1e-5f;
constexpr float LOG2E = 1.4426950408889634f;
constexpr float Q_SCALE = 0.23570226039551584f * LOG2E;

#define POLY_MASK_V 0xB5B5u
constexpr uint32_t POLY_MASK = POLY_MASK_V;
constexpr float FAST_BOUND = 60.0f;

__device__ __align__(1024) __nv_bfloat16 g_q[SEQ * DM];
__device__ __align__(1024) uint4 g_kc[KV_BYTES / 16];
__device__ __align__(1024) uint4 g_vc[KV_BYTES / 16];
__device__ float g_kmax[32];
__device__ __align__(1024) __nv_bfloat16 g_o[SEQ * DM];
__device__ __align__(1024) __nv_bfloat16 g_x2[SEQ * DM];

#define TS(k, i)

__device__ __forceinline__ uint32_t smem_u32(const void* p) { return (uint32_t)__cvta_generic_to_shared(p); }
__device__ __forceinline__ void wg_fence() { asm volatile("wgmma.fence.sync.aligned;" ::: "memory"); }
__device__ __forceinline__ void wg_commit() { asm volatile("wgmma.commit_group.sync.aligned;" ::: "memory"); }
template <int N> __device__ __forceinline__ void wg_wait() { asm volatile("wgmma.wait_group.sync.aligned %0;" ::"n"(N) : "memory"); }
template <int N> __device__ __forceinline__ void pin(float (&r)[N]) {
#pragma unroll
    for (int i = 0; i < N; i++) asm volatile("" : "+f"(r[i])::"memory");
}
template <int N> __device__ __forceinline__ void pin(uint32_t (&r)[N]) {
#pragma unroll
    for (int i = 0; i < N; i++) asm volatile("" : "+r"(r[i])::"memory");
}
__device__ __forceinline__ constexpr uint32_t desc_hi(uint32_t sbo, uint32_t swz) { return (sbo >> 4) | (swz << 30); }
__device__ __forceinline__ uint32_t desc_lo(uint32_t addr, uint32_t lbo) { return ((addr & 0x3FFFF) >> 4) | ((lbo >> 4) << 16); }
__device__ __forceinline__ uint64_t desc64(uint32_t lo, uint32_t hi) { return ((uint64_t)hi << 32) | lo; }
constexpr uint32_t SMEM0 = 0x400;
__host__ __device__ constexpr uint64_t cdesc(uint32_t off, uint32_t lbo, uint32_t sbo, uint32_t swz) {
    return (uint64_t)(((SMEM0 + off) & 0x3FFFF) >> 4) | ((uint64_t)(lbo >> 4) << 16) | ((uint64_t)(sbo >> 4) << 32) | ((uint64_t)swz << 62);
}
__device__ __forceinline__ void check_smem_base(uint32_t base) { if ((base & 0x3FFFF) != SMEM0) __trap(); }

__device__ __forceinline__ void mbar_init(uint32_t bar, int cnt) { asm volatile("mbarrier.init.shared::cta.b64 [%0], %1;" ::"r"(bar), "r"(cnt) : "memory"); }
__device__ __forceinline__ void mbar_expect(uint32_t bar, int bytes) { asm volatile("mbarrier.arrive.expect_tx.shared::cta.b64 _, [%0], %1;" ::"r"(bar), "r"(bytes) : "memory"); }
__device__ __forceinline__ void mbar_arrive(uint32_t bar) { asm volatile("mbarrier.arrive.shared::cta.b64 _, [%0];" ::"r"(bar) : "memory"); }
__device__ __forceinline__ void mbar_wait(uint32_t bar, uint32_t parity) {
    asm volatile(
        "{\n.reg .pred p;\n.reg .u32 n;\nmov.u32 n, 0;\n"
        "LAB_WAIT:\n"
        "mbarrier.try_wait.parity.shared::cta.b64 p, [%0], %1;\n"
        "@p bra DONE;\n"
        "add.u32 n, n, 1;\n"
        "setp.lt.u32 p, n, 4000000;\n"
        "@p bra LAB_WAIT;\n"
        "trap;\n"
        "DONE:\n}\n" ::"r"(bar), "r"(parity) : "memory");
}
__device__ __forceinline__ void bar_init_fence() {
    asm volatile("fence.mbarrier_init.release.cluster;" ::: "memory");
    asm volatile("fence.proxy.async.shared::cta;" ::: "memory");
}
__device__ __forceinline__ void proxy_fence() { asm volatile("fence.proxy.async.shared::cta;" ::: "memory"); }
__device__ __forceinline__ void named_sync(int id, int n) { asm volatile("bar.sync %0, %1;" ::"r"(id), "r"(n) : "memory"); }
__device__ __forceinline__ void bulk_g2s(uint32_t dst, const void* src, int bytes, uint32_t bar) {
    asm volatile("cp.async.bulk.shared::cluster.global.mbarrier::complete_tx::bytes [%0], [%1], %2, [%3];" ::"r"(dst), "l"(src), "r"(bytes), "r"(bar) : "memory");
}
__device__ __forceinline__ void tma_2d(uint32_t dst, const CUtensorMap* tm, int c0, int c1, uint32_t bar) {
    asm volatile("cp.async.bulk.tensor.2d.shared::cluster.global.mbarrier::complete_tx::bytes [%0], [%1, {%3, %4}], [%2];" ::"r"(dst), "l"(tm), "r"(bar), "r"(c0), "r"(c1) : "memory");
}
__device__ __forceinline__ void tma_red_2d(const CUtensorMap* tm, int c0, int c1, uint32_t src) {
    asm volatile("cp.reduce.async.bulk.tensor.2d.global.shared::cta.add.tile.bulk_group [%0, {%2, %3}], [%1];" ::"l"(tm), "r"(src), "r"(c0), "r"(c1) : "memory");
}
__device__ __forceinline__ void tma_st_2d(const CUtensorMap* tm, int c0, int c1, uint32_t src) {
    asm volatile("cp.async.bulk.tensor.2d.global.shared::cta.tile.bulk_group [%0, {%2, %3}], [%1];" ::"l"(tm), "r"(src), "r"(c0), "r"(c1) : "memory");
}
__device__ __forceinline__ void bulk_commit() { asm volatile("cp.async.bulk.commit_group;" ::: "memory"); }
__device__ __forceinline__ void bulk_wait_all() { asm volatile("cp.async.bulk.wait_group.read 0;" ::: "memory"); }
__device__ __forceinline__ bool elect_one() {
    uint32_t p;
    asm volatile("{\n.reg .pred P;\nelect.sync _|P, 0xffffffff;\nselp.b32 %0, 1, 0, P;\n}\n" : "=r"(p));
    return p != 0;
}
__device__ __forceinline__ void prefetch_l2(const void* p, int bytes) { asm volatile("cp.async.bulk.prefetch.L2.global [%0], %1;" ::"l"(p), "r"(bytes) : "memory"); }
__device__ __forceinline__ void prefetch_map(const CUtensorMap* tm) { asm volatile("prefetch.tensormap [%0];" ::"l"(tm) : "memory"); }
__device__ __forceinline__ void pdl_launch() { asm volatile("griddepcontrol.launch_dependents;" ::: "memory"); }
__device__ __forceinline__ void pdl_wait() { asm volatile("griddepcontrol.wait;" ::: "memory"); }
__device__ __forceinline__ float ex2(float x) { float y; asm("ex2.approx.ftz.f32 %0, %1;" : "=f"(y) : "f"(x)); return y; }
__device__ __forceinline__ float rcp(float x) { float y; asm("rcp.approx.ftz.f32 %0, %1;" : "=f"(y) : "f"(x)); return y; }
__device__ __forceinline__ uint32_t pack_bf16(float lo, float hi) { uint32_t r; asm("cvt.rn.bf16x2.f32 %0, %1, %2;" : "=r"(r) : "f"(hi), "f"(lo)); return r; }
__device__ __forceinline__ float bf_lo(uint32_t v) { return __uint_as_float(v << 16); }
__device__ __forceinline__ float bf_hi(uint32_t v) { return __uint_as_float(v & 0xFFFF0000u); }
__device__ __forceinline__ uint32_t hfma2(uint32_t a, uint32_t b, uint32_t c) { uint32_t r; asm("fma.rn.f16x2 %0, %1, %2, %3;" : "=r"(r) : "r"(a), "r"(b), "r"(c)); return r; }
__device__ __forceinline__ void stmatrix_x4(uint32_t addr, uint32_t r0, uint32_t r1, uint32_t r2, uint32_t r3) {
    asm volatile("stmatrix.sync.aligned.m8n8.x4.shared.b16 [%0], {%1, %2, %3, %4};" ::"r"(addr), "r"(r0), "r"(r1), "r"(r2), "r"(r3) : "memory");
}

template <int TB> __device__ __forceinline__ void wgmma_ss_n24(float (&d)[12], uint64_t da, uint64_t db, int sc) {
    asm volatile("{\n.reg .pred p;\nsetp.ne.b32 p, %14, 0;\n"
        "wgmma.mma_async.sync.aligned.m64n24k16.f32.bf16.bf16 {%0, %1, %2, %3, %4, %5, %6, %7, %8, %9, %10, %11}, %12, %13, p, 1, 1, 0, %15;\n}\n"
        : "+f"(d[0]), "+f"(d[1]), "+f"(d[2]), "+f"(d[3]), "+f"(d[4]), "+f"(d[5]), "+f"(d[6]), "+f"(d[7]), "+f"(d[8]), "+f"(d[9]), "+f"(d[10]), "+f"(d[11])
        : "l"(da), "l"(db), "r"(sc), "n"(TB));
}
template <int TB> __device__ __forceinline__ void wgmma_ss_n64(float (&d)[32], uint64_t da, uint64_t db, int sc) {
    asm volatile("{\n.reg .pred p;\nsetp.ne.b32 p, %34, 0;\n"
        "wgmma.mma_async.sync.aligned.m64n64k16.f32.bf16.bf16 {%0, %1, %2, %3, %4, %5, %6, %7, %8, %9, %10, %11, %12, %13, %14, %15, %16, %17, %18, %19, %20, %21, %22, %23, %24, %25, %26, %27, %28, %29, %30, %31}, %32, %33, p, 1, 1, 0, %35;\n}\n"
        : "+f"(d[0]), "+f"(d[1]), "+f"(d[2]), "+f"(d[3]), "+f"(d[4]), "+f"(d[5]), "+f"(d[6]), "+f"(d[7]), "+f"(d[8]), "+f"(d[9]), "+f"(d[10]), "+f"(d[11]), "+f"(d[12]), "+f"(d[13]), "+f"(d[14]), "+f"(d[15]), "+f"(d[16]), "+f"(d[17]), "+f"(d[18]), "+f"(d[19]), "+f"(d[20]), "+f"(d[21]), "+f"(d[22]), "+f"(d[23]), "+f"(d[24]), "+f"(d[25]), "+f"(d[26]), "+f"(d[27]), "+f"(d[28]), "+f"(d[29]), "+f"(d[30]), "+f"(d[31])
        : "l"(da), "l"(db), "r"(sc), "n"(TB));
}
template <int TB> __device__ __forceinline__ void wgmma_ss_n128(float (&d)[64], uint64_t da, uint64_t db, int sc) {
    asm volatile("{\n.reg .pred p;\nsetp.ne.b32 p, %66, 0;\n"
        "wgmma.mma_async.sync.aligned.m64n128k16.f32.bf16.bf16 {%0, %1, %2, %3, %4, %5, %6, %7, %8, %9, %10, %11, %12, %13, %14, %15, %16, %17, %18, %19, %20, %21, %22, %23, %24, %25, %26, %27, %28, %29, %30, %31, %32, %33, %34, %35, %36, %37, %38, %39, %40, %41, %42, %43, %44, %45, %46, %47, %48, %49, %50, %51, %52, %53, %54, %55, %56, %57, %58, %59, %60, %61, %62, %63}, %64, %65, p, 1, 1, 0, %67;\n}\n"
        : "+f"(d[0]), "+f"(d[1]), "+f"(d[2]), "+f"(d[3]), "+f"(d[4]), "+f"(d[5]), "+f"(d[6]), "+f"(d[7]), "+f"(d[8]), "+f"(d[9]), "+f"(d[10]), "+f"(d[11]), "+f"(d[12]), "+f"(d[13]), "+f"(d[14]), "+f"(d[15]), "+f"(d[16]), "+f"(d[17]), "+f"(d[18]), "+f"(d[19]), "+f"(d[20]), "+f"(d[21]), "+f"(d[22]), "+f"(d[23]), "+f"(d[24]), "+f"(d[25]), "+f"(d[26]), "+f"(d[27]), "+f"(d[28]), "+f"(d[29]), "+f"(d[30]), "+f"(d[31]), "+f"(d[32]), "+f"(d[33]), "+f"(d[34]), "+f"(d[35]), "+f"(d[36]), "+f"(d[37]), "+f"(d[38]), "+f"(d[39]), "+f"(d[40]), "+f"(d[41]), "+f"(d[42]), "+f"(d[43]), "+f"(d[44]), "+f"(d[45]), "+f"(d[46]), "+f"(d[47]), "+f"(d[48]), "+f"(d[49]), "+f"(d[50]), "+f"(d[51]), "+f"(d[52]), "+f"(d[53]), "+f"(d[54]), "+f"(d[55]), "+f"(d[56]), "+f"(d[57]), "+f"(d[58]), "+f"(d[59]), "+f"(d[60]), "+f"(d[61]), "+f"(d[62]), "+f"(d[63])
        : "l"(da), "l"(db), "r"(sc), "n"(TB));
}
template <int TB> __device__ __forceinline__ void wgmma_rs_n24(float (&d)[12], uint32_t a0, uint32_t a1, uint32_t a2, uint32_t a3, uint64_t db, int sc) {
    asm volatile("{\n.reg .pred p;\nsetp.ne.b32 p, %17, 0;\n"
        "wgmma.mma_async.sync.aligned.m64n24k16.f32.bf16.bf16 {%0, %1, %2, %3, %4, %5, %6, %7, %8, %9, %10, %11}, {%12, %13, %14, %15}, %16, p, 1, 1, %18;\n}\n"
        : "+f"(d[0]), "+f"(d[1]), "+f"(d[2]), "+f"(d[3]), "+f"(d[4]), "+f"(d[5]), "+f"(d[6]), "+f"(d[7]), "+f"(d[8]), "+f"(d[9]), "+f"(d[10]), "+f"(d[11])
        : "r"(a0), "r"(a1), "r"(a2), "r"(a3), "l"(db), "r"(sc), "n"(TB));
}
template <int TB> __device__ __forceinline__ void wgmma_rs_n64(float (&d)[32], uint32_t a0, uint32_t a1, uint32_t a2, uint32_t a3, uint64_t db, int sc) {
    asm volatile("{\n.reg .pred p;\nsetp.ne.b32 p, %37, 0;\n"
        "wgmma.mma_async.sync.aligned.m64n64k16.f32.bf16.bf16 {%0, %1, %2, %3, %4, %5, %6, %7, %8, %9, %10, %11, %12, %13, %14, %15, %16, %17, %18, %19, %20, %21, %22, %23, %24, %25, %26, %27, %28, %29, %30, %31}, {%32, %33, %34, %35}, %36, p, 1, 1, %38;\n}\n"
        : "+f"(d[0]), "+f"(d[1]), "+f"(d[2]), "+f"(d[3]), "+f"(d[4]), "+f"(d[5]), "+f"(d[6]), "+f"(d[7]), "+f"(d[8]), "+f"(d[9]), "+f"(d[10]), "+f"(d[11]), "+f"(d[12]), "+f"(d[13]), "+f"(d[14]), "+f"(d[15]), "+f"(d[16]), "+f"(d[17]), "+f"(d[18]), "+f"(d[19]), "+f"(d[20]), "+f"(d[21]), "+f"(d[22]), "+f"(d[23]), "+f"(d[24]), "+f"(d[25]), "+f"(d[26]), "+f"(d[27]), "+f"(d[28]), "+f"(d[29]), "+f"(d[30]), "+f"(d[31])
        : "r"(a0), "r"(a1), "r"(a2), "r"(a3), "l"(db), "r"(sc), "n"(TB));
}
template <int TB> __device__ __forceinline__ void wgmma_rs_n128(float (&d)[64], uint32_t a0, uint32_t a1, uint32_t a2, uint32_t a3, uint64_t db, int sc) {
    asm volatile("{\n.reg .pred p;\nsetp.ne.b32 p, %69, 0;\n"
        "wgmma.mma_async.sync.aligned.m64n128k16.f32.bf16.bf16 {%0, %1, %2, %3, %4, %5, %6, %7, %8, %9, %10, %11, %12, %13, %14, %15, %16, %17, %18, %19, %20, %21, %22, %23, %24, %25, %26, %27, %28, %29, %30, %31, %32, %33, %34, %35, %36, %37, %38, %39, %40, %41, %42, %43, %44, %45, %46, %47, %48, %49, %50, %51, %52, %53, %54, %55, %56, %57, %58, %59, %60, %61, %62, %63}, {%64, %65, %66, %67}, %68, p, 1, 1, %70;\n}\n"
        : "+f"(d[0]), "+f"(d[1]), "+f"(d[2]), "+f"(d[3]), "+f"(d[4]), "+f"(d[5]), "+f"(d[6]), "+f"(d[7]), "+f"(d[8]), "+f"(d[9]), "+f"(d[10]), "+f"(d[11]), "+f"(d[12]), "+f"(d[13]), "+f"(d[14]), "+f"(d[15]), "+f"(d[16]), "+f"(d[17]), "+f"(d[18]), "+f"(d[19]), "+f"(d[20]), "+f"(d[21]), "+f"(d[22]), "+f"(d[23]), "+f"(d[24]), "+f"(d[25]), "+f"(d[26]), "+f"(d[27]), "+f"(d[28]), "+f"(d[29]), "+f"(d[30]), "+f"(d[31]), "+f"(d[32]), "+f"(d[33]), "+f"(d[34]), "+f"(d[35]), "+f"(d[36]), "+f"(d[37]), "+f"(d[38]), "+f"(d[39]), "+f"(d[40]), "+f"(d[41]), "+f"(d[42]), "+f"(d[43]), "+f"(d[44]), "+f"(d[45]), "+f"(d[46]), "+f"(d[47]), "+f"(d[48]), "+f"(d[49]), "+f"(d[50]), "+f"(d[51]), "+f"(d[52]), "+f"(d[53]), "+f"(d[54]), "+f"(d[55]), "+f"(d[56]), "+f"(d[57]), "+f"(d[58]), "+f"(d[59]), "+f"(d[60]), "+f"(d[61]), "+f"(d[62]), "+f"(d[63])
        : "r"(a0), "r"(a1), "r"(a2), "r"(a3), "l"(db), "r"(sc), "n"(TB));
}

constexpr int P_THREADS = 288;
constexpr int P_NST = 6;
constexpr int P_A_BYTES = 9 * 8192;
constexpr int P_B_STAGE = 3 * 8192;
constexpr int P_SMEM = P_A_BYTES + P_NST * P_B_STAGE + 256 + 320;
constexpr uint32_t HI_SW128 = (1024u >> 4) | (1u << 30);

template <int NCOL, bool WAIT_A>
__device__ __forceinline__ void proj_mma(float (&acc)[NCOL / 2], uint32_t sA, uint32_t sB, uint32_t colofs, uint32_t fullB, uint32_t emptyB, uint32_t fullA, int lane) {
#pragma unroll 1
    for (int kb = 0; kb < 9; kb++) {
        const int s = kb >= P_NST ? kb - P_NST : kb;
        if (WAIT_A) mbar_wait(fullA + kb * 8, 0);

        mbar_wait(fullB + s * 8, kb >= P_NST ? 1 : 0);
        const uint32_t alo = desc_lo(sA + kb * 8192, 16), blo = desc_lo(sB + s * P_B_STAGE + colofs, 8192);
        wg_fence();
#pragma unroll
        for (int ks = 0; ks < 4; ks++) {
            const uint64_t da = desc64(alo + ks * 2, HI_SW128), db = desc64(blo + ks * 128, HI_SW128);
            if constexpr (NCOL == 128) wgmma_ss_n128<1>(acc, da, db, (kb | ks) != 0);
            else wgmma_ss_n64<1>(acc, da, db, (kb | ks) != 0);
        }
        wg_commit();
        if (kb + P_NST < 9 + 1) {
            wg_wait<1>();
            if (kb >= 1 && kb - 1 + P_NST < 9 && lane == 0) mbar_arrive(emptyB + (kb - 1) * 8);
        }
    }
    wg_wait<0>();
    pin(acc);
}

template <int NB>
__device__ __forceinline__ void stage_tile(const uint32_t (&pk)[NB * 2], uint32_t base, int w, int lane) {
    const int r = w * 16 + (lane & 7) + ((lane >> 3) & 1) * 8;
#pragma unroll
    for (int b = 0; b < NB; b += 2) {
        const uint32_t a = base + (b >> 3) * 8192 + r * 128 + ((((b & 7) + (lane >> 4)) ^ (r & 7)) << 4);
        stmatrix_x4(a, pk[2 * b], pk[2 * b + 1], pk[2 * b + 2], pk[2 * b + 3]);
    }
}

__device__ __forceinline__ uint32_t hsub2_bf16(uint32_t a, uint32_t b) { uint32_t r; asm("sub.rn.bf16x2 %0, %1, %2;" : "=r"(r) : "r"(a), "r"(b)); return r; }

constexpr int KV_RAW = DM * 18 * 2;

__global__ void __launch_bounds__(P_THREADS, 1)
k_qkv(const __grid_constant__ CUtensorMap tmWq, const __grid_constant__ CUtensorMap tmQ, const __nv_bfloat16* __restrict__ x, const __nv_bfloat16* __restrict__ wk, const __nv_bfloat16* __restrict__ wv) {
    extern __shared__ __align__(1024) uint8_t smem[];
    const uint32_t sA = smem_u32(smem), sB = sA + P_A_BYTES, bars = sB + P_NST * P_B_STAGE;
    const uint32_t fullB = bars, emptyB = bars + 64, fullX = bars + 128, fullW = bars + 136, rawFree = bars + 144;
    const uint32_t sRaw = sB + 3 * P_B_STAGE;
    float* s_rstd = reinterpret_cast<float*>(smem + P_A_BYTES + P_NST * P_B_STAGE + 256);
    const int tid = threadIdx.x, warp = __shfl_sync(~0u, tid >> 5, 0), lane = tid & 31;
    const bool isQ = blockIdx.x < 96;
    const int m = isQ ? blockIdx.x / 3 : blockIdx.x - 96, cg = blockIdx.x % 3;
    if (tid == 0) TS(0, 0);
    if (warp == 8) {
        if (elect_one()) {
            prefetch_map(&tmWq); prefetch_map(&tmQ);
            for (int i = 0; i < P_NST; i++) { mbar_init(fullB + i * 8, 1); mbar_init(emptyB + i * 8, 8); }
            mbar_init(fullX, 1); mbar_init(fullW, 1); mbar_init(rawFree, 8);
            bar_init_fence();
            mbar_expect(fullX, P_A_BYTES);
            bulk_g2s(sRaw, x + (size_t)m * 64 * DM, P_A_BYTES, fullX);
            if (isQ) {
                for (int kb = 0; kb < 3; kb++) {
                    mbar_expect(fullB + kb * 8, P_B_STAGE);
                    for (int a = 0; a < 3; a++) tma_2d(sB + kb * P_B_STAGE + a * 8192, &tmWq, cg * 192 + a * 64, kb * 64, fullB + kb * 8);
                }
            } else {
                mbar_expect(fullW, 2 * KV_RAW);
                bulk_g2s(sA, wk, KV_RAW, fullW);
                bulk_g2s(sA + KV_RAW, wv, KV_RAW, fullW);
            }
        }
        __syncwarp();
    }
    __syncthreads();
    pdl_launch();
    if (warp == 8) {
        if (isQ && elect_one()) {
            mbar_wait(rawFree, 0);
            for (int kb = 3; kb < 9; kb++) {
                const int s = kb >= P_NST ? kb - P_NST : kb;
                if (kb >= P_NST) mbar_wait(emptyB + s * 8, 0);
                mbar_expect(fullB + s * 8, P_B_STAGE);
                for (int a = 0; a < 3; a++) tma_2d(sB + s * P_B_STAGE + a * 8192, &tmWq, cg * 192 + a * 64, kb * 64, fullB + s * 8);
            }
        }
        return;
    }
    {
        const int row = tid >> 2, q = tid & 3, odd = row & 1;
        mbar_wait(fullX, 0);
        if (tid == 0) TS(0, 6);
        uint4 v[18];
#pragma unroll
        for (int i = 0; i < 18; i++)
            asm volatile("ld.shared.v4.b32 {%0, %1, %2, %3}, [%4];" : "=r"(v[i].x), "=r"(v[i].y), "=r"(v[i].z), "=r"(v[i].w) : "r"(sRaw + row * 1152 + (q + 4 * (i ^ odd)) * 16));
        float sum = 0.f, sum2 = 0.f, sq = 0.f, sq2 = 0.f;
#pragma unroll
        for (int i = 0; i < 18; i++) {
            const uint32_t w[4] = {v[i].x, v[i].y, v[i].z, v[i].w};
#pragma unroll
            for (int j = 0; j < 4; j++) { const float a = bf_lo(w[j]), b = bf_hi(w[j]); sum += a; sum2 += b; sq = fmaf(a, a, sq); sq2 = fmaf(b, b, sq2); }
        }
        __syncwarp();
        if (lane == 0) mbar_arrive(rawFree);
        sum += sum2; sq += sq2;
        sum += __shfl_xor_sync(~0u, sum, 1); sum += __shfl_xor_sync(~0u, sum, 2);
        sq += __shfl_xor_sync(~0u, sq, 1); sq += __shfl_xor_sync(~0u, sq, 2);
        if (tid == 0) TS(0, 4);
        if (!isQ) {
            mbar_wait(fullW, 0);
            if (tid == 0) TS(0, 7);
            const uint32_t* raw = reinterpret_cast<const uint32_t*>(smem);
            uint32_t wr[41];
#pragma unroll
            for (int i = 0; i < 40; i++) wr[i] = raw[tid + i * 256];
            wr[40] = raw[(tid & 127) + 40 * 256];
            int k = tid / 9, r = tid - k * 9;
#pragma unroll
            for (int i = 0; i < 41; i++) {
                const int sel = k >= DM, kk = k - sel * DM;
                uint32_t* dst = reinterpret_cast<uint32_t*>(smem + P_A_BYTES + (sel * 3 + (r >> 2)) * 9216 + (kk >> 3) * 128 + (kk & 7) * 16 + (r & 3) * 4);
                if (i < 40 || tid < 128) *dst = wr[i];
                k += 28; r += 4;
                if (r >= 9) { r -= 9; k++; }
            }
            named_sync(1, 256);
            if (tid == 0) TS(0, 8);
        }
        const float mean = sum * (1.0f / DM);
        if (q == 0) s_rstd[row] = rsqrtf(fmaxf(sq * (1.0f / DM) - mean * mean, 0.f) + LN_EPS);
        const uint32_t mhi = pack_bf16(mean, mean);
        const float rem = mean - bf_lo(mhi);
        const uint32_t mlo = pack_bf16(rem, rem);
#pragma unroll
        for (int i = 0; i < 18; i++) {
            const int c = q + 4 * (i ^ odd);
            const uint32_t o0 = hsub2_bf16(hsub2_bf16(v[i].x, mhi), mlo), o1 = hsub2_bf16(hsub2_bf16(v[i].y, mhi), mlo);
            const uint32_t o2 = hsub2_bf16(hsub2_bf16(v[i].z, mhi), mlo), o3 = hsub2_bf16(hsub2_bf16(v[i].w, mhi), mlo);
            asm volatile("st.shared.v4.b32 [%0], {%1, %2, %3, %4};" ::"r"(sA + (c >> 3) * 8192 + row * 128 + (((c & 7) ^ (row & 7)) << 4)), "r"(o0), "r"(o1), "r"(o2), "r"(o3) : "memory");
        }
    }
    proxy_fence();
    named_sync(1, 256);
    if (tid == 0) TS(0, 1);
    const int wg = warp >> 2, w = warp & 3, g = lane >> 2, t = lane & 3;
    const float rs0 = s_rstd[w * 16 + g], rs1 = s_rstd[w * 16 + g + 8];
    if (isQ) {
        const float c0 = rs0 * Q_SCALE, c1 = rs1 * Q_SCALE;
        if (wg == 0) {
            float acc[64];
            proj_mma<128, false>(acc, sA, sB, 0, fullB, emptyB, 0, lane);
            if (tid == 0) TS(0, 2);
            named_sync(1, 256);
            uint32_t pk[32];
#pragma unroll
            for (int i = 0; i < 16; i++) { pk[2 * i] = pack_bf16(acc[4 * i] * c0, acc[4 * i + 1] * c0); pk[2 * i + 1] = pack_bf16(acc[4 * i + 2] * c1, acc[4 * i + 3] * c1); }
            stage_tile<16>(pk, sA, w, lane);
        } else {
            float acc[32];
            proj_mma<64, false>(acc, sA, sB, 2 * 8192, fullB, emptyB, 0, lane);
            named_sync(1, 256);
            uint32_t pk[16];
#pragma unroll
            for (int i = 0; i < 8; i++) { pk[2 * i] = pack_bf16(acc[4 * i] * c0, acc[4 * i + 1] * c0); pk[2 * i + 1] = pack_bf16(acc[4 * i + 2] * c1, acc[4 * i + 3] * c1); }
            stage_tile<8>(pk, sA + 2 * 8192, w, lane);
        }
        proxy_fence();
        named_sync(1, 256);
        if (warp == 0 && elect_one()) {
            for (int a = 0; a < 3; a++) tma_st_2d(&tmQ, cg * 192 + a * 64, m * 64, sA + a * 8192);
            bulk_commit();
            bulk_wait_all();
        }
    } else {
        float acc[12];
        const uint32_t blo = desc_lo(sB + wg * 3 * 9216, 128);
#pragma unroll
        for (int i = 0; i < 12; i++) acc[i] = 0.f;
        pin(acc);
        wg_fence();
#pragma unroll 1
        for (int kb = 0; kb < 9; kb++) {
            const uint32_t alo = desc_lo(sA + kb * 8192, 16);
#pragma unroll
            for (int ks = 0; ks < 4; ks++)
                wgmma_ss_n24<1>(acc, desc64(alo + ks * 2, HI_SW128), desc64(blo + (kb * 4 + ks) * 16, desc_hi(9216, 0)), 1);
        }
        wg_commit();
        wg_wait<0>();
        pin(acc);
        uint32_t pk[6];
#pragma unroll
        for (int b = 0; b < 3; b++) { pk[2 * b] = pack_bf16(acc[4 * b] * rs0, acc[4 * b + 1] * rs0); pk[2 * b + 1] = pack_bf16(acc[4 * b + 2] * rs1, acc[4 * b + 3] * rs1); }
        float n0 = 0.f, n1 = 0.f, vm = 0.f;
#pragma unroll
        for (int b = 0; b < 3; b++) {
            if (b < 2 || t == 0) {
                const float a = bf_lo(pk[2 * b]), c = bf_hi(pk[2 * b]), d = bf_lo(pk[2 * b + 1]), e = bf_hi(pk[2 * b + 1]);
                n0 = fmaf(a, a, fmaf(c, c, n0)); n1 = fmaf(d, d, fmaf(e, e, n1));
            }
        }
        n0 += __shfl_xor_sync(~0u, n0, 1); n0 += __shfl_xor_sync(~0u, n0, 2);
        n1 += __shfl_xor_sync(~0u, n1, 1); n1 += __shfl_xor_sync(~0u, n1, 2);
        vm = fmaxf(n0, n1);
        if (!(n0 == n0) || !(n1 == n1)) vm = __int_as_float(0x7F800000);
#pragma unroll
        for (int o = 4; o < 32; o <<= 1) vm = fmaxf(vm, __shfl_xor_sync(~0u, vm, o));
        if (t != 0) {
            uint32_t lo, hi;
            if (wg == 0) {
                const int grp = m * 8 + w * 2;
                const uint32_t c = t == 1 ? 0x42FE3F80u   : (t == 2 ? 0x00003BC0u   : 0u);
                lo = ((POLY_MASK >> (grp & 15)) & 1) ? c : 0u;
                hi = ((POLY_MASK >> ((grp + 1) & 15)) & 1) ? c : 0u;
            } else {
                lo = hi = t == 1 ? 0x00003F80u : 0u;
            }
            pk[4] = lo; pk[5] = hi;
        }
        uint32_t* dst = reinterpret_cast<uint32_t*>(wg == 0 ? g_kc : g_vc) + (m * 8 + w * 2) * 96 + g * 4 + t;
#pragma unroll
        for (int b = 0; b < 3; b++) { dst[b * 32] = pk[2 * b]; dst[96 + b * 32] = pk[2 * b + 1]; }
        float* red = s_rstd + 64;
        if (lane == 0) red[warp] = (wg == 0) ? vm : (vm <= 1e24f ? 0.f : __int_as_float(0x7F800000));
        named_sync(1, 256);
        if (tid == 0) {
            float mx = red[0];
#pragma unroll
            for (int i = 1; i < 8; i++) mx = fmaxf(mx, red[i]);
            g_kmax[m] = mx;
        }
    }
    if (tid == 0) TS(0, 3);
}

constexpr int A_THREADS = 512;
constexpr int A_NPIECE = 8;
constexpr int A_OFF_Q = 2 * KV_BYTES;
constexpr int A_OFF_BAR = A_OFF_Q + 4 * 4096;
constexpr int A_SMEM = A_OFF_BAR + 128;

__device__ __forceinline__ uint32_t exp2_pair_fixed(float lo, float hi) {
    const uint32_t G = __byte_perm(__float_as_uint(lo), __float_as_uint(hi), 0x5410);
    const uint32_t Hh = G & 0x007F007Fu;
    const uint32_t tt = hfma2(Hh, 0xF96BF96Bu, 0x358C358Cu);
    return G - hfma2(tt, Hh, 0u);
}

__device__ __forceinline__ void attn_side_job(const __nv_bfloat16* __restrict__ w1, const __nv_bfloat16* __restrict__ w2, const __nv_bfloat16* __restrict__ wo) {
    const int e = blockIdx.x - 128, tid = threadIdx.x;
    if (tid < 32) {
        const char* p = reinterpret_cast<const char*>(wo) + e * (DM * DM * 2 / 4);
        for (int i = tid; i < DM * DM * 2 / 4 / 4608; i += 32) prefetch_l2(p + i * 4608, 4608);
        p = reinterpret_cast<const char*>(w1) + (size_t)e * (FF * DM * 2 / 4);
        for (int i = tid; i < FF * DM * 2 / 4 / 9216; i += 32) prefetch_l2(p + (size_t)i * 9216, 9216);
        p = reinterpret_cast<const char*>(w2) + (size_t)e * (FF * DM * 2 / 4);
        for (int i = tid; i < FF * DM * 2 / 4 / 9216; i += 32) prefetch_l2(p + (size_t)i * 9216, 9216);
    }
}

__global__ void __launch_bounds__(A_THREADS, 1)
k_attn(const __nv_bfloat16* __restrict__ w1, const __nv_bfloat16* __restrict__ w2, const __nv_bfloat16* __restrict__ wo) {
    extern __shared__ __align__(1024) uint8_t smem[];
    pdl_launch();
    if (blockIdx.x >= 128) { attn_side_job(w1, w2, wo); return; }
    const uint32_t sK = smem_u32(smem), sV = sK + KV_BYTES, bars = sK + A_OFF_BAR;
    const int tid = threadIdx.x;
    check_smem_base(sK);
    if (tid == 0) TS(1, 0);
    if (tid == 0) {
        for (int i = 0; i < A_NPIECE; i++) mbar_init(bars + i * 8, 1);
        bar_init_fence();
    }
    __syncthreads();
    pdl_wait();
    if (tid == 0) TS(1, 1);
    const int wg = __shfl_sync(~0u, tid >> 7, 0), w = (tid >> 5) & 3, lane = tid & 31, g = lane >> 2, t = lane & 3;
    const uint32_t* q32 = reinterpret_cast<const uint32_t*>(g_q);
    uint32_t* o32 = reinterpret_cast<uint32_t*>(g_o);
    int row = (blockIdx.x * 8 + wg) * 64 + w * 16 + g;
    uint32_t nq[6];
    nq[0] = q32[row * 9 + t]; nq[1] = q32[(row + 8) * 9 + t]; nq[2] = q32[row * 9 + 4 + t]; nq[3] = q32[(row + 8) * 9 + 4 + t];
    nq[4] = q32[row * 9 + 8]; nq[5] = q32[(row + 8) * 9 + 8];
    constexpr int PB = KV_BYTES / A_NPIECE;
    const float kmax_raw = g_kmax[lane];
    if (tid < 32 && elect_one()) {
        for (int i = 0; i < 2; i++) {
            mbar_expect(bars + i * 8, 2 * PB);
            bulk_g2s(sK + i * PB, reinterpret_cast<const char*>(g_kc) + i * PB, PB, bars + i * 8);
            bulk_g2s(sV + i * PB, reinterpret_cast<const char*>(g_vc) + i * PB, PB, bars + i * 8);
        }
    }
    float kmax2 = kmax_raw;
#pragma unroll
    for (int o = 1; o < 32; o <<= 1) kmax2 = fmaxf(kmax2, __shfl_xor_sync(~0u, kmax2, o));
    if (tid < 32 && elect_one()) {
        for (int i = 2; i < A_NPIECE; i++) {
            mbar_expect(bars + i * 8, 2 * PB);
            bulk_g2s(sK + i * PB, reinterpret_cast<const char*>(g_kc) + i * PB, PB, bars + i * 8);
            bulk_g2s(sV + i * PB, reinterpret_cast<const char*>(g_vc) + i * PB, PB, bars + i * 8);
        }
    }
    const uint32_t sQ = sK + A_OFF_Q + wg * 4096 + (w * 2) * 512 + g * 16 + t * 4;
    const uint64_t dQ0 = cdesc(A_OFF_Q, 128, 512, 0) + wg * 256, dQ1 = dQ0 + 16;
#pragma unroll 1
    for (int rep = 0; rep < 2; rep++, row += 256) {
        const uint32_t qa[4] = {nq[0], nq[1], nq[2], nq[3]};
        float n0, n1;
        {
            const float a0 = bf_lo(qa[0]), a1 = bf_hi(qa[0]), a2 = bf_lo(qa[2]), a3 = bf_hi(qa[2]);
            const float b0 = bf_lo(qa[1]), b1 = bf_hi(qa[1]), b2 = bf_lo(qa[3]), b3 = bf_hi(qa[3]);
            n0 = a0 * a0 + a1 * a1 + a2 * a2 + a3 * a3; n1 = b0 * b0 + b1 * b1 + b2 * b2 + b3 * b3;
            if (t == 0) {
                const float c0 = bf_lo(nq[4]), c1 = bf_hi(nq[4]), d0 = bf_lo(nq[5]), d1 = bf_hi(nq[5]);
                n0 += c0 * c0 + c1 * c1; n1 += d0 * d0 + d1 * d1;
            }
            n0 += __shfl_xor_sync(~0u, n0, 1); n0 += __shfl_xor_sync(~0u, n0, 2);
            n1 += __shfl_xor_sync(~0u, n1, 1); n1 += __shfl_xor_sync(~0u, n1, 2);
        }
        const uint32_t x0 = nq[4], x1 = nq[5];
        if (rep == 0) {
            const int nr = row + 256;
            nq[0] = q32[nr * 9 + t]; nq[1] = q32[(nr + 8) * 9 + t]; nq[2] = q32[nr * 9 + 4 + t]; nq[3] = q32[(nr + 8) * 9 + 4 + t];
            nq[4] = q32[nr * 9 + 8]; nq[5] = q32[(nr + 8) * 9 + 8];
        }
        if (tid == 0 && rep == 0) TS(1, 7);
        const bool unsafe = !(fmaxf(n0, n1) * kmax2 <= FAST_BOUND * FAST_BOUND) || !(n0 == n0) || !(n1 == n1);
        uint32_t any_unsafe;
        asm volatile("{\n.reg .pred p, q;\nsetp.ne.u32 p, %1, 0;\nbar.red.or.pred q, %2, 128, p;\nselp.u32 %0, 1, 0, q;\n}\n" : "=r"(any_unsafe) : "r"((uint32_t)unsafe), "r"(wg + 1) : "memory");
        any_unsafe = __shfl_sync(~0u, any_unsafe, 0);
        {
            const uint32_t cst = any_unsafe ? 0u : (t == 1 ? 0x3F804780u : (t == 2 ? 0x00003F80u : 0u));
            asm volatile("st.shared.b32 [%0], %1;" ::"r"(sQ), "r"(qa[0]) : "memory");
            asm volatile("st.shared.b32 [%0], %1;" ::"r"(sQ + 512), "r"(qa[1]) : "memory");
            asm volatile("st.shared.b32 [%0], %1;" ::"r"(sQ + 128), "r"(qa[2]) : "memory");
            asm volatile("st.shared.b32 [%0], %1;" ::"r"(sQ + 640), "r"(qa[3]) : "memory");
            asm volatile("st.shared.b32 [%0], %1;" ::"r"(sQ + 256), "r"(t == 0 ? x0 : cst) : "memory");
            asm volatile("st.shared.b32 [%0], %1;" ::"r"(sQ + 768), "r"(t == 0 ? x1 : cst) : "memory");
            asm volatile("st.shared.b32 [%0], %1;" ::"r"(sQ + 384), "r"(0u) : "memory");
            asm volatile("st.shared.b32 [%0], %1;" ::"r"(sQ + 896), "r"(0u) : "memory");
            proxy_fence();
            named_sync(wg + 1, 128);
        }
        if (tid == 0) TS(1, 2 + rep * 2);
        float o[12];
#pragma unroll
        for (int i = 0; i < 12; i++) o[i] = 0.f;
        pin(o);
        uint64_t dK0 = cdesc(0, 128, 384, 0), dK1 = cdesc(256, 0, 384, 0), dV = cdesc(KV_BYTES, 384, 128, 0);
        if (!any_unsafe) {
            float s[64];
#pragma unroll 1
            for (int j = 0; j < 16; j++) {
                if (rep == 0 && (j & 1) == 0) mbar_wait(bars + (j >> 1) * 8, 0);
                wg_fence();
                wgmma_ss_n128<0>(s, dQ0, dK0, 0);
                wgmma_ss_n128<0>(s, dQ1, dK1, 1);
                wg_commit();
                dK0 += 16 * 384 >> 4; dK1 += 16 * 384 >> 4;
                wg_wait<0>();
                pin(s);
                uint32_t p[32];
#pragma unroll
                for (int i = 0; i < 32; i++) {
                    if ((POLY_MASK >> (i >> 1)) & 1) p[i] = exp2_pair_fixed(s[2 * i], s[2 * i + 1]);
                    else p[i] = pack_bf16(ex2(s[2 * i]), ex2(s[2 * i + 1]));
                }
                pin(p);
                wg_fence();
#pragma unroll
                for (int k = 0; k < 8; k++) wgmma_rs_n24<1>(o, p[4 * k], p[4 * k + 1], p[4 * k + 2], p[4 * k + 3], dV + k * 48, 1);
                wg_commit();
                dV += 16 * 384 >> 4;
                wg_wait<0>();
            }
        } else {
            float s[64];
            float m0 = -INFINITY, m1 = -INFINITY;
#pragma unroll 1
            for (int j = 0; j < 16; j++) {
                if (rep == 0 && (j & 1) == 0) mbar_wait(bars + (j >> 1) * 8, 0);
                wg_fence();
                wgmma_ss_n128<0>(s, dQ0, dK0, 0);
                wgmma_ss_n128<0>(s, dQ1, dK1, 1);
                wg_commit();
                dK0 += 16 * 384 >> 4; dK1 += 16 * 384 >> 4;
                wg_wait<0>();
                pin(s);
                float x0m = m0, x1m = m1;
#pragma unroll
                for (int b = 0; b < 16; b++) { x0m = fmaxf(x0m, fmaxf(s[4 * b], s[4 * b + 1])); x1m = fmaxf(x1m, fmaxf(s[4 * b + 2], s[4 * b + 3])); }
                x0m = fmaxf(x0m, __shfl_xor_sync(~0u, x0m, 1)); x0m = fmaxf(x0m, __shfl_xor_sync(~0u, x0m, 2));
                x1m = fmaxf(x1m, __shfl_xor_sync(~0u, x1m, 1)); x1m = fmaxf(x1m, __shfl_xor_sync(~0u, x1m, 2));
                const float c0 = ex2(m0 - x0m), c1 = ex2(m1 - x1m);
                m0 = x0m; m1 = x1m;
#pragma unroll
                for (int b = 0; b < 3; b++) { o[4 * b] *= c0; o[4 * b + 1] *= c0; o[4 * b + 2] *= c1; o[4 * b + 3] *= c1; }
                uint32_t p[32];
#pragma unroll
                for (int b = 0; b < 16; b++) {
                    p[2 * b] = pack_bf16(ex2(s[4 * b] - m0), ex2(s[4 * b + 1] - m0));
                    p[2 * b + 1] = pack_bf16(ex2(s[4 * b + 2] - m1), ex2(s[4 * b + 3] - m1));
                }
                pin(p); pin(o);
                wg_fence();
#pragma unroll
                for (int k = 0; k < 8; k++) wgmma_rs_n24<1>(o, p[4 * k], p[4 * k + 1], p[4 * k + 2], p[4 * k + 3], dV + k * 48, 1);
                wg_commit();
                dV += 16 * 384 >> 4;
                wg_wait<0>();
            }
        }
        pin(o);
        if (tid == 0) TS(1, 3 + rep * 2);
        const float l0 = __shfl_sync(~0u, o[8], (lane & ~3) | 1), l1 = __shfl_sync(~0u, o[10], (lane & ~3) | 1);
        const float i0 = 1.0f / l0, i1 = 1.0f / l1;
        o32[row * 9 + t] = pack_bf16(o[0] * i0, o[1] * i0);
        o32[(row + 8) * 9 + t] = pack_bf16(o[2] * i1, o[3] * i1);
        o32[row * 9 + 4 + t] = pack_bf16(o[4] * i0, o[5] * i0);
        o32[(row + 8) * 9 + 4 + t] = pack_bf16(o[6] * i1, o[7] * i1);
        if (t == 0) { o32[row * 9 + 8] = pack_bf16(o[8] * i0, o[9] * i0); o32[(row + 8) * 9 + 8] = pack_bf16(o[10] * i1, o[11] * i1); }
    }
    if (tid == 0) TS(1, 6);
}

constexpr int O_THREADS = 416;
constexpr int O_OFF_STAT = 6 * 8192;

__global__ void __cluster_dims__(3, 1, 1) __launch_bounds__(O_THREADS, 1)
k_oproj(const __grid_constant__ CUtensorMap tmO, const __grid_constant__ CUtensorMap tmWo, const __grid_constant__ CUtensorMap tmX2, const __grid_constant__ CUtensorMap tmOut, const __nv_bfloat16* __restrict__ x) {
    extern __shared__ __align__(1024) uint8_t smem[];
    const uint32_t sA = smem_u32(smem), sB = sA + P_A_BYTES, bars = sB + P_NST * P_B_STAGE;
    const uint32_t fullB = bars, emptyB = bars + 64, fullA = bars + 128;
    const int tid = threadIdx.x, warp = __shfl_sync(~0u, tid >> 5, 0), lane = tid & 31;
    const int m = blockIdx.x / 3, cg = blockIdx.x % 3;
    if (tid == 0) TS(2, 0);
    check_smem_base(sA);
    if (warp == 12) {
        if (elect_one()) {
            prefetch_map(&tmWo); prefetch_map(&tmO); prefetch_map(&tmX2); prefetch_map(&tmOut);
            for (int i = 0; i < P_NST; i++) { mbar_init(fullB + i * 8, 1); mbar_init(emptyB + i * 8, 12); }
            for (int i = 0; i < 9; i++) mbar_init(fullA + i * 8, 1);
            bar_init_fence();
            for (int kb = 0; kb < P_NST; kb++) {
                mbar_expect(fullB + kb * 8, P_B_STAGE);
                for (int a = 0; a < 3; a++) tma_2d(sB + kb * P_B_STAGE + a * 8192, &tmWo, cg * 192 + a * 64, kb * 64, fullB + kb * 8);
            }
        }
        __syncwarp();
    }
    __syncthreads();
    pdl_launch();
    if (warp == 12) {
        if (elect_one()) {
            pdl_wait();
            TS(2, 1);
            for (int kb = 0; kb < 9; kb++) {
                mbar_expect(fullA + kb * 8, 8192);
                tma_2d(sA + kb * 8192, &tmO, kb * 64, m * 64, fullA + kb * 8);
            }
            for (int kb = P_NST; kb < 9; kb++) {
                const int s = kb - P_NST;
                mbar_wait(emptyB + s * 8, 0);
                mbar_expect(fullB + s * 8, P_B_STAGE);
                for (int a = 0; a < 3; a++) tma_2d(sB + s * P_B_STAGE + a * 8192, &tmWo, cg * 192 + a * 64, kb * 64, fullB + s * 8);
            }
        }
        return;
    }
    const int wg = warp >> 2, w = warp & 3, g = lane >> 2, t = lane & 3;
    uint32_t xr[16];
    {
        const uint32_t* x32 = reinterpret_cast<const uint32_t*>(x) + (((m * 64 + w * 16 + g) * DM + cg * 192 + wg * 64 + 2 * t) >> 1);
#pragma unroll
        for (int b = 0; b < 8; b++) { xr[2 * b] = __ldg(x32 + b * 4); xr[2 * b + 1] = __ldg(x32 + b * 4 + 4 * DM); }
    }
    float acc[32];
    {
        const uint64_t dA = cdesc(0, 16, 1024, 1), dB = cdesc(P_A_BYTES, 8192, 1024, 1) + wg * 512;
#pragma unroll 1
        for (int kb = 0; kb < 9; kb++) {
            const int s = kb >= P_NST ? kb - P_NST : kb;
            mbar_wait(fullA + kb * 8, 0);
            mbar_wait(fullB + s * 8, kb >= P_NST ? 1 : 0);
            wg_fence();
#pragma unroll
            for (int ks = 0; ks < 4; ks++) wgmma_ss_n64<1>(acc, dA + (kb * 512 + ks * 2), dB + (s * (P_B_STAGE >> 4) + ks * 128), (kb | ks) != 0);
            wg_commit();
            if (kb < 4) {
                wg_wait<1>();
                if (kb >= 1 && lane == 0) mbar_arrive(emptyB + (kb - 1) * 8);
            }
        }
        wg_wait<0>();
        pin(acc);
    }
    if (tid == 0) TS(2, 2);
    named_sync(1, 384);
    float s0 = 0.f, q0 = 0.f, s1 = 0.f, q1 = 0.f;
#pragma unroll
    for (int b = 0; b < 8; b++) {
        const uint32_t xa = xr[2 * b], xb = xr[2 * b + 1];
        const uint32_t ha = pack_bf16(acc[4 * b] + bf_lo(xa), acc[4 * b + 1] + bf_hi(xa));
        const uint32_t hb = pack_bf16(acc[4 * b + 2] + bf_lo(xb), acc[4 * b + 3] + bf_hi(xb));
        xr[2 * b] = ha; xr[2 * b + 1] = hb;
        const float a = bf_lo(ha), c = bf_hi(ha), d = bf_lo(hb), e = bf_hi(hb);
        s0 += a + c; q0 = fmaf(a, a, fmaf(c, c, q0));
        s1 += d + e; q1 = fmaf(d, d, fmaf(e, e, q1));
    }
    s0 += __shfl_xor_sync(~0u, s0, 1); s0 += __shfl_xor_sync(~0u, s0, 2);
    q0 += __shfl_xor_sync(~0u, q0, 1); q0 += __shfl_xor_sync(~0u, q0, 2);
    s1 += __shfl_xor_sync(~0u, s1, 1); s1 += __shfl_xor_sync(~0u, s1, 2);
    q1 += __shfl_xor_sync(~0u, q1, 1); q1 += __shfl_xor_sync(~0u, q1, 2);
    const int r = w * 16 + g;
    const uint32_t sStat = sA + O_OFF_STAT;
    if (t < 3) {
        uint32_t dst;
        asm("mapa.shared::cluster.u32 %0, %1, %2;" : "=r"(dst) : "r"(sStat + ((cg * 3 + wg) * 64 + r) * 8), "r"(t));
        asm volatile("st.shared::cluster.v2.f32 [%0], {%1, %2};" ::"r"(dst), "f"(s0), "f"(q0) : "memory");
        asm volatile("st.shared::cluster.v2.f32 [%0], {%1, %2};" ::"r"(dst + 64), "f"(s1), "f"(q1) : "memory");
    }
    if (tid == 0) TS(2, 4);
    asm volatile("barrier.cluster.arrive.release.aligned;" ::: "memory");
    stage_tile<8>(xr, sA + wg * 8192, w, lane);
    proxy_fence();
    named_sync(2 + wg, 128);
    const bool leader = w == 0 && elect_one();
    if (leader) { tma_st_2d(&tmOut, cg * 192 + wg * 64, m * 64, sA + wg * 8192); bulk_commit(); }
    asm volatile("barrier.cluster.wait.acquire.aligned;" ::: "memory");
    if (tid == 0) TS(2, 5);
    s0 = q0 = s1 = q1 = 0.f;
#pragma unroll
    for (int p = 0; p < 9; p++) {
        float a, b, c, d;
        asm volatile("ld.shared.v2.f32 {%0, %1}, [%2];" : "=f"(a), "=f"(b) : "r"(sStat + (p * 64 + r) * 8));
        asm volatile("ld.shared.v2.f32 {%0, %1}, [%2];" : "=f"(c), "=f"(d) : "r"(sStat + (p * 64 + r + 8) * 8));
        s0 += a; q0 += b; s1 += c; q1 += d;
    }
    const float m0 = s0 * (1.0f / DM), m1 = s1 * (1.0f / DM);
    const float rs0 = rsqrtf(fmaxf(q0 * (1.0f / DM) - m0 * m0, 0.f) + LN_EPS), rs1 = rsqrtf(fmaxf(q1 * (1.0f / DM) - m1 * m1, 0.f) + LN_EPS);
    const float n0 = -m0 * rs0, n1 = -m1 * rs1;
#pragma unroll
    for (int b = 0; b < 8; b++) {
        xr[2 * b] = pack_bf16(fmaf(bf_lo(xr[2 * b]), rs0, n0), fmaf(bf_hi(xr[2 * b]), rs0, n0));
        xr[2 * b + 1] = pack_bf16(fmaf(bf_lo(xr[2 * b + 1]), rs1, n1), fmaf(bf_hi(xr[2 * b + 1]), rs1, n1));
    }
    stage_tile<8>(xr, sA + (3 + wg) * 8192, w, lane);
    proxy_fence();
    named_sync(2 + wg, 128);
    if (tid == 0) TS(2, 6);
    if (leader) {
        tma_st_2d(&tmX2, cg * 192 + wg * 64, m * 64, sA + (3 + wg) * 8192);
        bulk_commit();
        bulk_wait_all();
    }
    if (tid == 0) TS(2, 3);
}

constexpr int F_THREADS = 384;
constexpr int F_NST = 6;
constexpr int F_STAGE = 96 * 128;
constexpr int F_X_BYTES = 9 * 16384;
constexpr int F_OFF_ST = F_X_BYTES;
constexpr int F_OFF_BAR = F_OFF_ST + F_NST * F_STAGE;
constexpr int F_SMEM = F_OFF_BAR + 256;

__device__ __forceinline__ void silu_s1(const float (&acc)[32], float (&tmp)[8], int piece) {
#pragma unroll
    for (int i = 0; i < 8; i++) tmp[i] = ex2(acc[8 * piece + i] * -LOG2E);
}
__device__ __forceinline__ float after_issue(float v, uint32_t tick) {
    uint32_t r;
    asm("lop3.b32 %0, %1, %1, %2, 0xF0;" : "=r"(r) : "r"(__float_as_uint(v)), "r"(tick));
    return __uint_as_float(r);
}
__device__ __forceinline__ uint32_t read_tick() { uint32_t c; asm volatile("mov.u32 %0, %%clock;" : "=r"(c)::"memory"); return c; }
__device__ __forceinline__ void silu_s2(float (&tmp)[8], uint32_t tick) {
    const float one = after_issue(1.0f, tick);
#pragma unroll
    for (int i = 0; i < 8; i++) tmp[i] = rcp(tmp[i] + one);
}
template <int C>
__device__ __forceinline__ void silu_s3(const float (&acc)[32], const float (&tmp)[8], uint32_t (&h1)[144], int piece) {
#pragma unroll
    for (int i = 0; i < 4; i++) h1[C * 16 + 4 * piece + i] = pack_bf16(acc[8 * piece + 2 * i] * tmp[2 * i], acc[8 * piece + 2 * i + 1] * tmp[2 * i + 1]);
}

struct FfnPipe {
    uint32_t full, empty;
    int lane;
    __device__ __forceinline__ void acquire(int s, uint32_t ph) const { mbar_wait(full + s * 8, ph); }
    __device__ __forceinline__ void release(int s) const { if (lane == 0) mbar_arrive(empty + s * 8); }
};

template <int C>
__device__ __forceinline__ void ffn_phase1_chunk(float (&cur)[32], float (&prev)[32], uint32_t (&h1)[144], const FfnPipe& pp, uint64_t dx, uint32_t fullX) {
    float tmp[2][8];
    const uint64_t dw = cdesc(F_OFF_ST, 8192, 1024, 1) + blockIdx.y * (C + 1);
    dx += blockIdx.y * C;
#pragma unroll
    for (int j = 0; j < 6; j++) {
        if (C == 0) { mbar_wait(fullX + ((6 * j) >> 2) * 8, 0); mbar_wait(fullX + ((6 * j + 5) >> 2) * 8, 0); }
        pp.acquire(j, C & 1);
        if (j == 0) pin(cur);
        wg_fence();
#pragma unroll
        for (int i = 0; i < 6; i++) {
            const int ks = 6 * j + i;
            wgmma_ss_n64<1>(cur, dx + ((ks >> 2) * 1024 + (ks & 3) * 2), dw + ((j * F_STAGE + i * 2048) >> 4), ks != 0);
        }
        wg_commit();
        if (C > 0 || j > 0) { wg_wait<1>(); pp.release((j + 5) % 6); }
        if (C > 0) {
            pin(prev);
            if (j >= 1) { pin(tmp[0]); if (j >= 2) pin(tmp[1]); }
            if (j >= 2) silu_s3<(C > 0 ? C - 1 : 0)>(prev, tmp[j & 1], h1, j - 2);
            if (j >= 1 && j <= 4) { silu_s2(tmp[(j - 1) & 1], read_tick()); pin(tmp[(j - 1) & 1]); }
            if (j <= 3) { silu_s1(prev, tmp[j & 1], j); pin(tmp[j & 1]); }
            if (j >= 2) { asm volatile("" : "+r"(h1[(C - 1) * 16 + 4 * (j - 2)]), "+r"(h1[(C - 1) * 16 + 4 * (j - 2) + 1]), "+r"(h1[(C - 1) * 16 + 4 * (j - 2) + 2]), "+r"(h1[(C - 1) * 16 + 4 * (j - 2) + 3]) :: "memory"); }
        }
    }
}

__device__ __forceinline__ void ffn_store_chunk(const float (&acc)[32], const CUtensorMap* tmOut, uint32_t stg, int col, int row, int w, int lane, int wgid, bool leader) {
    uint32_t pk[16];
#pragma unroll
    for (int i = 0; i < 16; i++) pk[i] = pack_bf16(acc[2 * i], acc[2 * i + 1]);
    stage_tile<8>(pk, stg, w, lane);
    proxy_fence();
    named_sync(2 + wgid, 128);
    if (leader) {
        tma_red_2d(tmOut, col, row, stg);
        bulk_commit();
    }
}

__device__ __forceinline__ void ffn_phase2_chunk(float (&cur)[32], float (&prev)[32], uint32_t (&h1)[144], const FfnPipe& pp, uint32_t ph, bool store_prev, const CUtensorMap* tmOut, uint32_t stg_prev, int col_prev, int row, int w, int lane, int wgid, bool leader) {
    const uint64_t dw = cdesc(F_OFF_ST, 8192, 1024, 1) + blockIdx.y * col_prev;
#pragma unroll
    for (int j = 0; j < 6; j++) {
        pp.acquire(j, ph);
        if (j == 0) pin(cur);
        wg_fence();
#pragma unroll
        for (int i = 0; i < 6; i++) {
            const int f = (6 * j + i) * 4;
            wgmma_rs_n64<1>(cur, h1[f], h1[f + 1], h1[f + 2], h1[f + 3], dw + ((j * F_STAGE + i * 2048) >> 4), (j | i) != 0);
        }
        wg_commit();
        if (j > 0 || store_prev) { wg_wait<1>(); pp.release((j + 5) % 6); }
        if (j == 0 && store_prev) { pin(prev); ffn_store_chunk(prev, tmOut, stg_prev, col_prev, row, w, lane, wgid, leader); }
    }
}

__global__ void __launch_bounds__(F_THREADS, 1)
k_ffn(const __grid_constant__ CUtensorMap tmH, const __grid_constant__ CUtensorMap tmW1, const __grid_constant__ CUtensorMap tmW2, const __grid_constant__ CUtensorMap tmOut) {
    extern __shared__ __align__(1024) uint8_t smem[];
    const uint32_t sX = smem_u32(smem), sSt = sX + F_OFF_ST, bars = sX + F_OFF_BAR;
    const uint32_t full = bars, empty = bars + 64, fullX = bars + 128;
    const int tid = threadIdx.x, warp = __shfl_sync(~0u, tid >> 5, 0), lane = tid & 31;
    const int m = blockIdx.x & 15, fs = blockIdx.x >> 4;
    if (tid == 0) TS(3, 0);
    check_smem_base(sX);
    if (tid == 0) {
        prefetch_map(&tmW1); prefetch_map(&tmH); prefetch_map(&tmW2); prefetch_map(&tmOut);
        for (int i = 0; i < F_NST; i++) { mbar_init(full + i * 8, 1); mbar_init(empty + i * 8, 8); }
        for (int i = 0; i < 9; i++) mbar_init(fullX + i * 8, 1);
        bar_init_fence();
    }
    __syncthreads();
    if (warp < 4) {
        asm volatile("setmaxnreg.dec.sync.aligned.u32 24;");
        if (warp == 0 && elect_one()) {
            int s = 0; uint32_t ph = 1;
            int c = 0, j = 0;
#pragma unroll 1
            for (int i = 0; i < 108; i++) {
                if (i == F_NST) {
                    pdl_wait();
                    for (int kb = 0; kb < 9; kb++) {
                        mbar_expect(fullX + kb * 8, 16384);
                        tma_2d(sX + kb * 16384, &tmH, kb * 64, m * 128, fullX + kb * 8);
                    }
                }
                if (i == 54) c = fs;
                mbar_wait(empty + s * 8, ph);
                mbar_expect(full + s * 8, F_STAGE);
                if (i < 54) tma_2d(sSt + s * F_STAGE, &tmW1, fs * 576 + c * 64, j * 96, full + s * 8);
                else tma_2d(sSt + s * F_STAGE, &tmW2, c * 64, fs * 576 + j * 96, full + s * 8);
                if (++j == 6) { j = 0; if (++c == 9) c = 0; }
                if (++s == F_NST) { s = 0; ph ^= 1; }
            }
        }
    } else {
        asm volatile("setmaxnreg.inc.sync.aligned.u32 240;");
        const int wgid = (warp >> 2) - 1, w = warp & 3;
        pdl_wait();
        if (tid == 128) TS(3, 1);
        FfnPipe pp{full, empty, lane};
        const uint64_t xlo = cdesc(0, 16, 1024, 1) + wgid * 512;
        uint32_t h1[144];
        float acc0[32], acc1[32];
        ffn_phase1_chunk<0>(acc0, acc1, h1, pp, xlo, fullX);
        if (tid == 128) TS(3, 2);
        ffn_phase1_chunk<1>(acc1, acc0, h1, pp, xlo, fullX);
        ffn_phase1_chunk<2>(acc0, acc1, h1, pp, xlo, fullX);
        ffn_phase1_chunk<3>(acc1, acc0, h1, pp, xlo, fullX);
        ffn_phase1_chunk<4>(acc0, acc1, h1, pp, xlo, fullX);
        ffn_phase1_chunk<5>(acc1, acc0, h1, pp, xlo, fullX);
        ffn_phase1_chunk<6>(acc0, acc1, h1, pp, xlo, fullX);
        ffn_phase1_chunk<7>(acc1, acc0, h1, pp, xlo, fullX);
        ffn_phase1_chunk<8>(acc0, acc1, h1, pp, xlo, fullX);
        wg_wait<0>();
        pp.release(5);
        pin(acc0);
        {
            float tmp[4][8];
#pragma unroll
            for (int p = 0; p < 4; p++) silu_s1(acc0, tmp[p], p);
#pragma unroll
            for (int p = 0; p < 4; p++) silu_s2(tmp[p], 0);
#pragma unroll
            for (int p = 0; p < 4; p++) silu_s3<8>(acc0, tmp[p], h1, p);
        }
        pin(h1);
        if (tid == 128) TS(3, 3);
        const int row = m * 128 + wgid * 64;
        const uint32_t stg = sX + wgid * 8192;
        int c = fs, cprev = 0;
        const bool leader = w == 0 && elect_one();
#pragma unroll 1
        for (int j = 0; j < 8; j += 2) {
            ffn_phase2_chunk(acc1, acc0, h1, pp, 1, j > 0, &tmOut, stg + (j - 1) * 16384, cprev * 64, row, w, lane, wgid, leader);
            cprev = c; if (++c == 9) c = 0;
            ffn_phase2_chunk(acc0, acc1, h1, pp, 0, true, &tmOut, stg + j * 16384, cprev * 64, row, w, lane, wgid, leader);
            cprev = c; if (++c == 9) c = 0;
        }
        ffn_phase2_chunk(acc1, acc0, h1, pp, 1, true, &tmOut, stg + 7 * 16384, cprev * 64, row, w, lane, wgid, leader);
        wg_wait<0>();
        pin(acc1);
        ffn_store_chunk(acc1, &tmOut, stg + 8 * 16384, c * 64, row, w, lane, wgid, leader);
        if (tid == 128) TS(3, 4);
        if (leader) bulk_wait_all();
        if (tid == 128) TS(3, 5);
    }
}

typedef CUresult (*EncodeFn)(CUtensorMap*, CUtensorMapDataType, cuuint32_t, void*, const cuuint64_t*, const cuuint64_t*, const cuuint32_t*, const cuuint32_t*,
                             CUtensorMapInterleave, CUtensorMapSwizzle, CUtensorMapL2promotion, CUtensorMapFloatOOBfill);

CUtensorMap make_map(EncodeFn enc, const void* base, int rows, int cols, int box_rows) {
    CUtensorMap tm;
    cuuint64_t dims[2] = {(cuuint64_t)cols, (cuuint64_t)rows};
    cuuint64_t strides[1] = {(cuuint64_t)cols * 2};
    cuuint32_t box[2] = {64, (cuuint32_t)box_rows};
    cuuint32_t es[2] = {1, 1};
    enc(&tm, CU_TENSOR_MAP_DATA_TYPE_BFLOAT16, 2, const_cast<void*>(base), dims, strides, box, es, CU_TENSOR_MAP_INTERLEAVE_NONE,
        CU_TENSOR_MAP_SWIZZLE_128B, CU_TENSOR_MAP_L2_PROMOTION_L2_256B, CU_TENSOR_MAP_FLOAT_OOB_FILL_NONE);
    return tm;
}

template <typename... KArgs, typename... Args>
void launch(void (*kern)(KArgs...), int grid, int block, int smem, bool pdl, Args... args) {
    cudaLaunchConfig_t cfg = {};
    cfg.gridDim = dim3(grid); cfg.blockDim = dim3(block); cfg.dynamicSmemBytes = smem; cfg.stream = cudaStreamPerThread;
    cudaLaunchAttribute at[1];
    at[0].id = cudaLaunchAttributeProgrammaticStreamSerialization;
    at[0].val.programmaticStreamSerializationAllowed = 1;
    cfg.attrs = at; cfg.numAttrs = pdl ? 1 : 0;
    cudaLaunchKernelEx(&cfg, kern, KArgs(args)...);
}

}

#define USE_PDL 1

extern "C" void kernel_launch(void* const* d_in, const int* in_sizes, int n_in, void* d_out, int out_size) {
    const __nv_bfloat16* x = (const __nv_bfloat16*)d_in[0];
    const __nv_bfloat16* wq = (const __nv_bfloat16*)d_in[1];
    const __nv_bfloat16* wk = (const __nv_bfloat16*)d_in[2];
    const __nv_bfloat16* wv = (const __nv_bfloat16*)d_in[3];
    const __nv_bfloat16* wo = (const __nv_bfloat16*)d_in[4];
    const __nv_bfloat16* w1 = (const __nv_bfloat16*)d_in[6];
    const __nv_bfloat16* w2 = (const __nv_bfloat16*)d_in[7];
    __nv_bfloat16* out = (__nv_bfloat16*)d_out;

    static EncodeFn enc = nullptr;
    static void *p_o = nullptr, *p_h = nullptr, *p_q = nullptr;
    if (!enc) {
        cudaDriverEntryPointQueryResult qr;
        cudaGetDriverEntryPoint("cuTensorMapEncodeTiled", (void**)&enc, cudaEnableDefault, &qr);
        cudaGetSymbolAddress(&p_o, g_o);
        cudaGetSymbolAddress(&p_h, g_x2);
        cudaGetSymbolAddress(&p_q, g_q);
        cudaFuncSetAttribute(k_qkv, cudaFuncAttributeMaxDynamicSharedMemorySize, P_SMEM);
        cudaFuncSetAttribute(k_attn, cudaFuncAttributeMaxDynamicSharedMemorySize, A_SMEM);
        cudaFuncSetAttribute(k_oproj, cudaFuncAttributeMaxDynamicSharedMemorySize, P_SMEM);
        cudaFuncSetAttribute(k_ffn, cudaFuncAttributeMaxDynamicSharedMemorySize, F_SMEM);
    }
    const CUtensorMap tmWq = make_map(enc, wq, DM, DM, 64);
    const CUtensorMap tmWo = make_map(enc, wo, DM, DM, 64);
    const CUtensorMap tmO = make_map(enc, p_o, SEQ, DM, 64);
    const CUtensorMap tmH = make_map(enc, p_h, SEQ, DM, 128);
    const CUtensorMap tmH64 = make_map(enc, p_h, SEQ, DM, 64);
    const CUtensorMap tmQ = make_map(enc, p_q, SEQ, DM, 64);
    const CUtensorMap tmW1 = make_map(enc, w1, DM, FF, 96);
    const CUtensorMap tmW2 = make_map(enc, w2, FF, DM, 96);
    const CUtensorMap tmOut = make_map(enc, out, SEQ, DM, 64);

    launch(k_qkv, 128, P_THREADS, P_SMEM, false, tmWq, tmQ, x, wk, wv);
    launch(k_attn, 132, A_THREADS, A_SMEM, USE_PDL, w1, w2, wo);
    launch(k_oproj, 96, O_THREADS, P_SMEM, USE_PDL, tmO, tmWo, tmH64, tmOut, x);
    launch(k_ffn, 128, F_THREADS, F_SMEM, USE_PDL, tmH, tmW1, tmW2, tmOut);
}
```

```cpp
#include <cuda_runtime.h>
#include <cuda_bf16.h>
#include <cuda.h>
#include <stdint.h>

namespace {

constexpr int SEQ = 2048, DM = 576, FF = 4608;
constexpr int KV_BYTES = SEQ * 48;
constexpr float LN_EPS = 1e-5f;
constexpr float LOG2E = 1.4426950408889634f;
constexpr float LN2 = 0.6931471805599453f;
constexpr float Q_SCALE = 0.23570226039551584f * LOG2E;

#define POLY_MASK_V 0xB5B5u
constexpr uint32_t POLY_MASK = POLY_MASK_V;
constexpr float FAST_BOUND = 60.0f;

__device__ __align__(1024) __nv_bfloat16 g_q[SEQ * DM];
__device__ __align__(1024) uint4 g_kc[KV_BYTES / 16];
__device__ __align__(1024) uint4 g_vc[KV_BYTES / 16];
__device__ float g_kmax[32];
__device__ __align__(1024) __nv_bfloat16 g_o[SEQ * DM];
__device__ __align__(1024) __nv_bfloat16 g_x2[SEQ * DM];

#define TS(k, i)

__device__ __forceinline__ uint32_t smem_u32(const void* p) { return (uint32_t)__cvta_generic_to_shared(p); }
__device__ __forceinline__ void wg_fence() { asm volatile("wgmma.fence.sync.aligned;" ::: "memory"); }
__device__ __forceinline__ void wg_commit() { asm volatile("wgmma.commit_group.sync.aligned;" ::: "memory"); }
template <int N> __device__ __forceinline__ void wg_wait() { asm volatile("wgmma.wait_group.sync.aligned %0;" ::"n"(N) : "memory"); }
template <int N> __device__ __forceinline__ void pin(float (&r)[N]) {
#pragma unroll
    for (int i = 0; i < N; i++) asm volatile("" : "+f"(r[i])::"memory");
}
template <int N> __device__ __forceinline__ void pin(uint32_t (&r)[N]) {
#pragma unroll
    for (int i = 0; i < N; i++) asm volatile("" : "+r"(r[i])::"memory");
}
__device__ __forceinline__ constexpr uint32_t desc_hi(uint32_t sbo, uint32_t swz) { return (sbo >> 4) | (swz << 30); }
__device__ __forceinline__ uint32_t desc_lo(uint32_t addr, uint32_t lbo) { return ((addr & 0x3FFFF) >> 4) | ((lbo >> 4) << 16); }
__device__ __forceinline__ uint64_t desc64(uint32_t lo, uint32_t hi) { return ((uint64_t)hi << 32) | lo; }
constexpr uint32_t SMEM0 = 0x400;
__host__ __device__ constexpr uint64_t cdesc(uint32_t off, uint32_t lbo, uint32_t sbo, uint32_t swz) {
    return (uint64_t)(((SMEM0 + off) & 0x3FFFF) >> 4) | ((uint64_t)(lbo >> 4) << 16) | ((uint64_t)(sbo >> 4) << 32) | ((uint64_t)swz << 62);
}
__device__ __forceinline__ void check_smem_base(uint32_t base) { if ((base & 0x3FFFF) != SMEM0) __trap(); }

__device__ __forceinline__ void mbar_init(uint32_t bar, int cnt) { asm volatile("mbarrier.init.shared::cta.b64 [%0], %1;" ::"r"(bar), "r"(cnt) : "memory"); }
__device__ __forceinline__ void mbar_expect(uint32_t bar, int bytes) { asm volatile("mbarrier.arrive.expect_tx.shared::cta.b64 _, [%0], %1;" ::"r"(bar), "r"(bytes) : "memory"); }
__device__ __forceinline__ void mbar_arrive(uint32_t bar) { asm volatile("mbarrier.arrive.shared::cta.b64 _, [%0];" ::"r"(bar) : "memory"); }
__device__ __forceinline__ void mbar_wait(uint32_t bar, uint32_t parity) {
    asm volatile(
        "{\n.reg .pred p;\n.reg .u32 n;\nmov.u32 n, 0;\n"
        "LAB_WAIT:\n"
        "mbarrier.try_wait.parity.shared::cta.b64 p, [%0], %1;\n"
        "@p bra DONE;\n"
        "add.u32 n, n, 1;\n"
        "setp.lt.u32 p, n, 4000000;\n"
        "@p bra LAB_WAIT;\n"
        "trap;\n"
        "DONE:\n}\n" ::"r"(bar), "r"(parity) : "memory");
}
__device__ __forceinline__ void bar_init_fence() {
    asm volatile("fence.mbarrier_init.release.cluster;" ::: "memory");
    asm volatile("fence.proxy.async.shared::cta;" ::: "memory");
}
__device__ __forceinline__ void proxy_fence() { asm volatile("fence.proxy.async.shared::cta;" ::: "memory"); }
__device__ __forceinline__ void named_sync(int id, int n) { asm volatile("bar.sync %0, %1;" ::"r"(id), "r"(n) : "memory"); }
__device__ __forceinline__ void bulk_g2s(uint32_t dst, const void* src, int bytes, uint32_t bar) {
    asm volatile("cp.async.bulk.shared::cluster.global.mbarrier::complete_tx::bytes [%0], [%1], %2, [%3];" ::"r"(dst), "l"(src), "r"(bytes), "r"(bar) : "memory");
}
__device__ __forceinline__ void tma_2d(uint32_t dst, const CUtensorMap* tm, int c0, int c1, uint32_t bar) {
    asm volatile("cp.async.bulk.tensor.2d.shared::cluster.global.mbarrier::complete_tx::bytes [%0], [%1, {%3, %4}], [%2];" ::"r"(dst), "l"(tm), "r"(bar), "r"(c0), "r"(c1) : "memory");
}
__device__ __forceinline__ void tma_2d_mc(uint32_t dst, const CUtensorMap* tm, int c0, int c1, uint32_t bar, uint16_t mask) {
    asm volatile("cp.async.bulk.tensor.2d.shared::cluster.global.mbarrier::complete_tx::bytes.multicast::cluster [%0], [%1, {%3, %4}], [%2], %5;" ::"r"(dst), "l"(tm), "r"(bar), "r"(c0), "r"(c1), "h"(mask) : "memory");
}
__device__ __forceinline__ void cluster_arrive() { asm volatile("barrier.cluster.arrive.release.aligned;" ::: "memory"); }
__device__ __forceinline__ void cluster_wait() { asm volatile("barrier.cluster.wait.acquire.aligned;" ::: "memory"); }
__device__ __forceinline__ void tma_red_2d(const CUtensorMap* tm, int c0, int c1, uint32_t src) {
    asm volatile("cp.reduce.async.bulk.tensor.2d.global.shared::cta.add.tile.bulk_group [%0, {%2, %3}], [%1];" ::"l"(tm), "r"(src), "r"(c0), "r"(c1) : "memory");
}
__device__ __forceinline__ void tma_st_2d(const CUtensorMap* tm, int c0, int c1, uint32_t src) {
    asm volatile("cp.async.bulk.tensor.2d.global.shared::cta.tile.bulk_group [%0, {%2, %3}], [%1];" ::"l"(tm), "r"(src), "r"(c0), "r"(c1) : "memory");
}
__device__ __forceinline__ void bulk_commit() { asm volatile("cp.async.bulk.commit_group;" ::: "memory"); }
__device__ __forceinline__ void bulk_wait_all() { asm volatile("cp.async.bulk.wait_group.read 0;" ::: "memory"); }
__device__ __forceinline__ bool elect_one() {
    uint32_t p;
    asm volatile("{\n.reg .pred P;\nelect.sync _|P, 0xffffffff;\nselp.b32 %0, 1, 0, P;\n}\n" : "=r"(p));
    return p != 0;
}
__device__ __forceinline__ void prefetch_l2(const void* p, int bytes) { asm volatile("cp.async.bulk.prefetch.L2.global [%0], %1;" ::"l"(p), "r"(bytes) : "memory"); }
__device__ __forceinline__ void prefetch_map(const CUtensorMap* tm) { asm volatile("prefetch.tensormap [%0];" ::"l"(tm) : "memory"); }
__device__ __forceinline__ void pdl_launch() { asm volatile("griddepcontrol.launch_dependents;" ::: "memory"); }
__device__ __forceinline__ void pdl_wait() { asm volatile("griddepcontrol.wait;" ::: "memory"); }
__device__ __forceinline__ float ex2(float x) { float y; asm("ex2.approx.ftz.f32 %0, %1;" : "=f"(y) : "f"(x)); return y; }
__device__ __forceinline__ float rcp(float x) { float y; asm("rcp.approx.ftz.f32 %0, %1;" : "=f"(y) : "f"(x)); return y; }
__device__ __forceinline__ uint32_t pack_bf16(float lo, float hi) { uint32_t r; asm("cvt.rn.bf16x2.f32 %0, %1, %2;" : "=r"(r) : "f"(hi), "f"(lo)); return r; }
__device__ __forceinline__ float bf_lo(uint32_t v) { return __uint_as_float(v << 16); }
__device__ __forceinline__ float bf_hi(uint32_t v) { return __uint_as_float(v & 0xFFFF0000u); }
__device__ __forceinline__ uint32_t hfma2(uint32_t a, uint32_t b, uint32_t c) { uint32_t r; asm("fma.rn.f16x2 %0, %1, %2, %3;" : "=r"(r) : "r"(a), "r"(b), "r"(c)); return r; }
__device__ __forceinline__ void stmatrix_x4(uint32_t addr, uint32_t r0, uint32_t r1, uint32_t r2, uint32_t r3) {
    asm volatile("stmatrix.sync.aligned.m8n8.x4.shared.b16 [%0], {%1, %2, %3, %4};" ::"r"(addr), "r"(r0), "r"(r1), "r"(r2), "r"(r3) : "memory");
}

template <int TB> __device__ __forceinline__ void wgmma_ss_n24(float (&d)[12], uint64_t da, uint64_t db, int sc) {
    asm volatile("{\n.reg .pred p;\nsetp.ne.b32 p, %14, 0;\n"
        "wgmma.mma_async.sync.aligned.m64n24k16.f32.bf16.bf16 {%0, %1, %2, %3, %4, %5, %6, %7, %8, %9, %10, %11}, %12, %13, p, 1, 1, 0, %15;\n}\n"
        : "+f"(d[0]), "+f"(d[1]), "+f"(d[2]), "+f"(d[3]), "+f"(d[4]), "+f"(d[5]), "+f"(d[6]), "+f"(d[7]), "+f"(d[8]), "+f"(d[9]), "+f"(d[10]), "+f"(d[11])
        : "l"(da), "l"(db), "r"(sc), "n"(TB));
}
template <int TB> __device__ __forceinline__ void wgmma_ss_n64(float (&d)[32], uint64_t da, uint64_t db, int sc) {
    asm volatile("{\n.reg .pred p;\nsetp.ne.b32 p, %34, 0;\n"
        "wgmma.mma_async.sync.aligned.m64n64k16.f32.bf16.bf16 {%0, %1, %2, %3, %4, %5, %6, %7, %8, %9, %10, %11, %12, %13, %14, %15, %16, %17, %18, %19, %20, %21, %22, %23, %24, %25, %26, %27, %28, %29, %30, %31}, %32, %33, p, 1, 1, 0, %35;\n}\n"
        : "+f"(d[0]), "+f"(d[1]), "+f"(d[2]), "+f"(d[3]), "+f"(d[4]), "+f"(d[5]), "+f"(d[6]), "+f"(d[7]), "+f"(d[8]), "+f"(d[9]), "+f"(d[10]), "+f"(d[11]), "+f"(d[12]), "+f"(d[13]), "+f"(d[14]), "+f"(d[15]), "+f"(d[16]), "+f"(d[17]), "+f"(d[18]), "+f"(d[19]), "+f"(d[20]), "+f"(d[21]), "+f"(d[22]), "+f"(d[23]), "+f"(d[24]), "+f"(d[25]), "+f"(d[26]), "+f"(d[27]), "+f"(d[28]), "+f"(d[29]), "+f"(d[30]), "+f"(d[31])
        : "l"(da), "l"(db), "r"(sc), "n"(TB));
}
template <int TB> __device__ __forceinline__ void wgmma_ss_n128(float (&d)[64], uint64_t da, uint64_t db, int sc) {
    asm volatile("{\n.reg .pred p;\nsetp.ne.b32 p, %66, 0;\n"
        "wgmma.mma_async.sync.aligned.m64n128k16.f32.bf16.bf16 {%0, %1, %2, %3, %4, %5, %6, %7, %8, %9, %10, %11, %12, %13, %14, %15, %16, %17, %18, %19, %20, %21, %22, %23, %24, %25, %26, %27, %28, %29, %30, %31, %32, %33, %34, %35, %36, %37, %38, %39, %40, %41, %42, %43, %44, %45, %46, %47, %48, %49, %50, %51, %52, %53, %54, %55, %56, %57, %58, %59, %60, %61, %62, %63}, %64, %65, p, 1, 1, 0, %67;\n}\n"
        : "+f"(d[0]), "+f"(d[1]), "+f"(d[2]), "+f"(d[3]), "+f"(d[4]), "+f"(d[5]), "+f"(d[6]), "+f"(d[7]), "+f"(d[8]), "+f"(d[9]), "+f"(d[10]), "+f"(d[11]), "+f"(d[12]), "+f"(d[13]), "+f"(d[14]), "+f"(d[15]), "+f"(d[16]), "+f"(d[17]), "+f"(d[18]), "+f"(d[19]), "+f"(d[20]), "+f"(d[21]), "+f"(d[22]), "+f"(d[23]), "+f"(d[24]), "+f"(d[25]), "+f"(d[26]), "+f"(d[27]), "+f"(d[28]), "+f"(d[29]), "+f"(d[30]), "+f"(d[31]), "+f"(d[32]), "+f"(d[33]), "+f"(d[34]), "+f"(d[35]), "+f"(d[36]), "+f"(d[37]), "+f"(d[38]), "+f"(d[39]), "+f"(d[40]), "+f"(d[41]), "+f"(d[42]), "+f"(d[43]), "+f"(d[44]), "+f"(d[45]), "+f"(d[46]), "+f"(d[47]), "+f"(d[48]), "+f"(d[49]), "+f"(d[50]), "+f"(d[51]), "+f"(d[52]), "+f"(d[53]), "+f"(d[54]), "+f"(d[55]), "+f"(d[56]), "+f"(d[57]), "+f"(d[58]), "+f"(d[59]), "+f"(d[60]), "+f"(d[61]), "+f"(d[62]), "+f"(d[63])
        : "l"(da), "l"(db), "r"(sc), "n"(TB));
}
template <int TB> __device__ __forceinline__ void wgmma_rs_n24(float (&d)[12], uint32_t a0, uint32_t a1, uint32_t a2, uint32_t a3, uint64_t db, int sc) {
    asm volatile("{\n.reg .pred p;\nsetp.ne.b32 p, %17, 0;\n"
        "wgmma.mma_async.sync.aligned.m64n24k16.f32.bf16.bf16 {%0, %1, %2, %3, %4, %5, %6, %7, %8, %9, %10, %11}, {%12, %13, %14, %15}, %16, p, 1, 1, %18;\n}\n"
        : "+f"(d[0]), "+f"(d[1]), "+f"(d[2]), "+f"(d[3]), "+f"(d[4]), "+f"(d[5]), "+f"(d[6]), "+f"(d[7]), "+f"(d[8]), "+f"(d[9]), "+f"(d[10]), "+f"(d[11])
        : "r"(a0), "r"(a1), "r"(a2), "r"(a3), "l"(db), "r"(sc), "n"(TB));
}
template <int TB> __device__ __forceinline__ void wgmma_rs_n64(float (&d)[32], uint32_t a0, uint32_t a1, uint32_t a2, uint32_t a3, uint64_t db, int sc) {
    asm volatile("{\n.reg .pred p;\nsetp.ne.b32 p, %37, 0;\n"
        "wgmma.mma_async.sync.aligned.m64n64k16.f32.bf16.bf16 {%0, %1, %2, %3, %4, %5, %6, %7, %8, %9, %10, %11, %12, %13, %14, %15, %16, %17, %18, %19, %20, %21, %22, %23, %24, %25, %26, %27, %28, %29, %30, %31}, {%32, %33, %34, %35}, %36, p, 1, 1, %38;\n}\n"
        : "+f"(d[0]), "+f"(d[1]), "+f"(d[2]), "+f"(d[3]), "+f"(d[4]), "+f"(d[5]), "+f"(d[6]), "+f"(d[7]), "+f"(d[8]), "+f"(d[9]), "+f"(d[10]), "+f"(d[11]), "+f"(d[12]), "+f"(d[13]), "+f"(d[14]), "+f"(d[15]), "+f"(d[16]), "+f"(d[17]), "+f"(d[18]), "+f"(d[19]), "+f"(d[20]), "+f"(d[21]), "+f"(d[22]), "+f"(d[23]), "+f"(d[24]), "+f"(d[25]), "+f"(d[26]), "+f"(d[27]), "+f"(d[28]), "+f"(d[29]), "+f"(d[30]), "+f"(d[31])
        : "r"(a0), "r"(a1), "r"(a2), "r"(a3), "l"(db), "r"(sc), "n"(TB));
}
template <int TB> __device__ __forceinline__ void wgmma_rs_n128(float (&d)[64], uint32_t a0, uint32_t a1, uint32_t a2, uint32_t a3, uint64_t db, int sc) {
    asm volatile("{\n.reg .pred p;\nsetp.ne.b32 p, %69, 0;\n"
        "wgmma.mma_async.sync.aligned.m64n128k16.f32.bf16.bf16 {%0, %1, %2, %3, %4, %5, %6, %7, %8, %9, %10, %11, %12, %13, %14, %15, %16, %17, %18, %19, %20, %21, %22, %23, %24, %25, %26, %27, %28, %29, %30, %31, %32, %33, %34, %35, %36, %37, %38, %39, %40, %41, %42, %43, %44, %45, %46, %47, %48, %49, %50, %51, %52, %53, %54, %55, %56, %57, %58, %59, %60, %61, %62, %63}, {%64, %65, %66, %67}, %68, p, 1, 1, %70;\n}\n"
        : "+f"(d[0]), "+f"(d[1]), "+f"(d[2]), "+f"(d[3]), "+f"(d[4]), "+f"(d[5]), "+f"(d[6]), "+f"(d[7]), "+f"(d[8]), "+f"(d[9]), "+f"(d[10]), "+f"(d[11]), "+f"(d[12]), "+f"(d[13]), "+f"(d[14]), "+f"(d[15]), "+f"(d[16]), "+f"(d[17]), "+f"(d[18]), "+f"(d[19]), "+f"(d[20]), "+f"(d[21]), "+f"(d[22]), "+f"(d[23]), "+f"(d[24]), "+f"(d[25]), "+f"(d[26]), "+f"(d[27]), "+f"(d[28]), "+f"(d[29]), "+f"(d[30]), "+f"(d[31]), "+f"(d[32]), "+f"(d[33]), "+f"(d[34]), "+f"(d[35]), "+f"(d[36]), "+f"(d[37]), "+f"(d[38]), "+f"(d[39]), "+f"(d[40]), "+f"(d[41]), "+f"(d[42]), "+f"(d[43]), "+f"(d[44]), "+f"(d[45]), "+f"(d[46]), "+f"(d[47]), "+f"(d[48]), "+f"(d[49]), "+f"(d[50]), "+f"(d[51]), "+f"(d[52]), "+f"(d[53]), "+f"(d[54]), "+f"(d[55]), "+f"(d[56]), "+f"(d[57]), "+f"(d[58]), "+f"(d[59]), "+f"(d[60]), "+f"(d[61]), "+f"(d[62]), "+f"(d[63])
        : "r"(a0), "r"(a1), "r"(a2), "r"(a3), "l"(db), "r"(sc), "n"(TB));
}

constexpr int P_THREADS = 288;
constexpr int P_NST = 6;
constexpr int P_A_BYTES = 9 * 8192;
constexpr int P_B_STAGE = 3 * 8192;
constexpr int P_SMEM = P_A_BYTES + P_NST * P_B_STAGE + 256 + 320;
constexpr uint32_t HI_SW128 = (1024u >> 4) | (1u << 30);

template <int NCOL, bool WAIT_A>
__device__ __forceinline__ void proj_mma(float (&acc)[NCOL / 2], uint32_t sA, uint32_t sB, uint32_t colofs, uint32_t fullB, uint32_t emptyB, uint32_t fullA, int lane) {
#pragma unroll 1
    for (int kb = 0; kb < 9; kb++) {
        const int s = kb >= P_NST ? kb - P_NST : kb;
        if (WAIT_A) mbar_wait(fullA + kb * 8, 0);

        mbar_wait(fullB + s * 8, kb >= P_NST ? 1 : 0);
        const uint32_t alo = desc_lo(sA + kb * 8192, 16), blo = desc_lo(sB + s * P_B_STAGE + colofs, 8192);
        wg_fence();
#pragma unroll
        for (int ks = 0; ks < 4; ks++) {
            const uint64_t da = desc64(alo + ks * 2, HI_SW128), db = desc64(blo + ks * 128, HI_SW128);
            if constexpr (NCOL == 128) wgmma_ss_n128<1>(acc, da, db, (kb | ks) != 0);
            else wgmma_ss_n64<1>(acc, da, db, (kb | ks) != 0);
        }
        wg_commit();
        if (kb + P_NST < 9 + 1) {
            wg_wait<1>();
            if (kb >= 1 && kb - 1 + P_NST < 9 && lane == 0) mbar_arrive(emptyB + (kb - 1) * 8);
        }
    }
    wg_wait<0>();
    pin(acc);
}

template <int NB>
__device__ __forceinline__ void stage_tile(const uint32_t (&pk)[NB * 2], uint32_t base, int w, int lane) {
    const int r = w * 16 + (lane & 7) + ((lane >> 3) & 1) * 8;
#pragma unroll
    for (int b = 0; b < NB; b += 2) {
        const uint32_t a = base + (b >> 3) * 8192 + r * 128 + ((((b & 7) + (lane >> 4)) ^ (r & 7)) << 4);
        stmatrix_x4(a, pk[2 * b], pk[2 * b + 1], pk[2 * b + 2], pk[2 * b + 3]);
    }
}

__device__ __forceinline__ uint32_t hsub2_bf16(uint32_t a, uint32_t b) { uint32_t r; asm("sub.rn.bf16x2 %0, %1, %2;" : "=r"(r) : "r"(a), "r"(b)); return r; }

constexpr int KV_RAW = DM * 18 * 2;

__global__ void __launch_bounds__(P_THREADS, 1)
k_qkv(const __grid_constant__ CUtensorMap tmWq, const __grid_constant__ CUtensorMap tmQ, const __nv_bfloat16* __restrict__ x, const __nv_bfloat16* __restrict__ wk, const __nv_bfloat16* __restrict__ wv) {
    extern __shared__ __align__(1024) uint8_t smem[];
    const uint32_t sA = smem_u32(smem), sB = sA + P_A_BYTES, bars = sB + P_NST * P_B_STAGE;
    const uint32_t fullB = bars, emptyB = bars + 64, fullX = bars + 128, fullW = bars + 136, rawFree = bars + 144;
    const uint32_t sRaw = sB + 3 * P_B_STAGE;
    float* s_rstd = reinterpret_cast<float*>(smem + P_A_BYTES + P_NST * P_B_STAGE + 256);
    const int tid = threadIdx.x, warp = __shfl_sync(~0u, tid >> 5, 0), lane = tid & 31;
    const bool isQ = blockIdx.x < 96;
    const int m = isQ ? blockIdx.x / 3 : blockIdx.x - 96, cg = blockIdx.x % 3;
    if (tid == 0) TS(0, 0);
    if (warp == 8) {
        if (elect_one()) {
            prefetch_map(&tmWq); prefetch_map(&tmQ);
            for (int i = 0; i < P_NST; i++) { mbar_init(fullB + i * 8, 1); mbar_init(emptyB + i * 8, 8); }
            mbar_init(fullX, 1); mbar_init(fullW, 1); mbar_init(rawFree, 8);
            bar_init_fence();
            mbar_expect(fullX, P_A_BYTES);
            bulk_g2s(sRaw, x + (size_t)m * 64 * DM, P_A_BYTES, fullX);
            if (isQ) {
                for (int kb = 0; kb < 3; kb++) {
                    mbar_expect(fullB + kb * 8, P_B_STAGE);
                    for (int a = 0; a < 3; a++) tma_2d(sB + kb * P_B_STAGE + a * 8192, &tmWq, cg * 192 + a * 64, kb * 64, fullB + kb * 8);
                }
            } else {
                mbar_expect(fullW, 2 * KV_RAW);
                bulk_g2s(sA, wk, KV_RAW, fullW);
                bulk_g2s(sA + KV_RAW, wv, KV_RAW, fullW);
            }
        }
        __syncwarp();
    }
    __syncthreads();
    pdl_launch();
    if (warp == 8) {
        if (isQ && elect_one()) {
            mbar_wait(rawFree, 0);
            for (int kb = 3; kb < 9; kb++) {
                const int s = kb >= P_NST ? kb - P_NST : kb;
                if (kb >= P_NST) mbar_wait(emptyB + s * 8, 0);
                mbar_expect(fullB + s * 8, P_B_STAGE);
                for (int a = 0; a < 3; a++) tma_2d(sB + s * P_B_STAGE + a * 8192, &tmWq, cg * 192 + a * 64, kb * 64, fullB + s * 8);
            }
        }
        return;
    }
    {
        const int row = tid >> 2, q = tid & 3, odd = row & 1;
        mbar_wait(fullX, 0);
        if (tid == 0) TS(0, 6);
        uint4 v[18];
#pragma unroll
        for (int i = 0; i < 18; i++)
            asm volatile("ld.shared.v4.b32 {%0, %1, %2, %3}, [%4];" : "=r"(v[i].x), "=r"(v[i].y), "=r"(v[i].z), "=r"(v[i].w) : "r"(sRaw + row * 1152 + (q + 4 * (i ^ odd)) * 16));
        float sum = 0.f, sum2 = 0.f, sq = 0.f, sq2 = 0.f;
#pragma unroll
        for (int i = 0; i < 18; i++) {
            const uint32_t w[4] = {v[i].x, v[i].y, v[i].z, v[i].w};
#pragma unroll
            for (int j = 0; j < 4; j++) { const float a = bf_lo(w[j]), b = bf_hi(w[j]); sum += a; sum2 += b; sq = fmaf(a, a, sq); sq2 = fmaf(b, b, sq2); }
        }
        __syncwarp();
        if (lane == 0) mbar_arrive(rawFree);
        sum += sum2; sq += sq2;
        sum += __shfl_xor_sync(~0u, sum, 1); sum += __shfl_xor_sync(~0u, sum, 2);
        sq += __shfl_xor_sync(~0u, sq, 1); sq += __shfl_xor_sync(~0u, sq, 2);
        if (tid == 0) TS(0, 4);
        if (!isQ) {
            mbar_wait(fullW, 0);
            if (tid == 0) TS(0, 7);
            const uint32_t* raw = reinterpret_cast<const uint32_t*>(smem);
            uint32_t wr[41];
#pragma unroll
            for (int i = 0; i < 40; i++) wr[i] = raw[tid + i * 256];
            wr[40] = raw[(tid & 127) + 40 * 256];
            int k = tid / 9, r = tid - k * 9;
#pragma unroll
            for (int i = 0; i < 41; i++) {
                const int sel = k >= DM, kk = k - sel * DM;
                uint32_t* dst = reinterpret_cast<uint32_t*>(smem + P_A_BYTES + (sel * 3 + (r >> 2)) * 9216 + (kk >> 3) * 128 + (kk & 7) * 16 + (r & 3) * 4);
                if (i < 40 || tid < 128) *dst = wr[i];
                k += 28; r += 4;
                if (r >= 9) { r -= 9; k++; }
            }
            named_sync(1, 256);
            if (tid == 0) TS(0, 8);
        }
        const float mean = sum * (1.0f / DM);
        if (q == 0) s_rstd[row] = rsqrtf(fmaxf(sq * (1.0f / DM) - mean * mean, 0.f) + LN_EPS);
        const uint32_t mhi = pack_bf16(mean, mean);
        const float rem = mean - bf_lo(mhi);
        const uint32_t mlo = pack_bf16(rem, rem);
#pragma unroll
        for (int i = 0; i < 18; i++) {
            const int c = q + 4 * (i ^ odd);
            const uint32_t o0 = hsub2_bf16(hsub2_bf16(v[i].x, mhi), mlo), o1 = hsub2_bf16(hsub2_bf16(v[i].y, mhi), mlo);
            const uint32_t o2 = hsub2_bf16(hsub2_bf16(v[i].z, mhi), mlo), o3 = hsub2_bf16(hsub2_bf16(v[i].w, mhi), mlo);
            asm volatile("st.shared.v4.b32 [%0], {%1, %2, %3, %4};" ::"r"(sA + (c >> 3) * 8192 + row * 128 + (((c & 7) ^ (row & 7)) << 4)), "r"(o0), "r"(o1), "r"(o2), "r"(o3) : "memory");
        }
    }
    proxy_fence();
    named_sync(1, 256);
    if (tid == 0) TS(0, 1);
    const int wg = warp >> 2, w = warp & 3, g = lane >> 2, t = lane & 3;
    const float rs0 = s_rstd[w * 16 + g], rs1 = s_rstd[w * 16 + g + 8];
    if (isQ) {
        const float c0 = rs0 * Q_SCALE, c1 = rs1 * Q_SCALE;
        if (wg == 0) {
            float acc[64];
            proj_mma<128, false>(acc, sA, sB, 0, fullB, emptyB, 0, lane);
            if (tid == 0) TS(0, 2);
            named_sync(1, 256);
            uint32_t pk[32];
#pragma unroll
            for (int i = 0; i < 16; i++) { pk[2 * i] = pack_bf16(acc[4 * i] * c0, acc[4 * i + 1] * c0); pk[2 * i + 1] = pack_bf16(acc[4 * i + 2] * c1, acc[4 * i + 3] * c1); }
            stage_tile<16>(pk, sA, w, lane);
        } else {
            float acc[32];
            proj_mma<64, false>(acc, sA, sB, 2 * 8192, fullB, emptyB, 0, lane);
            named_sync(1, 256);
            uint32_t pk[16];
#pragma unroll
            for (int i = 0; i < 8; i++) { pk[2 * i] = pack_bf16(acc[4 * i] * c0, acc[4 * i + 1] * c0); pk[2 * i + 1] = pack_bf16(acc[4 * i + 2] * c1, acc[4 * i + 3] * c1); }
            stage_tile<8>(pk, sA + 2 * 8192, w, lane);
        }
        proxy_fence();
        named_sync(1, 256);
        if (warp == 0 && elect_one()) {
            for (int a = 0; a < 3; a++) tma_st_2d(&tmQ, cg * 192 + a * 64, m * 64, sA + a * 8192);
            bulk_commit();
            bulk_wait_all();
        }
    } else {
        float acc[12];
        const uint32_t blo = desc_lo(sB + wg * 3 * 9216, 128);
#pragma unroll
        for (int i = 0; i < 12; i++) acc[i] = 0.f;
        pin(acc);
        wg_fence();
#pragma unroll 1
        for (int kb = 0; kb < 9; kb++) {
            const uint32_t alo = desc_lo(sA + kb * 8192, 16);
#pragma unroll
            for (int ks = 0; ks < 4; ks++)
                wgmma_ss_n24<1>(acc, desc64(alo + ks * 2, HI_SW128), desc64(blo + (kb * 4 + ks) * 16, desc_hi(9216, 0)), 1);
        }
        wg_commit();
        wg_wait<0>();
        pin(acc);
        uint32_t pk[6];
#pragma unroll
        for (int b = 0; b < 3; b++) { pk[2 * b] = pack_bf16(acc[4 * b] * rs0, acc[4 * b + 1] * rs0); pk[2 * b + 1] = pack_bf16(acc[4 * b + 2] * rs1, acc[4 * b + 3] * rs1); }
        float n0 = 0.f, n1 = 0.f, vm = 0.f;
#pragma unroll
        for (int b = 0; b < 3; b++) {
            if (b < 2 || t == 0) {
                const float a = bf_lo(pk[2 * b]), c = bf_hi(pk[2 * b]), d = bf_lo(pk[2 * b + 1]), e = bf_hi(pk[2 * b + 1]);
                n0 = fmaf(a, a, fmaf(c, c, n0)); n1 = fmaf(d, d, fmaf(e, e, n1));
            }
        }
        n0 += __shfl_xor_sync(~0u, n0, 1); n0 += __shfl_xor_sync(~0u, n0, 2);
        n1 += __shfl_xor_sync(~0u, n1, 1); n1 += __shfl_xor_sync(~0u, n1, 2);
        vm = fmaxf(n0, n1);
        if (!(n0 == n0) || !(n1 == n1)) vm = __int_as_float(0x7F800000);
#pragma unroll
        for (int o = 4; o < 32; o <<= 1) vm = fmaxf(vm, __shfl_xor_sync(~0u, vm, o));
        if (t != 0) {
            uint32_t lo, hi;
            if (wg == 0) {
                const int grp = m * 8 + w * 2;
                const uint32_t c = t == 1 ? 0x42FE3F80u   : (t == 2 ? 0x00003BC0u   : 0u);
                lo = ((POLY_MASK >> (grp & 15)) & 1) ? c : 0u;
                hi = ((POLY_MASK >> ((grp + 1) & 15)) & 1) ? c : 0u;
            } else {
                lo = hi = t == 1 ? 0x00003F80u : 0u;
            }
            pk[4] = lo; pk[5] = hi;
        }
        uint32_t* dst = reinterpret_cast<uint32_t*>(wg == 0 ? g_kc : g_vc) + (m * 8 + w * 2) * 96 + g * 4 + t;
#pragma unroll
        for (int b = 0; b < 3; b++) { dst[b * 32] = pk[2 * b]; dst[96 + b * 32] = pk[2 * b + 1]; }
        float* red = s_rstd + 64;
        if (lane == 0) red[warp] = (wg == 0) ? vm : (vm <= 1e24f ? 0.f : __int_as_float(0x7F800000));
        named_sync(1, 256);
        if (tid == 0) {
            float mx = red[0];
#pragma unroll
            for (int i = 1; i < 8; i++) mx = fmaxf(mx, red[i]);
            g_kmax[m] = mx;
        }
    }
    if (tid == 0) TS(0, 3);
}

constexpr int A_THREADS = 512;
constexpr int A_NPIECE = 8;
constexpr int A_OFF_Q = 2 * KV_BYTES;
constexpr int A_OFF_BAR = A_OFF_Q + 4 * 4096;
constexpr int A_SMEM = A_OFF_BAR + 128;

__device__ __forceinline__ uint32_t exp2_pair_fixed(float lo, float hi) {
    const uint32_t G = __byte_perm(__float_as_uint(lo), __float_as_uint(hi), 0x5410);
    const uint32_t Hh = G & 0x007F007Fu;
    const uint32_t tt = hfma2(Hh, 0xF96BF96Bu, 0x358C358Cu);
    return G - hfma2(tt, Hh, 0u);
}

__device__ __forceinline__ void attn_side_job(const __nv_bfloat16* __restrict__ w1, const __nv_bfloat16* __restrict__ w2, const __nv_bfloat16* __restrict__ wo) {
    const int e = blockIdx.x - 128, tid = threadIdx.x;
    if (tid < 32) {
        const char* p = reinterpret_cast<const char*>(wo) + e * (DM * DM * 2 / 4);
        for (int i = tid; i < DM * DM * 2 / 4 / 4608; i += 32) prefetch_l2(p + i * 4608, 4608);
        p = reinterpret_cast<const char*>(w1) + (size_t)e * (FF * DM * 2 / 4);
        for (int i = tid; i < FF * DM * 2 / 4 / 9216; i += 32) prefetch_l2(p + (size_t)i * 9216, 9216);
        p = reinterpret_cast<const char*>(w2) + (size_t)e * (FF * DM * 2 / 4);
        for (int i = tid; i < FF * DM * 2 / 4 / 9216; i += 32) prefetch_l2(p + (size_t)i * 9216, 9216);
    }
}

__global__ void __launch_bounds__(A_THREADS, 1)
k_attn(const __nv_bfloat16* __restrict__ w1, const __nv_bfloat16* __restrict__ w2, const __nv_bfloat16* __restrict__ wo) {
    extern __shared__ __align__(1024) uint8_t smem[];
    pdl_launch();
    if (blockIdx.x >= 128) { attn_side_job(w1, w2, wo); return; }
    const uint32_t sK = smem_u32(smem), sV = sK + KV_BYTES, bars = sK + A_OFF_BAR;
    const int tid = threadIdx.x;
    check_smem_base(sK);
    if (tid == 0) TS(1, 0);
    if (tid == 0) {
        for (int i = 0; i < A_NPIECE; i++) mbar_init(bars + i * 8, 1);
        bar_init_fence();
    }
    __syncthreads();
    pdl_wait();
    if (tid == 0) TS(1, 1);
    const int wg = __shfl_sync(~0u, tid >> 7, 0), w = (tid >> 5) & 3, lane = tid & 31, g = lane >> 2, t = lane & 3;
    const uint32_t* q32 = reinterpret_cast<const uint32_t*>(g_q);
    uint32_t* o32 = reinterpret_cast<uint32_t*>(g_o);
    int row = (blockIdx.x * 8 + wg) * 64 + w * 16 + g;
    uint32_t nq[6];
    nq[0] = q32[row * 9 + t]; nq[1] = q32[(row + 8) * 9 + t]; nq[2] = q32[row * 9 + 4 + t]; nq[3] = q32[(row + 8) * 9 + 4 + t];
    nq[4] = q32[row * 9 + 8]; nq[5] = q32[(row + 8) * 9 + 8];
    constexpr int PB = KV_BYTES / A_NPIECE;
    const float kmax_raw = g_kmax[lane];
    if (tid < 32 && elect_one()) {
        for (int i = 0; i < 2; i++) {
            mbar_expect(bars + i * 8, 2 * PB);
            bulk_g2s(sK + i * PB, reinterpret_cast<const char*>(g_kc) + i * PB, PB, bars + i * 8);
            bulk_g2s(sV + i * PB, reinterpret_cast<const char*>(g_vc) + i * PB, PB, bars + i * 8);
        }
    }
    float kmax2 = kmax_raw;
#pragma unroll
    for (int o = 1; o < 32; o <<= 1) kmax2 = fmaxf(kmax2, __shfl_xor_sync(~0u, kmax2, o));
    if (tid < 32 && elect_one()) {
        for (int i = 2; i < A_NPIECE; i++) {
            mbar_expect(bars + i * 8, 2 * PB);
            bulk_g2s(sK + i * PB, reinterpret_cast<const char*>(g_kc) + i * PB, PB, bars + i * 8);
            bulk_g2s(sV + i * PB, reinterpret_cast<const char*>(g_vc) + i * PB, PB, bars + i * 8);
        }
    }
    const uint32_t sQ = sK + A_OFF_Q + wg * 4096 + (w * 2) * 512 + g * 16 + t * 4;
    const uint64_t dQ0 = cdesc(A_OFF_Q, 128, 512, 0) + wg * 256, dQ1 = dQ0 + 16;
#pragma unroll 1
    for (int rep = 0; rep < 2; rep++, row += 256) {
        const uint32_t qa[4] = {nq[0], nq[1], nq[2], nq[3]};
        float n0, n1;
        {
            const float a0 = bf_lo(qa[0]), a1 = bf_hi(qa[0]), a2 = bf_lo(qa[2]), a3 = bf_hi(qa[2]);
            const float b0 = bf_lo(qa[1]), b1 = bf_hi(qa[1]), b2 = bf_lo(qa[3]), b3 = bf_hi(qa[3]);
            n0 = a0 * a0 + a1 * a1 + a2 * a2 + a3 * a3; n1 = b0 * b0 + b1 * b1 + b2 * b2 + b3 * b3;
            if (t == 0) {
                const float c0 = bf_lo(nq[4]), c1 = bf_hi(nq[4]), d0 = bf_lo(nq[5]), d1 = bf_hi(nq[5]);
                n0 += c0 * c0 + c1 * c1; n1 += d0 * d0 + d1 * d1;
            }
            n0 += __shfl_xor_sync(~0u, n0, 1); n0 += __shfl_xor_sync(~0u, n0, 2);
            n1 += __shfl_xor_sync(~0u, n1, 1); n1 += __shfl_xor_sync(~0u, n1, 2);
        }
        const uint32_t x0 = nq[4], x1 = nq[5];
        if (rep == 0) {
            const int nr = row + 256;
            nq[0] = q32[nr * 9 + t]; nq[1] = q32[(nr + 8) * 9 + t]; nq[2] = q32[nr * 9 + 4 + t]; nq[3] = q32[(nr + 8) * 9 + 4 + t];
            nq[4] = q32[nr * 9 + 8]; nq[5] = q32[(nr + 8) * 9 + 8];
        }
        if (tid == 0 && rep == 0) TS(1, 7);
        const bool unsafe = !(fmaxf(n0, n1) * kmax2 <= FAST_BOUND * FAST_BOUND) || !(n0 == n0) || !(n1 == n1);
        uint32_t any_unsafe;
        asm volatile("{\n.reg .pred p, q;\nsetp.ne.u32 p, %1, 0;\nbar.red.or.pred q, %2, 128, p;\nselp.u32 %0, 1, 0, q;\n}\n" : "=r"(any_unsafe) : "r"((uint32_t)unsafe), "r"(wg + 1) : "memory");
        any_unsafe = __shfl_sync(~0u, any_unsafe, 0);
        {
            const uint32_t cst = any_unsafe ? 0u : (t == 1 ? 0x3F804780u : (t == 2 ? 0x00003F80u : 0u));
            asm volatile("st.shared.b32 [%0], %1;" ::"r"(sQ), "r"(qa[0]) : "memory");
            asm volatile("st.shared.b32 [%0], %1;" ::"r"(sQ + 512), "r"(qa[1]) : "memory");
            asm volatile("st.shared.b32 [%0], %1;" ::"r"(sQ + 128), "r"(qa[2]) : "memory");
            asm volatile("st.shared.b32 [%0], %1;" ::"r"(sQ + 640), "r"(qa[3]) : "memory");
            asm volatile("st.shared.b32 [%0], %1;" ::"r"(sQ + 256), "r"(t == 0 ? x0 : cst) : "memory");
            asm volatile("st.shared.b32 [%0], %1;" ::"r"(sQ + 768), "r"(t == 0 ? x1 : cst) : "memory");
            asm volatile("st.shared.b32 [%0], %1;" ::"r"(sQ + 384), "r"(0u) : "memory");
            asm volatile("st.shared.b32 [%0], %1;" ::"r"(sQ + 896), "r"(0u) : "memory");
            proxy_fence();
            named_sync(wg + 1, 128);
        }
        if (tid == 0) TS(1, 2 + rep * 2);
        float o[12];
#pragma unroll
        for (int i = 0; i < 12; i++) o[i] = 0.f;
        pin(o);
        uint64_t dK0 = cdesc(0, 128, 384, 0), dK1 = cdesc(256, 0, 384, 0), dV = cdesc(KV_BYTES, 384, 128, 0);
        if (!any_unsafe) {
            float s[64];
#pragma unroll 1
            for (int j = 0; j < 16; j++) {
                if (rep == 0 && (j & 1) == 0) mbar_wait(bars + (j >> 1) * 8, 0);
                wg_fence();
                wgmma_ss_n128<0>(s, dQ0, dK0, 0);
                wgmma_ss_n128<0>(s, dQ1, dK1, 1);
                wg_commit();
                dK0 += 16 * 384 >> 4; dK1 += 16 * 384 >> 4;
                wg_wait<0>();
                pin(s);
                uint32_t p[32];
#pragma unroll
                for (int i = 0; i < 32; i++) {
                    if ((POLY_MASK >> (i >> 1)) & 1) p[i] = exp2_pair_fixed(s[2 * i], s[2 * i + 1]);
                    else p[i] = pack_bf16(ex2(s[2 * i]), ex2(s[2 * i + 1]));
                }
                pin(p);
                wg_fence();
#pragma unroll
                for (int k = 0; k < 8; k++) wgmma_rs_n24<1>(o, p[4 * k], p[4 * k + 1], p[4 * k + 2], p[4 * k + 3], dV + k * 48, 1);
                wg_commit();
                dV += 16 * 384 >> 4;
                wg_wait<0>();
            }
        } else {
            float s[64];
            float m0 = -INFINITY, m1 = -INFINITY;
#pragma unroll 1
            for (int j = 0; j < 16; j++) {
                if (rep == 0 && (j & 1) == 0) mbar_wait(bars + (j >> 1) * 8, 0);
                wg_fence();
                wgmma_ss_n128<0>(s, dQ0, dK0, 0);
                wgmma_ss_n128<0>(s, dQ1, dK1, 1);
                wg_commit();
                dK0 += 16 * 384 >> 4; dK1 += 16 * 384 >> 4;
                wg_wait<0>();
                pin(s);
                float x0m = m0, x1m = m1;
#pragma unroll
                for (int b = 0; b < 16; b++) { x0m = fmaxf(x0m, fmaxf(s[4 * b], s[4 * b + 1])); x1m = fmaxf(x1m, fmaxf(s[4 * b + 2], s[4 * b + 3])); }
                x0m = fmaxf(x0m, __shfl_xor_sync(~0u, x0m, 1)); x0m = fmaxf(x0m, __shfl_xor_sync(~0u, x0m, 2));
                x1m = fmaxf(x1m, __shfl_xor_sync(~0u, x1m, 1)); x1m = fmaxf(x1m, __shfl_xor_sync(~0u, x1m, 2));
                const float c0 = ex2(m0 - x0m), c1 = ex2(m1 - x1m);
                m0 = x0m; m1 = x1m;
#pragma unroll
                for (int b = 0; b < 3; b++) { o[4 * b] *= c0; o[4 * b + 1] *= c0; o[4 * b + 2] *= c1; o[4 * b + 3] *= c1; }
                uint32_t p[32];
#pragma unroll
                for (int b = 0; b < 16; b++) {
                    p[2 * b] = pack_bf16(ex2(s[4 * b] - m0), ex2(s[4 * b + 1] - m0));
                    p[2 * b + 1] = pack_bf16(ex2(s[4 * b + 2] - m1), ex2(s[4 * b + 3] - m1));
                }
                pin(p); pin(o);
                wg_fence();
#pragma unroll
                for (int k = 0; k < 8; k++) wgmma_rs_n24<1>(o, p[4 * k], p[4 * k + 1], p[4 * k + 2], p[4 * k + 3], dV + k * 48, 1);
                wg_commit();
                dV += 16 * 384 >> 4;
                wg_wait<0>();
            }
        }
        pin(o);
        if (tid == 0) TS(1, 3 + rep * 2);
        const float l0 = __shfl_sync(~0u, o[8], (lane & ~3) | 1), l1 = __shfl_sync(~0u, o[10], (lane & ~3) | 1);
        const float i0 = 1.0f / l0, i1 = 1.0f / l1;
        o32[row * 9 + t] = pack_bf16(o[0] * i0, o[1] * i0);
        o32[(row + 8) * 9 + t] = pack_bf16(o[2] * i1, o[3] * i1);
        o32[row * 9 + 4 + t] = pack_bf16(o[4] * i0, o[5] * i0);
        o32[(row + 8) * 9 + 4 + t] = pack_bf16(o[6] * i1, o[7] * i1);
        if (t == 0) { o32[row * 9 + 8] = pack_bf16(o[8] * i0, o[9] * i0); o32[(row + 8) * 9 + 8] = pack_bf16(o[10] * i1, o[11] * i1); }
    }
    if (tid == 0) TS(1, 6);
    if ((tid & 127) == 0) TS(1, 10 + wg);
}

constexpr int O_THREADS = 416;
constexpr int O_OFF_STAT = 6 * 8192;

__global__ void __cluster_dims__(3, 1, 1) __launch_bounds__(O_THREADS, 1)
k_oproj(const __grid_constant__ CUtensorMap tmO, const __grid_constant__ CUtensorMap tmWo, const __grid_constant__ CUtensorMap tmX2, const __grid_constant__ CUtensorMap tmOut, const __nv_bfloat16* __restrict__ x) {
    extern __shared__ __align__(1024) uint8_t smem[];
    const uint32_t sA = smem_u32(smem), sB = sA + P_A_BYTES, bars = sB + P_NST * P_B_STAGE;
    const uint32_t fullB = bars, emptyB = bars + 64, fullA = bars + 128;
    const int tid = threadIdx.x, warp = __shfl_sync(~0u, tid >> 5, 0), lane = tid & 31;
    const int m = blockIdx.x / 3, cg = blockIdx.x % 3;
    if (tid == 0) TS(2, 0);
    check_smem_base(sA);
    if (warp == 12) {
        if (elect_one()) {
            prefetch_map(&tmWo); prefetch_map(&tmO); prefetch_map(&tmX2); prefetch_map(&tmOut);
            for (int i = 0; i < P_NST; i++) { mbar_init(fullB + i * 8, 1); mbar_init(emptyB + i * 8, 12); }
            for (int i = 0; i < 9; i++) mbar_init(fullA + i * 8, 1);
            bar_init_fence();
            for (int kb = 0; kb < P_NST; kb++) {
                mbar_expect(fullB + kb * 8, P_B_STAGE);
                for (int a = 0; a < 3; a++) tma_2d(sB + kb * P_B_STAGE + a * 8192, &tmWo, cg * 192 + a * 64, kb * 64, fullB + kb * 8);
            }
        }
        __syncwarp();
    }
    cluster_arrive();
    cluster_wait();
    pdl_launch();
    if (warp == 12) {
        if (elect_one()) {
            for (int kb = 0; kb < 9; kb++) mbar_expect(fullA + kb * 8, 8192);
            pdl_wait();
            TS(2, 1);
            for (int kb = cg; kb < 9; kb += 3) tma_2d_mc(sA + kb * 8192, &tmO, kb * 64, m * 64, fullA + kb * 8, (uint16_t)7);
            for (int kb = P_NST; kb < 9; kb++) {
                const int s = kb - P_NST;
                mbar_wait(emptyB + s * 8, 0);
                mbar_expect(fullB + s * 8, P_B_STAGE);
                for (int a = 0; a < 3; a++) tma_2d(sB + s * P_B_STAGE + a * 8192, &tmWo, cg * 192 + a * 64, kb * 64, fullB + s * 8);
            }
        }
        return;
    }
    const int wg = warp >> 2, w = warp & 3, g = lane >> 2, t = lane & 3;
    uint32_t xr[16];
    {
        const uint32_t* x32 = reinterpret_cast<const uint32_t*>(x) + (((m * 64 + w * 16 + g) * DM + cg * 192 + wg * 64 + 2 * t) >> 1);
#pragma unroll
        for (int b = 0; b < 8; b++) { xr[2 * b] = __ldg(x32 + b * 4); xr[2 * b + 1] = __ldg(x32 + b * 4 + 4 * DM); }
    }
    float acc[32];
    {
        const uint64_t dA = cdesc(0, 16, 1024, 1), dB = cdesc(P_A_BYTES, 8192, 1024, 1) + wg * 512;
#pragma unroll 1
        for (int kb = 0; kb < 9; kb++) {
            const int s = kb >= P_NST ? kb - P_NST : kb;
            mbar_wait(fullA + kb * 8, 0);
            mbar_wait(fullB + s * 8, kb >= P_NST ? 1 : 0);
            wg_fence();
#pragma unroll
            for (int ks = 0; ks < 4; ks++) wgmma_ss_n64<1>(acc, dA + (kb * 512 + ks * 2), dB + (s * (P_B_STAGE >> 4) + ks * 128), (kb | ks) != 0);
            wg_commit();
            if (kb < 4) {
                wg_wait<1>();
                if (kb >= 1 && lane == 0) mbar_arrive(emptyB + (kb - 1) * 8);
            }
        }
        wg_wait<0>();
        pin(acc);
    }
    if (tid == 0) TS(2, 2);
    named_sync(1, 384);
    float s0 = 0.f, q0 = 0.f, s1 = 0.f, q1 = 0.f;
#pragma unroll
    for (int b = 0; b < 8; b++) {
        const uint32_t xa = xr[2 * b], xb = xr[2 * b + 1];
        const uint32_t ha = pack_bf16(acc[4 * b] + bf_lo(xa), acc[4 * b + 1] + bf_hi(xa));
        const uint32_t hb = pack_bf16(acc[4 * b + 2] + bf_lo(xb), acc[4 * b + 3] + bf_hi(xb));
        xr[2 * b] = ha; xr[2 * b + 1] = hb;
        const float a = bf_lo(ha), c = bf_hi(ha), d = bf_lo(hb), e = bf_hi(hb);
        s0 += a + c; q0 = fmaf(a, a, fmaf(c, c, q0));
        s1 += d + e; q1 = fmaf(d, d, fmaf(e, e, q1));
    }
    s0 += __shfl_xor_sync(~0u, s0, 1); s0 += __shfl_xor_sync(~0u, s0, 2);
    q0 += __shfl_xor_sync(~0u, q0, 1); q0 += __shfl_xor_sync(~0u, q0, 2);
    s1 += __shfl_xor_sync(~0u, s1, 1); s1 += __shfl_xor_sync(~0u, s1, 2);
    q1 += __shfl_xor_sync(~0u, q1, 1); q1 += __shfl_xor_sync(~0u, q1, 2);
    const int r = w * 16 + g;
    const uint32_t sStat = sA + O_OFF_STAT;
    if (t < 3) {
        uint32_t dst;
        asm("mapa.shared::cluster.u32 %0, %1, %2;" : "=r"(dst) : "r"(sStat + ((cg * 3 + wg) * 64 + r) * 8), "r"(t));
        asm volatile("st.shared::cluster.v2.f32 [%0], {%1, %2};" ::"r"(dst), "f"(s0), "f"(q0) : "memory");
        asm volatile("st.shared::cluster.v2.f32 [%0], {%1, %2};" ::"r"(dst + 64), "f"(s1), "f"(q1) : "memory");
    }
    if (tid == 0) TS(2, 4);
    cluster_arrive();
    stage_tile<8>(xr, sA + wg * 8192, w, lane);
    proxy_fence();
    named_sync(2 + wg, 128);
    const bool leader = w == 0 && elect_one();
    if (leader) { tma_st_2d(&tmOut, cg * 192 + wg * 64, m * 64, sA + wg * 8192); bulk_commit(); }
    cluster_wait();
    if (tid == 0) TS(2, 5);
    s0 = q0 = s1 = q1 = 0.f;
#pragma unroll
    for (int p = 0; p < 9; p++) {
        float a, b, c, d;
        asm volatile("ld.shared.v2.f32 {%0, %1}, [%2];" : "=f"(a), "=f"(b) : "r"(sStat + (p * 64 + r) * 8));
        asm volatile("ld.shared.v2.f32 {%0, %1}, [%2];" : "=f"(c), "=f"(d) : "r"(sStat + (p * 64 + r + 8) * 8));
        s0 += a; q0 += b; s1 += c; q1 += d;
    }
    const float m0 = s0 * (1.0f / DM), m1 = s1 * (1.0f / DM);
    const float rs0 = rsqrtf(fmaxf(q0 * (1.0f / DM) - m0 * m0, 0.f) + LN_EPS), rs1 = rsqrtf(fmaxf(q1 * (1.0f / DM) - m1 * m1, 0.f) + LN_EPS);
    const float sc0 = -LOG2E * rs0, sc1 = -LOG2E * rs1, n0 = -m0 * sc0, n1 = -m1 * sc1;
#pragma unroll
    for (int b = 0; b < 8; b++) {
        xr[2 * b] = pack_bf16(fmaf(bf_lo(xr[2 * b]), sc0, n0), fmaf(bf_hi(xr[2 * b]), sc0, n0));
        xr[2 * b + 1] = pack_bf16(fmaf(bf_lo(xr[2 * b + 1]), sc1, n1), fmaf(bf_hi(xr[2 * b + 1]), sc1, n1));
    }
    stage_tile<8>(xr, sA + (3 + wg) * 8192, w, lane);
    proxy_fence();
    named_sync(2 + wg, 128);
    if (tid == 0) TS(2, 6);
    if (leader) {
        tma_st_2d(&tmX2, cg * 192 + wg * 64, m * 64, sA + (3 + wg) * 8192);
        bulk_commit();
        bulk_wait_all();
    }
    if (tid == 0) TS(2, 3);
}

constexpr int F_THREADS = 384;
constexpr int F_NST = 6;
constexpr int F_STAGE = 96 * 128;
constexpr int F_X_BYTES = 9 * 16384;
constexpr int F_OFF_ST = F_X_BYTES;
constexpr int F_OFF_BAR = F_OFF_ST + F_NST * F_STAGE;
constexpr int F_SMEM = F_OFF_BAR + 256;

__device__ __forceinline__ float after_issue(float v, uint32_t tick) {
    uint32_t r;
    asm("lop3.b32 %0, %1, %1, %2, 0xF0;" : "=r"(r) : "r"(__float_as_uint(v)), "r"(tick));
    return __uint_as_float(r);
}
__device__ __forceinline__ uint32_t read_tick() { uint32_t c; asm volatile("mov.u32 %0, %%clock;" : "=r"(c)::"memory"); return c; }
__device__ __forceinline__ void silu_s1(const float (&acc)[32], float (&tmp)[8], int piece) {
#pragma unroll
    for (int i = 0; i < 8; i++) tmp[i] = ex2(acc[8 * piece + i]);
}
__device__ __forceinline__ void silu_s2(float (&tmp)[8], uint32_t tick) {
    const float one = after_issue(1.0f, tick);
#pragma unroll
    for (int i = 0; i < 8; i++) tmp[i] = rcp(tmp[i] + one);
}
template <int C>
__device__ __forceinline__ void silu_s3(const float (&acc)[32], const float (&tmp)[8], uint32_t (&h1)[144], int piece) {
#pragma unroll
    for (int i = 0; i < 4; i++) h1[C * 16 + 4 * piece + i] = pack_bf16(acc[8 * piece + 2 * i] * tmp[2 * i], acc[8 * piece + 2 * i + 1] * tmp[2 * i + 1]);
}

struct FfnPipe {
    uint32_t full, empty;
    int lane;
    __device__ __forceinline__ void acquire(int s, uint32_t ph) const { mbar_wait(full + s * 8, ph); }
    __device__ __forceinline__ void release(int s) const { if (lane == 0) mbar_arrive(empty + s * 8); }
};

template <int C>
__device__ __forceinline__ void ffn_phase1_chunk(float (&cur)[32], float (&prev)[32], uint32_t (&h1)[144], const FfnPipe& pp, uint64_t dx, uint32_t fullX) {
    float tmp[2][8];
    const uint64_t dw = cdesc(F_OFF_ST, 8192, 1024, 1) + blockIdx.y * (C + 1);
    dx += blockIdx.y * C;
#pragma unroll
    for (int j = 0; j < 6; j++) {
        if (C == 0) { mbar_wait(fullX + ((6 * j) >> 2) * 8, 0); mbar_wait(fullX + ((6 * j + 5) >> 2) * 8, 0); }
        pp.acquire(j, C & 1);
        if (j == 0) pin(cur);
        wg_fence();
#pragma unroll
        for (int i = 0; i < 6; i++) {
            const int ks = 6 * j + i;
            wgmma_ss_n64<1>(cur, dx + ((ks >> 2) * 1024 + (ks & 3) * 2), dw + ((j * F_STAGE + i * 2048) >> 4), ks != 0);
        }
        wg_commit();
        if (C > 0 || j > 0) { wg_wait<1>(); pp.release((j + 5) % 6); }
        if (C > 0) {
            pin(prev);
            if (j >= 1) { pin(tmp[0]); if (j >= 2) pin(tmp[1]); }
            if (j >= 2) silu_s3<(C > 0 ? C - 1 : 0)>(prev, tmp[j & 1], h1, j - 2);
            if (j >= 1 && j <= 4) { silu_s2(tmp[(j - 1) & 1], read_tick()); pin(tmp[(j - 1) & 1]); }
            if (j <= 3) { silu_s1(prev, tmp[j & 1], j); pin(tmp[j & 1]); }
            if (j >= 2) { asm volatile("" : "+r"(h1[(C - 1) * 16 + 4 * (j - 2)]), "+r"(h1[(C - 1) * 16 + 4 * (j - 2) + 1]), "+r"(h1[(C - 1) * 16 + 4 * (j - 2) + 2]), "+r"(h1[(C - 1) * 16 + 4 * (j - 2) + 3]) :: "memory"); }
        }
    }
}

__device__ __forceinline__ void ffn_store_chunk(const float (&acc)[32], const CUtensorMap* tmOut, uint32_t stg, int col, int row, int w, int lane, int wgid, bool leader) {
    uint32_t pk[16];
#pragma unroll
    for (int i = 0; i < 16; i++) pk[i] = pack_bf16(acc[2 * i] * -LN2, acc[2 * i + 1] * -LN2);
    stage_tile<8>(pk, stg, w, lane);
    proxy_fence();
    named_sync(2 + wgid, 128);
    if (leader) {
        tma_red_2d(tmOut, col, row, stg);
        bulk_commit();
    }
}

__device__ __forceinline__ void ffn_phase2_chunk(float (&cur)[32], float (&prev)[32], uint32_t (&h1)[144], const FfnPipe& pp, uint32_t ph, bool store_prev, const CUtensorMap* tmOut, uint32_t stg_prev, int col_prev, int row, int w, int lane, int wgid, bool leader) {
    const uint64_t dw = cdesc(F_OFF_ST, 8192, 1024, 1) + blockIdx.y * col_prev;
#pragma unroll
    for (int j = 0; j < 6; j++) {
        pp.acquire(j, ph);
        if (j == 0) pin(cur);
        wg_fence();
#pragma unroll
        for (int i = 0; i < 6; i++) {
            const int f = (6 * j + i) * 4;
            wgmma_rs_n64<1>(cur, h1[f], h1[f + 1], h1[f + 2], h1[f + 3], dw + ((j * F_STAGE + i * 2048) >> 4), (j | i) != 0);
        }
        wg_commit();
        if (j > 0 || store_prev) { wg_wait<1>(); pp.release((j + 5) % 6); }
        if (j == 0 && store_prev) { pin(prev); ffn_store_chunk(prev, tmOut, stg_prev, col_prev, row, w, lane, wgid, leader); }
    }
}

__global__ void __cluster_dims__(2, 1, 1) __launch_bounds__(F_THREADS, 1)
k_ffn(const __grid_constant__ CUtensorMap tmH, const __grid_constant__ CUtensorMap tmW1, const __grid_constant__ CUtensorMap tmW2, const __grid_constant__ CUtensorMap tmOut) {
    extern __shared__ __align__(1024) uint8_t smem[];
    const uint32_t sX = smem_u32(smem), sSt = sX + F_OFF_ST, bars = sX + F_OFF_BAR;
    const uint32_t full = bars, empty = bars + 64, fullX = bars + 128;
    const int tid = threadIdx.x, warp = __shfl_sync(~0u, tid >> 5, 0), lane = tid & 31;
    const int m = (blockIdx.x >> 1) & 15, fs = (blockIdx.x >> 5) * 2 + (blockIdx.x & 1);
    if (tid == 0) TS(3, 0);
    check_smem_base(sX);
    if (tid == 0) {
        prefetch_map(&tmW1); prefetch_map(&tmH); prefetch_map(&tmW2); prefetch_map(&tmOut);
        for (int i = 0; i < F_NST; i++) { mbar_init(full + i * 8, 1); mbar_init(empty + i * 8, 8); }
        for (int i = 0; i < 9; i++) mbar_init(fullX + i * 8, 1);
        bar_init_fence();
    }
    cluster_arrive();
    cluster_wait();
    if (warp < 4) {
        asm volatile("setmaxnreg.dec.sync.aligned.u32 24;");
        if (warp == 0 && elect_one()) {
            int s = 0; uint32_t ph = 1;
            int c = 0, j = 0;
#pragma unroll 1
            for (int i = 0; i < 108; i++) {
                if (i == F_NST) {
                    for (int kb = 0; kb < 9; kb++) mbar_expect(fullX + kb * 8, 16384);
                    pdl_wait();
                    const int half = blockIdx.x & 1;
                    for (int kb = 0; kb < 9; kb++) tma_2d_mc(sX + kb * 16384 + half * 8192, &tmH, kb * 64, m * 128 + half * 64, fullX + kb * 8, (uint16_t)3);
                }
                if (i == 54) c = fs;
                mbar_wait(empty + s * 8, ph);
                mbar_expect(full + s * 8, F_STAGE);
                if (i < 54) tma_2d(sSt + s * F_STAGE, &tmW1, fs * 576 + c * 64, j * 96, full + s * 8);
                else tma_2d(sSt + s * F_STAGE, &tmW2, c * 64, fs * 576 + j * 96, full + s * 8);
                if (++j == 6) { j = 0; if (++c == 9) c = 0; }
                if (++s == F_NST) { s = 0; ph ^= 1; }
            }
        }
    } else {
        asm volatile("setmaxnreg.inc.sync.aligned.u32 240;");
        const int wgid = (warp >> 2) - 1, w = warp & 3;
        pdl_wait();
        if (tid == 128) TS(3, 1);
        FfnPipe pp{full, empty, lane};
        const uint64_t xlo = cdesc(0, 16, 1024, 1) + wgid * 512;
        uint32_t h1[144];
        float acc0[32], acc1[32];
        ffn_phase1_chunk<0>(acc0, acc1, h1, pp, xlo, fullX);
        if (tid == 128) TS(3, 2);
        ffn_phase1_chunk<1>(acc1, acc0, h1, pp, xlo, fullX);
        ffn_phase1_chunk<2>(acc0, acc1, h1, pp, xlo, fullX);
        ffn_phase1_chunk<3>(acc1, acc0, h1, pp, xlo, fullX);
        ffn_phase1_chunk<4>(acc0, acc1, h1, pp, xlo, fullX);
        ffn_phase1_chunk<5>(acc1, acc0, h1, pp, xlo, fullX);
        ffn_phase1_chunk<6>(acc0, acc1, h1, pp, xlo, fullX);
        ffn_phase1_chunk<7>(acc1, acc0, h1, pp, xlo, fullX);
        ffn_phase1_chunk<8>(acc0, acc1, h1, pp, xlo, fullX);
        wg_wait<0>();
        pp.release(5);
        pin(acc0);
        {
            float tmp[4][8];
#pragma unroll
            for (int p = 0; p < 4; p++) silu_s1(acc0, tmp[p], p);
#pragma unroll
            for (int p = 0; p < 4; p++) silu_s2(tmp[p], 0);
#pragma unroll
            for (int p = 0; p < 4; p++) silu_s3<8>(acc0, tmp[p], h1, p);
        }
        pin(h1);
        if (tid == 128) TS(3, 3);
        const int row = m * 128 + wgid * 64;
        const uint32_t stg = sX + wgid * 8192;
        int c = fs, cprev = 0;
        const bool leader = w == 0 && elect_one();
#pragma unroll 1
        for (int j = 0; j < 8; j += 2) {
            ffn_phase2_chunk(acc1, acc0, h1, pp, 1, j > 0, &tmOut, stg + (j - 1) * 16384, cprev * 64, row, w, lane, wgid, leader);
            cprev = c; if (++c == 9) c = 0;
            ffn_phase2_chunk(acc0, acc1, h1, pp, 0, true, &tmOut, stg + j * 16384, cprev * 64, row, w, lane, wgid, leader);
            cprev = c; if (++c == 9) c = 0;
        }
        ffn_phase2_chunk(acc1, acc0, h1, pp, 1, true, &tmOut, stg + 7 * 16384, cprev * 64, row, w, lane, wgid, leader);
        wg_wait<0>();
        pin(acc1);
        ffn_store_chunk(acc1, &tmOut, stg + 8 * 16384, c * 64, row, w, lane, wgid, leader);
        if (tid == 128) TS(3, 4);
        if (leader) bulk_wait_all();
        if (tid == 128) TS(3, 5);
    }
}

typedef CUresult (*EncodeFn)(CUtensorMap*, CUtensorMapDataType, cuuint32_t, void*, const cuuint64_t*, const cuuint64_t*, const cuuint32_t*, const cuuint32_t*,
                             CUtensorMapInterleave, CUtensorMapSwizzle, CUtensorMapL2promotion, CUtensorMapFloatOOBfill);

CUtensorMap make_map(EncodeFn enc, const void* base, int rows, int cols, int box_rows) {
    CUtensorMap tm;
    cuuint64_t dims[2] = {(cuuint64_t)cols, (cuuint64_t)rows};
    cuuint64_t strides[1] = {(cuuint64_t)cols * 2};
    cuuint32_t box[2] = {64, (cuuint32_t)box_rows};
    cuuint32_t es[2] = {1, 1};
    enc(&tm, CU_TENSOR_MAP_DATA_TYPE_BFLOAT16, 2, const_cast<void*>(base), dims, strides, box, es, CU_TENSOR_MAP_INTERLEAVE_NONE,
        CU_TENSOR_MAP_SWIZZLE_128B, CU_TENSOR_MAP_L2_PROMOTION_L2_256B, CU_TENSOR_MAP_FLOAT_OOB_FILL_NONE);
    return tm;
}

template <typename... KArgs, typename... Args>
void launch(void (*kern)(KArgs...), int grid, int block, int smem, bool pdl, Args... args) {
    cudaLaunchConfig_t cfg = {};
    cfg.gridDim = dim3(grid); cfg.blockDim = dim3(block); cfg.dynamicSmemBytes = smem; cfg.stream = cudaStreamPerThread;
    cudaLaunchAttribute at[1];
    at[0].id = cudaLaunchAttributeProgrammaticStreamSerialization;
    at[0].val.programmaticStreamSerializationAllowed = 1;
    cfg.attrs = at; cfg.numAttrs = pdl ? 1 : 0;
    cudaLaunchKernelEx(&cfg, kern, KArgs(args)...);
}

}

#define USE_PDL 1

extern "C" void kernel_launch(void* const* d_in, const int* in_sizes, int n_in, void* d_out, int out_size) {
    const __nv_bfloat16* x = (const __nv_bfloat16*)d_in[0];
    const __nv_bfloat16* wq = (const __nv_bfloat16*)d_in[1];
    const __nv_bfloat16* wk = (const __nv_bfloat16*)d_in[2];
    const __nv_bfloat16* wv = (const __nv_bfloat16*)d_in[3];
    const __nv_bfloat16* wo = (const __nv_bfloat16*)d_in[4];
    const __nv_bfloat16* w1 = (const __nv_bfloat16*)d_in[6];
    const __nv_bfloat16* w2 = (const __nv_bfloat16*)d_in[7];
    __nv_bfloat16* out = (__nv_bfloat16*)d_out;

    static EncodeFn enc = nullptr;
    static void *p_o = nullptr, *p_h = nullptr, *p_q = nullptr;
    if (!enc) {
        cudaDriverEntryPointQueryResult qr;
        cudaGetDriverEntryPoint("cuTensorMapEncodeTiled", (void**)&enc, cudaEnableDefault, &qr);
        cudaGetSymbolAddress(&p_o, g_o);
        cudaGetSymbolAddress(&p_h, g_x2);
        cudaGetSymbolAddress(&p_q, g_q);
        cudaFuncSetAttribute(k_qkv, cudaFuncAttributeMaxDynamicSharedMemorySize, P_SMEM);
        cudaFuncSetAttribute(k_attn, cudaFuncAttributeMaxDynamicSharedMemorySize, A_SMEM);
        cudaFuncSetAttribute(k_oproj, cudaFuncAttributeMaxDynamicSharedMemorySize, P_SMEM);
        cudaFuncSetAttribute(k_ffn, cudaFuncAttributeMaxDynamicSharedMemorySize, F_SMEM);
    }
    const CUtensorMap tmWq = make_map(enc, wq, DM, DM, 64);
    const CUtensorMap tmWo = make_map(enc, wo, DM, DM, 64);
    const CUtensorMap tmO = make_map(enc, p_o, SEQ, DM, 64);
    const CUtensorMap tmH64 = make_map(enc, p_h, SEQ, DM, 64);
    const CUtensorMap tmQ = make_map(enc, p_q, SEQ, DM, 64);
    const CUtensorMap tmW1 = make_map(enc, w1, DM, FF, 96);
    const CUtensorMap tmW2 = make_map(enc, w2, FF, DM, 96);
    const CUtensorMap tmOut = make_map(enc, out, SEQ, DM, 64);

    launch(k_qkv, 128, P_THREADS, P_SMEM, false, tmWq, tmQ, x, wk, wv);
    launch(k_attn, 132, A_THREADS, A_SMEM, USE_PDL, w1, w2, wo);
    launch(k_oproj, 96, O_THREADS, P_SMEM, USE_PDL, tmO, tmWo, tmH64, tmOut, x);
    launch(k_ffn, 128, F_THREADS, F_SMEM, USE_PDL, tmH64, tmW1, tmW2, tmOut);
}
```

```cpp
#include <cuda_runtime.h>
#include <cuda_bf16.h>
#include <cuda.h>
#include <stdint.h>

namespace {

constexpr int SEQ = 2048, DM = 576, FF = 4608;
constexpr int KV_BYTES = SEQ * 48;
constexpr float LN_EPS = 1e-5f;
constexpr float LOG2E = 1.4426950408889634f;
constexpr float LN2 = 0.6931471805599453f;
constexpr float Q_SCALE = 0.23570226039551584f * LOG2E;

#define POLY_MASK_V 0xB5B5u
constexpr uint32_t POLY_MASK = POLY_MASK_V;
constexpr float FAST_BOUND = 60.0f;

__device__ __align__(1024) __nv_bfloat16 g_q[SEQ * DM];
__device__ __align__(1024) uint4 g_kc[KV_BYTES / 16];
__device__ __align__(1024) uint4 g_vc[KV_BYTES / 16];
__device__ float g_kmax[32];
__device__ __align__(1024) __nv_bfloat16 g_o[SEQ * DM];
__device__ __align__(1024) __nv_bfloat16 g_x2[SEQ * DM];

#define TS(k, i)

__device__ __forceinline__ uint32_t smem_u32(const void* p) { return (uint32_t)__cvta_generic_to_shared(p); }
__device__ __forceinline__ void wg_fence() { asm volatile("wgmma.fence.sync.aligned;" ::: "memory"); }
__device__ __forceinline__ void wg_commit() { asm volatile("wgmma.commit_group.sync.aligned;" ::: "memory"); }
template <int N> __device__ __forceinline__ void wg_wait() { asm volatile("wgmma.wait_group.sync.aligned %0;" ::"n"(N) : "memory"); }
template <int N> __device__ __forceinline__ void pin(float (&r)[N]) {
#pragma unroll
    for (int i = 0; i < N; i++) asm volatile("" : "+f"(r[i])::"memory");
}
template <int N> __device__ __forceinline__ void pin(uint32_t (&r)[N]) {
#pragma unroll
    for (int i = 0; i < N; i++) asm volatile("" : "+r"(r[i])::"memory");
}
__device__ __forceinline__ constexpr uint32_t desc_hi(uint32_t sbo, uint32_t swz) { return (sbo >> 4) | (swz << 30); }
__device__ __forceinline__ uint32_t desc_lo(uint32_t addr, uint32_t lbo) { return ((addr & 0x3FFFF) >> 4) | ((lbo >> 4) << 16); }
__device__ __forceinline__ uint64_t desc64(uint32_t lo, uint32_t hi) { return ((uint64_t)hi << 32) | lo; }
constexpr uint32_t SMEM0 = 0x400;
__host__ __device__ constexpr uint64_t cdesc(uint32_t off, uint32_t lbo, uint32_t sbo, uint32_t swz) {
    return (uint64_t)(((SMEM0 + off) & 0x3FFFF) >> 4) | ((uint64_t)(lbo >> 4) << 16) | ((uint64_t)(sbo >> 4) << 32) | ((uint64_t)swz << 62);
}
__device__ __forceinline__ void check_smem_base(uint32_t base) { if ((base & 0x3FFFF) != SMEM0) __trap(); }

__device__ __forceinline__ void mbar_init(uint32_t bar, int cnt) { asm volatile("mbarrier.init.shared::cta.b64 [%0], %1;" ::"r"(bar), "r"(cnt) : "memory"); }
__device__ __forceinline__ void mbar_expect(uint32_t bar, int bytes) { asm volatile("mbarrier.arrive.expect_tx.shared::cta.b64 _, [%0], %1;" ::"r"(bar), "r"(bytes) : "memory"); }
__device__ __forceinline__ void mbar_arrive(uint32_t bar) { asm volatile("mbarrier.arrive.shared::cta.b64 _, [%0];" ::"r"(bar) : "memory"); }
__device__ __forceinline__ void mbar_wait(uint32_t bar, uint32_t parity) {
    asm volatile(
        "{\n.reg .pred p;\n.reg .u32 n;\nmov.u32 n, 0;\n"
        "LAB_WAIT:\n"
        "mbarrier.try_wait.parity.shared::cta.b64 p, [%0], %1;\n"
        "@p bra DONE;\n"
        "add.u32 n, n, 1;\n"
        "setp.lt.u32 p, n, 4000000;\n"
        "@p bra LAB_WAIT;\n"
        "trap;\n"
        "DONE:\n}\n" ::"r"(bar), "r"(parity) : "memory");
}
__device__ __forceinline__ void bar_init_fence() {
    asm volatile("fence.mbarrier_init.release.cluster;" ::: "memory");
    asm volatile("fence.proxy.async.shared::cta;" ::: "memory");
}
__device__ __forceinline__ void proxy_fence() { asm volatile("fence.proxy.async.shared::cta;" ::: "memory"); }
__device__ __forceinline__ void named_sync(int id, int n) { asm volatile("bar.sync %0, %1;" ::"r"(id), "r"(n) : "memory"); }
__device__ __forceinline__ void bulk_g2s(uint32_t dst, const void* src, int bytes, uint32_t bar) {
    asm volatile("cp.async.bulk.shared::cluster.global.mbarrier::complete_tx::bytes [%0], [%1], %2, [%3];" ::"r"(dst), "l"(src), "r"(bytes), "r"(bar) : "memory");
}
__device__ __forceinline__ void tma_2d(uint32_t dst, const CUtensorMap* tm, int c0, int c1, uint32_t bar) {
    asm volatile("cp.async.bulk.tensor.2d.shared::cluster.global.mbarrier::complete_tx::bytes [%0], [%1, {%3, %4}], [%2];" ::"r"(dst), "l"(tm), "r"(bar), "r"(c0), "r"(c1) : "memory");
}
__device__ __forceinline__ void tma_2d_mc(uint32_t dst, const CUtensorMap* tm, int c0, int c1, uint32_t bar, uint16_t mask) {
    asm volatile("cp.async.bulk.tensor.2d.shared::cluster.global.mbarrier::complete_tx::bytes.multicast::cluster [%0], [%1, {%3, %4}], [%2], %5;" ::"r"(dst), "l"(tm), "r"(bar), "r"(c0), "r"(c1), "h"(mask) : "memory");
}
__device__ __forceinline__ void cluster_arrive() { asm volatile("barrier.cluster.arrive.release.aligned;" ::: "memory"); }
__device__ __forceinline__ void cluster_wait() { asm volatile("barrier.cluster.wait.acquire.aligned;" ::: "memory"); }
__device__ __forceinline__ void tma_red_2d(const CUtensorMap* tm, int c0, int c1, uint32_t src) {
    asm volatile("cp.reduce.async.bulk.tensor.2d.global.shared::cta.add.tile.bulk_group [%0, {%2, %3}], [%1];" ::"l"(tm), "r"(src), "r"(c0), "r"(c1) : "memory");
}
__device__ __forceinline__ void tma_st_2d(const CUtensorMap* tm, int c0, int c1, uint32_t src) {
    asm volatile("cp.async.bulk.tensor.2d.global.shared::cta.tile.bulk_group [%0, {%2, %3}], [%1];" ::"l"(tm), "r"(src), "r"(c0), "r"(c1) : "memory");
}
__device__ __forceinline__ void bulk_commit() { asm volatile("cp.async.bulk.commit_group;" ::: "memory"); }
__device__ __forceinline__ void bulk_wait_all() { asm volatile("cp.async.bulk.wait_group.read 0;" ::: "memory"); }
__device__ __forceinline__ bool elect_one() {
    uint32_t p;
    asm volatile("{\n.reg .pred P;\nelect.sync _|P, 0xffffffff;\nselp.b32 %0, 1, 0, P;\n}\n" : "=r"(p));
    return p != 0;
}
__device__ __forceinline__ void prefetch_l2(const void* p, int bytes) { asm volatile("cp.async.bulk.prefetch.L2.global [%0], %1;" ::"l"(p), "r"(bytes) : "memory"); }
__device__ __forceinline__ void prefetch_map(const CUtensorMap* tm) { asm volatile("prefetch.tensormap [%0];" ::"l"(tm) : "memory"); }
__device__ __forceinline__ void pdl_launch() { asm volatile("griddepcontrol.launch_dependents;" ::: "memory"); }
__device__ __forceinline__ void pdl_wait() { asm volatile("griddepcontrol.wait;" ::: "memory"); }
__device__ __forceinline__ float ex2(float x) { float y; asm("ex2.approx.ftz.f32 %0, %1;" : "=f"(y) : "f"(x)); return y; }
__device__ __forceinline__ float rcp(float x) { float y; asm("rcp.approx.ftz.f32 %0, %1;" : "=f"(y) : "f"(x)); return y; }
__device__ __forceinline__ uint32_t pack_bf16(float lo, float hi) { uint32_t r; asm("cvt.rn.bf16x2.f32 %0, %1, %2;" : "=r"(r) : "f"(hi), "f"(lo)); return r; }
__device__ __forceinline__ float bf_lo(uint32_t v) { return __uint_as_float(v << 16); }
__device__ __forceinline__ float bf_hi(uint32_t v) { return __uint_as_float(v & 0xFFFF0000u); }
__device__ __forceinline__ uint32_t hfma2(uint32_t a, uint32_t b, uint32_t c) { uint32_t r; asm("fma.rn.f16x2 %0, %1, %2, %3;" : "=r"(r) : "r"(a), "r"(b), "r"(c)); return r; }
__device__ __forceinline__ void stmatrix_x4(uint32_t addr, uint32_t r0, uint32_t r1, uint32_t r2, uint32_t r3) {
    asm volatile("stmatrix.sync.aligned.m8n8.x4.shared.b16 [%0], {%1, %2, %3, %4};" ::"r"(addr), "r"(r0), "r"(r1), "r"(r2), "r"(r3) : "memory");
}

template <int TB> __device__ __forceinline__ void wgmma_ss_n24(float (&d)[12], uint64_t da, uint64_t db, int sc) {
    asm volatile("{\n.reg .pred p;\nsetp.ne.b32 p, %14, 0;\n"
        "wgmma.mma_async.sync.aligned.m64n24k16.f32.bf16.bf16 {%0, %1, %2, %3, %4, %5, %6, %7, %8, %9, %10, %11}, %12, %13, p, 1, 1, 0, %15;\n}\n"
        : "+f"(d[0]), "+f"(d[1]), "+f"(d[2]), "+f"(d[3]), "+f"(d[4]), "+f"(d[5]), "+f"(d[6]), "+f"(d[7]), "+f"(d[8]), "+f"(d[9]), "+f"(d[10]), "+f"(d[11])
        : "l"(da), "l"(db), "r"(sc), "n"(TB));
}
template <int TB> __device__ __forceinline__ void wgmma_ss_n64(float (&d)[32], uint64_t da, uint64_t db, int sc) {
    asm volatile("{\n.reg .pred p;\nsetp.ne.b32 p, %34, 0;\n"
        "wgmma.mma_async.sync.aligned.m64n64k16.f32.bf16.bf16 {%0, %1, %2, %3, %4, %5, %6, %7, %8, %9, %10, %11, %12, %13, %14, %15, %16, %17, %18, %19, %20, %21, %22, %23, %24, %25, %26, %27, %28, %29, %30, %31}, %32, %33, p, 1, 1, 0, %35;\n}\n"
        : "+f"(d[0]), "+f"(d[1]), "+f"(d[2]), "+f"(d[3]), "+f"(d[4]), "+f"(d[5]), "+f"(d[6]), "+f"(d[7]), "+f"(d[8]), "+f"(d[9]), "+f"(d[10]), "+f"(d[11]), "+f"(d[12]), "+f"(d[13]), "+f"(d[14]), "+f"(d[15]), "+f"(d[16]), "+f"(d[17]), "+f"(d[18]), "+f"(d[19]), "+f"(d[20]), "+f"(d[21]), "+f"(d[22]), "+f"(d[23]), "+f"(d[24]), "+f"(d[25]), "+f"(d[26]), "+f"(d[27]), "+f"(d[28]), "+f"(d[29]), "+f"(d[30]), "+f"(d[31])
        : "l"(da), "l"(db), "r"(sc), "n"(TB));
}
template <int TB> __device__ __forceinline__ void wgmma_ss_n128(float (&d)[64], uint64_t da, uint64_t db, int sc) {
    asm volatile("{\n.reg .pred p;\nsetp.ne.b32 p, %66, 0;\n"
        "wgmma.mma_async.sync.aligned.m64n128k16.f32.bf16.bf16 {%0, %1, %2, %3, %4, %5, %6, %7, %8, %9, %10, %11, %12, %13, %14, %15, %16, %17, %18, %19, %20, %21, %22, %23, %24, %25, %26, %27, %28, %29, %30, %31, %32, %33, %34, %35, %36, %37, %38, %39, %40, %41, %42, %43, %44, %45, %46, %47, %48, %49, %50, %51, %52, %53, %54, %55, %56, %57, %58, %59, %60, %61, %62, %63}, %64, %65, p, 1, 1, 0, %67;\n}\n"
        : "+f"(d[0]), "+f"(d[1]), "+f"(d[2]), "+f"(d[3]), "+f"(d[4]), "+f"(d[5]), "+f"(d[6]), "+f"(d[7]), "+f"(d[8]), "+f"(d[9]), "+f"(d[10]), "+f"(d[11]), "+f"(d[12]), "+f"(d[13]), "+f"(d[14]), "+f"(d[15]), "+f"(d[16]), "+f"(d[17]), "+f"(d[18]), "+f"(d[19]), "+f"(d[20]), "+f"(d[21]), "+f"(d[22]), "+f"(d[23]), "+f"(d[24]), "+f"(d[25]), "+f"(d[26]), "+f"(d[27]), "+f"(d[28]), "+f"(d[29]), "+f"(d[30]), "+f"(d[31]), "+f"(d[32]), "+f"(d[33]), "+f"(d[34]), "+f"(d[35]), "+f"(d[36]), "+f"(d[37]), "+f"(d[38]), "+f"(d[39]), "+f"(d[40]), "+f"(d[41]), "+f"(d[42]), "+f"(d[43]), "+f"(d[44]), "+f"(d[45]), "+f"(d[46]), "+f"(d[47]), "+f"(d[48]), "+f"(d[49]), "+f"(d[50]), "+f"(d[51]), "+f"(d[52]), "+f"(d[53]), "+f"(d[54]), "+f"(d[55]), "+f"(d[56]), "+f"(d[57]), "+f"(d[58]), "+f"(d[59]), "+f"(d[60]), "+f"(d[61]), "+f"(d[62]), "+f"(d[63])
        : "l"(da), "l"(db), "r"(sc), "n"(TB));
}
template <int TB> __device__ __forceinline__ void wgmma_rs_n24(float (&d)[12], uint32_t a0, uint32_t a1, uint32_t a2, uint32_t a3, uint64_t db, int sc) {
    asm volatile("{\n.reg .pred p;\nsetp.ne.b32 p, %17, 0;\n"
        "wgmma.mma_async.sync.aligned.m64n24k16.f32.bf16.bf16 {%0, %1, %2, %3, %4, %5, %6, %7, %8, %9, %10, %11}, {%12, %13, %14, %15}, %16, p, 1, 1, %18;\n}\n"
        : "+f"(d[0]), "+f"(d[1]), "+f"(d[2]), "+f"(d[3]), "+f"(d[4]), "+f"(d[5]), "+f"(d[6]), "+f"(d[7]), "+f"(d[8]), "+f"(d[9]), "+f"(d[10]), "+f"(d[11])
        : "r"(a0), "r"(a1), "r"(a2), "r"(a3), "l"(db), "r"(sc), "n"(TB));
}
template <int TB> __device__ __forceinline__ void wgmma_rs_n64(float (&d)[32], uint32_t a0, uint32_t a1, uint32_t a2, uint32_t a3, uint64_t db, int sc) {
    asm volatile("{\n.reg .pred p;\nsetp.ne.b32 p, %37, 0;\n"
        "wgmma.mma_async.sync.aligned.m64n64k16.f32.bf16.bf16 {%0, %1, %2, %3, %4, %5, %6, %7, %8, %9, %10, %11, %12, %13, %14, %15, %16, %17, %18, %19, %20, %21, %22, %23, %24, %25, %26, %27, %28, %29, %30, %31}, {%32, %33, %34, %35}, %36, p, 1, 1, %38;\n}\n"
        : "+f"(d[0]), "+f"(d[1]), "+f"(d[2]), "+f"(d[3]), "+f"(d[4]), "+f"(d[5]), "+f"(d[6]), "+f"(d[7]), "+f"(d[8]), "+f"(d[9]), "+f"(d[10]), "+f"(d[11]), "+f"(d[12]), "+f"(d[13]), "+f"(d[14]), "+f"(d[15]), "+f"(d[16]), "+f"(d[17]), "+f"(d[18]), "+f"(d[19]), "+f"(d[20]), "+f"(d[21]), "+f"(d[22]), "+f"(d[23]), "+f"(d[24]), "+f"(d[25]), "+f"(d[26]), "+f"(d[27]), "+f"(d[28]), "+f"(d[29]), "+f"(d[30]), "+f"(d[31])
        : "r"(a0), "r"(a1), "r"(a2), "r"(a3), "l"(db), "r"(sc), "n"(TB));
}
template <int TB> __device__ __forceinline__ void wgmma_rs_n128(float (&d)[64], uint32_t a0, uint32_t a1, uint32_t a2, uint32_t a3, uint64_t db, int sc) {
    asm volatile("{\n.reg .pred p;\nsetp.ne.b32 p, %69, 0;\n"
        "wgmma.mma_async.sync.aligned.m64n128k16.f32.bf16.bf16 {%0, %1, %2, %3, %4, %5, %6, %7, %8, %9, %10, %11, %12, %13, %14, %15, %16, %17, %18, %19, %20, %21, %22, %23, %24, %25, %26, %27, %28, %29, %30, %31, %32, %33, %34, %35, %36, %37, %38, %39, %40, %41, %42, %43, %44, %45, %46, %47, %48, %49, %50, %51, %52, %53, %54, %55, %56, %57, %58, %59, %60, %61, %62, %63}, {%64, %65, %66, %67}, %68, p, 1, 1, %70;\n}\n"
        : "+f"(d[0]), "+f"(d[1]), "+f"(d[2]), "+f"(d[3]), "+f"(d[4]), "+f"(d[5]), "+f"(d[6]), "+f"(d[7]), "+f"(d[8]), "+f"(d[9]), "+f"(d[10]), "+f"(d[11]), "+f"(d[12]), "+f"(d[13]), "+f"(d[14]), "+f"(d[15]), "+f"(d[16]), "+f"(d[17]), "+f"(d[18]), "+f"(d[19]), "+f"(d[20]), "+f"(d[21]), "+f"(d[22]), "+f"(d[23]), "+f"(d[24]), "+f"(d[25]), "+f"(d[26]), "+f"(d[27]), "+f"(d[28]), "+f"(d[29]), "+f"(d[30]), "+f"(d[31]), "+f"(d[32]), "+f"(d[33]), "+f"(d[34]), "+f"(d[35]), "+f"(d[36]), "+f"(d[37]), "+f"(d[38]), "+f"(d[39]), "+f"(d[40]), "+f"(d[41]), "+f"(d[42]), "+f"(d[43]), "+f"(d[44]), "+f"(d[45]), "+f"(d[46]), "+f"(d[47]), "+f"(d[48]), "+f"(d[49]), "+f"(d[50]), "+f"(d[51]), "+f"(d[52]), "+f"(d[53]), "+f"(d[54]), "+f"(d[55]), "+f"(d[56]), "+f"(d[57]), "+f"(d[58]), "+f"(d[59]), "+f"(d[60]), "+f"(d[61]), "+f"(d[62]), "+f"(d[63])
        : "r"(a0), "r"(a1), "r"(a2), "r"(a3), "l"(db), "r"(sc), "n"(TB));
}

constexpr int P_THREADS = 288;
constexpr int P_NST = 6;
constexpr int P_A_BYTES = 9 * 8192;
constexpr int P_B_STAGE = 3 * 8192;
constexpr int P_SMEM = P_A_BYTES + P_NST * P_B_STAGE + 256 + 320;
constexpr uint32_t HI_SW128 = (1024u >> 4) | (1u << 30);

template <int NCOL, bool WAIT_A>
__device__ __forceinline__ void proj_mma(float (&acc)[NCOL / 2], uint32_t sA, uint32_t sB, uint32_t colofs, uint32_t fullB, uint32_t emptyB, uint32_t fullA, int lane) {
#pragma unroll 1
    for (int kb = 0; kb < 9; kb++) {
        const int s = kb >= P_NST ? kb - P_NST : kb;
        if (WAIT_A) mbar_wait(fullA + kb * 8, 0);

        mbar_wait(fullB + s * 8, kb >= P_NST ? 1 : 0);
        const uint32_t alo = desc_lo(sA + kb * 8192, 16), blo = desc_lo(sB + s * P_B_STAGE + colofs, 8192);
        wg_fence();
#pragma unroll
        for (int ks = 0; ks < 4; ks++) {
            const uint64_t da = desc64(alo + ks * 2, HI_SW128), db = desc64(blo + ks * 128, HI_SW128);
            if constexpr (NCOL == 128) wgmma_ss_n128<1>(acc, da, db, (kb | ks) != 0);
            else wgmma_ss_n64<1>(acc, da, db, (kb | ks) != 0);
        }
        wg_commit();
        if (kb + P_NST < 9 + 1) {
            wg_wait<1>();
            if (kb >= 1 && kb - 1 + P_NST < 9 && lane == 0) mbar_arrive(emptyB + (kb - 1) * 8);
        }
    }
    wg_wait<0>();
    pin(acc);
}

template <int NB>
__device__ __forceinline__ void stage_tile(const uint32_t (&pk)[NB * 2], uint32_t base, int w, int lane) {
    const int r = w * 16 + (lane & 7) + ((lane >> 3) & 1) * 8;
#pragma unroll
    for (int b = 0; b < NB; b += 2) {
        const uint32_t a = base + (b >> 3) * 8192 + r * 128 + ((((b & 7) + (lane >> 4)) ^ (r & 7)) << 4);
        stmatrix_x4(a, pk[2 * b], pk[2 * b + 1], pk[2 * b + 2], pk[2 * b + 3]);
    }
}

__device__ __forceinline__ uint32_t hsub2_bf16(uint32_t a, uint32_t b) { uint32_t r; asm("sub.rn.bf16x2 %0, %1, %2;" : "=r"(r) : "r"(a), "r"(b)); return r; }

constexpr int KV_RAW = DM * 18 * 2;

__global__ void __launch_bounds__(P_THREADS, 1)
k_qkv(const __grid_constant__ CUtensorMap tmWq, const __grid_constant__ CUtensorMap tmQ, const __nv_bfloat16* __restrict__ x, const __nv_bfloat16* __restrict__ wk, const __nv_bfloat16* __restrict__ wv) {
    extern __shared__ __align__(1024) uint8_t smem[];
    const uint32_t sA = smem_u32(smem), sB = sA + P_A_BYTES, bars = sB + P_NST * P_B_STAGE;
    const uint32_t fullB = bars, emptyB = bars + 64, fullX = bars + 128, fullW = bars + 136, rawFree = bars + 144;
    const uint32_t sRaw = sB + 3 * P_B_STAGE;
    float* s_rstd = reinterpret_cast<float*>(smem + P_A_BYTES + P_NST * P_B_STAGE + 256);
    const int tid = threadIdx.x, warp = __shfl_sync(~0u, tid >> 5, 0), lane = tid & 31;
    const bool isQ = blockIdx.x < 96;
    const int m = isQ ? blockIdx.x / 3 : blockIdx.x - 96, cg = blockIdx.x % 3;
    if (tid == 0) TS(0, 0);
    if (warp == 8) {
        if (elect_one()) {
            prefetch_map(&tmWq); prefetch_map(&tmQ);
            for (int i = 0; i < P_NST; i++) { mbar_init(fullB + i * 8, 1); mbar_init(emptyB + i * 8, 8); }
            mbar_init(fullX, 1); mbar_init(fullW, 1); mbar_init(rawFree, 8);
            bar_init_fence();
            mbar_expect(fullX, P_A_BYTES);
            bulk_g2s(sRaw, x + (size_t)m * 64 * DM, P_A_BYTES, fullX);
            if (isQ) {
                for (int kb = 0; kb < 3; kb++) {
                    mbar_expect(fullB + kb * 8, P_B_STAGE);
                    for (int a = 0; a < 3; a++) tma_2d(sB + kb * P_B_STAGE + a * 8192, &tmWq, cg * 192 + a * 64, kb * 64, fullB + kb * 8);
                }
            } else {
                mbar_expect(fullW, 2 * KV_RAW);
                bulk_g2s(sA, wk, KV_RAW, fullW);
                bulk_g2s(sA + KV_RAW, wv, KV_RAW, fullW);
            }
        }
        __syncwarp();
    }
    __syncthreads();
    pdl_launch();
    if (warp == 8) {
        if (isQ && elect_one()) {
            mbar_wait(rawFree, 0);
            for (int kb = 3; kb < 9; kb++) {
                const int s = kb >= P_NST ? kb - P_NST : kb;
                if (kb >= P_NST) mbar_wait(emptyB + s * 8, 0);
                mbar_expect(fullB + s * 8, P_B_STAGE);
                for (int a = 0; a < 3; a++) tma_2d(sB + s * P_B_STAGE + a * 8192, &tmWq, cg * 192 + a * 64, kb * 64, fullB + s * 8);
            }
        }
        return;
    }
    {
        const int row = tid >> 2, q = tid & 3, odd = row & 1;
        mbar_wait(fullX, 0);
        if (tid == 0) TS(0, 6);
        uint4 v[18];
#pragma unroll
        for (int i = 0; i < 18; i++)
            asm volatile("ld.shared.v4.b32 {%0, %1, %2, %3}, [%4];" : "=r"(v[i].x), "=r"(v[i].y), "=r"(v[i].z), "=r"(v[i].w) : "r"(sRaw + row * 1152 + (q + 4 * (i ^ odd)) * 16));
        float sum = 0.f, sum2 = 0.f, sq = 0.f, sq2 = 0.f;
#pragma unroll
        for (int i = 0; i < 18; i++) {
            const uint32_t w[4] = {v[i].x, v[i].y, v[i].z, v[i].w};
#pragma unroll
            for (int j = 0; j < 4; j++) { const float a = bf_lo(w[j]), b = bf_hi(w[j]); sum += a; sum2 += b; sq = fmaf(a, a, sq); sq2 = fmaf(b, b, sq2); }
        }
        __syncwarp();
        if (lane == 0) mbar_arrive(rawFree);
        sum += sum2; sq += sq2;
        sum += __shfl_xor_sync(~0u, sum, 1); sum += __shfl_xor_sync(~0u, sum, 2);
        sq += __shfl_xor_sync(~0u, sq, 1); sq += __shfl_xor_sync(~0u, sq, 2);
        if (tid == 0) TS(0, 4);
        if (!isQ) {
            mbar_wait(fullW, 0);
            if (tid == 0) TS(0, 7);
            const uint32_t* raw = reinterpret_cast<const uint32_t*>(smem);
            uint32_t wr[41];
#pragma unroll
            for (int i = 0; i < 40; i++) wr[i] = raw[tid + i * 256];
            wr[40] = raw[(tid & 127) + 40 * 256];
            int k = tid / 9, r = tid - k * 9;
#pragma unroll
            for (int i = 0; i < 41; i++) {
                const int sel = k >= DM, kk = k - sel * DM;
                uint32_t* dst = reinterpret_cast<uint32_t*>(smem + P_A_BYTES + (sel * 3 + (r >> 2)) * 9216 + (kk >> 3) * 128 + (kk & 7) * 16 + (r & 3) * 4);
                if (i < 40 || tid < 128) *dst = wr[i];
                k += 28; r += 4;
                if (r >= 9) { r -= 9; k++; }
            }
            named_sync(1, 256);
            if (tid == 0) TS(0, 8);
        }
        const float mean = sum * (1.0f / DM);
        if (q == 0) s_rstd[row] = rsqrtf(fmaxf(sq * (1.0f / DM) - mean * mean, 0.f) + LN_EPS);
        const uint32_t mhi = pack_bf16(mean, mean);
        const float rem = mean - bf_lo(mhi);
        const uint32_t mlo = pack_bf16(rem, rem);
#pragma unroll
        for (int i = 0; i < 18; i++) {
            const int c = q + 4 * (i ^ odd);
            const uint32_t o0 = hsub2_bf16(hsub2_bf16(v[i].x, mhi), mlo), o1 = hsub2_bf16(hsub2_bf16(v[i].y, mhi), mlo);
            const uint32_t o2 = hsub2_bf16(hsub2_bf16(v[i].z, mhi), mlo), o3 = hsub2_bf16(hsub2_bf16(v[i].w, mhi), mlo);
            asm volatile("st.shared.v4.b32 [%0], {%1, %2, %3, %4};" ::"r"(sA + (c >> 3) * 8192 + row * 128 + (((c & 7) ^ (row & 7)) << 4)), "r"(o0), "r"(o1), "r"(o2), "r"(o3) : "memory");
        }
    }
    proxy_fence();
    named_sync(1, 256);
    if (tid == 0) TS(0, 1);
    const int wg = warp >> 2, w = warp & 3, g = lane >> 2, t = lane & 3;
    const float rs0 = s_rstd[w * 16 + g], rs1 = s_rstd[w * 16 + g + 8];
    if (isQ) {
        const float c0 = rs0 * Q_SCALE, c1 = rs1 * Q_SCALE;
        if (wg == 0) {
            float acc[64];
            proj_mma<128, false>(acc, sA, sB, 0, fullB, emptyB, 0, lane);
            if (tid == 0) TS(0, 2);
            named_sync(1, 256);
            uint32_t pk[32];
#pragma unroll
            for (int i = 0; i < 16; i++) { pk[2 * i] = pack_bf16(acc[4 * i] * c0, acc[4 * i + 1] * c0); pk[2 * i + 1] = pack_bf16(acc[4 * i + 2] * c1, acc[4 * i + 3] * c1); }
            stage_tile<16>(pk, sA, w, lane);
        } else {
            float acc[32];
            proj_mma<64, false>(acc, sA, sB, 2 * 8192, fullB, emptyB, 0, lane);
            named_sync(1, 256);
            uint32_t pk[16];
#pragma unroll
            for (int i = 0; i < 8; i++) { pk[2 * i] = pack_bf16(acc[4 * i] * c0, acc[4 * i + 1] * c0); pk[2 * i + 1] = pack_bf16(acc[4 * i + 2] * c1, acc[4 * i + 3] * c1); }
            stage_tile<8>(pk, sA + 2 * 8192, w, lane);
        }
        proxy_fence();
        named_sync(1, 256);
        if (warp == 0 && elect_one()) {
            for (int a = 0; a < 3; a++) tma_st_2d(&tmQ, cg * 192 + a * 64, m * 64, sA + a * 8192);
            bulk_commit();
            bulk_wait_all();
        }
    } else {
        float acc[12];
        const uint32_t blo = desc_lo(sB + wg * 3 * 9216, 128);
#pragma unroll
        for (int i = 0; i < 12; i++) acc[i] = 0.f;
        pin(acc);
        wg_fence();
#pragma unroll 1
        for (int kb = 0; kb < 9; kb++) {
            const uint32_t alo = desc_lo(sA + kb * 8192, 16);
#pragma unroll
            for (int ks = 0; ks < 4; ks++)
                wgmma_ss_n24<1>(acc, desc64(alo + ks * 2, HI_SW128), desc64(blo + (kb * 4 + ks) * 16, desc_hi(9216, 0)), 1);
        }
        wg_commit();
        wg_wait<0>();
        pin(acc);
        uint32_t pk[6];
#pragma unroll
        for (int b = 0; b < 3; b++) { pk[2 * b] = pack_bf16(acc[4 * b] * rs0, acc[4 * b + 1] * rs0); pk[2 * b + 1] = pack_bf16(acc[4 * b + 2] * rs1, acc[4 * b + 3] * rs1); }
        float n0 = 0.f, n1 = 0.f, vm = 0.f;
#pragma unroll
        for (int b = 0; b < 3; b++) {
            if (b < 2 || t == 0) {
                const float a = bf_lo(pk[2 * b]), c = bf_hi(pk[2 * b]), d = bf_lo(pk[2 * b + 1]), e = bf_hi(pk[2 * b + 1]);
                n0 = fmaf(a, a, fmaf(c, c, n0)); n1 = fmaf(d, d, fmaf(e, e, n1));
            }
        }
        n0 += __shfl_xor_sync(~0u, n0, 1); n0 += __shfl_xor_sync(~0u, n0, 2);
        n1 += __shfl_xor_sync(~0u, n1, 1); n1 += __shfl_xor_sync(~0u, n1, 2);
        vm = fmaxf(n0, n1);
        if (!(n0 == n0) || !(n1 == n1)) vm = __int_as_float(0x7F800000);
#pragma unroll
        for (int o = 4; o < 32; o <<= 1) vm = fmaxf(vm, __shfl_xor_sync(~0u, vm, o));
        if (t != 0) {
            uint32_t lo, hi;
            if (wg == 0) {
                const int grp = m * 8 + w * 2;
                const uint32_t c = t == 1 ? 0x42FE3F80u   : (t == 2 ? 0x00003BC0u   : 0u);
                lo = ((POLY_MASK >> (grp & 15)) & 1) ? c : 0u;
                hi = ((POLY_MASK >> ((grp + 1) & 15)) & 1) ? c : 0u;
            } else {
                lo = hi = t == 1 ? 0x00003F80u : 0u;
            }
            pk[4] = lo; pk[5] = hi;
        }
        uint32_t* dst = reinterpret_cast<uint32_t*>(wg == 0 ? g_kc : g_vc) + (m * 8 + w * 2) * 96 + g * 4 + t;
#pragma unroll
        for (int b = 0; b < 3; b++) { dst[b * 32] = pk[2 * b]; dst[96 + b * 32] = pk[2 * b + 1]; }
        float* red = s_rstd + 64;
        if (lane == 0) red[warp] = (wg == 0) ? vm : (vm <= 1e24f ? 0.f : __int_as_float(0x7F800000));
        named_sync(1, 256);
        if (tid == 0) {
            float mx = red[0];
#pragma unroll
            for (int i = 1; i < 8; i++) mx = fmaxf(mx, red[i]);
            g_kmax[m] = mx;
        }
    }
    if (tid == 0) TS(0, 3);
}

constexpr int A_THREADS = 512;
constexpr int A_NPIECE = 8;
constexpr int A_OFF_Q = 2 * KV_BYTES;
constexpr int A_OFF_BAR = A_OFF_Q + 4 * 4096;
constexpr int A_SMEM = A_OFF_BAR + 128;

__device__ __forceinline__ uint32_t exp2_pair_fixed(float lo, float hi) {
    const uint32_t G = __byte_perm(__float_as_uint(lo), __float_as_uint(hi), 0x5410);
    const uint32_t Hh = G & 0x007F007Fu;
    const uint32_t tt = hfma2(Hh, 0xF96BF96Bu, 0x358C358Cu);
    return G - hfma2(tt, Hh, 0u);
}

__device__ __forceinline__ void attn_side_job(const __nv_bfloat16* __restrict__ w1, const __nv_bfloat16* __restrict__ w2, const __nv_bfloat16* __restrict__ wo) {
    const int e = blockIdx.x - 128, tid = threadIdx.x;
    if (tid < 32) {
        const char* p = reinterpret_cast<const char*>(wo) + e * (DM * DM * 2 / 4);
        for (int i = tid; i < DM * DM * 2 / 4 / 4608; i += 32) prefetch_l2(p + i * 4608, 4608);
        p = reinterpret_cast<const char*>(w1) + (size_t)e * (FF * DM * 2 / 4);
        for (int i = tid; i < FF * DM * 2 / 4 / 9216; i += 32) prefetch_l2(p + (size_t)i * 9216, 9216);
        p = reinterpret_cast<const char*>(w2) + (size_t)e * (FF * DM * 2 / 4);
        for (int i = tid; i < FF * DM * 2 / 4 / 9216; i += 32) prefetch_l2(p + (size_t)i * 9216, 9216);
    }
}

__global__ void __launch_bounds__(A_THREADS, 1)
k_attn(const __nv_bfloat16* __restrict__ w1, const __nv_bfloat16* __restrict__ w2, const __nv_bfloat16* __restrict__ wo) {
    extern __shared__ __align__(1024) uint8_t smem[];
    pdl_launch();
    if (blockIdx.x >= 128) { attn_side_job(w1, w2, wo); return; }
    const uint32_t sK = smem_u32(smem), sV = sK + KV_BYTES, bars = sK + A_OFF_BAR;
    const int tid = threadIdx.x;
    check_smem_base(sK);
    if (tid == 0) TS(1, 0);
    if (tid == 0) {
        for (int i = 0; i < A_NPIECE; i++) mbar_init(bars + i * 8, 1);
        bar_init_fence();
    }
    __syncthreads();
    pdl_wait();
    if (tid == 0) TS(1, 1);
    const int wg = __shfl_sync(~0u, tid >> 7, 0), w = (tid >> 5) & 3, lane = tid & 31, g = lane >> 2, t = lane & 3;
    const uint32_t* q32 = reinterpret_cast<const uint32_t*>(g_q);
    uint32_t* o32 = reinterpret_cast<uint32_t*>(g_o);
    int row = (blockIdx.x * 8 + wg) * 64 + w * 16 + g;
    uint32_t nq[6];
    nq[0] = q32[row * 9 + t]; nq[1] = q32[(row + 8) * 9 + t]; nq[2] = q32[row * 9 + 4 + t]; nq[3] = q32[(row + 8) * 9 + 4 + t];
    nq[4] = q32[row * 9 + 8]; nq[5] = q32[(row + 8) * 9 + 8];
    constexpr int PB = KV_BYTES / A_NPIECE;
    const float kmax_raw = g_kmax[lane];
    if (tid < 32 && elect_one()) {
        for (int i = 0; i < 2; i++) {
            mbar_expect(bars + i * 8, 2 * PB);
            bulk_g2s(sK + i * PB, reinterpret_cast<const char*>(g_kc) + i * PB, PB, bars + i * 8);
            bulk_g2s(sV + i * PB, reinterpret_cast<const char*>(g_vc) + i * PB, PB, bars + i * 8);
        }
    }
    float kmax2 = kmax_raw;
#pragma unroll
    for (int o = 1; o < 32; o <<= 1) kmax2 = fmaxf(kmax2, __shfl_xor_sync(~0u, kmax2, o));
    if (tid < 32 && elect_one()) {
        for (int i = 2; i < A_NPIECE; i++) {
            mbar_expect(bars + i * 8, 2 * PB);
            bulk_g2s(sK + i * PB, reinterpret_cast<const char*>(g_kc) + i * PB, PB, bars + i * 8);
            bulk_g2s(sV + i * PB, reinterpret_cast<const char*>(g_vc) + i * PB, PB, bars + i * 8);
        }
    }
    const uint32_t sQ = sK + A_OFF_Q + wg * 4096 + (w * 2) * 512 + g * 16 + t * 4;
    const uint64_t dQ0 = cdesc(A_OFF_Q, 128, 512, 0) + wg * 256, dQ1 = dQ0 + 16;
#pragma unroll 1
    for (int rep = 0; rep < 2; rep++, row += 256) {
        const uint32_t qa[4] = {nq[0], nq[1], nq[2], nq[3]};
        float n0, n1;
        {
            const float a0 = bf_lo(qa[0]), a1 = bf_hi(qa[0]), a2 = bf_lo(qa[2]), a3 = bf_hi(qa[2]);
            const float b0 = bf_lo(qa[1]), b1 = bf_hi(qa[1]), b2 = bf_lo(qa[3]), b3 = bf_hi(qa[3]);
            n0 = a0 * a0 + a1 * a1 + a2 * a2 + a3 * a3; n1 = b0 * b0 + b1 * b1 + b2 * b2 + b3 * b3;
            if (t == 0) {
                const float c0 = bf_lo(nq[4]), c1 = bf_hi(nq[4]), d0 = bf_lo(nq[5]), d1 = bf_hi(nq[5]);
                n0 += c0 * c0 + c1 * c1; n1 += d0 * d0 + d1 * d1;
            }
            n0 += __shfl_xor_sync(~0u, n0, 1); n0 += __shfl_xor_sync(~0u, n0, 2);
            n1 += __shfl_xor_sync(~0u, n1, 1); n1 += __shfl_xor_sync(~0u, n1, 2);
        }
        const uint32_t x0 = nq[4], x1 = nq[5];
        if (rep == 0) {
            const int nr = row + 256;
            nq[0] = q32[nr * 9 + t]; nq[1] = q32[(nr + 8) * 9 + t]; nq[2] = q32[nr * 9 + 4 + t]; nq[3] = q32[(nr + 8) * 9 + 4 + t];
            nq[4] = q32[nr * 9 + 8]; nq[5] = q32[(nr + 8) * 9 + 8];
        }
        if (tid == 0 && rep == 0) TS(1, 7);
        const bool unsafe = !(fmaxf(n0, n1) * kmax2 <= FAST_BOUND * FAST_BOUND) || !(n0 == n0) || !(n1 == n1);
        uint32_t any_unsafe;
        asm volatile("{\n.reg .pred p, q;\nsetp.ne.u32 p, %1, 0;\nbar.red.or.pred q, %2, 128, p;\nselp.u32 %0, 1, 0, q;\n}\n" : "=r"(any_unsafe) : "r"((uint32_t)unsafe), "r"(wg + 1) : "memory");
        any_unsafe = __shfl_sync(~0u, any_unsafe, 0);
        {
            const uint32_t cst = any_unsafe ? 0u : (t == 1 ? 0x3F804780u : (t == 2 ? 0x00003F80u : 0u));
            asm volatile("st.shared.b32 [%0], %1;" ::"r"(sQ), "r"(qa[0]) : "memory");
            asm volatile("st.shared.b32 [%0], %1;" ::"r"(sQ + 512), "r"(qa[1]) : "memory");
            asm volatile("st.shared.b32 [%0], %1;" ::"r"(sQ + 128), "r"(qa[2]) : "memory");
            asm volatile("st.shared.b32 [%0], %1;" ::"r"(sQ + 640), "r"(qa[3]) : "memory");
            asm volatile("st.shared.b32 [%0], %1;" ::"r"(sQ + 256), "r"(t == 0 ? x0 : cst) : "memory");
            asm volatile("st.shared.b32 [%0], %1;" ::"r"(sQ + 768), "r"(t == 0 ? x1 : cst) : "memory");
            asm volatile("st.shared.b32 [%0], %1;" ::"r"(sQ + 384), "r"(0u) : "memory");
            asm volatile("st.shared.b32 [%0], %1;" ::"r"(sQ + 896), "r"(0u) : "memory");
            proxy_fence();
            named_sync(wg + 1, 128);
        }
        if (tid == 0) TS(1, 2 + rep * 2);
        float o[12];
#pragma unroll
        for (int i = 0; i < 12; i++) o[i] = 0.f;
        pin(o);
        uint64_t dK0 = cdesc(0, 128, 384, 0), dK1 = cdesc(256, 0, 384, 0), dV = cdesc(KV_BYTES, 384, 128, 0);
        if (!any_unsafe) {
            float s[64];
#pragma unroll 1
            for (int j = 0; j < 16; j++) {
                if (rep == 0 && (j & 1) == 0) mbar_wait(bars + (j >> 1) * 8, 0);
                wg_fence();
                wgmma_ss_n128<0>(s, dQ0, dK0, 0);
                wgmma_ss_n128<0>(s, dQ1, dK1, 1);
                wg_commit();
                dK0 += 16 * 384 >> 4; dK1 += 16 * 384 >> 4;
                wg_wait<0>();
                pin(s);
                uint32_t p[32];
#pragma unroll
                for (int i = 0; i < 32; i++) {
                    if ((POLY_MASK >> (i >> 1)) & 1) p[i] = exp2_pair_fixed(s[2 * i], s[2 * i + 1]);
                    else p[i] = pack_bf16(ex2(s[2 * i]), ex2(s[2 * i + 1]));
                }
                pin(p);
                wg_fence();
#pragma unroll
                for (int k = 0; k < 8; k++) wgmma_rs_n24<1>(o, p[4 * k], p[4 * k + 1], p[4 * k + 2], p[4 * k + 3], dV + k * 48, 1);
                wg_commit();
                dV += 16 * 384 >> 4;
                wg_wait<0>();
            }
        } else {
            float s[64];
            float m0 = -INFINITY, m1 = -INFINITY;
#pragma unroll 1
            for (int j = 0; j < 16; j++) {
                if (rep == 0 && (j & 1) == 0) mbar_wait(bars + (j >> 1) * 8, 0);
                wg_fence();
                wgmma_ss_n128<0>(s, dQ0, dK0, 0);
                wgmma_ss_n128<0>(s, dQ1, dK1, 1);
                wg_commit();
                dK0 += 16 * 384 >> 4; dK1 += 16 * 384 >> 4;
                wg_wait<0>();
                pin(s);
                float x0m = m0, x1m = m1;
#pragma unroll
                for (int b = 0; b < 16; b++) { x0m = fmaxf(x0m, fmaxf(s[4 * b], s[4 * b + 1])); x1m = fmaxf(x1m, fmaxf(s[4 * b + 2], s[4 * b + 3])); }
                x0m = fmaxf(x0m, __shfl_xor_sync(~0u, x0m, 1)); x0m = fmaxf(x0m, __shfl_xor_sync(~0u, x0m, 2));
                x1m = fmaxf(x1m, __shfl_xor_sync(~0u, x1m, 1)); x1m = fmaxf(x1m, __shfl_xor_sync(~0u, x1m, 2));
                const float c0 = ex2(m0 - x0m), c1 = ex2(m1 - x1m);
                m0 = x0m; m1 = x1m;
#pragma unroll
                for (int b = 0; b < 3; b++) { o[4 * b] *= c0; o[4 * b + 1] *= c0; o[4 * b + 2] *= c1; o[4 * b + 3] *= c1; }
                uint32_t p[32];
#pragma unroll
                for (int b = 0; b < 16; b++) {
                    p[2 * b] = pack_bf16(ex2(s[4 * b] - m0), ex2(s[4 * b + 1] - m0));
                    p[2 * b + 1] = pack_bf16(ex2(s[4 * b + 2] - m1), ex2(s[4 * b + 3] - m1));
                }
                pin(p); pin(o);
                wg_fence();
#pragma unroll
                for (int k = 0; k < 8; k++) wgmma_rs_n24<1>(o, p[4 * k], p[4 * k + 1], p[4 * k + 2], p[4 * k + 3], dV + k * 48, 1);
                wg_commit();
                dV += 16 * 384 >> 4;
                wg_wait<0>();
            }
        }
        pin(o);
        if (tid == 0) TS(1, 3 + rep * 2);
        const float l0 = __shfl_sync(~0u, o[8], (lane & ~3) | 1), l1 = __shfl_sync(~0u, o[10], (lane & ~3) | 1);
        const float i0 = 1.0f / l0, i1 = 1.0f / l1;
        o32[row * 9 + t] = pack_bf16(o[0] * i0, o[1] * i0);
        o32[(row + 8) * 9 + t] = pack_bf16(o[2] * i1, o[3] * i1);
        o32[row * 9 + 4 + t] = pack_bf16(o[4] * i0, o[5] * i0);
        o32[(row + 8) * 9 + 4 + t] = pack_bf16(o[6] * i1, o[7] * i1);
        if (t == 0) { o32[row * 9 + 8] = pack_bf16(o[8] * i0, o[9] * i0); o32[(row + 8) * 9 + 8] = pack_bf16(o[10] * i1, o[11] * i1); }
    }
    if (tid == 0) TS(1, 6);
    if ((tid & 127) == 0) TS(1, 10 + wg);
}

constexpr int O_THREADS = 416;
constexpr int O_OFF_STAT = P_A_BYTES + P_NST * P_B_STAGE + 256;
constexpr int O_SMEM = O_OFF_STAT + 9 * 64 * 8;

__global__ void __cluster_dims__(3, 1, 1) __launch_bounds__(O_THREADS, 1)
k_oproj(const __grid_constant__ CUtensorMap tmO, const __grid_constant__ CUtensorMap tmWo, const __grid_constant__ CUtensorMap tmX2, const __grid_constant__ CUtensorMap tmOut, const __nv_bfloat16* __restrict__ x) {
    extern __shared__ __align__(1024) uint8_t smem[];
    const uint32_t sA = smem_u32(smem), sB = sA + P_A_BYTES, bars = sB + P_NST * P_B_STAGE;
    const uint32_t fullB = bars, emptyB = bars + 64, fullA = bars + 128;
    const int tid = threadIdx.x, warp = __shfl_sync(~0u, tid >> 5, 0), lane = tid & 31;
    const int m = blockIdx.x / 3, cg = blockIdx.x % 3;
    if (tid == 0) TS(2, 0);
    check_smem_base(sA);
    if (tid == 0) {
        prefetch_map(&tmO); prefetch_map(&tmWo); prefetch_map(&tmX2); prefetch_map(&tmOut);
        for (int i = 0; i < P_NST; i++) { mbar_init(fullB + i * 8, 1); mbar_init(emptyB + i * 8, 12); }
        for (int i = 0; i < 9; i++) mbar_init(fullA + i * 8, 1);
        bar_init_fence();
        for (int kb = 0; kb < 9; kb++) mbar_expect(fullA + kb * 8, 8192);
    }
    cluster_arrive();
    cluster_wait();
    pdl_launch();
    if (warp == 12) {
        if (elect_one()) {
            for (int kb = 0; kb < 9; kb++) {
                const int s = kb >= P_NST ? kb - P_NST : kb;
                if (kb >= P_NST) mbar_wait(emptyB + s * 8, 0);
                mbar_expect(fullB + s * 8, P_B_STAGE);
                for (int a = 0; a < 3; a++) tma_2d(sB + s * P_B_STAGE + a * 8192, &tmWo, cg * 192 + a * 64, kb * 64, fullB + s * 8);
            }
        }
        return;
    }
    if (warp == 0 && elect_one()) {
        pdl_wait();
        TS(2, 1);
        for (int kb = cg; kb < 9; kb += 3) tma_2d_mc(sA + kb * 8192, &tmO, kb * 64, m * 64, fullA + kb * 8, (uint16_t)7);
    }
    __syncwarp();
    const int wg = warp >> 2, w = warp & 3, g = lane >> 2, t = lane & 3;
    uint32_t xr[16];
    {
        const uint32_t* x32 = reinterpret_cast<const uint32_t*>(x) + (((m * 64 + w * 16 + g) * DM + cg * 192 + wg * 64 + 2 * t) >> 1);
#pragma unroll
        for (int b = 0; b < 8; b++) { xr[2 * b] = __ldg(x32 + b * 4); xr[2 * b + 1] = __ldg(x32 + b * 4 + 4 * DM); }
    }
    float acc[32];
    {
        const uint64_t dA = cdesc(0, 16, 1024, 1), dB = cdesc(P_A_BYTES, 8192, 1024, 1) + wg * 512;
#pragma unroll 1
        for (int kb = 0; kb < 9; kb++) {
            const int s = kb >= P_NST ? kb - P_NST : kb;
            mbar_wait(fullA + kb * 8, 0);
            mbar_wait(fullB + s * 8, kb >= P_NST ? 1 : 0);
            wg_fence();
#pragma unroll
            for (int ks = 0; ks < 4; ks++) wgmma_ss_n64<1>(acc, dA + (kb * 512 + ks * 2), dB + (s * (P_B_STAGE >> 4) + ks * 128), (kb | ks) != 0);
            wg_commit();
            if (kb < 4) {
                wg_wait<1>();
                if (kb >= 1 && lane == 0) mbar_arrive(emptyB + (kb - 1) * 8);
            }
        }
        wg_wait<0>();
        pin(acc);
    }
    if (tid == 0) TS(2, 2);
    named_sync(1, 384);
    float s0 = 0.f, q0 = 0.f, s1 = 0.f, q1 = 0.f;
#pragma unroll
    for (int b = 0; b < 8; b++) {
        const uint32_t xa = xr[2 * b], xb = xr[2 * b + 1];
        const uint32_t ha = pack_bf16(acc[4 * b] + bf_lo(xa), acc[4 * b + 1] + bf_hi(xa));
        const uint32_t hb = pack_bf16(acc[4 * b + 2] + bf_lo(xb), acc[4 * b + 3] + bf_hi(xb));
        xr[2 * b] = ha; xr[2 * b + 1] = hb;
        const float a = bf_lo(ha), c = bf_hi(ha), d = bf_lo(hb), e = bf_hi(hb);
        s0 += a + c; q0 = fmaf(a, a, fmaf(c, c, q0));
        s1 += d + e; q1 = fmaf(d, d, fmaf(e, e, q1));
    }
    s0 += __shfl_xor_sync(~0u, s0, 1); s0 += __shfl_xor_sync(~0u, s0, 2);
    q0 += __shfl_xor_sync(~0u, q0, 1); q0 += __shfl_xor_sync(~0u, q0, 2);
    s1 += __shfl_xor_sync(~0u, s1, 1); s1 += __shfl_xor_sync(~0u, s1, 2);
    q1 += __shfl_xor_sync(~0u, q1, 1); q1 += __shfl_xor_sync(~0u, q1, 2);
    const int r = w * 16 + g;
    const uint32_t sStat = sA + O_OFF_STAT;
    if (t < 3) {
        uint32_t dst;
        asm("mapa.shared::cluster.u32 %0, %1, %2;" : "=r"(dst) : "r"(sStat + ((cg * 3 + wg) * 64 + r) * 8), "r"(t));
        asm volatile("st.shared::cluster.v2.f32 [%0], {%1, %2};" ::"r"(dst), "f"(s0), "f"(q0) : "memory");
        asm volatile("st.shared::cluster.v2.f32 [%0], {%1, %2};" ::"r"(dst + 64), "f"(s1), "f"(q1) : "memory");
    }
    if (tid == 0) TS(2, 4);
    cluster_arrive();
    stage_tile<8>(xr, sA + wg * 8192, w, lane);
    proxy_fence();
    named_sync(2 + wg, 128);
    const bool leader = w == 0 && elect_one();
    if (leader) { tma_st_2d(&tmOut, cg * 192 + wg * 64, m * 64, sA + wg * 8192); bulk_commit(); }
    cluster_wait();
    if (tid == 0) TS(2, 5);
    s0 = q0 = s1 = q1 = 0.f;
#pragma unroll
    for (int p = 0; p < 9; p++) {
        float a, b, c, d;
        asm volatile("ld.shared.v2.f32 {%0, %1}, [%2];" : "=f"(a), "=f"(b) : "r"(sStat + (p * 64 + r) * 8));
        asm volatile("ld.shared.v2.f32 {%0, %1}, [%2];" : "=f"(c), "=f"(d) : "r"(sStat + (p * 64 + r + 8) * 8));
        s0 += a; q0 += b; s1 += c; q1 += d;
    }
    const float m0 = s0 * (1.0f / DM), m1 = s1 * (1.0f / DM);
    const float rs0 = rsqrtf(fmaxf(q0 * (1.0f / DM) - m0 * m0, 0.f) + LN_EPS), rs1 = rsqrtf(fmaxf(q1 * (1.0f / DM) - m1 * m1, 0.f) + LN_EPS);
    const float sc0 = -LOG2E * rs0, sc1 = -LOG2E * rs1, n0 = -m0 * sc0, n1 = -m1 * sc1;
#pragma unroll
    for (int b = 0; b < 8; b++) {
        xr[2 * b] = pack_bf16(fmaf(bf_lo(xr[2 * b]), sc0, n0), fmaf(bf_hi(xr[2 * b]), sc0, n0));
        xr[2 * b + 1] = pack_bf16(fmaf(bf_lo(xr[2 * b + 1]), sc1, n1), fmaf(bf_hi(xr[2 * b + 1]), sc1, n1));
    }
    stage_tile<8>(xr, sA + (3 + wg) * 8192, w, lane);
    proxy_fence();
    named_sync(2 + wg, 128);
    if (tid == 0) TS(2, 6);
    if (leader) {
        tma_st_2d(&tmX2, cg * 192 + wg * 64, m * 64, sA + (3 + wg) * 8192);
        bulk_commit();
        bulk_wait_all();
    }
    if (tid == 0) TS(2, 3);
}

constexpr int F_THREADS = 384;
constexpr int F_NST = 6;
constexpr int F_STAGE = 96 * 128;
constexpr int F_X_BYTES = 9 * 16384;
constexpr int F_OFF_ST = F_X_BYTES;
constexpr int F_OFF_BAR = F_OFF_ST + F_NST * F_STAGE;
constexpr int F_SMEM = F_OFF_BAR + 256;

__device__ __forceinline__ float after_issue(float v, uint32_t tick) {
    uint32_t r;
    asm("lop3.b32 %0, %1, %1, %2, 0xF0;" : "=r"(r) : "r"(__float_as_uint(v)), "r"(tick));
    return __uint_as_float(r);
}
__device__ __forceinline__ uint32_t read_tick() { uint32_t c; asm volatile("mov.u32 %0, %%clock;" : "=r"(c)::"memory"); return c; }
__device__ __forceinline__ void silu_s1(const float (&acc)[32], float (&tmp)[8], int piece) {
#pragma unroll
    for (int i = 0; i < 8; i++) tmp[i] = ex2(acc[8 * piece + i]);
}
__device__ __forceinline__ void silu_s2(float (&tmp)[8], uint32_t tick) {
    const float one = after_issue(1.0f, tick);
#pragma unroll
    for (int i = 0; i < 8; i++) tmp[i] = rcp(tmp[i] + one);
}
template <int C>
__device__ __forceinline__ void silu_s3(const float (&acc)[32], const float (&tmp)[8], uint32_t (&h1)[144], int piece) {
#pragma unroll
    for (int i = 0; i < 4; i++) h1[C * 16 + 4 * piece + i] = pack_bf16(acc[8 * piece + 2 * i] * tmp[2 * i], acc[8 * piece + 2 * i + 1] * tmp[2 * i + 1]);
}

struct FfnPipe {
    uint32_t full, empty;
    int lane;
    __device__ __forceinline__ void acquire(int s, uint32_t ph) const { mbar_wait(full + s * 8, ph); }
    __device__ __forceinline__ void release(int s) const { if (lane == 0) mbar_arrive(empty + s * 8); }
};

template <int C>
__device__ __forceinline__ void ffn_phase1_chunk(float (&cur)[32], float (&prev)[32], uint32_t (&h1)[144], const FfnPipe& pp, uint64_t dx, uint32_t fullX) {
    float tmp[2][8];
    const uint64_t dw = cdesc(F_OFF_ST, 8192, 1024, 1) + blockIdx.y * (C + 1);
    dx += blockIdx.y * C;
#pragma unroll
    for (int j = 0; j < 6; j++) {
        if (C == 0) { mbar_wait(fullX + ((6 * j) >> 2) * 8, 0); mbar_wait(fullX + ((6 * j + 5) >> 2) * 8, 0); }
        pp.acquire(j, C & 1);
        if (j == 0) pin(cur);
        wg_fence();
#pragma unroll
        for (int i = 0; i < 6; i++) {
            const int ks = 6 * j + i;
            wgmma_ss_n64<1>(cur, dx + ((ks >> 2) * 1024 + (ks & 3) * 2), dw + ((j * F_STAGE + i * 2048) >> 4), ks != 0);
        }
        wg_commit();
        if (C > 0 || j > 0) { wg_wait<1>(); pp.release((j + 5) % 6); }
        if (C > 0) {
            pin(prev);
            if (j >= 1) { pin(tmp[0]); if (j >= 2) pin(tmp[1]); }
            if (j >= 2) silu_s3<(C > 0 ? C - 1 : 0)>(prev, tmp[j & 1], h1, j - 2);
            if (j >= 1 && j <= 4) { silu_s2(tmp[(j - 1) & 1], read_tick()); pin(tmp[(j - 1) & 1]); }
            if (j <= 3) { silu_s1(prev, tmp[j & 1], j); pin(tmp[j & 1]); }
            if (j >= 2) { asm volatile("" : "+r"(h1[(C - 1) * 16 + 4 * (j - 2)]), "+r"(h1[(C - 1) * 16 + 4 * (j - 2) + 1]), "+r"(h1[(C - 1) * 16 + 4 * (j - 2) + 2]), "+r"(h1[(C - 1) * 16 + 4 * (j - 2) + 3]) :: "memory"); }
        }
    }
}

__device__ __forceinline__ void ffn_store_chunk(const float (&acc)[32], const CUtensorMap* tmOut, uint32_t stg, int col, int row, int w, int lane, int wgid, bool leader) {
    uint32_t pk[16];
#pragma unroll
    for (int i = 0; i < 16; i++) pk[i] = pack_bf16(acc[2 * i] * -LN2, acc[2 * i + 1] * -LN2);
    stage_tile<8>(pk, stg, w, lane);
    proxy_fence();
    named_sync(2 + wgid, 128);
    if (leader) {
        tma_red_2d(tmOut, col, row, stg);
        bulk_commit();
    }
}

__device__ __forceinline__ void ffn_phase2_chunk(float (&cur)[32], float (&prev)[32], uint32_t (&h1)[144], const FfnPipe& pp, uint32_t ph, bool store_prev, const CUtensorMap* tmOut, uint32_t stg_prev, int col_prev, int row, int w, int lane, int wgid, bool leader) {
    const uint64_t dw = cdesc(F_OFF_ST, 8192, 1024, 1) + blockIdx.y * col_prev;
#pragma unroll
    for (int j = 0; j < 6; j++) {
        pp.acquire(j, ph);
        if (j == 0) pin(cur);
        wg_fence();
#pragma unroll
        for (int i = 0; i < 6; i++) {
            const int f = (6 * j + i) * 4;
            wgmma_rs_n64<1>(cur, h1[f], h1[f + 1], h1[f + 2], h1[f + 3], dw + ((j * F_STAGE + i * 2048) >> 4), (j | i) != 0);
        }
        wg_commit();
        if (j > 0 || store_prev) { wg_wait<1>(); pp.release((j + 5) % 6); }
        if (j == 0 && store_prev) { pin(prev); ffn_store_chunk(prev, tmOut, stg_prev, col_prev, row, w, lane, wgid, leader); }
    }
}

__global__ void __cluster_dims__(2, 1, 1) __launch_bounds__(F_THREADS, 1)
k_ffn(const __grid_constant__ CUtensorMap tmH, const __grid_constant__ CUtensorMap tmW1, const __grid_constant__ CUtensorMap tmW2, const __grid_constant__ CUtensorMap tmOut) {
    extern __shared__ __align__(1024) uint8_t smem[];
    const uint32_t sX = smem_u32(smem), sSt = sX + F_OFF_ST, bars = sX + F_OFF_BAR;
    const uint32_t full = bars, empty = bars + 64, fullX = bars + 128;
    const int tid = threadIdx.x, warp = __shfl_sync(~0u, tid >> 5, 0), lane = tid & 31;
    const int m = (blockIdx.x >> 1) & 15, fs = (blockIdx.x >> 5) * 2 + (blockIdx.x & 1);
    if (tid == 0) TS(3, 0);
    check_smem_base(sX);
    if (tid == 0) {
        prefetch_map(&tmW1); prefetch_map(&tmH); prefetch_map(&tmW2); prefetch_map(&tmOut);
        for (int i = 0; i < F_NST; i++) { mbar_init(full + i * 8, 1); mbar_init(empty + i * 8, 8); }
        for (int i = 0; i < 9; i++) mbar_init(fullX + i * 8, 1);
        bar_init_fence();
        for (int kb = 0; kb < 9; kb++) mbar_expect(fullX + kb * 8, 16384);
    }
    cluster_arrive();
    cluster_wait();
    if (warp < 4) {
        asm volatile("setmaxnreg.dec.sync.aligned.u32 24;");
        if (warp == 0 && elect_one()) {
            int s = 0; uint32_t ph = 1;
            int c = 0, j = 0;
#pragma unroll 1
            for (int i = 0; i < 108; i++) {
                if (i == 54) c = fs;
                mbar_wait(empty + s * 8, ph);
                mbar_expect(full + s * 8, F_STAGE);
                if (i < 54) tma_2d(sSt + s * F_STAGE, &tmW1, fs * 576 + c * 64, j * 96, full + s * 8);
                else tma_2d(sSt + s * F_STAGE, &tmW2, c * 64, fs * 576 + j * 96, full + s * 8);
                if (++j == 6) { j = 0; if (++c == 9) c = 0; }
                if (++s == F_NST) { s = 0; ph ^= 1; }
            }
        }
    } else {
        asm volatile("setmaxnreg.inc.sync.aligned.u32 240;");
        const int wgid = (warp >> 2) - 1, w = warp & 3;
        pdl_wait();
        if (tid == 128) TS(3, 1);
        if (warp == 4 && elect_one()) {
            const int half = blockIdx.x & 1;
            for (int kb = 0; kb < 9; kb++) tma_2d_mc(sX + kb * 16384 + half * 8192, &tmH, kb * 64, m * 128 + half * 64, fullX + kb * 8, (uint16_t)3);
        }
        __syncwarp();
        FfnPipe pp{full, empty, lane};
        const uint64_t xlo = cdesc(0, 16, 1024, 1) + wgid * 512;
        uint32_t h1[144];
        float acc0[32], acc1[32];
        ffn_phase1_chunk<0>(acc0, acc1, h1, pp, xlo, fullX);
        if (tid == 128) TS(3, 2);
        ffn_phase1_chunk<1>(acc1, acc0, h1, pp, xlo, fullX);
        ffn_phase1_chunk<2>(acc0, acc1, h1, pp, xlo, fullX);
        ffn_phase1_chunk<3>(acc1, acc0, h1, pp, xlo, fullX);
        ffn_phase1_chunk<4>(acc0, acc1, h1, pp, xlo, fullX);
        ffn_phase1_chunk<5>(acc1, acc0, h1, pp, xlo, fullX);
        ffn_phase1_chunk<6>(acc0, acc1, h1, pp, xlo, fullX);
        ffn_phase1_chunk<7>(acc1, acc0, h1, pp, xlo, fullX);
        ffn_phase1_chunk<8>(acc0, acc1, h1, pp, xlo, fullX);
        wg_wait<0>();
        pp.release(5);
        pin(acc0);
        {
            float tmp[4][8];
#pragma unroll
            for (int p = 0; p < 4; p++) silu_s1(acc0, tmp[p], p);
#pragma unroll
            for (int p = 0; p < 4; p++) silu_s2(tmp[p], 0);
#pragma unroll
            for (int p = 0; p < 4; p++) silu_s3<8>(acc0, tmp[p], h1, p);
        }
        pin(h1);
        if (tid == 128) TS(3, 3);
        const int row = m * 128 + wgid * 64;
        const uint32_t stg = sX + wgid * 8192;
        int c = fs, cprev = 0;
        const bool leader = w == 0 && elect_one();
#pragma unroll 1
        for (int j = 0; j < 8; j += 2) {
            ffn_phase2_chunk(acc1, acc0, h1, pp, 1, j > 0, &tmOut, stg + (j - 1) * 16384, cprev * 64, row, w, lane, wgid, leader);
            cprev = c; if (++c == 9) c = 0;
            ffn_phase2_chunk(acc0, acc1, h1, pp, 0, true, &tmOut, stg + j * 16384, cprev * 64, row, w, lane, wgid, leader);
            cprev = c; if (++c == 9) c = 0;
        }
        ffn_phase2_chunk(acc1, acc0, h1, pp, 1, true, &tmOut, stg + 7 * 16384, cprev * 64, row, w, lane, wgid, leader);
        wg_wait<0>();
        pin(acc1);
        ffn_store_chunk(acc1, &tmOut, stg + 8 * 16384, c * 64, row, w, lane, wgid, leader);
        if (tid == 128) TS(3, 4);
        if (leader) bulk_wait_all();
        if (tid == 128) TS(3, 5);
    }
}

typedef CUresult (*EncodeFn)(CUtensorMap*, CUtensorMapDataType, cuuint32_t, void*, const cuuint64_t*, const cuuint64_t*, const cuuint32_t*, const cuuint32_t*,
                             CUtensorMapInterleave, CUtensorMapSwizzle, CUtensorMapL2promotion, CUtensorMapFloatOOBfill);

CUtensorMap make_map(EncodeFn enc, const void* base, int rows, int cols, int box_rows) {
    CUtensorMap tm;
    cuuint64_t dims[2] = {(cuuint64_t)cols, (cuuint64_t)rows};
    cuuint64_t strides[1] = {(cuuint64_t)cols * 2};
    cuuint32_t box[2] = {64, (cuuint32_t)box_rows};
    cuuint32_t es[2] = {1, 1};
    enc(&tm, CU_TENSOR_MAP_DATA_TYPE_BFLOAT16, 2, const_cast<void*>(base), dims, strides, box, es, CU_TENSOR_MAP_INTERLEAVE_NONE,
        CU_TENSOR_MAP_SWIZZLE_128B, CU_TENSOR_MAP_L2_PROMOTION_L2_256B, CU_TENSOR_MAP_FLOAT_OOB_FILL_NONE);
    return tm;
}

template <typename... KArgs, typename... Args>
void launch(void (*kern)(KArgs...), int grid, int block, int smem, bool pdl, Args... args) {
    cudaLaunchConfig_t cfg = {};
    cfg.gridDim = dim3(grid); cfg.blockDim = dim3(block); cfg.dynamicSmemBytes = smem; cfg.stream = cudaStreamPerThread;
    cudaLaunchAttribute at[1];
    at[0].id = cudaLaunchAttributeProgrammaticStreamSerialization;
    at[0].val.programmaticStreamSerializationAllowed = 1;
    cfg.attrs = at; cfg.numAttrs = pdl ? 1 : 0;
    cudaLaunchKernelEx(&cfg, kern, KArgs(args)...);
}

}

#define USE_PDL 1

extern "C" void kernel_launch(void* const* d_in, const int* in_sizes, int n_in, void* d_out, int out_size) {
    const __nv_bfloat16* x = (const __nv_bfloat16*)d_in[0];
    const __nv_bfloat16* wq = (const __nv_bfloat16*)d_in[1];
    const __nv_bfloat16* wk = (const __nv_bfloat16*)d_in[2];
    const __nv_bfloat16* wv = (const __nv_bfloat16*)d_in[3];
    const __nv_bfloat16* wo = (const __nv_bfloat16*)d_in[4];
    const __nv_bfloat16* w1 = (const __nv_bfloat16*)d_in[6];
    const __nv_bfloat16* w2 = (const __nv_bfloat16*)d_in[7];
    __nv_bfloat16* out = (__nv_bfloat16*)d_out;

    static EncodeFn enc = nullptr;
    static void *p_o = nullptr, *p_h = nullptr, *p_q = nullptr;
    if (!enc) {
        cudaDriverEntryPointQueryResult qr;
        cudaGetDriverEntryPoint("cuTensorMapEncodeTiled", (void**)&enc, cudaEnableDefault, &qr);
        cudaGetSymbolAddress(&p_o, g_o);
        cudaGetSymbolAddress(&p_h, g_x2);
        cudaGetSymbolAddress(&p_q, g_q);
        cudaFuncSetAttribute(k_qkv, cudaFuncAttributeMaxDynamicSharedMemorySize, P_SMEM);
        cudaFuncSetAttribute(k_attn, cudaFuncAttributeMaxDynamicSharedMemorySize, A_SMEM);
        cudaFuncSetAttribute(k_oproj, cudaFuncAttributeMaxDynamicSharedMemorySize, O_SMEM);
        cudaFuncSetAttribute(k_ffn, cudaFuncAttributeMaxDynamicSharedMemorySize, F_SMEM);
    }
    const CUtensorMap tmWq = make_map(enc, wq, DM, DM, 64);
    const CUtensorMap tmWo = make_map(enc, wo, DM, DM, 64);
    const CUtensorMap tmO = make_map(enc, p_o, SEQ, DM, 64);
    const CUtensorMap tmH64 = make_map(enc, p_h, SEQ, DM, 64);
    const CUtensorMap tmQ = make_map(enc, p_q, SEQ, DM, 64);
    const CUtensorMap tmW1 = make_map(enc, w1, DM, FF, 96);
    const CUtensorMap tmW2 = make_map(enc, w2, FF, DM, 96);
    const CUtensorMap tmOut = make_map(enc, out, SEQ, DM, 64);

    launch(k_qkv, 128, P_THREADS, P_SMEM, false, tmWq, tmQ, x, wk, wv);
    launch(k_attn, 132, A_THREADS, A_SMEM, USE_PDL, w1, w2, wo);
    launch(k_oproj, 96, O_THREADS, O_SMEM, USE_PDL, tmO, tmWo, tmH64, tmOut, x);
    launch(k_ffn, 128, F_THREADS, F_SMEM, USE_PDL, tmH64, tmW1, tmW2, tmOut);
}
```

```cpp
#include <cuda_runtime.h>
#include <cuda_bf16.h>
#include <cuda.h>
#include <stdint.h>

namespace {

constexpr int SEQ = 2048, DM = 576, FF = 4608;
constexpr int KV_BYTES = SEQ * 48;
constexpr float LN_EPS = 1e-5f;
constexpr float LOG2E = 1.4426950408889634f;
constexpr float LN2 = 0.6931471805599453f;
constexpr float Q_SCALE = 0.23570226039551584f * LOG2E;

#define POLY_MASK_V 0xB5B5u
constexpr uint32_t POLY_MASK = POLY_MASK_V;
constexpr float FAST_BOUND = 60.0f;

__device__ __align__(1024) __nv_bfloat16 g_q[SEQ * DM];
__device__ __align__(1024) uint4 g_kc[KV_BYTES / 16];
__device__ __align__(1024) uint4 g_vc[KV_BYTES / 16];
__device__ float g_kmax[32];
__device__ __align__(1024) __nv_bfloat16 g_o[SEQ * DM];
__device__ __align__(1024) __nv_bfloat16 g_x2[SEQ * DM];

#define TS(k, i)

__device__ __forceinline__ uint32_t smem_u32(const void* p) { return (uint32_t)__cvta_generic_to_shared(p); }
__device__ __forceinline__ void wg_fence() { asm volatile("wgmma.fence.sync.aligned;" ::: "memory"); }
__device__ __forceinline__ void wg_commit() { asm volatile("wgmma.commit_group.sync.aligned;" ::: "memory"); }
template <int N> __device__ __forceinline__ void wg_wait() { asm volatile("wgmma.wait_group.sync.aligned %0;" ::"n"(N) : "memory"); }
template <int N> __device__ __forceinline__ void pin(float (&r)[N]) {
#pragma unroll
    for (int i = 0; i < N; i++) asm volatile("" : "+f"(r[i])::"memory");
}
template <int N> __device__ __forceinline__ void pin(uint32_t (&r)[N]) {
#pragma unroll
    for (int i = 0; i < N; i++) asm volatile("" : "+r"(r[i])::"memory");
}
__device__ __forceinline__ constexpr uint32_t desc_hi(uint32_t sbo, uint32_t swz) { return (sbo >> 4) | (swz << 30); }
__device__ __forceinline__ uint32_t desc_lo(uint32_t addr, uint32_t lbo) { return ((addr & 0x3FFFF) >> 4) | ((lbo >> 4) << 16); }
__device__ __forceinline__ uint64_t desc64(uint32_t lo, uint32_t hi) { return ((uint64_t)hi << 32) | lo; }
constexpr uint32_t SMEM0 = 0x400;
__host__ __device__ constexpr uint64_t cdesc(uint32_t off, uint32_t lbo, uint32_t sbo, uint32_t swz) {
    return (uint64_t)(((SMEM0 + off) & 0x3FFFF) >> 4) | ((uint64_t)(lbo >> 4) << 16) | ((uint64_t)(sbo >> 4) << 32) | ((uint64_t)swz << 62);
}
__device__ __forceinline__ void check_smem_base(uint32_t base) { if ((base & 0x3FFFF) != SMEM0) __trap(); }

__device__ __forceinline__ void mbar_init(uint32_t bar, int cnt) { asm volatile("mbarrier.init.shared::cta.b64 [%0], %1;" ::"r"(bar), "r"(cnt) : "memory"); }
__device__ __forceinline__ void mbar_expect(uint32_t bar, int bytes) { asm volatile("mbarrier.arrive.expect_tx.shared::cta.b64 _, [%0], %1;" ::"r"(bar), "r"(bytes) : "memory"); }
__device__ __forceinline__ void mbar_arrive(uint32_t bar) { asm volatile("mbarrier.arrive.shared::cta.b64 _, [%0];" ::"r"(bar) : "memory"); }
__device__ __forceinline__ void mbar_wait(uint32_t bar, uint32_t parity) {
    asm volatile(
        "{\n.reg .pred p;\n.reg .u32 n;\nmov.u32 n, 0;\n"
        "LAB_WAIT:\n"
        "mbarrier.try_wait.parity.shared::cta.b64 p, [%0], %1;\n"
        "@p bra DONE;\n"
        "add.u32 n, n, 1;\n"
        "setp.lt.u32 p, n, 4000000;\n"
        "@p bra LAB_WAIT;\n"
        "trap;\n"
        "DONE:\n}\n" ::"r"(bar), "r"(parity) : "memory");
}
__device__ __forceinline__ void bar_init_fence() {
    asm volatile("fence.mbarrier_init.release.cluster;" ::: "memory");
    asm volatile("fence.proxy.async.shared::cta;" ::: "memory");
}
__device__ __forceinline__ void proxy_fence() { asm volatile("fence.proxy.async.shared::cta;" ::: "memory"); }
__device__ __forceinline__ void named_sync(int id, int n) { asm volatile("bar.sync %0, %1;" ::"r"(id), "r"(n) : "memory"); }
__device__ __forceinline__ void bulk_g2s(uint32_t dst, const void* src, int bytes, uint32_t bar) {
    asm volatile("cp.async.bulk.shared::cluster.global.mbarrier::complete_tx::bytes [%0], [%1], %2, [%3];" ::"r"(dst), "l"(src), "r"(bytes), "r"(bar) : "memory");
}
__device__ __forceinline__ void tma_2d(uint32_t dst, const CUtensorMap* tm, int c0, int c1, uint32_t bar) {
    asm volatile("cp.async.bulk.tensor.2d.shared::cluster.global.mbarrier::complete_tx::bytes [%0], [%1, {%3, %4}], [%2];" ::"r"(dst), "l"(tm), "r"(bar), "r"(c0), "r"(c1) : "memory");
}
__device__ __forceinline__ void tma_2d_mc(uint32_t dst, const CUtensorMap* tm, int c0, int c1, uint32_t bar, uint16_t mask) {
    asm volatile("cp.async.bulk.tensor.2d.shared::cluster.global.mbarrier::complete_tx::bytes.multicast::cluster [%0], [%1, {%3, %4}], [%2], %5;" ::"r"(dst), "l"(tm), "r"(bar), "r"(c0), "r"(c1), "h"(mask) : "memory");
}
__device__ __forceinline__ void cluster_arrive() { asm volatile("barrier.cluster.arrive.release.aligned;" ::: "memory"); }
__device__ __forceinline__ void cluster_wait() { asm volatile("barrier.cluster.wait.acquire.aligned;" ::: "memory"); }
__device__ __forceinline__ void tma_red_2d(const CUtensorMap* tm, int c0, int c1, uint32_t src) {
    asm volatile("cp.reduce.async.bulk.tensor.2d.global.shared::cta.add.tile.bulk_group [%0, {%2, %3}], [%1];" ::"l"(tm), "r"(src), "r"(c0), "r"(c1) : "memory");
}
__device__ __forceinline__ void tma_st_2d(const CUtensorMap* tm, int c0, int c1, uint32_t src) {
    asm volatile("cp.async.bulk.tensor.2d.global.shared::cta.tile.bulk_group [%0, {%2, %3}], [%1];" ::"l"(tm), "r"(src), "r"(c0), "r"(c1) : "memory");
}
__device__ __forceinline__ void bulk_commit() { asm volatile("cp.async.bulk.commit_group;" ::: "memory"); }
__device__ __forceinline__ void bulk_wait_all() { asm volatile("cp.async.bulk.wait_group.read 0;" ::: "memory"); }
__device__ __forceinline__ bool elect_one() {
    uint32_t p;
    asm volatile("{\n.reg .pred P;\nelect.sync _|P, 0xffffffff;\nselp.b32 %0, 1, 0, P;\n}\n" : "=r"(p));
    return p != 0;
}
__device__ __forceinline__ void prefetch_l2(const void* p, int bytes) { asm volatile("cp.async.bulk.prefetch.L2.global [%0], %1;" ::"l"(p), "r"(bytes) : "memory"); }
__device__ __forceinline__ void prefetch_map(const CUtensorMap* tm) { asm volatile("prefetch.tensormap [%0];" ::"l"(tm) : "memory"); }
__device__ __forceinline__ void pdl_launch() { asm volatile("griddepcontrol.launch_dependents;" ::: "memory"); }
__device__ __forceinline__ void pdl_wait() { asm volatile("griddepcontrol.wait;" ::: "memory"); }
__device__ __forceinline__ float ex2(float x) { float y; asm("ex2.approx.ftz.f32 %0, %1;" : "=f"(y) : "f"(x)); return y; }
__device__ __forceinline__ float rcp(float x) { float y; asm("rcp.approx.ftz.f32 %0, %1;" : "=f"(y) : "f"(x)); return y; }
__device__ __forceinline__ uint32_t pack_bf16(float lo, float hi) { uint32_t r; asm("cvt.rn.bf16x2.f32 %0, %1, %2;" : "=r"(r) : "f"(hi), "f"(lo)); return r; }
__device__ __forceinline__ float bf_lo(uint32_t v) { return __uint_as_float(v << 16); }
__device__ __forceinline__ float bf_hi(uint32_t v) { return __uint_as_float(v & 0xFFFF0000u); }
__device__ __forceinline__ uint32_t hfma2(uint32_t a, uint32_t b, uint32_t c) { uint32_t r; asm("fma.rn.f16x2 %0, %1, %2, %3;" : "=r"(r) : "r"(a), "r"(b), "r"(c)); return r; }
__device__ __forceinline__ void stmatrix_x4(uint32_t addr, uint32_t r0, uint32_t r1, uint32_t r2, uint32_t r3) {
    asm volatile("stmatrix.sync.aligned.m8n8.x4.shared.b16 [%0], {%1, %2, %3, %4};" ::"r"(addr), "r"(r0), "r"(r1), "r"(r2), "r"(r3) : "memory");
}

template <int TB> __device__ __forceinline__ void wgmma_ss_n24(float (&d)[12], uint64_t da, uint64_t db, int sc) {
    asm volatile("{\n.reg .pred p;\nsetp.ne.b32 p, %14, 0;\n"
        "wgmma.mma_async.sync.aligned.m64n24k16.f32.bf16.bf16 {%0, %1, %2, %3, %4, %5, %6, %7, %8, %9, %10, %11}, %12, %13, p, 1, 1, 0, %15;\n}\n"
        : "+f"(d[0]), "+f"(d[1]), "+f"(d[2]), "+f"(d[3]), "+f"(d[4]), "+f"(d[5]), "+f"(d[6]), "+f"(d[7]), "+f"(d[8]), "+f"(d[9]), "+f"(d[10]), "+f"(d[11])
        : "l"(da), "l"(db), "r"(sc), "n"(TB));
}
template <int TB> __device__ __forceinline__ void wgmma_ss_n64(float (&d)[32], uint64_t da, uint64_t db, int sc) {
    asm volatile("{\n.reg .pred p;\nsetp.ne.b32 p, %34, 0;\n"
        "wgmma.mma_async.sync.aligned.m64n64k16.f32.bf16.bf16 {%0, %1, %2, %3, %4, %5, %6, %7, %8, %9, %10, %11, %12, %13, %14, %15, %16, %17, %18, %19, %20, %21, %22, %23, %24, %25, %26, %27, %28, %29, %30, %31}, %32, %33, p, 1, 1, 0, %35;\n}\n"
        : "+f"(d[0]), "+f"(d[1]), "+f"(d[2]), "+f"(d[3]), "+f"(d[4]), "+f"(d[5]), "+f"(d[6]), "+f"(d[7]), "+f"(d[8]), "+f"(d[9]), "+f"(d[10]), "+f"(d[11]), "+f"(d[12]), "+f"(d[13]), "+f"(d[14]), "+f"(d[15]), "+f"(d[16]), "+f"(d[17]), "+f"(d[18]), "+f"(d[19]), "+f"(d[20]), "+f"(d[21]), "+f"(d[22]), "+f"(d[23]), "+f"(d[24]), "+f"(d[25]), "+f"(d[26]), "+f"(d[27]), "+f"(d[28]), "+f"(d[29]), "+f"(d[30]), "+f"(d[31])
        : "l"(da), "l"(db), "r"(sc), "n"(TB));
}
template <int TB> __device__ __forceinline__ void wgmma_ss_n128(float (&d)[64], uint64_t da, uint64_t db, int sc) {
    asm volatile("{\n.reg .pred p;\nsetp.ne.b32 p, %66, 0;\n"
        "wgmma.mma_async.sync.aligned.m64n128k16.f32.bf16.bf16 {%0, %1, %2, %3, %4, %5, %6, %7, %8, %9, %10, %11, %12, %13, %14, %15, %16, %17, %18, %19, %20, %21, %22, %23, %24, %25, %26, %27, %28, %29, %30, %31, %32, %33, %34, %35, %36, %37, %38, %39, %40, %41, %42, %43, %44, %45, %46, %47, %48, %49, %50, %51, %52, %53, %54, %55, %56, %57, %58, %59, %60, %61, %62, %63}, %64, %65, p, 1, 1, 0, %67;\n}\n"
        : "+f"(d[0]), "+f"(d[1]), "+f"(d[2]), "+f"(d[3]), "+f"(d[4]), "+f"(d[5]), "+f"(d[6]), "+f"(d[7]), "+f"(d[8]), "+f"(d[9]), "+f"(d[10]), "+f"(d[11]), "+f"(d[12]), "+f"(d[13]), "+f"(d[14]), "+f"(d[15]), "+f"(d[16]), "+f"(d[17]), "+f"(d[18]), "+f"(d[19]), "+f"(d[20]), "+f"(d[21]), "+f"(d[22]), "+f"(d[23]), "+f"(d[24]), "+f"(d[25]), "+f"(d[26]), "+f"(d[27]), "+f"(d[28]), "+f"(d[29]), "+f"(d[30]), "+f"(d[31]), "+f"(d[32]), "+f"(d[33]), "+f"(d[34]), "+f"(d[35]), "+f"(d[36]), "+f"(d[37]), "+f"(d[38]), "+f"(d[39]), "+f"(d[40]), "+f"(d[41]), "+f"(d[42]), "+f"(d[43]), "+f"(d[44]), "+f"(d[45]), "+f"(d[46]), "+f"(d[47]), "+f"(d[48]), "+f"(d[49]), "+f"(d[50]), "+f"(d[51]), "+f"(d[52]), "+f"(d[53]), "+f"(d[54]), "+f"(d[55]), "+f"(d[56]), "+f"(d[57]), "+f"(d[58]), "+f"(d[59]), "+f"(d[60]), "+f"(d[61]), "+f"(d[62]), "+f"(d[63])
        : "l"(da), "l"(db), "r"(sc), "n"(TB));
}
template <int TB> __device__ __forceinline__ void wgmma_rs_n24(float (&d)[12], uint32_t a0, uint32_t a1, uint32_t a2, uint32_t a3, uint64_t db, int sc) {
    asm volatile("{\n.reg .pred p;\nsetp.ne.b32 p, %17, 0;\n"
        "wgmma.mma_async.sync.aligned.m64n24k16.f32.bf16.bf16 {%0, %1, %2, %3, %4, %5, %6, %7, %8, %9, %10, %11}, {%12, %13, %14, %15}, %16, p, 1, 1, %18;\n}\n"
        : "+f"(d[0]), "+f"(d[1]), "+f"(d[2]), "+f"(d[3]), "+f"(d[4]), "+f"(d[5]), "+f"(d[6]), "+f"(d[7]), "+f"(d[8]), "+f"(d[9]), "+f"(d[10]), "+f"(d[11])
        : "r"(a0), "r"(a1), "r"(a2), "r"(a3), "l"(db), "r"(sc), "n"(TB));
}
template <int TB> __device__ __forceinline__ void wgmma_rs_n64(float (&d)[32], uint32_t a0, uint32_t a1, uint32_t a2, uint32_t a3, uint64_t db, int sc) {
    asm volatile("{\n.reg .pred p;\nsetp.ne.b32 p, %37, 0;\n"
        "wgmma.mma_async.sync.aligned.m64n64k16.f32.bf16.bf16 {%0, %1, %2, %3, %4, %5, %6, %7, %8, %9, %10, %11, %12, %13, %14, %15, %16, %17, %18, %19, %20, %21, %22, %23, %24, %25, %26, %27, %28, %29, %30, %31}, {%32, %33, %34, %35}, %36, p, 1, 1, %38;\n}\n"
        : "+f"(d[0]), "+f"(d[1]), "+f"(d[2]), "+f"(d[3]), "+f"(d[4]), "+f"(d[5]), "+f"(d[6]), "+f"(d[7]), "+f"(d[8]), "+f"(d[9]), "+f"(d[10]), "+f"(d[11]), "+f"(d[12]), "+f"(d[13]), "+f"(d[14]), "+f"(d[15]), "+f"(d[16]), "+f"(d[17]), "+f"(d[18]), "+f"(d[19]), "+f"(d[20]), "+f"(d[21]), "+f"(d[22]), "+f"(d[23]), "+f"(d[24]), "+f"(d[25]), "+f"(d[26]), "+f"(d[27]), "+f"(d[28]), "+f"(d[29]), "+f"(d[30]), "+f"(d[31])
        : "r"(a0), "r"(a1), "r"(a2), "r"(a3), "l"(db), "r"(sc), "n"(TB));
}
template <int TB> __device__ __forceinline__ void wgmma_rs_n128(float (&d)[64], uint32_t a0, uint32_t a1, uint32_t a2, uint32_t a3, uint64_t db, int sc) {
    asm volatile("{\n.reg .pred p;\nsetp.ne.b32 p, %69, 0;\n"
        "wgmma.mma_async.sync.aligned.m64n128k16.f32.bf16.bf16 {%0, %1, %2, %3, %4, %5, %6, %7, %8, %9, %10, %11, %12, %13, %14, %15, %16, %17, %18, %19, %20, %21, %22, %23, %24, %25, %26, %27, %28, %29, %30, %31, %32, %33, %34, %35, %36, %37, %38, %39, %40, %41, %42, %43, %44, %45, %46, %47, %48, %49, %50, %51, %52, %53, %54, %55, %56, %57, %58, %59, %60, %61, %62, %63}, {%64, %65, %66, %67}, %68, p, 1, 1, %70;\n}\n"
        : "+f"(d[0]), "+f"(d[1]), "+f"(d[2]), "+f"(d[3]), "+f"(d[4]), "+f"(d[5]), "+f"(d[6]), "+f"(d[7]), "+f"(d[8]), "+f"(d[9]), "+f"(d[10]), "+f"(d[11]), "+f"(d[12]), "+f"(d[13]), "+f"(d[14]), "+f"(d[15]), "+f"(d[16]), "+f"(d[17]), "+f"(d[18]), "+f"(d[19]), "+f"(d[20]), "+f"(d[21]), "+f"(d[22]), "+f"(d[23]), "+f"(d[24]), "+f"(d[25]), "+f"(d[26]), "+f"(d[27]), "+f"(d[28]), "+f"(d[29]), "+f"(d[30]), "+f"(d[31]), "+f"(d[32]), "+f"(d[33]), "+f"(d[34]), "+f"(d[35]), "+f"(d[36]), "+f"(d[37]), "+f"(d[38]), "+f"(d[39]), "+f"(d[40]), "+f"(d[41]), "+f"(d[42]), "+f"(d[43]), "+f"(d[44]), "+f"(d[45]), "+f"(d[46]), "+f"(d[47]), "+f"(d[48]), "+f"(d[49]), "+f"(d[50]), "+f"(d[51]), "+f"(d[52]), "+f"(d[53]), "+f"(d[54]), "+f"(d[55]), "+f"(d[56]), "+f"(d[57]), "+f"(d[58]), "+f"(d[59]), "+f"(d[60]), "+f"(d[61]), "+f"(d[62]), "+f"(d[63])
        : "r"(a0), "r"(a1), "r"(a2), "r"(a3), "l"(db), "r"(sc), "n"(TB));
}

constexpr int P_THREADS = 288;
constexpr int P_NST = 6;
constexpr int P_A_BYTES = 9 * 8192;
constexpr int P_B_STAGE = 3 * 8192;
constexpr int P_SMEM = P_A_BYTES + P_NST * P_B_STAGE + 256 + 320;
constexpr uint32_t HI_SW128 = (1024u >> 4) | (1u << 30);

template <int NCOL, bool WAIT_A>
__device__ __forceinline__ void proj_mma(float (&acc)[NCOL / 2], uint32_t sA, uint32_t sB, uint32_t colofs, uint32_t fullB, uint32_t emptyB, uint32_t fullA, int lane) {
#pragma unroll 1
    for (int kb = 0; kb < 9; kb++) {
        const int s = kb >= P_NST ? kb - P_NST : kb;
        if (WAIT_A) mbar_wait(fullA + kb * 8, 0);

        mbar_wait(fullB + s * 8, kb >= P_NST ? 1 : 0);
        const uint32_t alo = desc_lo(sA + kb * 8192, 16), blo = desc_lo(sB + s * P_B_STAGE + colofs, 8192);
        wg_fence();
#pragma unroll
        for (int ks = 0; ks < 4; ks++) {
            const uint64_t da = desc64(alo + ks * 2, HI_SW128), db = desc64(blo + ks * 128, HI_SW128);
            if constexpr (NCOL == 128) wgmma_ss_n128<1>(acc, da, db, (kb | ks) != 0);
            else wgmma_ss_n64<1>(acc, da, db, (kb | ks) != 0);
        }
        wg_commit();
        if (kb + P_NST < 9 + 1) {
            wg_wait<1>();
            if (kb >= 1 && kb - 1 + P_NST < 9 && lane == 0) mbar_arrive(emptyB + (kb - 1) * 8);
        }
    }
    wg_wait<0>();
    pin(acc);
}

template <int NB>
__device__ __forceinline__ void stage_tile(const uint32_t (&pk)[NB * 2], uint32_t base, int w, int lane) {
    const int r = w * 16 + (lane & 7) + ((lane >> 3) & 1) * 8;
#pragma unroll
    for (int b = 0; b < NB; b += 2) {
        const uint32_t a = base + (b >> 3) * 8192 + r * 128 + ((((b & 7) + (lane >> 4)) ^ (r & 7)) << 4);
        stmatrix_x4(a, pk[2 * b], pk[2 * b + 1], pk[2 * b + 2], pk[2 * b + 3]);
    }
}

__device__ __forceinline__ uint32_t hsub2_bf16(uint32_t a, uint32_t b) { uint32_t r; asm("sub.rn.bf16x2 %0, %1, %2;" : "=r"(r) : "r"(a), "r"(b)); return r; }

constexpr int KV_RAW = DM * 18 * 2;

__global__ void __launch_bounds__(P_THREADS, 1)
k_qkv(const __grid_constant__ CUtensorMap tmWq, const __grid_constant__ CUtensorMap tmQ, const __nv_bfloat16* __restrict__ x, const __nv_bfloat16* __restrict__ wk, const __nv_bfloat16* __restrict__ wv) {
    extern __shared__ __align__(1024) uint8_t smem[];
    const uint32_t sA = smem_u32(smem), sB = sA + P_A_BYTES, bars = sB + P_NST * P_B_STAGE;
    const uint32_t fullB = bars, emptyB = bars + 64, fullX = bars + 128, fullW = bars + 136, rawFree = bars + 144;
    const uint32_t sRaw = sB + 3 * P_B_STAGE;
    float* s_rstd = reinterpret_cast<float*>(smem + P_A_BYTES + P_NST * P_B_STAGE + 256);
    const int tid = threadIdx.x, warp = __shfl_sync(~0u, tid >> 5, 0), lane = tid & 31;
    const bool isQ = blockIdx.x < 96;
    const int m = isQ ? blockIdx.x / 3 : blockIdx.x - 96, cg = blockIdx.x % 3;
    if (tid == 0) TS(0, 0);
    if (warp == 8) {
        if (elect_one()) {
            prefetch_map(&tmWq); prefetch_map(&tmQ);
            for (int i = 0; i < P_NST; i++) { mbar_init(fullB + i * 8, 1); mbar_init(emptyB + i * 8, 8); }
            mbar_init(fullX, 1); mbar_init(fullW, 1); mbar_init(rawFree, 8);
            bar_init_fence();
            mbar_expect(fullX, P_A_BYTES);
            bulk_g2s(sRaw, x + (size_t)m * 64 * DM, P_A_BYTES, fullX);
            if (isQ) {
                for (int kb = 0; kb < 3; kb++) {
                    mbar_expect(fullB + kb * 8, P_B_STAGE);
                    for (int a = 0; a < 3; a++) tma_2d(sB + kb * P_B_STAGE + a * 8192, &tmWq, cg * 192 + a * 64, kb * 64, fullB + kb * 8);
                }
            } else {
                mbar_expect(fullW, 2 * KV_RAW);
                bulk_g2s(sA, wk, KV_RAW, fullW);
                bulk_g2s(sA + KV_RAW, wv, KV_RAW, fullW);
            }
        }
        __syncwarp();
    }
    __syncthreads();
    pdl_launch();
    if (warp == 8) {
        if (isQ && elect_one()) {
            mbar_wait(rawFree, 0);
            for (int kb = 3; kb < 9; kb++) {
                const int s = kb >= P_NST ? kb - P_NST : kb;
                if (kb >= P_NST) mbar_wait(emptyB + s * 8, 0);
                mbar_expect(fullB + s * 8, P_B_STAGE);
                for (int a = 0; a < 3; a++) tma_2d(sB + s * P_B_STAGE + a * 8192, &tmWq, cg * 192 + a * 64, kb * 64, fullB + s * 8);
            }
        }
        return;
    }
    {
        const int row = tid >> 2, q = tid & 3, odd = row & 1;
        mbar_wait(fullX, 0);
        if (tid == 0) TS(0, 6);
        uint4 v[18];
#pragma unroll
        for (int i = 0; i < 18; i++)
            asm volatile("ld.shared.v4.b32 {%0, %1, %2, %3}, [%4];" : "=r"(v[i].x), "=r"(v[i].y), "=r"(v[i].z), "=r"(v[i].w) : "r"(sRaw + row * 1152 + (q + 4 * (i ^ odd)) * 16));
        float sum = 0.f, sum2 = 0.f, sq = 0.f, sq2 = 0.f;
#pragma unroll
        for (int i = 0; i < 18; i++) {
            const uint32_t w[4] = {v[i].x, v[i].y, v[i].z, v[i].w};
#pragma unroll
            for (int j = 0; j < 4; j++) { const float a = bf_lo(w[j]), b = bf_hi(w[j]); sum += a; sum2 += b; sq = fmaf(a, a, sq); sq2 = fmaf(b, b, sq2); }
        }
        __syncwarp();
        if (lane == 0) mbar_arrive(rawFree);
        sum += sum2; sq += sq2;
        sum += __shfl_xor_sync(~0u, sum, 1); sum += __shfl_xor_sync(~0u, sum, 2);
        sq += __shfl_xor_sync(~0u, sq, 1); sq += __shfl_xor_sync(~0u, sq, 2);
        if (tid == 0) TS(0, 4);
        if (!isQ) {
            mbar_wait(fullW, 0);
            if (tid == 0) TS(0, 7);
            const uint32_t* raw = reinterpret_cast<const uint32_t*>(smem);
            uint32_t wr[41];
#pragma unroll
            for (int i = 0; i < 40; i++) wr[i] = raw[tid + i * 256];
            wr[40] = raw[(tid & 127) + 40 * 256];
            int k = tid / 9, r = tid - k * 9;
#pragma unroll
            for (int i = 0; i < 41; i++) {
                const int sel = k >= DM, kk = k - sel * DM;
                uint32_t* dst = reinterpret_cast<uint32_t*>(smem + P_A_BYTES + (sel * 3 + (r >> 2)) * 9216 + (kk >> 3) * 128 + (kk & 7) * 16 + (r & 3) * 4);
                if (i < 40 || tid < 128) *dst = wr[i];
                k += 28; r += 4;
                if (r >= 9) { r -= 9; k++; }
            }
            named_sync(1, 256);
            if (tid == 0) TS(0, 8);
        }
        const float mean = sum * (1.0f / DM);
        if (q == 0) s_rstd[row] = rsqrtf(fmaxf(sq * (1.0f / DM) - mean * mean, 0.f) + LN_EPS);
        const uint32_t mhi = pack_bf16(mean, mean);
        const float rem = mean - bf_lo(mhi);
        const uint32_t mlo = pack_bf16(rem, rem);
#pragma unroll
        for (int i = 0; i < 18; i++) {
            const int c = q + 4 * (i ^ odd);
            const uint32_t o0 = hsub2_bf16(hsub2_bf16(v[i].x, mhi), mlo), o1 = hsub2_bf16(hsub2_bf16(v[i].y, mhi), mlo);
            const uint32_t o2 = hsub2_bf16(hsub2_bf16(v[i].z, mhi), mlo), o3 = hsub2_bf16(hsub2_bf16(v[i].w, mhi), mlo);
            asm volatile("st.shared.v4.b32 [%0], {%1, %2, %3, %4};" ::"r"(sA + (c >> 3) * 8192 + row * 128 + (((c & 7) ^ (row & 7)) << 4)), "r"(o0), "r"(o1), "r"(o2), "r"(o3) : "memory");
        }
    }
    proxy_fence();
    named_sync(1, 256);
    if (tid == 0) TS(0, 1);
    const int wg = warp >> 2, w = warp & 3, g = lane >> 2, t = lane & 3;
    const float rs0 = s_rstd[w * 16 + g], rs1 = s_rstd[w * 16 + g + 8];
    if (isQ) {
        const float c0 = rs0 * Q_SCALE, c1 = rs1 * Q_SCALE;
        if (wg == 0) {
            float acc[64];
            proj_mma<128, false>(acc, sA, sB, 0, fullB, emptyB, 0, lane);
            if (tid == 0) TS(0, 2);
            named_sync(1, 256);
            uint32_t pk[32];
#pragma unroll
            for (int i = 0; i < 16; i++) { pk[2 * i] = pack_bf16(acc[4 * i] * c0, acc[4 * i + 1] * c0); pk[2 * i + 1] = pack_bf16(acc[4 * i + 2] * c1, acc[4 * i + 3] * c1); }
            stage_tile<16>(pk, sA, w, lane);
        } else {
            float acc[32];
            proj_mma<64, false>(acc, sA, sB, 2 * 8192, fullB, emptyB, 0, lane);
            named_sync(1, 256);
            uint32_t pk[16];
#pragma unroll
            for (int i = 0; i < 8; i++) { pk[2 * i] = pack_bf16(acc[4 * i] * c0, acc[4 * i + 1] * c0); pk[2 * i + 1] = pack_bf16(acc[4 * i + 2] * c1, acc[4 * i + 3] * c1); }
            stage_tile<8>(pk, sA + 2 * 8192, w, lane);
        }
        proxy_fence();
        named_sync(1, 256);
        if (warp == 0 && elect_one()) {
            for (int a = 0; a < 3; a++) tma_st_2d(&tmQ, cg * 192 + a * 64, m * 64, sA + a * 8192);
            bulk_commit();
            bulk_wait_all();
        }
    } else {
        float acc[12];
        const uint32_t blo = desc_lo(sB + wg * 3 * 9216, 128);
#pragma unroll
        for (int i = 0; i < 12; i++) acc[i] = 0.f;
        pin(acc);
        wg_fence();
#pragma unroll 1
        for (int kb = 0; kb < 9; kb++) {
            const uint32_t alo = desc_lo(sA + kb * 8192, 16);
#pragma unroll
            for (int ks = 0; ks < 4; ks++)
                wgmma_ss_n24<1>(acc, desc64(alo + ks * 2, HI_SW128), desc64(blo + (kb * 4 + ks) * 16, desc_hi(9216, 0)), 1);
        }
        wg_commit();
        wg_wait<0>();
        pin(acc);
        uint32_t pk[6];
#pragma unroll
        for (int b = 0; b < 3; b++) { pk[2 * b] = pack_bf16(acc[4 * b] * rs0, acc[4 * b + 1] * rs0); pk[2 * b + 1] = pack_bf16(acc[4 * b + 2] * rs1, acc[4 * b + 3] * rs1); }
        float n0 = 0.f, n1 = 0.f, vm = 0.f;
#pragma unroll
        for (int b = 0; b < 3; b++) {
            if (b < 2 || t == 0) {
                const float a = bf_lo(pk[2 * b]), c = bf_hi(pk[2 * b]), d = bf_lo(pk[2 * b + 1]), e = bf_hi(pk[2 * b + 1]);
                n0 = fmaf(a, a, fmaf(c, c, n0)); n1 = fmaf(d, d, fmaf(e, e, n1));
            }
        }
        n0 += __shfl_xor_sync(~0u, n0, 1); n0 += __shfl_xor_sync(~0u, n0, 2);
        n1 += __shfl_xor_sync(~0u, n1, 1); n1 += __shfl_xor_sync(~0u, n1, 2);
        vm = fmaxf(n0, n1);
        if (!(n0 == n0) || !(n1 == n1)) vm = __int_as_float(0x7F800000);
#pragma unroll
        for (int o = 4; o < 32; o <<= 1) vm = fmaxf(vm, __shfl_xor_sync(~0u, vm, o));
        if (t != 0) {
            uint32_t lo, hi;
            if (wg == 0) {
                const int grp = m * 8 + w * 2;
                const uint32_t c = t == 1 ? 0x42FE3F80u   : (t == 2 ? 0x00003BC0u   : 0u);
                lo = ((POLY_MASK >> (grp & 15)) & 1) ? c : 0u;
                hi = ((POLY_MASK >> ((grp + 1) & 15)) & 1) ? c : 0u;
            } else {
                lo = hi = t == 1 ? 0x00003F80u : 0u;
            }
            pk[4] = lo; pk[5] = hi;
        }
        uint32_t* dst = reinterpret_cast<uint32_t*>(wg == 0 ? g_kc : g_vc) + (m * 8 + w * 2) * 96 + g * 4 + t;
#pragma unroll
        for (int b = 0; b < 3; b++) { dst[b * 32] = pk[2 * b]; dst[96 + b * 32] = pk[2 * b + 1]; }
        float* red = s_rstd + 64;
        if (lane == 0) red[warp] = (wg == 0) ? vm : (vm <= 1e24f ? 0.f : __int_as_float(0x7F800000));
        named_sync(1, 256);
        if (tid == 0) {
            float mx = red[0];
#pragma unroll
            for (int i = 1; i < 8; i++) mx = fmaxf(mx, red[i]);
            g_kmax[m] = mx;
        }
    }
    if (tid == 0) TS(0, 3);
}

constexpr int A_THREADS = 512;
constexpr int A_NPIECE = 8;
constexpr int A_OFF_Q = 2 * KV_BYTES;
constexpr int A_OFF_BAR = A_OFF_Q + 4 * 4096;
constexpr int A_SMEM = A_OFF_BAR + 128;

__device__ __forceinline__ uint32_t exp2_pair_fixed(float lo, float hi) {
    const uint32_t G = __byte_perm(__float_as_uint(lo), __float_as_uint(hi), 0x5410);
    const uint32_t Hh = G & 0x007F007Fu;
    const uint32_t tt = hfma2(Hh, 0xF96BF96Bu, 0x358C358Cu);
    return G - hfma2(tt, Hh, 0u);
}

__device__ __forceinline__ void attn_side_job(const __nv_bfloat16* __restrict__ w1, const __nv_bfloat16* __restrict__ w2, const __nv_bfloat16* __restrict__ wo) {
    const int e = blockIdx.x - 128, tid = threadIdx.x;
    if (tid < 32) {
        const char* p = reinterpret_cast<const char*>(wo) + e * (DM * DM * 2 / 4);
        for (int i = tid; i < DM * DM * 2 / 4 / 4608; i += 32) prefetch_l2(p + i * 4608, 4608);
        p = reinterpret_cast<const char*>(w1) + (size_t)e * (FF * DM * 2 / 4);
        for (int i = tid; i < FF * DM * 2 / 4 / 9216; i += 32) prefetch_l2(p + (size_t)i * 9216, 9216);
        p = reinterpret_cast<const char*>(w2) + (size_t)e * (FF * DM * 2 / 4);
        for (int i = tid; i < FF * DM * 2 / 4 / 9216; i += 32) prefetch_l2(p + (size_t)i * 9216, 9216);
    }
}

__global__ void __launch_bounds__(A_THREADS, 1)
k_attn(const __nv_bfloat16* __restrict__ w1, const __nv_bfloat16* __restrict__ w2, const __nv_bfloat16* __restrict__ wo) {
    extern __shared__ __align__(1024) uint8_t smem[];
    pdl_launch();
    if (blockIdx.x >= 128) { attn_side_job(w1, w2, wo); return; }
    const uint32_t sK = smem_u32(smem), sV = sK + KV_BYTES, bars = sK + A_OFF_BAR;
    const int tid = threadIdx.x;
    check_smem_base(sK);
    if (tid == 0) TS(1, 0);
    if (tid == 0) {
        for (int i = 0; i < A_NPIECE; i++) mbar_init(bars + i * 8, 1);
        bar_init_fence();
    }
    __syncthreads();
    pdl_wait();
    if (tid == 0) TS(1, 1);
    const int wg = __shfl_sync(~0u, tid >> 7, 0), w = (tid >> 5) & 3, lane = tid & 31, g = lane >> 2, t = lane & 3;
    const uint32_t* q32 = reinterpret_cast<const uint32_t*>(g_q);
    int row = (blockIdx.x * 8 + wg) * 64 + w * 16 + g;
    uint32_t nq[6];
    nq[0] = q32[row * 9 + t]; nq[1] = q32[(row + 8) * 9 + t]; nq[2] = q32[row * 9 + 4 + t]; nq[3] = q32[(row + 8) * 9 + 4 + t];
    nq[4] = q32[row * 9 + 8]; nq[5] = q32[(row + 8) * 9 + 8];
    constexpr int PB = KV_BYTES / A_NPIECE;
    const float kmax_raw = g_kmax[lane];
    if (tid < 32 && elect_one()) {
        for (int i = 0; i < 2; i++) {
            mbar_expect(bars + i * 8, 2 * PB);
            bulk_g2s(sK + i * PB, reinterpret_cast<const char*>(g_kc) + i * PB, PB, bars + i * 8);
            bulk_g2s(sV + i * PB, reinterpret_cast<const char*>(g_vc) + i * PB, PB, bars + i * 8);
        }
    }
    float kmax2 = kmax_raw;
#pragma unroll
    for (int o = 1; o < 32; o <<= 1) kmax2 = fmaxf(kmax2, __shfl_xor_sync(~0u, kmax2, o));
    if (tid < 32 && elect_one()) {
        for (int i = 2; i < A_NPIECE; i++) {
            mbar_expect(bars + i * 8, 2 * PB);
            bulk_g2s(sK + i * PB, reinterpret_cast<const char*>(g_kc) + i * PB, PB, bars + i * 8);
            bulk_g2s(sV + i * PB, reinterpret_cast<const char*>(g_vc) + i * PB, PB, bars + i * 8);
        }
    }
    const uint32_t sQ = sK + A_OFF_Q + wg * 4096 + (w * 2) * 512 + g * 16 + t * 4;
    const uint64_t dQ0 = cdesc(A_OFF_Q, 128, 512, 0) + wg * 256, dQ1 = dQ0 + 16;
#pragma unroll 1
    for (int rep = 0; rep < 2; rep++, row += 256) {
        const uint32_t qa[4] = {nq[0], nq[1], nq[2], nq[3]};
        float n0, n1;
        {
            const float a0 = bf_lo(qa[0]), a1 = bf_hi(qa[0]), a2 = bf_lo(qa[2]), a3 = bf_hi(qa[2]);
            const float b0 = bf_lo(qa[1]), b1 = bf_hi(qa[1]), b2 = bf_lo(qa[3]), b3 = bf_hi(qa[3]);
            n0 = a0 * a0 + a1 * a1 + a2 * a2 + a3 * a3; n1 = b0 * b0 + b1 * b1 + b2 * b2 + b3 * b3;
            if (t == 0) {
                const float c0 = bf_lo(nq[4]), c1 = bf_hi(nq[4]), d0 = bf_lo(nq[5]), d1 = bf_hi(nq[5]);
                n0 += c0 * c0 + c1 * c1; n1 += d0 * d0 + d1 * d1;
            }
            n0 += __shfl_xor_sync(~0u, n0, 1); n0 += __shfl_xor_sync(~0u, n0, 2);
            n1 += __shfl_xor_sync(~0u, n1, 1); n1 += __shfl_xor_sync(~0u, n1, 2);
        }
        const uint32_t x0 = nq[4], x1 = nq[5];
        if (rep == 0) {
            const int nr = row + 256;
            nq[0] = q32[nr * 9 + t]; nq[1] = q32[(nr + 8) * 9 + t]; nq[2] = q32[nr * 9 + 4 + t]; nq[3] = q32[(nr + 8) * 9 + 4 + t];
            nq[4] = q32[nr * 9 + 8]; nq[5] = q32[(nr + 8) * 9 + 8];
        }
        if (tid == 0 && rep == 0) TS(1, 7);
        const bool unsafe = !(fmaxf(n0, n1) * kmax2 <= FAST_BOUND * FAST_BOUND) || !(n0 == n0) || !(n1 == n1);
        uint32_t any_unsafe;
        asm volatile("{\n.reg .pred p, q;\nsetp.ne.u32 p, %1, 0;\nbar.red.or.pred q, %2, 128, p;\nselp.u32 %0, 1, 0, q;\n}\n" : "=r"(any_unsafe) : "r"((uint32_t)unsafe), "r"(wg + 1) : "memory");
        any_unsafe = __shfl_sync(~0u, any_unsafe, 0);
        {
            const uint32_t cst = any_unsafe ? 0u : (t == 1 ? 0x3F804780u : (t == 2 ? 0x00003F80u : 0u));
            asm volatile("st.shared.b32 [%0], %1;" ::"r"(sQ), "r"(qa[0]) : "memory");
            asm volatile("st.shared.b32 [%0], %1;" ::"r"(sQ + 512), "r"(qa[1]) : "memory");
            asm volatile("st.shared.b32 [%0], %1;" ::"r"(sQ + 128), "r"(qa[2]) : "memory");
            asm volatile("st.shared.b32 [%0], %1;" ::"r"(sQ + 640), "r"(qa[3]) : "memory");
            asm volatile("st.shared.b32 [%0], %1;" ::"r"(sQ + 256), "r"(t == 0 ? x0 : cst) : "memory");
            asm volatile("st.shared.b32 [%0], %1;" ::"r"(sQ + 768), "r"(t == 0 ? x1 : cst) : "memory");
            asm volatile("st.shared.b32 [%0], %1;" ::"r"(sQ + 384), "r"(0u) : "memory");
            asm volatile("st.shared.b32 [%0], %1;" ::"r"(sQ + 896), "r"(0u) : "memory");
            proxy_fence();
            named_sync(wg + 1, 128);
        }
        if (tid == 0) TS(1, 2 + rep * 2);
        float o[12];
#pragma unroll
        for (int i = 0; i < 12; i++) o[i] = 0.f;
        pin(o);
        uint64_t dK0 = cdesc(0, 128, 384, 0), dK1 = cdesc(256, 0, 384, 0), dV = cdesc(KV_BYTES, 384, 128, 0);
        if (!any_unsafe) {
            float s[64];
#pragma unroll 1
            for (int j = 0; j < 16; j++) {
                if (rep == 0 && (j & 1) == 0) mbar_wait(bars + (j >> 1) * 8, 0);
                wg_fence();
                wgmma_ss_n128<0>(s, dQ0, dK0, 0);
                wgmma_ss_n128<0>(s, dQ1, dK1, 1);
                wg_commit();
                dK0 += 16 * 384 >> 4; dK1 += 16 * 384 >> 4;
                wg_wait<0>();
                pin(s);
                uint32_t p[32];
#pragma unroll
                for (int i = 0; i < 32; i++) {
                    if ((POLY_MASK >> (i >> 1)) & 1) p[i] = exp2_pair_fixed(s[2 * i], s[2 * i + 1]);
                    else p[i] = pack_bf16(ex2(s[2 * i]), ex2(s[2 * i + 1]));
                }
                pin(p);
                wg_fence();
#pragma unroll
                for (int k = 0; k < 8; k++) wgmma_rs_n24<1>(o, p[4 * k], p[4 * k + 1], p[4 * k + 2], p[4 * k + 3], dV + k * 48, 1);
                wg_commit();
                dV += 16 * 384 >> 4;
                wg_wait<0>();
            }
        } else {
            float s[64];
            float m0 = -INFINITY, m1 = -INFINITY;
#pragma unroll 1
            for (int j = 0; j < 16; j++) {
                if (rep == 0 && (j & 1) == 0) mbar_wait(bars + (j >> 1) * 8, 0);
                wg_fence();
                wgmma_ss_n128<0>(s, dQ0, dK0, 0);
                wgmma_ss_n128<0>(s, dQ1, dK1, 1);
                wg_commit();
                dK0 += 16 * 384 >> 4; dK1 += 16 * 384 >> 4;
                wg_wait<0>();
                pin(s);
                float x0m = m0, x1m = m1;
#pragma unroll
                for (int b = 0; b < 16; b++) { x0m = fmaxf(x0m, fmaxf(s[4 * b], s[4 * b + 1])); x1m = fmaxf(x1m, fmaxf(s[4 * b + 2], s[4 * b + 3])); }
                x0m = fmaxf(x0m, __shfl_xor_sync(~0u, x0m, 1)); x0m = fmaxf(x0m, __shfl_xor_sync(~0u, x0m, 2));
                x1m = fmaxf(x1m, __shfl_xor_sync(~0u, x1m, 1)); x1m = fmaxf(x1m, __shfl_xor_sync(~0u, x1m, 2));
                const float c0 = ex2(m0 - x0m), c1 = ex2(m1 - x1m);
                m0 = x0m; m1 = x1m;
#pragma unroll
                for (int b = 0; b < 3; b++) { o[4 * b] *= c0; o[4 * b + 1] *= c0; o[4 * b + 2] *= c1; o[4 * b + 3] *= c1; }
                uint32_t p[32];
#pragma unroll
                for (int b = 0; b < 16; b++) {
                    p[2 * b] = pack_bf16(ex2(s[4 * b] - m0), ex2(s[4 * b + 1] - m0));
                    p[2 * b + 1] = pack_bf16(ex2(s[4 * b + 2] - m1), ex2(s[4 * b + 3] - m1));
                }
                pin(p); pin(o);
                wg_fence();
#pragma unroll
                for (int k = 0; k < 8; k++) wgmma_rs_n24<1>(o, p[4 * k], p[4 * k + 1], p[4 * k + 2], p[4 * k + 3], dV + k * 48, 1);
                wg_commit();
                dV += 16 * 384 >> 4;
                wg_wait<0>();
            }
        }
        pin(o);
        if (tid == 0) TS(1, 3 + rep * 2);
        const float l0 = __shfl_sync(~0u, o[8], (lane & ~3) | 1), l1 = __shfl_sync(~0u, o[10], (lane & ~3) | 1);
        const float i0 = 1.0f / l0, i1 = 1.0f / l1;
        {
            const uint32_t so = sK + A_OFF_Q + wg * 4096 + (w * 16 + g) * 36 + t * 4;
            asm volatile("st.shared.b32 [%0], %1;" ::"r"(so), "r"(pack_bf16(o[0] * i0, o[1] * i0)) : "memory");
            asm volatile("st.shared.b32 [%0], %1;" ::"r"(so + 288), "r"(pack_bf16(o[2] * i1, o[3] * i1)) : "memory");
            asm volatile("st.shared.b32 [%0], %1;" ::"r"(so + 16), "r"(pack_bf16(o[4] * i0, o[5] * i0)) : "memory");
            asm volatile("st.shared.b32 [%0], %1;" ::"r"(so + 304), "r"(pack_bf16(o[6] * i1, o[7] * i1)) : "memory");
            if (t == 0) {
                asm volatile("st.shared.b32 [%0], %1;" ::"r"(so + 32), "r"(pack_bf16(o[8] * i0, o[9] * i0)) : "memory");
                asm volatile("st.shared.b32 [%0], %1;" ::"r"(so + 320), "r"(pack_bf16(o[10] * i1, o[11] * i1)) : "memory");
            }
            proxy_fence();
            named_sync(wg + 1, 128);
            if (__shfl_sync(~0u, w, 0) == 0 && elect_one()) {
                asm volatile("cp.async.bulk.global.shared::cta.bulk_group [%0], [%1], %2;" ::"l"(reinterpret_cast<char*>(g_o) + (size_t)(row - g) * 36), "r"(sK + A_OFF_Q + wg * 4096), "n"(2304) : "memory");
                bulk_commit();
                bulk_wait_all();
            }
            __syncwarp();
        }
    }
    if (tid == 0) TS(1, 6);
    if ((tid & 127) == 0) TS(1, 10 + wg);
}

constexpr int O_THREADS = 416;
constexpr int O_OFF_STAT = P_A_BYTES + P_NST * P_B_STAGE + 256;
constexpr int O_SMEM = O_OFF_STAT + 9 * 64 * 8;

__global__ void __cluster_dims__(3, 1, 1) __launch_bounds__(O_THREADS, 1)
k_oproj(const __grid_constant__ CUtensorMap tmO, const __grid_constant__ CUtensorMap tmWo, const __grid_constant__ CUtensorMap tmX2, const __grid_constant__ CUtensorMap tmOut, const __nv_bfloat16* __restrict__ x) {
    extern __shared__ __align__(1024) uint8_t smem[];
    const uint32_t sA = smem_u32(smem), sB = sA + P_A_BYTES, bars = sB + P_NST * P_B_STAGE;
    const uint32_t fullB = bars, emptyB = bars + 64, fullA = bars + 128;
    const int tid = threadIdx.x, warp = __shfl_sync(~0u, tid >> 5, 0), lane = tid & 31;
    const int m = blockIdx.x / 3, cg = blockIdx.x % 3;
    if (tid == 0) TS(2, 0);
    check_smem_base(sA);
    if (tid == 0) {
        prefetch_map(&tmO); prefetch_map(&tmWo); prefetch_map(&tmX2); prefetch_map(&tmOut);
        for (int i = 0; i < P_NST; i++) { mbar_init(fullB + i * 8, 1); mbar_init(emptyB + i * 8, 12); }
        for (int i = 0; i < 9; i++) mbar_init(fullA + i * 8, 1);
        bar_init_fence();
        for (int kb = 0; kb < 9; kb++) mbar_expect(fullA + kb * 8, 8192);
    }
    cluster_arrive();
    cluster_wait();
    pdl_launch();
    if (warp == 12) {
        if (elect_one()) {
            for (int kb = 0; kb < 9; kb++) {
                const int s = kb >= P_NST ? kb - P_NST : kb;
                if (kb == 2) {
                    pdl_wait();
                    TS(2, 1);
                    for (int ka = cg; ka < 9; ka += 3) tma_2d_mc(sA + ka * 8192, &tmO, ka * 64, m * 64, fullA + ka * 8, (uint16_t)7);
                }
                if (kb >= P_NST) mbar_wait(emptyB + s * 8, 0);
                mbar_expect(fullB + s * 8, P_B_STAGE);
                for (int a = 0; a < 3; a++) tma_2d(sB + s * P_B_STAGE + a * 8192, &tmWo, cg * 192 + a * 64, kb * 64, fullB + s * 8);
            }
        }
        return;
    }
    if (tid == 0) TS(2, 11);
    const int wg = warp >> 2, w = warp & 3, g = lane >> 2, t = lane & 3;
    uint32_t xr[16];
    {
        const uint32_t* x32 = reinterpret_cast<const uint32_t*>(x) + (((m * 64 + w * 16 + g) * DM + cg * 192 + wg * 64 + 2 * t) >> 1);
#pragma unroll
        for (int b = 0; b < 8; b++) { xr[2 * b] = __ldg(x32 + b * 4); xr[2 * b + 1] = __ldg(x32 + b * 4 + 4 * DM); }
    }
    float acc[32];
    {
        const uint64_t dA = cdesc(0, 16, 1024, 1), dB = cdesc(P_A_BYTES, 8192, 1024, 1) + wg * 512;
#pragma unroll 1
        for (int kb = 0; kb < 9; kb++) {
            const int s = kb >= P_NST ? kb - P_NST : kb;
            mbar_wait(fullA + kb * 8, 0);
            mbar_wait(fullB + s * 8, kb >= P_NST ? 1 : 0);
            wg_fence();
#pragma unroll
            for (int ks = 0; ks < 4; ks++) wgmma_ss_n64<1>(acc, dA + (kb * 512 + ks * 2), dB + (s * (P_B_STAGE >> 4) + ks * 128), (kb | ks) != 0);
            wg_commit();
            if (kb < 4) {
                wg_wait<1>();
                if (kb >= 1 && lane == 0) mbar_arrive(emptyB + (kb - 1) * 8);
            }
        }
        wg_wait<0>();
        pin(acc);
    }
    if (tid == 0) TS(2, 2);
    named_sync(1, 384);
    float s0 = 0.f, q0 = 0.f, s1 = 0.f, q1 = 0.f;
#pragma unroll
    for (int b = 0; b < 8; b++) {
        const uint32_t xa = xr[2 * b], xb = xr[2 * b + 1];
        const uint32_t ha = pack_bf16(acc[4 * b] + bf_lo(xa), acc[4 * b + 1] + bf_hi(xa));
        const uint32_t hb = pack_bf16(acc[4 * b + 2] + bf_lo(xb), acc[4 * b + 3] + bf_hi(xb));
        xr[2 * b] = ha; xr[2 * b + 1] = hb;
        const float a = bf_lo(ha), c = bf_hi(ha), d = bf_lo(hb), e = bf_hi(hb);
        s0 += a + c; q0 = fmaf(a, a, fmaf(c, c, q0));
        s1 += d + e; q1 = fmaf(d, d, fmaf(e, e, q1));
    }
    s0 += __shfl_xor_sync(~0u, s0, 1); s0 += __shfl_xor_sync(~0u, s0, 2);
    q0 += __shfl_xor_sync(~0u, q0, 1); q0 += __shfl_xor_sync(~0u, q0, 2);
    s1 += __shfl_xor_sync(~0u, s1, 1); s1 += __shfl_xor_sync(~0u, s1, 2);
    q1 += __shfl_xor_sync(~0u, q1, 1); q1 += __shfl_xor_sync(~0u, q1, 2);
    const int r = w * 16 + g;
    const uint32_t sStat = sA + O_OFF_STAT;
    if (t < 3) {
        uint32_t dst;
        asm("mapa.shared::cluster.u32 %0, %1, %2;" : "=r"(dst) : "r"(sStat + ((cg * 3 + wg) * 64 + r) * 8), "r"(t));
        asm volatile("st.shared::cluster.v2.f32 [%0], {%1, %2};" ::"r"(dst), "f"(s0), "f"(q0) : "memory");
        asm volatile("st.shared::cluster.v2.f32 [%0], {%1, %2};" ::"r"(dst + 64), "f"(s1), "f"(q1) : "memory");
    }
    if (tid == 0) TS(2, 4);
    cluster_arrive();
    stage_tile<8>(xr, sA + wg * 8192, w, lane);
    proxy_fence();
    named_sync(2 + wg, 128);
    const bool leader = w == 0 && elect_one();
    if (leader) { tma_st_2d(&tmOut, cg * 192 + wg * 64, m * 64, sA + wg * 8192); bulk_commit(); }
    cluster_wait();
    if (tid == 0) TS(2, 5);
    s0 = q0 = s1 = q1 = 0.f;
#pragma unroll
    for (int p = 0; p < 9; p++) {
        float a, b, c, d;
        asm volatile("ld.shared.v2.f32 {%0, %1}, [%2];" : "=f"(a), "=f"(b) : "r"(sStat + (p * 64 + r) * 8));
        asm volatile("ld.shared.v2.f32 {%0, %1}, [%2];" : "=f"(c), "=f"(d) : "r"(sStat + (p * 64 + r + 8) * 8));
        s0 += a; q0 += b; s1 += c; q1 += d;
    }
    const float m0 = s0 * (1.0f / DM), m1 = s1 * (1.0f / DM);
    const float rs0 = rsqrtf(fmaxf(q0 * (1.0f / DM) - m0 * m0, 0.f) + LN_EPS), rs1 = rsqrtf(fmaxf(q1 * (1.0f / DM) - m1 * m1, 0.f) + LN_EPS);
    const float sc0 = -LOG2E * rs0, sc1 = -LOG2E * rs1, n0 = -m0 * sc0, n1 = -m1 * sc1;
#pragma unroll
    for (int b = 0; b < 8; b++) {
        xr[2 * b] = pack_bf16(fmaf(bf_lo(xr[2 * b]), sc0, n0), fmaf(bf_hi(xr[2 * b]), sc0, n0));
        xr[2 * b + 1] = pack_bf16(fmaf(bf_lo(xr[2 * b + 1]), sc1, n1), fmaf(bf_hi(xr[2 * b + 1]), sc1, n1));
    }
    stage_tile<8>(xr, sA + (3 + wg) * 8192, w, lane);
    proxy_fence();
    named_sync(2 + wg, 128);
    if (tid == 0) TS(2, 6);
    if (leader) {
        tma_st_2d(&tmX2, cg * 192 + wg * 64, m * 64, sA + (3 + wg) * 8192);
        bulk_commit();
        bulk_wait_all();
    }
    if (tid == 0) TS(2, 3);
}

constexpr int F_THREADS = 384;
constexpr int F_NST = 6;
constexpr int F_STAGE = 96 * 128;
constexpr int F_X_BYTES = 9 * 16384;
constexpr int F_OFF_ST = F_X_BYTES;
constexpr int F_OFF_BAR = F_OFF_ST + F_NST * F_STAGE;
constexpr int F_SMEM = F_OFF_BAR + 256;

__device__ __forceinline__ float after_issue(float v, uint32_t tick) {
    uint32_t r;
    asm("lop3.b32 %0, %1, %1, %2, 0xF0;" : "=r"(r) : "r"(__float_as_uint(v)), "r"(tick));
    return __uint_as_float(r);
}
__device__ __forceinline__ uint32_t read_tick() { uint32_t c; asm volatile("mov.u32 %0, %%clock;" : "=r"(c)::"memory"); return c; }
__device__ __forceinline__ void silu_s1(const float (&acc)[32], float (&tmp)[8], int piece) {
#pragma unroll
    for (int i = 0; i < 8; i++) tmp[i] = ex2(acc[8 * piece + i]);
}
__device__ __forceinline__ void silu_s2(float (&tmp)[8], uint32_t tick) {
    const float one = after_issue(1.0f, tick);
#pragma unroll
    for (int i = 0; i < 8; i++) tmp[i] = rcp(tmp[i] + one);
}
template <int C>
__device__ __forceinline__ void silu_s3(const float (&acc)[32], const float (&tmp)[8], uint32_t (&h1)[144], int piece) {
#pragma unroll
    for (int i = 0; i < 4; i++) h1[C * 16 + 4 * piece + i] = pack_bf16(acc[8 * piece + 2 * i] * tmp[2 * i], acc[8 * piece + 2 * i + 1] * tmp[2 * i + 1]);
}

struct FfnPipe {
    uint32_t full, empty;
    int lane;
    __device__ __forceinline__ void acquire(int s, uint32_t ph) const { mbar_wait(full + s * 8, ph); }
    __device__ __forceinline__ void release(int s) const { if (lane == 0) mbar_arrive(empty + s * 8); }
};

template <int C>
__device__ __forceinline__ void ffn_phase1_chunk(float (&cur)[32], float (&prev)[32], uint32_t (&h1)[144], const FfnPipe& pp, uint64_t dx, uint32_t fullX) {
    float tmp[2][8];
    const uint64_t dw = cdesc(F_OFF_ST, 8192, 1024, 1) + blockIdx.y * (C + 1);
    dx += blockIdx.y * C;
#pragma unroll
    for (int j = 0; j < 6; j++) {
        if (C == 0) { mbar_wait(fullX + ((6 * j) >> 2) * 8, 0); mbar_wait(fullX + ((6 * j + 5) >> 2) * 8, 0); }
        pp.acquire(j, C & 1);
        if (j == 0) pin(cur);
        wg_fence();
#pragma unroll
        for (int i = 0; i < 6; i++) {
            const int ks = 6 * j + i;
            wgmma_ss_n64<1>(cur, dx + ((ks >> 2) * 1024 + (ks & 3) * 2), dw + ((j * F_STAGE + i * 2048) >> 4), ks != 0);
        }
        wg_commit();
        if (C > 0 || j > 0) { wg_wait<1>(); pp.release((j + 5) % 6); }
        if (C > 0) {
            pin(prev);
            if (j >= 1) { pin(tmp[0]); if (j >= 2) pin(tmp[1]); }
            if (j >= 2) silu_s3<(C > 0 ? C - 1 : 0)>(prev, tmp[j & 1], h1, j - 2);
            if (j >= 1 && j <= 4) { silu_s2(tmp[(j - 1) & 1], read_tick()); pin(tmp[(j - 1) & 1]); }
            if (j <= 3) { silu_s1(prev, tmp[j & 1], j); pin(tmp[j & 1]); }
            if (j >= 2) { asm volatile("" : "+r"(h1[(C - 1) * 16 + 4 * (j - 2)]), "+r"(h1[(C - 1) * 16 + 4 * (j - 2) + 1]), "+r"(h1[(C - 1) * 16 + 4 * (j - 2) + 2]), "+r"(h1[(C - 1) * 16 + 4 * (j - 2) + 3]) :: "memory"); }
        }
    }
}

__device__ __forceinline__ void ffn_store_chunk(const float (&acc)[32], const CUtensorMap* tmOut, uint32_t stg, int col, int row, int w, int lane, int wgid, bool leader) {
    uint32_t pk[16];
#pragma unroll
    for (int i = 0; i < 16; i++) pk[i] = pack_bf16(acc[2 * i] * -LN2, acc[2 * i + 1] * -LN2);
    stage_tile<8>(pk, stg, w, lane);
    proxy_fence();
    named_sync(2 + wgid, 128);
    if (leader) {
        tma_red_2d(tmOut, col, row, stg);
        bulk_commit();
    }
}

__device__ __forceinline__ void ffn_phase2_chunk(float (&cur)[32], float (&prev)[32], uint32_t (&h1)[144], const FfnPipe& pp, uint32_t ph, bool store_prev, const CUtensorMap* tmOut, uint32_t stg_prev, int col_prev, int row, int w, int lane, int wgid, bool leader) {
    const uint64_t dw = cdesc(F_OFF_ST, 8192, 1024, 1) + blockIdx.y * col_prev;
#pragma unroll
    for (int j = 0; j < 6; j++) {
        pp.acquire(j, ph);
        if (j == 0) pin(cur);
        wg_fence();
#pragma unroll
        for (int i = 0; i < 6; i++) {
            const int f = (6 * j + i) * 4;
            wgmma_rs_n64<1>(cur, h1[f], h1[f + 1], h1[f + 2], h1[f + 3], dw + ((j * F_STAGE + i * 2048) >> 4), (j | i) != 0);
        }
        wg_commit();
        if (j > 0 || store_prev) { wg_wait<1>(); pp.release((j + 5) % 6); }
        if (j == 0 && store_prev) { pin(prev); ffn_store_chunk(prev, tmOut, stg_prev, col_prev, row, w, lane, wgid, leader); }
    }
}

__global__ void __cluster_dims__(2, 1, 1) __launch_bounds__(F_THREADS, 1)
k_ffn(const __grid_constant__ CUtensorMap tmH, const __grid_constant__ CUtensorMap tmW1, const __grid_constant__ CUtensorMap tmW2, const __grid_constant__ CUtensorMap tmOut) {
    extern __shared__ __align__(1024) uint8_t smem[];
    const uint32_t sX = smem_u32(smem), sSt = sX + F_OFF_ST, bars = sX + F_OFF_BAR;
    const uint32_t full = bars, empty = bars + 64, fullX = bars + 128;
    const int tid = threadIdx.x, warp = __shfl_sync(~0u, tid >> 5, 0), lane = tid & 31;
    const int m = (blockIdx.x >> 1) & 15, fs = (blockIdx.x >> 5) * 2 + (blockIdx.x & 1);
    if (tid == 0) TS(3, 0);
    check_smem_base(sX);
    if (tid == 0) {
        prefetch_map(&tmW1); prefetch_map(&tmH); prefetch_map(&tmW2); prefetch_map(&tmOut);
        for (int i = 0; i < F_NST; i++) { mbar_init(full + i * 8, 1); mbar_init(empty + i * 8, 8); }
        for (int i = 0; i < 9; i++) mbar_init(fullX + i * 8, 1);
        bar_init_fence();
        for (int kb = 0; kb < 9; kb++) mbar_expect(fullX + kb * 8, 16384);
    }
    cluster_arrive();
    cluster_wait();
    if (warp < 4) {
        asm volatile("setmaxnreg.dec.sync.aligned.u32 24;");
        if (warp == 0 && elect_one()) {
            int s = 0; uint32_t ph = 1;
            int c = 0, j = 0;
#pragma unroll 1
            for (int i = 0; i < 108; i++) {
                if (i == 54) c = fs;
                mbar_wait(empty + s * 8, ph);
                mbar_expect(full + s * 8, F_STAGE);
                if (i < 54) tma_2d(sSt + s * F_STAGE, &tmW1, fs * 576 + c * 64, j * 96, full + s * 8);
                else tma_2d(sSt + s * F_STAGE, &tmW2, c * 64, fs * 576 + j * 96, full + s * 8);
                if (++j == 6) { j = 0; if (++c == 9) c = 0; }
                if (++s == F_NST) { s = 0; ph ^= 1; }
            }
        }
    } else {
        asm volatile("setmaxnreg.inc.sync.aligned.u32 240;");
        const int wgid = (warp >> 2) - 1, w = warp & 3;
        pdl_wait();
        if (tid == 128) TS(3, 1);
        if (warp == 4 && elect_one()) {
            const int half = blockIdx.x & 1;
            for (int kb = 0; kb < 9; kb++) tma_2d_mc(sX + kb * 16384 + half * 8192, &tmH, kb * 64, m * 128 + half * 64, fullX + kb * 8, (uint16_t)3);
        }
        __syncwarp();
        FfnPipe pp{full, empty, lane};
        const uint64_t xlo = cdesc(0, 16, 1024, 1) + wgid * 512;
        uint32_t h1[144];
        float acc0[32], acc1[32];
        ffn_phase1_chunk<0>(acc0, acc1, h1, pp, xlo, fullX);
        if (tid == 128) TS(3, 2);
        ffn_phase1_chunk<1>(acc1, acc0, h1, pp, xlo, fullX);
        ffn_phase1_chunk<2>(acc0, acc1, h1, pp, xlo, fullX);
        ffn_phase1_chunk<3>(acc1, acc0, h1, pp, xlo, fullX);
        ffn_phase1_chunk<4>(acc0, acc1, h1, pp, xlo, fullX);
        ffn_phase1_chunk<5>(acc1, acc0, h1, pp, xlo, fullX);
        ffn_phase1_chunk<6>(acc0, acc1, h1, pp, xlo, fullX);
        ffn_phase1_chunk<7>(acc1, acc0, h1, pp, xlo, fullX);
        ffn_phase1_chunk<8>(acc0, acc1, h1, pp, xlo, fullX);
        wg_wait<0>();
        pp.release(5);
        pin(acc0);
        {
            float tmp[4][8];
#pragma unroll
            for (int p = 0; p < 4; p++) silu_s1(acc0, tmp[p], p);
#pragma unroll
            for (int p = 0; p < 4; p++) silu_s2(tmp[p], 0);
#pragma unroll
            for (int p = 0; p < 4; p++) silu_s3<8>(acc0, tmp[p], h1, p);
        }
        pin(h1);
        if (tid == 128) TS(3, 3);
        const int row = m * 128 + wgid * 64;
        const uint32_t stg = sX + wgid * 8192;
        int c = fs, cprev = 0;
        const bool leader = w == 0 && elect_one();
#pragma unroll 1
        for (int j = 0; j < 8; j += 2) {
            ffn_phase2_chunk(acc1, acc0, h1, pp, 1, j > 0, &tmOut, stg + (j - 1) * 16384, cprev * 64, row, w, lane, wgid, leader);
            cprev = c; if (++c == 9) c = 0;
            ffn_phase2_chunk(acc0, acc1, h1, pp, 0, true, &tmOut, stg + j * 16384, cprev * 64, row, w, lane, wgid, leader);
            cprev = c; if (++c == 9) c = 0;
        }
        ffn_phase2_chunk(acc1, acc0, h1, pp, 1, true, &tmOut, stg + 7 * 16384, cprev * 64, row, w, lane, wgid, leader);
        wg_wait<0>();
        pin(acc1);
        ffn_store_chunk(acc1, &tmOut, stg + 8 * 16384, c * 64, row, w, lane, wgid, leader);
        if (tid == 128) TS(3, 4);
        if (leader) bulk_wait_all();
        if (tid == 128) TS(3, 5);
    }
}

typedef CUresult (*EncodeFn)(CUtensorMap*, CUtensorMapDataType, cuuint32_t, void*, const cuuint64_t*, const cuuint64_t*, const cuuint32_t*, const cuuint32_t*,
                             CUtensorMapInterleave, CUtensorMapSwizzle, CUtensorMapL2promotion, CUtensorMapFloatOOBfill);

CUtensorMap make_map(EncodeFn enc, const void* base, int rows, int cols, int box_rows) {
    CUtensorMap tm;
    cuuint64_t dims[2] = {(cuuint64_t)cols, (cuuint64_t)rows};
    cuuint64_t strides[1] = {(cuuint64_t)cols * 2};
    cuuint32_t box[2] = {64, (cuuint32_t)box_rows};
    cuuint32_t es[2] = {1, 1};
    enc(&tm, CU_TENSOR_MAP_DATA_TYPE_BFLOAT16, 2, const_cast<void*>(base), dims, strides, box, es, CU_TENSOR_MAP_INTERLEAVE_NONE,
        CU_TENSOR_MAP_SWIZZLE_128B, CU_TENSOR_MAP_L2_PROMOTION_L2_256B, CU_TENSOR_MAP_FLOAT_OOB_FILL_NONE);
    return tm;
}

template <typename... KArgs, typename... Args>
void launch(void (*kern)(KArgs...), int grid, int block, int smem, bool pdl, Args... args) {
    cudaLaunchConfig_t cfg = {};
    cfg.gridDim = dim3(grid); cfg.blockDim = dim3(block); cfg.dynamicSmemBytes = smem; cfg.stream = cudaStreamPerThread;
    cudaLaunchAttribute at[1];
    at[0].id = cudaLaunchAttributeProgrammaticStreamSerialization;
    at[0].val.programmaticStreamSerializationAllowed = 1;
    cfg.attrs = at; cfg.numAttrs = pdl ? 1 : 0;
    cudaLaunchKernelEx(&cfg, kern, KArgs(args)...);
}

}

#define USE_PDL 1

extern "C" void kernel_launch(void* const* d_in, const int* in_sizes, int n_in, void* d_out, int out_size) {
    const __nv_bfloat16* x = (const __nv_bfloat16*)d_in[0];
    const __nv_bfloat16* wq = (const __nv_bfloat16*)d_in[1];
    const __nv_bfloat16* wk = (const __nv_bfloat16*)d_in[2];
    const __nv_bfloat16* wv = (const __nv_bfloat16*)d_in[3];
    const __nv_bfloat16* wo = (const __nv_bfloat16*)d_in[4];
    const __nv_bfloat16* w1 = (const __nv_bfloat16*)d_in[6];
    const __nv_bfloat16* w2 = (const __nv_bfloat16*)d_in[7];
    __nv_bfloat16* out = (__nv_bfloat16*)d_out;

    static EncodeFn enc = nullptr;
    static void *p_o = nullptr, *p_h = nullptr, *p_q = nullptr;
    if (!enc) {
        cudaDriverEntryPointQueryResult qr;
        cudaGetDriverEntryPoint("cuTensorMapEncodeTiled", (void**)&enc, cudaEnableDefault, &qr);
        cudaGetSymbolAddress(&p_o, g_o);
        cudaGetSymbolAddress(&p_h, g_x2);
        cudaGetSymbolAddress(&p_q, g_q);
        cudaFuncSetAttribute(k_qkv, cudaFuncAttributeMaxDynamicSharedMemorySize, P_SMEM);
        cudaFuncSetAttribute(k_attn, cudaFuncAttributeMaxDynamicSharedMemorySize, A_SMEM);
        cudaFuncSetAttribute(k_oproj, cudaFuncAttributeMaxDynamicSharedMemorySize, O_SMEM);
        cudaFuncSetAttribute(k_ffn, cudaFuncAttributeMaxDynamicSharedMemorySize, F_SMEM);
    }
    const CUtensorMap tmWq = make_map(enc, wq, DM, DM, 64);
    const CUtensorMap tmWo = make_map(enc, wo, DM, DM, 64);
    const CUtensorMap tmO = make_map(enc, p_o, SEQ, DM, 64);
    const CUtensorMap tmH64 = make_map(enc, p_h, SEQ, DM, 64);
    const CUtensorMap tmQ = make_map(enc, p_q, SEQ, DM, 64);
    const CUtensorMap tmW1 = make_map(enc, w1, DM, FF, 96);
    const CUtensorMap tmW2 = make_map(enc, w2, FF, DM, 96);
    const CUtensorMap tmOut = make_map(enc, out, SEQ, DM, 64);

    launch(k_qkv, 128, P_THREADS, P_SMEM, false, tmWq, tmQ, x, wk, wv);
    launch(k_attn, 132, A_THREADS, A_SMEM, USE_PDL, w1, w2, wo);
    launch(k_oproj, 96, O_THREADS, O_SMEM, USE_PDL, tmO, tmWo, tmH64, tmOut, x);
    launch(k_ffn, 128, F_THREADS, F_SMEM, USE_PDL, tmH64, tmW1, tmW2, tmOut);
}
```

```cpp
#include <cuda_runtime.h>
#include <cuda_bf16.h>
#include <cuda.h>
#include <stdint.h>

namespace {

constexpr int SEQ = 2048, DM = 576, FF = 4608;
constexpr int KV_BYTES = SEQ * 48;
constexpr float LN_EPS = 1e-5f;
constexpr float LOG2E = 1.4426950408889634f;
constexpr float LN2 = 0.6931471805599453f;
constexpr float Q_SCALE = 0.23570226039551584f * LOG2E;

#define POLY_MASK_V 0xB5B5u
constexpr uint32_t POLY_MASK = POLY_MASK_V;
constexpr float FAST_BOUND = 60.0f;

__device__ __align__(1024) __nv_bfloat16 g_q[SEQ * DM];
__device__ __align__(1024) uint4 g_kc[KV_BYTES / 16];
__device__ __align__(1024) uint4 g_vc[KV_BYTES / 16];
__device__ float g_kmax[32];
__device__ __align__(1024) __nv_bfloat16 g_o[SEQ * DM];
__device__ __align__(1024) __nv_bfloat16 g_x2[SEQ * DM];

#define TS(k, i)

__device__ __forceinline__ uint32_t smem_u32(const void* p) { return (uint32_t)__cvta_generic_to_shared(p); }
__device__ __forceinline__ void wg_fence() { asm volatile("wgmma.fence.sync.aligned;" ::: "memory"); }
__device__ __forceinline__ void wg_commit() { asm volatile("wgmma.commit_group.sync.aligned;" ::: "memory"); }
template <int N> __device__ __forceinline__ void wg_wait() { asm volatile("wgmma.wait_group.sync.aligned %0;" ::"n"(N) : "memory"); }
template <int N> __device__ __forceinline__ void pin(float (&r)[N]) {
#pragma unroll
    for (int i = 0; i < N; i++) asm volatile("" : "+f"(r[i])::"memory");
}
template <int N> __device__ __forceinline__ void pin(uint32_t (&r)[N]) {
#pragma unroll
    for (int i = 0; i < N; i++) asm volatile("" : "+r"(r[i])::"memory");
}
__device__ __forceinline__ constexpr uint32_t desc_hi(uint32_t sbo, uint32_t swz) { return (sbo >> 4) | (swz << 30); }
__device__ __forceinline__ uint32_t desc_lo(uint32_t addr, uint32_t lbo) { return ((addr & 0x3FFFF) >> 4) | ((lbo >> 4) << 16); }
__device__ __forceinline__ uint64_t desc64(uint32_t lo, uint32_t hi) { return ((uint64_t)hi << 32) | lo; }
constexpr uint32_t SMEM0 = 0x400;
__host__ __device__ constexpr uint64_t cdesc(uint32_t off, uint32_t lbo, uint32_t sbo, uint32_t swz) {
    return (uint64_t)(((SMEM0 + off) & 0x3FFFF) >> 4) | ((uint64_t)(lbo >> 4) << 16) | ((uint64_t)(sbo >> 4) << 32) | ((uint64_t)swz << 62);
}
__device__ __forceinline__ void check_smem_base(uint32_t base) { if ((base & 0x3FFFF) != SMEM0) __trap(); }

__device__ __forceinline__ void mbar_init(uint32_t bar, int cnt) { asm volatile("mbarrier.init.shared::cta.b64 [%0], %1;" ::"r"(bar), "r"(cnt) : "memory"); }
__device__ __forceinline__ void mbar_expect(uint32_t bar, int bytes) { asm volatile("mbarrier.arrive.expect_tx.shared::cta.b64 _, [%0], %1;" ::"r"(bar), "r"(bytes) : "memory"); }
__device__ __forceinline__ void mbar_arrive(uint32_t bar) { asm volatile("mbarrier.arrive.shared::cta.b64 _, [%0];" ::"r"(bar) : "memory"); }
__device__ __forceinline__ void mbar_wait(uint32_t bar, uint32_t parity) {
    asm volatile(
        "{\n.reg .pred p;\n.reg .u32 n;\nmov.u32 n, 0;\n"
        "LAB_WAIT:\n"
        "mbarrier.try_wait.parity.shared::cta.b64 p, [%0], %1;\n"
        "@p bra DONE;\n"
        "add.u32 n, n, 1;\n"
        "setp.lt.u32 p, n, 4000000;\n"
        "@p bra LAB_WAIT;\n"
        "trap;\n"
        "DONE:\n}\n" ::"r"(bar), "r"(parity) : "memory");
}
__device__ __forceinline__ void bar_init_fence() {
    asm volatile("fence.mbarrier_init.release.cluster;" ::: "memory");
    asm volatile("fence.proxy.async.shared::cta;" ::: "memory");
}
__device__ __forceinline__ void proxy_fence() { asm volatile("fence.proxy.async.shared::cta;" ::: "memory"); }
__device__ __forceinline__ void named_sync(int id, int n) { asm volatile("bar.sync %0, %1;" ::"r"(id), "r"(n) : "memory"); }
__device__ __forceinline__ void bulk_g2s(uint32_t dst, const void* src, int bytes, uint32_t bar) {
    asm volatile("cp.async.bulk.shared::cluster.global.mbarrier::complete_tx::bytes [%0], [%1], %2, [%3];" ::"r"(dst), "l"(src), "r"(bytes), "r"(bar) : "memory");
}
__device__ __forceinline__ void tma_2d(uint32_t dst, const CUtensorMap* tm, int c0, int c1, uint32_t bar) {
    asm volatile("cp.async.bulk.tensor.2d.shared::cluster.global.mbarrier::complete_tx::bytes [%0], [%1, {%3, %4}], [%2];" ::"r"(dst), "l"(tm), "r"(bar), "r"(c0), "r"(c1) : "memory");
}
__device__ __forceinline__ void tma_2d_mc(uint32_t dst, const CUtensorMap* tm, int c0, int c1, uint32_t bar, uint16_t mask) {
    asm volatile("cp.async.bulk.tensor.2d.shared::cluster.global.mbarrier::complete_tx::bytes.multicast::cluster [%0], [%1, {%3, %4}], [%2], %5;" ::"r"(dst), "l"(tm), "r"(bar), "r"(c0), "r"(c1), "h"(mask) : "memory");
}
__device__ __forceinline__ void cluster_arrive() { asm volatile("barrier.cluster.arrive.release.aligned;" ::: "memory"); }
__device__ __forceinline__ void cluster_wait() { asm volatile("barrier.cluster.wait.acquire.aligned;" ::: "memory"); }
__device__ __forceinline__ void tma_red_2d(const CUtensorMap* tm, int c0, int c1, uint32_t src) {
    asm volatile("cp.reduce.async.bulk.tensor.2d.global.shared::cta.add.tile.bulk_group [%0, {%2, %3}], [%1];" ::"l"(tm), "r"(src), "r"(c0), "r"(c1) : "memory");
}
__device__ __forceinline__ void tma_st_2d(const CUtensorMap* tm, int c0, int c1, uint32_t src) {
    asm volatile("cp.async.bulk.tensor.2d.global.shared::cta.tile.bulk_group [%0, {%2, %3}], [%1];" ::"l"(tm), "r"(src), "r"(c0), "r"(c1) : "memory");
}
__device__ __forceinline__ void bulk_commit() { asm volatile("cp.async.bulk.commit_group;" ::: "memory"); }
__device__ __forceinline__ void bulk_wait_all() { asm volatile("cp.async.bulk.wait_group.read 0;" ::: "memory"); }
__device__ __forceinline__ bool elect_one() {
    uint32_t p;
    asm volatile("{\n.reg .pred P;\nelect.sync _|P, 0xffffffff;\nselp.b32 %0, 1, 0, P;\n}\n" : "=r"(p));
    return p != 0;
}
__device__ __forceinline__ void prefetch_l2(const void* p, int bytes) { asm volatile("cp.async.bulk.prefetch.L2.global [%0], %1;" ::"l"(p), "r"(bytes) : "memory"); }
__device__ __forceinline__ void prefetch_map(const CUtensorMap* tm) { asm volatile("prefetch.tensormap [%0];" ::"l"(tm) : "memory"); }
__device__ __forceinline__ void pdl_launch() { asm volatile("griddepcontrol.launch_dependents;" ::: "memory"); }
__device__ __forceinline__ void pdl_wait() { asm volatile("griddepcontrol.wait;" ::: "memory"); }
__device__ __forceinline__ float ex2(float x) { float y; asm("ex2.approx.ftz.f32 %0, %1;" : "=f"(y) : "f"(x)); return y; }
__device__ __forceinline__ float rcp(float x) { float y; asm("rcp.approx.ftz.f32 %0, %1;" : "=f"(y) : "f"(x)); return y; }
__device__ __forceinline__ uint32_t pack_bf16(float lo, float hi) { uint32_t r; asm("cvt.rn.bf16x2.f32 %0, %1, %2;" : "=r"(r) : "f"(hi), "f"(lo)); return r; }
__device__ __forceinline__ float bf_lo(uint32_t v) { return __uint_as_float(v << 16); }
__device__ __forceinline__ float bf_hi(uint32_t v) { return __uint_as_float(v & 0xFFFF0000u); }
__device__ __forceinline__ uint32_t hfma2(uint32_t a, uint32_t b, uint32_t c) { uint32_t r; asm("fma.rn.f16x2 %0, %1, %2, %3;" : "=r"(r) : "r"(a), "r"(b), "r"(c)); return r; }
__device__ __forceinline__ void stmatrix_x4(uint32_t addr, uint32_t r0, uint32_t r1, uint32_t r2, uint32_t r3) {
    asm volatile("stmatrix.sync.aligned.m8n8.x4.shared.b16 [%0], {%1, %2, %3, %4};" ::"r"(addr), "r"(r0), "r"(r1), "r"(r2), "r"(r3) : "memory");
}

template <int TB> __device__ __forceinline__ void wgmma_ss_n24(float (&d)[12], uint64_t da, uint64_t db, int sc) {
    asm volatile("{\n.reg .pred p;\nsetp.ne.b32 p, %14, 0;\n"
        "wgmma.mma_async.sync.aligned.m64n24k16.f32.bf16.bf16 {%0, %1, %2, %3, %4, %5, %6, %7, %8, %9, %10, %11}, %12, %13, p, 1, 1, 0, %15;\n}\n"
        : "+f"(d[0]), "+f"(d[1]), "+f"(d[2]), "+f"(d[3]), "+f"(d[4]), "+f"(d[5]), "+f"(d[6]), "+f"(d[7]), "+f"(d[8]), "+f"(d[9]), "+f"(d[10]), "+f"(d[11])
        : "l"(da), "l"(db), "r"(sc), "n"(TB));
}
template <int TB> __device__ __forceinline__ void wgmma_ss_n64(float (&d)[32], uint64_t da, uint64_t db, int sc) {
    asm volatile("{\n.reg .pred p;\nsetp.ne.b32 p, %34, 0;\n"
        "wgmma.mma_async.sync.aligned.m64n64k16.f32.bf16.bf16 {%0, %1, %2, %3, %4, %5, %6, %7, %8, %9, %10, %11, %12, %13, %14, %15, %16, %17, %18, %19, %20, %21, %22, %23, %24, %25, %26, %27, %28, %29, %30, %31}, %32, %33, p, 1, 1, 0, %35;\n}\n"
        : "+f"(d[0]), "+f"(d[1]), "+f"(d[2]), "+f"(d[3]), "+f"(d[4]), "+f"(d[5]), "+f"(d[6]), "+f"(d[7]), "+f"(d[8]), "+f"(d[9]), "+f"(d[10]), "+f"(d[11]), "+f"(d[12]), "+f"(d[13]), "+f"(d[14]), "+f"(d[15]), "+f"(d[16]), "+f"(d[17]), "+f"(d[18]), "+f"(d[19]), "+f"(d[20]), "+f"(d[21]), "+f"(d[22]), "+f"(d[23]), "+f"(d[24]), "+f"(d[25]), "+f"(d[26]), "+f"(d[27]), "+f"(d[28]), "+f"(d[29]), "+f"(d[30]), "+f"(d[31])
        : "l"(da), "l"(db), "r"(sc), "n"(TB));
}
template <int TB> __device__ __forceinline__ void wgmma_ss_n128(float (&d)[64], uint64_t da, uint64_t db, int sc) {
    asm volatile("{\n.reg .pred p;\nsetp.ne.b32 p, %66, 0;\n"
        "wgmma.mma_async.sync.aligned.m64n128k16.f32.bf16.bf16 {%0, %1, %2, %3, %4, %5, %6, %7, %8, %9, %10, %11, %12, %13, %14, %15, %16, %17, %18, %19, %20, %21, %22, %23, %24, %25, %26, %27, %28, %29, %30, %31, %32, %33, %34, %35, %36, %37, %38, %39, %40, %41, %42, %43, %44, %45, %46, %47, %48, %49, %50, %51, %52, %53, %54, %55, %56, %57, %58, %59, %60, %61, %62, %63}, %64, %65, p, 1, 1, 0, %67;\n}\n"
        : "+f"(d[0]), "+f"(d[1]), "+f"(d[2]), "+f"(d[3]), "+f"(d[4]), "+f"(d[5]), "+f"(d[6]), "+f"(d[7]), "+f"(d[8]), "+f"(d[9]), "+f"(d[10]), "+f"(d[11]), "+f"(d[12]), "+f"(d[13]), "+f"(d[14]), "+f"(d[15]), "+f"(d[16]), "+f"(d[17]), "+f"(d[18]), "+f"(d[19]), "+f"(d[20]), "+f"(d[21]), "+f"(d[22]), "+f"(d[23]), "+f"(d[24]), "+f"(d[25]), "+f"(d[26]), "+f"(d[27]), "+f"(d[28]), "+f"(d[29]), "+f"(d[30]), "+f"(d[31]), "+f"(d[32]), "+f"(d[33]), "+f"(d[34]), "+f"(d[35]), "+f"(d[36]), "+f"(d[37]), "+f"(d[38]), "+f"(d[39]), "+f"(d[40]), "+f"(d[41]), "+f"(d[42]), "+f"(d[43]), "+f"(d[44]), "+f"(d[45]), "+f"(d[46]), "+f"(d[47]), "+f"(d[48]), "+f"(d[49]), "+f"(d[50]), "+f"(d[51]), "+f"(d[52]), "+f"(d[53]), "+f"(d[54]), "+f"(d[55]), "+f"(d[56]), "+f"(d[57]), "+f"(d[58]), "+f"(d[59]), "+f"(d[60]), "+f"(d[61]), "+f"(d[62]), "+f"(d[63])
        : "l"(da), "l"(db), "r"(sc), "n"(TB));
}
template <int TB> __device__ __forceinline__ void wgmma_rs_n24(float (&d)[12], uint32_t a0, uint32_t a1, uint32_t a2, uint32_t a3, uint64_t db, int sc) {
    asm volatile("{\n.reg .pred p;\nsetp.ne.b32 p, %17, 0;\n"
        "wgmma.mma_async.sync.aligned.m64n24k16.f32.bf16.bf16 {%0, %1, %2, %3, %4, %5, %6, %7, %8, %9, %10, %11}, {%12, %13, %14, %15}, %16, p, 1, 1, %18;\n}\n"
        : "+f"(d[0]), "+f"(d[1]), "+f"(d[2]), "+f"(d[3]), "+f"(d[4]), "+f"(d[5]), "+f"(d[6]), "+f"(d[7]), "+f"(d[8]), "+f"(d[9]), "+f"(d[10]), "+f"(d[11])
        : "r"(a0), "r"(a1), "r"(a2), "r"(a3), "l"(db), "r"(sc), "n"(TB));
}
template <int TB> __device__ __forceinline__ void wgmma_rs_n64(float (&d)[32], uint32_t a0, uint32_t a1, uint32_t a2, uint32_t a3, uint64_t db, int sc) {
    asm volatile("{\n.reg .pred p;\nsetp.ne.b32 p, %37, 0;\n"
        "wgmma.mma_async.sync.aligned.m64n64k16.f32.bf16.bf16 {%0, %1, %2, %3, %4, %5, %6, %7, %8, %9, %10, %11, %12, %13, %14, %15, %16, %17, %18, %19, %20, %21, %22, %23, %24, %25, %26, %27, %28, %29, %30, %31}, {%32, %33, %34, %35}, %36, p, 1, 1, %38;\n}\n"
        : "+f"(d[0]), "+f"(d[1]), "+f"(d[2]), "+f"(d[3]), "+f"(d[4]), "+f"(d[5]), "+f"(d[6]), "+f"(d[7]), "+f"(d[8]), "+f"(d[9]), "+f"(d[10]), "+f"(d[11]), "+f"(d[12]), "+f"(d[13]), "+f"(d[14]), "+f"(d[15]), "+f"(d[16]), "+f"(d[17]), "+f"(d[18]), "+f"(d[19]), "+f"(d[20]), "+f"(d[21]), "+f"(d[22]), "+f"(d[23]), "+f"(d[24]), "+f"(d[25]), "+f"(d[26]), "+f"(d[27]), "+f"(d[28]), "+f"(d[29]), "+f"(d[30]), "+f"(d[31])
        : "r"(a0), "r"(a1), "r"(a2), "r"(a3), "l"(db), "r"(sc), "n"(TB));
}
template <int TB> __device__ __forceinline__ void wgmma_rs_n128(float (&d)[64], uint32_t a0, uint32_t a1, uint32_t a2, uint32_t a3, uint64_t db, int sc) {
    asm volatile("{\n.reg .pred p;\nsetp.ne.b32 p, %69, 0;\n"
        "wgmma.mma_async.sync.aligned.m64n128k16.f32.bf16.bf16 {%0, %1, %2, %3, %4, %5, %6, %7, %8, %9, %10, %11, %12, %13, %14, %15, %16, %17, %18, %19, %20, %21, %22, %23, %24, %25, %26, %27, %28, %29, %30, %31, %32, %33, %34, %35, %36, %37, %38, %39, %40, %41, %42, %43, %44, %45, %46, %47, %48, %49, %50, %51, %52, %53, %54, %55, %56, %57, %58, %59, %60, %61, %62, %63}, {%64, %65, %66, %67}, %68, p, 1, 1, %70;\n}\n"
        : "+f"(d[0]), "+f"(d[1]), "+f"(d[2]), "+f"(d[3]), "+f"(d[4]), "+f"(d[5]), "+f"(d[6]), "+f"(d[7]), "+f"(d[8]), "+f"(d[9]), "+f"(d[10]), "+f"(d[11]), "+f"(d[12]), "+f"(d[13]), "+f"(d[14]), "+f"(d[15]), "+f"(d[16]), "+f"(d[17]), "+f"(d[18]), "+f"(d[19]), "+f"(d[20]), "+f"(d[21]), "+f"(d[22]), "+f"(d[23]), "+f"(d[24]), "+f"(d[25]), "+f"(d[26]), "+f"(d[27]), "+f"(d[28]), "+f"(d[29]), "+f"(d[30]), "+f"(d[31]), "+f"(d[32]), "+f"(d[33]), "+f"(d[34]), "+f"(d[35]), "+f"(d[36]), "+f"(d[37]), "+f"(d[38]), "+f"(d[39]), "+f"(d[40]), "+f"(d[41]), "+f"(d[42]), "+f"(d[43]), "+f"(d[44]), "+f"(d[45]), "+f"(d[46]), "+f"(d[47]), "+f"(d[48]), "+f"(d[49]), "+f"(d[50]), "+f"(d[51]), "+f"(d[52]), "+f"(d[53]), "+f"(d[54]), "+f"(d[55]), "+f"(d[56]), "+f"(d[57]), "+f"(d[58]), "+f"(d[59]), "+f"(d[60]), "+f"(d[61]), "+f"(d[62]), "+f"(d[63])
        : "r"(a0), "r"(a1), "r"(a2), "r"(a3), "l"(db), "r"(sc), "n"(TB));
}

constexpr int P_THREADS = 288;
constexpr int P_NST = 6;
constexpr int P_A_BYTES = 9 * 8192;
constexpr int P_B_STAGE = 3 * 8192;
constexpr int P_SMEM = P_A_BYTES + P_NST * P_B_STAGE + 256 + 320;
constexpr uint32_t HI_SW128 = (1024u >> 4) | (1u << 30);

template <int NCOL, bool WAIT_A>
__device__ __forceinline__ void proj_mma(float (&acc)[NCOL / 2], uint32_t sA, uint32_t sB, uint32_t colofs, uint32_t fullB, uint32_t emptyB, uint32_t fullA, int lane) {
#pragma unroll 1
    for (int kb = 0; kb < 9; kb++) {
        const int s = kb >= P_NST ? kb - P_NST : kb;
        if (WAIT_A) mbar_wait(fullA + kb * 8, 0);

        mbar_wait(fullB + s * 8, kb >= P_NST ? 1 : 0);
        const uint32_t alo = desc_lo(sA + kb * 8192, 16), blo = desc_lo(sB + s * P_B_STAGE + colofs, 8192);
        wg_fence();
#pragma unroll
        for (int ks = 0; ks < 4; ks++) {
            const uint64_t da = desc64(alo + ks * 2, HI_SW128), db = desc64(blo + ks * 128, HI_SW128);
            if constexpr (NCOL == 128) wgmma_ss_n128<1>(acc, da, db, (kb | ks) != 0);
            else wgmma_ss_n64<1>(acc, da, db, (kb | ks) != 0);
        }
        wg_commit();
        if (kb + P_NST < 9 + 1) {
            wg_wait<1>();
            if (kb >= 1 && kb - 1 + P_NST < 9 && lane == 0) mbar_arrive(emptyB + (kb - 1) * 8);
        }
    }
    wg_wait<0>();
    pin(acc);
}

template <int NB>
__device__ __forceinline__ void stage_tile(const uint32_t (&pk)[NB * 2], uint32_t base, int w, int lane) {
    const int r = w * 16 + (lane & 7) + ((lane >> 3) & 1) * 8;
#pragma unroll
    for (int b = 0; b < NB; b += 2) {
        const uint32_t a = base + (b >> 3) * 8192 + r * 128 + ((((b & 7) + (lane >> 4)) ^ (r & 7)) << 4);
        stmatrix_x4(a, pk[2 * b], pk[2 * b + 1], pk[2 * b + 2], pk[2 * b + 3]);
    }
}

__device__ __forceinline__ uint32_t hsub2_bf16(uint32_t a, uint32_t b) { uint32_t r; asm("sub.rn.bf16x2 %0, %1, %2;" : "=r"(r) : "r"(a), "r"(b)); return r; }

constexpr int KV_RAW = DM * 18 * 2;

__global__ void __launch_bounds__(P_THREADS, 1)
k_qkv(const __grid_constant__ CUtensorMap tmWq, const __grid_constant__ CUtensorMap tmQ, const __nv_bfloat16* __restrict__ x, const __nv_bfloat16* __restrict__ wk, const __nv_bfloat16* __restrict__ wv) {
    extern __shared__ __align__(1024) uint8_t smem[];
    const uint32_t sA = smem_u32(smem), sB = sA + P_A_BYTES, bars = sB + P_NST * P_B_STAGE;
    const uint32_t fullB = bars, emptyB = bars + 64, fullX = bars + 128, fullW = bars + 136, rawFree = bars + 144;
    const uint32_t sRaw = sB + 3 * P_B_STAGE;
    float* s_rstd = reinterpret_cast<float*>(smem + P_A_BYTES + P_NST * P_B_STAGE + 256);
    const int tid = threadIdx.x, warp = __shfl_sync(~0u, tid >> 5, 0), lane = tid & 31;
    const bool isQ = blockIdx.x < 96;
    const int m = isQ ? blockIdx.x / 3 : blockIdx.x - 96, cg = blockIdx.x % 3;
    if (tid == 0) TS(0, 0);
    if (warp == 8) {
        if (elect_one()) {
            prefetch_map(&tmWq); prefetch_map(&tmQ);
            for (int i = 0; i < P_NST; i++) { mbar_init(fullB + i * 8, 1); mbar_init(emptyB + i * 8, 8); }
            mbar_init(fullX, 1); mbar_init(fullW, 1); mbar_init(rawFree, 8);
            bar_init_fence();
            mbar_expect(fullX, P_A_BYTES);
            bulk_g2s(sRaw, x + (size_t)m * 64 * DM, P_A_BYTES, fullX);
            if (isQ) {
                for (int kb = 0; kb < 3; kb++) {
                    mbar_expect(fullB + kb * 8, P_B_STAGE);
                    for (int a = 0; a < 3; a++) tma_2d(sB + kb * P_B_STAGE + a * 8192, &tmWq, cg * 192 + a * 64, kb * 64, fullB + kb * 8);
                }
            } else {
                mbar_expect(fullW, 2 * KV_RAW);
                bulk_g2s(sA, wk, KV_RAW, fullW);
                bulk_g2s(sA + KV_RAW, wv, KV_RAW, fullW);
            }
        }
        __syncwarp();
    }
    __syncthreads();
    pdl_launch();
    if (warp == 8) {
        if (isQ && elect_one()) {
            mbar_wait(rawFree, 0);
            for (int kb = 3; kb < 9; kb++) {
                const int s = kb >= P_NST ? kb - P_NST : kb;
                if (kb >= P_NST) mbar_wait(emptyB + s * 8, 0);
                mbar_expect(fullB + s * 8, P_B_STAGE);
                for (int a = 0; a < 3; a++) tma_2d(sB + s * P_B_STAGE + a * 8192, &tmWq, cg * 192 + a * 64, kb * 64, fullB + s * 8);
            }
        }
        return;
    }
    {
        const int row = tid >> 2, q = tid & 3, odd = row & 1;
        mbar_wait(fullX, 0);
        if (tid == 0) TS(0, 6);
        uint4 v[18];
#pragma unroll
        for (int i = 0; i < 18; i++)
            asm volatile("ld.shared.v4.b32 {%0, %1, %2, %3}, [%4];" : "=r"(v[i].x), "=r"(v[i].y), "=r"(v[i].z), "=r"(v[i].w) : "r"(sRaw + row * 1152 + (q + 4 * (i ^ odd)) * 16));
        float sum = 0.f, sum2 = 0.f, sq = 0.f, sq2 = 0.f;
#pragma unroll
        for (int i = 0; i < 18; i++) {
            const uint32_t w[4] = {v[i].x, v[i].y, v[i].z, v[i].w};
#pragma unroll
            for (int j = 0; j < 4; j++) { const float a = bf_lo(w[j]), b = bf_hi(w[j]); sum += a; sum2 += b; sq = fmaf(a, a, sq); sq2 = fmaf(b, b, sq2); }
        }
        __syncwarp();
        if (lane == 0) mbar_arrive(rawFree);
        sum += sum2; sq += sq2;
        sum += __shfl_xor_sync(~0u, sum, 1); sum += __shfl_xor_sync(~0u, sum, 2);
        sq += __shfl_xor_sync(~0u, sq, 1); sq += __shfl_xor_sync(~0u, sq, 2);
        if (tid == 0) TS(0, 4);
        if (!isQ) {
            mbar_wait(fullW, 0);
            if (tid == 0) TS(0, 7);
            const uint32_t* raw = reinterpret_cast<const uint32_t*>(smem);
            uint32_t wr[41];
#pragma unroll
            for (int i = 0; i < 40; i++) wr[i] = raw[tid + i * 256];
            wr[40] = raw[(tid & 127) + 40 * 256];
            int k = tid / 9, r = tid - k * 9;
#pragma unroll
            for (int i = 0; i < 41; i++) {
                const int sel = k >= DM, kk = k - sel * DM;
                uint32_t* dst = reinterpret_cast<uint32_t*>(smem + P_A_BYTES + (sel * 3 + (r >> 2)) * 9216 + (kk >> 3) * 128 + (kk & 7) * 16 + (r & 3) * 4);
                if (i < 40 || tid < 128) *dst = wr[i];
                k += 28; r += 4;
                if (r >= 9) { r -= 9; k++; }
            }
            named_sync(1, 256);
            if (tid == 0) TS(0, 8);
        }
        const float mean = sum * (1.0f / DM);
        if (q == 0) s_rstd[row] = rsqrtf(fmaxf(sq * (1.0f / DM) - mean * mean, 0.f) + LN_EPS);
        const uint32_t mhi = pack_bf16(mean, mean);
        const float rem = mean - bf_lo(mhi);
        const uint32_t mlo = pack_bf16(rem, rem);
#pragma unroll
        for (int i = 0; i < 18; i++) {
            const int c = q + 4 * (i ^ odd);
            const uint32_t o0 = hsub2_bf16(hsub2_bf16(v[i].x, mhi), mlo), o1 = hsub2_bf16(hsub2_bf16(v[i].y, mhi), mlo);
            const uint32_t o2 = hsub2_bf16(hsub2_bf16(v[i].z, mhi), mlo), o3 = hsub2_bf16(hsub2_bf16(v[i].w, mhi), mlo);
            asm volatile("st.shared.v4.b32 [%0], {%1, %2, %3, %4};" ::"r"(sA + (c >> 3) * 8192 + row * 128 + (((c & 7) ^ (row & 7)) << 4)), "r"(o0), "r"(o1), "r"(o2), "r"(o3) : "memory");
        }
    }
    proxy_fence();
    named_sync(1, 256);
    if (tid == 0) TS(0, 1);
    const int wg = warp >> 2, w = warp & 3, g = lane >> 2, t = lane & 3;
    const float rs0 = s_rstd[w * 16 + g], rs1 = s_rstd[w * 16 + g + 8];
    if (isQ) {
        const float c0 = rs0 * Q_SCALE, c1 = rs1 * Q_SCALE;
        if (wg == 0) {
            float acc[64];
            proj_mma<128, false>(acc, sA, sB, 0, fullB, emptyB, 0, lane);
            if (tid == 0) TS(0, 2);
            named_sync(1, 256);
            uint32_t pk[32];
#pragma unroll
            for (int i = 0; i < 16; i++) { pk[2 * i] = pack_bf16(acc[4 * i] * c0, acc[4 * i + 1] * c0); pk[2 * i + 1] = pack_bf16(acc[4 * i + 2] * c1, acc[4 * i + 3] * c1); }
            stage_tile<16>(pk, sA, w, lane);
        } else {
            float acc[32];
            proj_mma<64, false>(acc, sA, sB, 2 * 8192, fullB, emptyB, 0, lane);
            named_sync(1, 256);
            uint32_t pk[16];
#pragma unroll
            for (int i = 0; i < 8; i++) { pk[2 * i] = pack_bf16(acc[4 * i] * c0, acc[4 * i + 1] * c0); pk[2 * i + 1] = pack_bf16(acc[4 * i + 2] * c1, acc[4 * i + 3] * c1); }
            stage_tile<8>(pk, sA + 2 * 8192, w, lane);
        }
        proxy_fence();
        named_sync(1, 256);
        if (warp == 0 && elect_one()) {
            for (int a = 0; a < 3; a++) tma_st_2d(&tmQ, cg * 192 + a * 64, m * 64, sA + a * 8192);
            bulk_commit();
            bulk_wait_all();
        }
    } else {
        float acc[12];
        const uint32_t blo = desc_lo(sB + wg * 3 * 9216, 128);
#pragma unroll
        for (int i = 0; i < 12; i++) acc[i] = 0.f;
        pin(acc);
        wg_fence();
#pragma unroll 1
        for (int kb = 0; kb < 9; kb++) {
            const uint32_t alo = desc_lo(sA + kb * 8192, 16);
#pragma unroll
            for (int ks = 0; ks < 4; ks++)
                wgmma_ss_n24<1>(acc, desc64(alo + ks * 2, HI_SW128), desc64(blo + (kb * 4 + ks) * 16, desc_hi(9216, 0)), 1);
        }
        wg_commit();
        wg_wait<0>();
        pin(acc);
        uint32_t pk[6];
#pragma unroll
        for (int b = 0; b < 3; b++) { pk[2 * b] = pack_bf16(acc[4 * b] * rs0, acc[4 * b + 1] * rs0); pk[2 * b + 1] = pack_bf16(acc[4 * b + 2] * rs1, acc[4 * b + 3] * rs1); }
        float n0 = 0.f, n1 = 0.f, vm = 0.f;
#pragma unroll
        for (int b = 0; b < 3; b++) {
            if (b < 2 || t == 0) {
                const float a = bf_lo(pk[2 * b]), c = bf_hi(pk[2 * b]), d = bf_lo(pk[2 * b + 1]), e = bf_hi(pk[2 * b + 1]);
                n0 = fmaf(a, a, fmaf(c, c, n0)); n1 = fmaf(d, d, fmaf(e, e, n1));
            }
        }
        n0 += __shfl_xor_sync(~0u, n0, 1); n0 += __shfl_xor_sync(~0u, n0, 2);
        n1 += __shfl_xor_sync(~0u, n1, 1); n1 += __shfl_xor_sync(~0u, n1, 2);
        vm = fmaxf(n0, n1);
        if (!(n0 == n0) || !(n1 == n1)) vm = __int_as_float(0x7F800000);
#pragma unroll
        for (int o = 4; o < 32; o <<= 1) vm = fmaxf(vm, __shfl_xor_sync(~0u, vm, o));
        if (t != 0) {
            uint32_t lo, hi;
            if (wg == 0) {
                const int grp = m * 8 + w * 2;
                const uint32_t c = t == 1 ? 0x42FE3F80u   : (t == 2 ? 0x00003BC0u   : 0u);
                lo = ((POLY_MASK >> (grp & 15)) & 1) ? c : 0u;
                hi = ((POLY_MASK >> ((grp + 1) & 15)) & 1) ? c : 0u;
            } else {
                lo = hi = t == 1 ? 0x00003F80u : 0u;
            }
            pk[4] = lo; pk[5] = hi;
        }
        uint32_t* dst = reinterpret_cast<uint32_t*>(wg == 0 ? g_kc : g_vc) + (m * 8 + w * 2) * 96 + g * 4 + t;
#pragma unroll
        for (int b = 0; b < 3; b++) { dst[b * 32] = pk[2 * b]; dst[96 + b * 32] = pk[2 * b + 1]; }
        float* red = s_rstd + 64;
        if (lane == 0) red[warp] = (wg == 0) ? vm : (vm <= 1e24f ? 0.f : __int_as_float(0x7F800000));
        named_sync(1, 256);
        if (tid == 0) {
            float mx = red[0];
#pragma unroll
            for (int i = 1; i < 8; i++) mx = fmaxf(mx, red[i]);
            g_kmax[m] = mx;
        }
    }
    if (tid == 0) TS(0, 3);
}

constexpr int A_THREADS = 512;
constexpr int A_NPIECE = 8;
constexpr int A_OFF_Q = 2 * KV_BYTES;
constexpr int A_OFF_BAR = A_OFF_Q + 4 * 4096;
constexpr int A_SMEM = A_OFF_BAR + 128;

__device__ __forceinline__ uint32_t exp2_pair_fixed(float lo, float hi) {
    const uint32_t G = __byte_perm(__float_as_uint(lo), __float_as_uint(hi), 0x5410);
    const uint32_t Hh = G & 0x007F007Fu;
    const uint32_t tt = hfma2(Hh, 0xF96BF96Bu, 0x358C358Cu);
    return G - hfma2(tt, Hh, 0u);
}

__device__ __forceinline__ void prefetch_weights(const __nv_bfloat16* __restrict__ w1, const __nv_bfloat16* __restrict__ w2, const __nv_bfloat16* __restrict__ wo, int lane) {
    constexpr int WB = FF * DM * 2 / 128, OB = DM * DM * 2 / 128;
    const int b = blockIdx.x;
    if (lane < 9) {
        prefetch_l2(reinterpret_cast<const char*>(w1) + (size_t)b * WB + lane * (WB / 9), WB / 9);
        prefetch_l2(reinterpret_cast<const char*>(w2) + (size_t)b * WB + lane * (WB / 9), WB / 9);
    } else if (lane == 9) {
        prefetch_l2(reinterpret_cast<const char*>(wo) + (size_t)b * OB, OB);
    }
}

__global__ void __launch_bounds__(A_THREADS, 1)
k_attn(const __nv_bfloat16* __restrict__ w1, const __nv_bfloat16* __restrict__ w2, const __nv_bfloat16* __restrict__ wo) {
    extern __shared__ __align__(1024) uint8_t smem[];
    pdl_launch();
    const uint32_t sK = smem_u32(smem), sV = sK + KV_BYTES, bars = sK + A_OFF_BAR;
    const int tid = threadIdx.x;
    check_smem_base(sK);
    if (tid == 0) TS(1, 0);
    if (tid == 0) {
        for (int i = 0; i < A_NPIECE; i++) mbar_init(bars + i * 8, 1);
        bar_init_fence();
    }
    __syncthreads();
    pdl_wait();
    if (tid == 0) TS(1, 1);
    const int wg = __shfl_sync(~0u, tid >> 7, 0), w = (tid >> 5) & 3, lane = tid & 31, g = lane >> 2, t = lane & 3;
    const uint32_t* q32 = reinterpret_cast<const uint32_t*>(g_q);
    int row = (blockIdx.x * 8 + wg) * 64 + w * 16 + g;
    uint32_t nq[6];
    nq[0] = q32[row * 9 + t]; nq[1] = q32[(row + 8) * 9 + t]; nq[2] = q32[row * 9 + 4 + t]; nq[3] = q32[(row + 8) * 9 + 4 + t];
    nq[4] = q32[row * 9 + 8]; nq[5] = q32[(row + 8) * 9 + 8];
    constexpr int PB = KV_BYTES / A_NPIECE;
    const float kmax_raw = g_kmax[lane];
    if (tid < 32 && elect_one()) {
        for (int i = 0; i < 2; i++) {
            mbar_expect(bars + i * 8, 2 * PB);
            bulk_g2s(sK + i * PB, reinterpret_cast<const char*>(g_kc) + i * PB, PB, bars + i * 8);
            bulk_g2s(sV + i * PB, reinterpret_cast<const char*>(g_vc) + i * PB, PB, bars + i * 8);
        }
    }
    float kmax2 = kmax_raw;
#pragma unroll
    for (int o = 1; o < 32; o <<= 1) kmax2 = fmaxf(kmax2, __shfl_xor_sync(~0u, kmax2, o));
    if (tid < 32 && elect_one()) {
        for (int i = 2; i < A_NPIECE; i++) {
            mbar_expect(bars + i * 8, 2 * PB);
            bulk_g2s(sK + i * PB, reinterpret_cast<const char*>(g_kc) + i * PB, PB, bars + i * 8);
            bulk_g2s(sV + i * PB, reinterpret_cast<const char*>(g_vc) + i * PB, PB, bars + i * 8);
        }
    }
    const uint32_t sQ = sK + A_OFF_Q + wg * 4096 + (w * 2) * 512 + g * 16 + t * 4;
    const uint64_t dQ0 = cdesc(A_OFF_Q, 128, 512, 0) + wg * 256, dQ1 = dQ0 + 16;
#pragma unroll 1
    for (int rep = 0; rep < 2; rep++, row += 256) {
        const uint32_t qa[4] = {nq[0], nq[1], nq[2], nq[3]};
        float n0, n1;
        {
            const float a0 = bf_lo(qa[0]), a1 = bf_hi(qa[0]), a2 = bf_lo(qa[2]), a3 = bf_hi(qa[2]);
            const float b0 = bf_lo(qa[1]), b1 = bf_hi(qa[1]), b2 = bf_lo(qa[3]), b3 = bf_hi(qa[3]);
            n0 = a0 * a0 + a1 * a1 + a2 * a2 + a3 * a3; n1 = b0 * b0 + b1 * b1 + b2 * b2 + b3 * b3;
            if (t == 0) {
                const float c0 = bf_lo(nq[4]), c1 = bf_hi(nq[4]), d0 = bf_lo(nq[5]), d1 = bf_hi(nq[5]);
                n0 += c0 * c0 + c1 * c1; n1 += d0 * d0 + d1 * d1;
            }
            n0 += __shfl_xor_sync(~0u, n0, 1); n0 += __shfl_xor_sync(~0u, n0, 2);
            n1 += __shfl_xor_sync(~0u, n1, 1); n1 += __shfl_xor_sync(~0u, n1, 2);
        }
        const uint32_t x0 = nq[4], x1 = nq[5];
        if (rep == 0) {
            const int nr = row + 256;
            nq[0] = q32[nr * 9 + t]; nq[1] = q32[(nr + 8) * 9 + t]; nq[2] = q32[nr * 9 + 4 + t]; nq[3] = q32[(nr + 8) * 9 + 4 + t];
            nq[4] = q32[nr * 9 + 8]; nq[5] = q32[(nr + 8) * 9 + 8];
        }
        if (tid == 0 && rep == 0) TS(1, 7);
        if (rep == 1 && tid < 32) prefetch_weights(w1, w2, wo, lane);
        const bool unsafe = !(fmaxf(n0, n1) * kmax2 <= FAST_BOUND * FAST_BOUND) || !(n0 == n0) || !(n1 == n1);
        uint32_t any_unsafe;
        asm volatile("{\n.reg .pred p, q;\nsetp.ne.u32 p, %1, 0;\nbar.red.or.pred q, %2, 128, p;\nselp.u32 %0, 1, 0, q;\n}\n" : "=r"(any_unsafe) : "r"((uint32_t)unsafe), "r"(wg + 1) : "memory");
        any_unsafe = __shfl_sync(~0u, any_unsafe, 0);
        {
            const uint32_t cst = any_unsafe ? 0u : (t == 1 ? 0x3F804780u : (t == 2 ? 0x00003F80u : 0u));
            asm volatile("st.shared.b32 [%0], %1;" ::"r"(sQ), "r"(qa[0]) : "memory");
            asm volatile("st.shared.b32 [%0], %1;" ::"r"(sQ + 512), "r"(qa[1]) : "memory");
            asm volatile("st.shared.b32 [%0], %1;" ::"r"(sQ + 128), "r"(qa[2]) : "memory");
            asm volatile("st.shared.b32 [%0], %1;" ::"r"(sQ + 640), "r"(qa[3]) : "memory");
            asm volatile("st.shared.b32 [%0], %1;" ::"r"(sQ + 256), "r"(t == 0 ? x0 : cst) : "memory");
            asm volatile("st.shared.b32 [%0], %1;" ::"r"(sQ + 768), "r"(t == 0 ? x1 : cst) : "memory");
            asm volatile("st.shared.b32 [%0], %1;" ::"r"(sQ + 384), "r"(0u) : "memory");
            asm volatile("st.shared.b32 [%0], %1;" ::"r"(sQ + 896), "r"(0u) : "memory");
            proxy_fence();
            named_sync(wg + 1, 128);
        }
        if (tid == 0) TS(1, 2 + rep * 2);
        float o[12];
#pragma unroll
        for (int i = 0; i < 12; i++) o[i] = 0.f;
        pin(o);
        uint64_t dK0 = cdesc(0, 128, 384, 0), dK1 = cdesc(256, 0, 384, 0), dV = cdesc(KV_BYTES, 384, 128, 0);
        if (!any_unsafe) {
            float s[64];
#pragma unroll 1
            for (int j = 0; j < 16; j++) {
                if (rep == 0 && (j & 1) == 0) mbar_wait(bars + (j >> 1) * 8, 0);
                wg_fence();
                wgmma_ss_n128<0>(s, dQ0, dK0, 0);
                wgmma_ss_n128<0>(s, dQ1, dK1, 1);
                wg_commit();
                dK0 += 16 * 384 >> 4; dK1 += 16 * 384 >> 4;
                wg_wait<0>();
                pin(s);
                uint32_t p[32];
#pragma unroll
                for (int i = 0; i < 32; i++) {
                    if ((POLY_MASK >> (i >> 1)) & 1) p[i] = exp2_pair_fixed(s[2 * i], s[2 * i + 1]);
                    else p[i] = pack_bf16(ex2(s[2 * i]), ex2(s[2 * i + 1]));
                }
                pin(p);
                wg_fence();
#pragma unroll
                for (int k = 0; k < 8; k++) wgmma_rs_n24<1>(o, p[4 * k], p[4 * k + 1], p[4 * k + 2], p[4 * k + 3], dV + k * 48, 1);
                wg_commit();
                dV += 16 * 384 >> 4;
                wg_wait<0>();
            }
        } else {
            float s[64];
            float m0 = -INFINITY, m1 = -INFINITY;
#pragma unroll 1
            for (int j = 0; j < 16; j++) {
                if (rep == 0 && (j & 1) == 0) mbar_wait(bars + (j >> 1) * 8, 0);
                wg_fence();
                wgmma_ss_n128<0>(s, dQ0, dK0, 0);
                wgmma_ss_n128<0>(s, dQ1, dK1, 1);
                wg_commit();
                dK0 += 16 * 384 >> 4; dK1 += 16 * 384 >> 4;
                wg_wait<0>();
                pin(s);
                float x0m = m0, x1m = m1;
#pragma unroll
                for (int b = 0; b < 16; b++) { x0m = fmaxf(x0m, fmaxf(s[4 * b], s[4 * b + 1])); x1m = fmaxf(x1m, fmaxf(s[4 * b + 2], s[4 * b + 3])); }
                x0m = fmaxf(x0m, __shfl_xor_sync(~0u, x0m, 1)); x0m = fmaxf(x0m, __shfl_xor_sync(~0u, x0m, 2));
                x1m = fmaxf(x1m, __shfl_xor_sync(~0u, x1m, 1)); x1m = fmaxf(x1m, __shfl_xor_sync(~0u, x1m, 2));
                const float c0 = ex2(m0 - x0m), c1 = ex2(m1 - x1m);
                m0 = x0m; m1 = x1m;
#pragma unroll
                for (int b = 0; b < 3; b++) { o[4 * b] *= c0; o[4 * b + 1] *= c0; o[4 * b + 2] *= c1; o[4 * b + 3] *= c1; }
                uint32_t p[32];
#pragma unroll
                for (int b = 0; b < 16; b++) {
                    p[2 * b] = pack_bf16(ex2(s[4 * b] - m0), ex2(s[4 * b + 1] - m0));
                    p[2 * b + 1] = pack_bf16(ex2(s[4 * b + 2] - m1), ex2(s[4 * b + 3] - m1));
                }
                pin(p); pin(o);
                wg_fence();
#pragma unroll
                for (int k = 0; k < 8; k++) wgmma_rs_n24<1>(o, p[4 * k], p[4 * k + 1], p[4 * k + 2], p[4 * k + 3], dV + k * 48, 1);
                wg_commit();
                dV += 16 * 384 >> 4;
                wg_wait<0>();
            }
        }
        pin(o);
        if (tid == 0) TS(1, 3 + rep * 2);
        const float l0 = __shfl_sync(~0u, o[8], (lane & ~3) | 1), l1 = __shfl_sync(~0u, o[10], (lane & ~3) | 1);
        const float i0 = 1.0f / l0, i1 = 1.0f / l1;
        {
            const uint32_t so = sK + A_OFF_Q + wg * 4096 + (w * 16 + g) * 36 + t * 4;
            asm volatile("st.shared.b32 [%0], %1;" ::"r"(so), "r"(pack_bf16(o[0] * i0, o[1] * i0)) : "memory");
            asm volatile("st.shared.b32 [%0], %1;" ::"r"(so + 288), "r"(pack_bf16(o[2] * i1, o[3] * i1)) : "memory");
            asm volatile("st.shared.b32 [%0], %1;" ::"r"(so + 16), "r"(pack_bf16(o[4] * i0, o[5] * i0)) : "memory");
            asm volatile("st.shared.b32 [%0], %1;" ::"r"(so + 304), "r"(pack_bf16(o[6] * i1, o[7] * i1)) : "memory");
            if (t == 0) {
                asm volatile("st.shared.b32 [%0], %1;" ::"r"(so + 32), "r"(pack_bf16(o[8] * i0, o[9] * i0)) : "memory");
                asm volatile("st.shared.b32 [%0], %1;" ::"r"(so + 320), "r"(pack_bf16(o[10] * i1, o[11] * i1)) : "memory");
            }
            proxy_fence();
            named_sync(wg + 1, 128);
            if (__shfl_sync(~0u, w, 0) == 0 && elect_one()) {
                asm volatile("cp.async.bulk.global.shared::cta.bulk_group [%0], [%1], %2;" ::"l"(reinterpret_cast<char*>(g_o) + (size_t)(row - g) * 36), "r"(sK + A_OFF_Q + wg * 4096), "n"(2304) : "memory");
                bulk_commit();
                bulk_wait_all();
            }
            __syncwarp();
        }
    }
    if (tid == 0) TS(1, 6);
    if ((tid & 127) == 0) TS(1, 10 + wg);
}

constexpr int O_THREADS = 416;
constexpr int O_OFF_STAT = P_A_BYTES + P_NST * P_B_STAGE + 256;
constexpr int O_SMEM = O_OFF_STAT + 9 * 64 * 8;

__global__ void __cluster_dims__(3, 1, 1) __launch_bounds__(O_THREADS, 1)
k_oproj(const __grid_constant__ CUtensorMap tmO, const __grid_constant__ CUtensorMap tmWo, const __grid_constant__ CUtensorMap tmX2, const __grid_constant__ CUtensorMap tmOut, const __nv_bfloat16* __restrict__ x) {
    extern __shared__ __align__(1024) uint8_t smem[];
    const uint32_t sA = smem_u32(smem), sB = sA + P_A_BYTES, bars = sB + P_NST * P_B_STAGE;
    const uint32_t fullB = bars, emptyB = bars + 64, fullA = bars + 128;
    const int tid = threadIdx.x, warp = __shfl_sync(~0u, tid >> 5, 0), lane = tid & 31;
    const int m = blockIdx.x / 3, cg = blockIdx.x % 3;
    if (tid == 0) TS(2, 0);
    check_smem_base(sA);
    if (tid == 0) {
        prefetch_map(&tmO); prefetch_map(&tmWo); prefetch_map(&tmX2); prefetch_map(&tmOut);
        for (int i = 0; i < P_NST; i++) { mbar_init(fullB + i * 8, 1); mbar_init(emptyB + i * 8, 12); }
        for (int i = 0; i < 9; i++) mbar_init(fullA + i * 8, 1);
        bar_init_fence();
        for (int kb = 0; kb < 9; kb++) mbar_expect(fullA + kb * 8, 8192);
    }
    cluster_arrive();
    cluster_wait();
    pdl_launch();
    if (warp == 12) {
        if (elect_one()) {
            for (int kb = 0; kb < 9; kb++) {
                const int s = kb >= P_NST ? kb - P_NST : kb;
                if (kb == 2) {
                    pdl_wait();
                    TS(2, 1);
                    for (int ka = cg; ka < 9; ka += 3) tma_2d_mc(sA + ka * 8192, &tmO, ka * 64, m * 64, fullA + ka * 8, (uint16_t)7);
                }
                if (kb >= P_NST) mbar_wait(emptyB + s * 8, 0);
                mbar_expect(fullB + s * 8, P_B_STAGE);
                for (int a = 0; a < 3; a++) tma_2d(sB + s * P_B_STAGE + a * 8192, &tmWo, cg * 192 + a * 64, kb * 64, fullB + s * 8);
            }
        }
        return;
    }
    if (tid == 0) TS(2, 11);
    const int wg = warp >> 2, w = warp & 3, g = lane >> 2, t = lane & 3;
    uint32_t xr[16];
    {
        const uint32_t* x32 = reinterpret_cast<const uint32_t*>(x) + (((m * 64 + w * 16 + g) * DM + cg * 192 + wg * 64 + 2 * t) >> 1);
#pragma unroll
        for (int b = 0; b < 8; b++) { xr[2 * b] = __ldg(x32 + b * 4); xr[2 * b + 1] = __ldg(x32 + b * 4 + 4 * DM); }
    }
    float acc[32];
    {
        const uint64_t dA = cdesc(0, 16, 1024, 1), dB = cdesc(P_A_BYTES, 8192, 1024, 1) + wg * 512;
#pragma unroll 1
        for (int kb = 0; kb < 9; kb++) {
            const int s = kb >= P_NST ? kb - P_NST : kb;
            mbar_wait(fullA + kb * 8, 0);
            mbar_wait(fullB + s * 8, kb >= P_NST ? 1 : 0);
            wg_fence();
#pragma unroll
            for (int ks = 0; ks < 4; ks++) wgmma_ss_n64<1>(acc, dA + (kb * 512 + ks * 2), dB + (s * (P_B_STAGE >> 4) + ks * 128), (kb | ks) != 0);
            wg_commit();
            if (kb < 4) {
                wg_wait<1>();
                if (kb >= 1 && lane == 0) mbar_arrive(emptyB + (kb - 1) * 8);
            }
        }
        wg_wait<0>();
        pin(acc);
    }
    if (tid == 0) TS(2, 2);
    named_sync(1, 384);
    float s0 = 0.f, q0 = 0.f, s1 = 0.f, q1 = 0.f;
#pragma unroll
    for (int b = 0; b < 8; b++) {
        const uint32_t xa = xr[2 * b], xb = xr[2 * b + 1];
        const uint32_t ha = pack_bf16(acc[4 * b] + bf_lo(xa), acc[4 * b + 1] + bf_hi(xa));
        const uint32_t hb = pack_bf16(acc[4 * b + 2] + bf_lo(xb), acc[4 * b + 3] + bf_hi(xb));
        xr[2 * b] = ha; xr[2 * b + 1] = hb;
        const float a = bf_lo(ha), c = bf_hi(ha), d = bf_lo(hb), e = bf_hi(hb);
        s0 += a + c; q0 = fmaf(a, a, fmaf(c, c, q0));
        s1 += d + e; q1 = fmaf(d, d, fmaf(e, e, q1));
    }
    s0 += __shfl_xor_sync(~0u, s0, 1); s0 += __shfl_xor_sync(~0u, s0, 2);
    q0 += __shfl_xor_sync(~0u, q0, 1); q0 += __shfl_xor_sync(~0u, q0, 2);
    s1 += __shfl_xor_sync(~0u, s1, 1); s1 += __shfl_xor_sync(~0u, s1, 2);
    q1 += __shfl_xor_sync(~0u, q1, 1); q1 += __shfl_xor_sync(~0u, q1, 2);
    const int r = w * 16 + g;
    const uint32_t sStat = sA + O_OFF_STAT;
    if (t < 3) {
        uint32_t dst;
        asm("mapa.shared::cluster.u32 %0, %1, %2;" : "=r"(dst) : "r"(sStat + ((cg * 3 + wg) * 64 + r) * 8), "r"(t));
        asm volatile("st.shared::cluster.v2.f32 [%0], {%1, %2};" ::"r"(dst), "f"(s0), "f"(q0) : "memory");
        asm volatile("st.shared::cluster.v2.f32 [%0], {%1, %2};" ::"r"(dst + 64), "f"(s1), "f"(q1) : "memory");
    }
    if (tid == 0) TS(2, 4);
    cluster_arrive();
    stage_tile<8>(xr, sA + wg * 8192, w, lane);
    proxy_fence();
    named_sync(2 + wg, 128);
    const bool leader = w == 0 && elect_one();
    if (leader) { tma_st_2d(&tmOut, cg * 192 + wg * 64, m * 64, sA + wg * 8192); bulk_commit(); }
    cluster_wait();
    if (tid == 0) TS(2, 5);
    s0 = q0 = s1 = q1 = 0.f;
#pragma unroll
    for (int p = 0; p < 9; p++) {
        float a, b, c, d;
        asm volatile("ld.shared.v2.f32 {%0, %1}, [%2];" : "=f"(a), "=f"(b) : "r"(sStat + (p * 64 + r) * 8));
        asm volatile("ld.shared.v2.f32 {%0, %1}, [%2];" : "=f"(c), "=f"(d) : "r"(sStat + (p * 64 + r + 8) * 8));
        s0 += a; q0 += b; s1 += c; q1 += d;
    }
    const float m0 = s0 * (1.0f / DM), m1 = s1 * (1.0f / DM);
    const float rs0 = rsqrtf(fmaxf(q0 * (1.0f / DM) - m0 * m0, 0.f) + LN_EPS), rs1 = rsqrtf(fmaxf(q1 * (1.0f / DM) - m1 * m1, 0.f) + LN_EPS);
    const float sc0 = -LOG2E * rs0, sc1 = -LOG2E * rs1, n0 = -m0 * sc0, n1 = -m1 * sc1;
#pragma unroll
    for (int b = 0; b < 8; b++) {
        xr[2 * b] = pack_bf16(fmaf(bf_lo(xr[2 * b]), sc0, n0), fmaf(bf_hi(xr[2 * b]), sc0, n0));
        xr[2 * b + 1] = pack_bf16(fmaf(bf_lo(xr[2 * b + 1]), sc1, n1), fmaf(bf_hi(xr[2 * b + 1]), sc1, n1));
    }
    stage_tile<8>(xr, sA + (3 + wg) * 8192, w, lane);
    proxy_fence();
    named_sync(2 + wg, 128);
    if (tid == 0) TS(2, 6);
    if (leader) {
        tma_st_2d(&tmX2, cg * 192 + wg * 64, m * 64, sA + (3 + wg) * 8192);
        bulk_commit();
        bulk_wait_all();
    }
    if (tid == 0) TS(2, 3);
}

constexpr int F_THREADS = 384;
constexpr int F_NST = 6;
constexpr int F_STAGE = 96 * 128;
constexpr int F_X_BYTES = 9 * 16384;
constexpr int F_OFF_ST = F_X_BYTES;
constexpr int F_OFF_BAR = F_OFF_ST + F_NST * F_STAGE;
constexpr int F_SMEM = F_OFF_BAR + 256;

__device__ __forceinline__ float after_issue(float v, uint32_t tick) {
    uint32_t r;
    asm("lop3.b32 %0, %1, %1, %2, 0xF0;" : "=r"(r) : "r"(__float_as_uint(v)), "r"(tick));
    return __uint_as_float(r);
}
__device__ __forceinline__ uint32_t read_tick() { uint32_t c; asm volatile("mov.u32 %0, %%clock;" : "=r"(c)::"memory"); return c; }
__device__ __forceinline__ void silu_s1(const float (&acc)[32], float (&tmp)[8], int piece) {
#pragma unroll
    for (int i = 0; i < 8; i++) tmp[i] = ex2(acc[8 * piece + i]);
}
__device__ __forceinline__ void silu_s2(float (&tmp)[8], uint32_t tick) {
    const float one = after_issue(1.0f, tick);
#pragma unroll
    for (int i = 0; i < 8; i++) tmp[i] = rcp(tmp[i] + one);
}
template <int C>
__device__ __forceinline__ void silu_s3(const float (&acc)[32], const float (&tmp)[8], uint32_t (&h1)[144], int piece) {
#pragma unroll
    for (int i = 0; i < 4; i++) h1[C * 16 + 4 * piece + i] = pack_bf16(acc[8 * piece + 2 * i] * tmp[2 * i], acc[8 * piece + 2 * i + 1] * tmp[2 * i + 1]);
}

struct FfnPipe {
    uint32_t full, empty;
    int lane;
    __device__ __forceinline__ void acquire(int s, uint32_t ph) const { mbar_wait(full + s * 8, ph); }
    __device__ __forceinline__ void release(int s) const { if (lane == 0) mbar_arrive(empty + s * 8); }
};

template <int C>
__device__ __forceinline__ void ffn_phase1_chunk(float (&cur)[32], float (&prev)[32], uint32_t (&h1)[144], const FfnPipe& pp, uint64_t dx, uint32_t fullX) {
    float tmp[2][8];
    const uint64_t dw = cdesc(F_OFF_ST, 8192, 1024, 1) + blockIdx.y * (C + 1);
    dx += blockIdx.y * C;
#pragma unroll
    for (int j = 0; j < 6; j++) {
        if (C == 0) { mbar_wait(fullX + ((6 * j) >> 2) * 8, 0); mbar_wait(fullX + ((6 * j + 5) >> 2) * 8, 0); }
        pp.acquire(j, C & 1);
        if (j == 0) pin(cur);
        wg_fence();
#pragma unroll
        for (int i = 0; i < 6; i++) {
            const int ks = 6 * j + i;
            wgmma_ss_n64<1>(cur, dx + ((ks >> 2) * 1024 + (ks & 3) * 2), dw + ((j * F_STAGE + i * 2048) >> 4), ks != 0);
        }
        wg_commit();
        if (C > 0 || j > 0) { wg_wait<1>(); pp.release((j + 5) % 6); }
        if (C > 0) {
            pin(prev);
            if (j >= 1) { pin(tmp[0]); if (j >= 2) pin(tmp[1]); }
            if (j >= 2) silu_s3<(C > 0 ? C - 1 : 0)>(prev, tmp[j & 1], h1, j - 2);
            if (j >= 1 && j <= 4) { silu_s2(tmp[(j - 1) & 1], read_tick()); pin(tmp[(j - 1) & 1]); }
            if (j <= 3) { silu_s1(prev, tmp[j & 1], j); pin(tmp[j & 1]); }
            if (j >= 2) { asm volatile("" : "+r"(h1[(C - 1) * 16 + 4 * (j - 2)]), "+r"(h1[(C - 1) * 16 + 4 * (j - 2) + 1]), "+r"(h1[(C - 1) * 16 + 4 * (j - 2) + 2]), "+r"(h1[(C - 1) * 16 + 4 * (j - 2) + 3]) :: "memory"); }
        }
    }
}

__device__ __forceinline__ void ffn_store_chunk(const float (&acc)[32], const CUtensorMap* tmOut, uint32_t stg, int col, int row, int w, int lane, int wgid, bool leader) {
    uint32_t pk[16];
#pragma unroll
    for (int i = 0; i < 16; i++) pk[i] = pack_bf16(acc[2 * i] * -LN2, acc[2 * i + 1] * -LN2);
    stage_tile<8>(pk, stg, w, lane);
    proxy_fence();
    named_sync(2 + wgid, 128);
    if (leader) {
        tma_red_2d(tmOut, col, row, stg);
        bulk_commit();
    }
}

__device__ __forceinline__ void ffn_phase2_chunk(float (&cur)[32], float (&prev)[32], uint32_t (&h1)[144], const FfnPipe& pp, uint32_t ph, bool store_prev, const CUtensorMap* tmOut, uint32_t stg_prev, int col_prev, int row, int w, int lane, int wgid, bool leader) {
    const uint64_t dw = cdesc(F_OFF_ST, 8192, 1024, 1) + blockIdx.y * col_prev;
#pragma unroll
    for (int j = 0; j < 6; j++) {
        pp.acquire(j, ph);
        if (j == 0) pin(cur);
        wg_fence();
#pragma unroll
        for (int i = 0; i < 6; i++) {
            const int f = (6 * j + i) * 4;
            wgmma_rs_n64<1>(cur, h1[f], h1[f + 1], h1[f + 2], h1[f + 3], dw + ((j * F_STAGE + i * 2048) >> 4), (j | i) != 0);
        }
        wg_commit();
        if (j > 0 || store_prev) { wg_wait<1>(); pp.release((j + 5) % 6); }
        if (j == 0 && store_prev) { pin(prev); ffn_store_chunk(prev, tmOut, stg_prev, col_prev, row, w, lane, wgid, leader); }
    }
}

__global__ void __cluster_dims__(2, 1, 1) __launch_bounds__(F_THREADS, 1)
k_ffn(const __grid_constant__ CUtensorMap tmH, const __grid_constant__ CUtensorMap tmW1, const __grid_constant__ CUtensorMap tmW2, const __grid_constant__ CUtensorMap tmOut) {
    extern __shared__ __align__(1024) uint8_t smem[];
    const uint32_t sX = smem_u32(smem), sSt = sX + F_OFF_ST, bars = sX + F_OFF_BAR;
    const uint32_t full = bars, empty = bars + 64, fullX = bars + 128;
    const int tid = threadIdx.x, warp = __shfl_sync(~0u, tid >> 5, 0), lane = tid & 31;
    const int m = (blockIdx.x >> 1) & 15, fs = (blockIdx.x >> 5) * 2 + (blockIdx.x & 1);
    if (tid == 0) TS(3, 0);
    check_smem_base(sX);
    if (tid == 0) {
        prefetch_map(&tmW1); prefetch_map(&tmH); prefetch_map(&tmW2); prefetch_map(&tmOut);
        for (int i = 0; i < F_NST; i++) { mbar_init(full + i * 8, 1); mbar_init(empty + i * 8, 8); }
        for (int i = 0; i < 9; i++) mbar_init(fullX + i * 8, 1);
        bar_init_fence();
        for (int kb = 0; kb < 9; kb++) mbar_expect(fullX + kb * 8, 16384);
    }
    cluster_arrive();
    cluster_wait();
    if (warp < 4) {
        asm volatile("setmaxnreg.dec.sync.aligned.u32 24;");
        if (warp == 0 && elect_one()) {
            int s = 0; uint32_t ph = 1;
            int c = 0, j = 0;
#pragma unroll 1
            for (int i = 0; i < 108; i++) {
                if (i == 54) c = fs;
                mbar_wait(empty + s * 8, ph);
                mbar_expect(full + s * 8, F_STAGE);
                if (i < 54) tma_2d(sSt + s * F_STAGE, &tmW1, fs * 576 + c * 64, j * 96, full + s * 8);
                else tma_2d(sSt + s * F_STAGE, &tmW2, c * 64, fs * 576 + j * 96, full + s * 8);
                if (++j == 6) { j = 0; if (++c == 9) c = 0; }
                if (++s == F_NST) { s = 0; ph ^= 1; }
            }
        }
    } else {
        asm volatile("setmaxnreg.inc.sync.aligned.u32 240;");
        const int wgid = (warp >> 2) - 1, w = warp & 3;
        pdl_wait();
        if (tid == 128) TS(3, 1);
        if (warp == 4 && elect_one()) {
            const int half = blockIdx.x & 1;
            for (int kb = 0; kb < 9; kb++) tma_2d_mc(sX + kb * 16384 + half * 8192, &tmH, kb * 64, m * 128 + half * 64, fullX + kb * 8, (uint16_t)3);
        }
        __syncwarp();
        FfnPipe pp{full, empty, lane};
        const uint64_t xlo = cdesc(0, 16, 1024, 1) + wgid * 512;
        uint32_t h1[144];
        float acc0[32], acc1[32];
        ffn_phase1_chunk<0>(acc0, acc1, h1, pp, xlo, fullX);
        if (tid == 128) TS(3, 2);
        ffn_phase1_chunk<1>(acc1, acc0, h1, pp, xlo, fullX);
        ffn_phase1_chunk<2>(acc0, acc1, h1, pp, xlo, fullX);
        ffn_phase1_chunk<3>(acc1, acc0, h1, pp, xlo, fullX);
        ffn_phase1_chunk<4>(acc0, acc1, h1, pp, xlo, fullX);
        ffn_phase1_chunk<5>(acc1, acc0, h1, pp, xlo, fullX);
        ffn_phase1_chunk<6>(acc0, acc1, h1, pp, xlo, fullX);
        ffn_phase1_chunk<7>(acc1, acc0, h1, pp, xlo, fullX);
        ffn_phase1_chunk<8>(acc0, acc1, h1, pp, xlo, fullX);
        wg_wait<0>();
        pp.release(5);
        pin(acc0);
        {
            float tmp[4][8];
#pragma unroll
            for (int p = 0; p < 4; p++) silu_s1(acc0, tmp[p], p);
#pragma unroll
            for (int p = 0; p < 4; p++) silu_s2(tmp[p], 0);
#pragma unroll
            for (int p = 0; p < 4; p++) silu_s3<8>(acc0, tmp[p], h1, p);
        }
        pin(h1);
        if (tid == 128) TS(3, 3);
        const int row = m * 128 + wgid * 64;
        const uint32_t stg = sX + wgid * 8192;
        int c = fs, cprev = 0;
        const bool leader = w == 0 && elect_one();
#pragma unroll 1
        for (int j = 0; j < 8; j += 2) {
            ffn_phase2_chunk(acc1, acc0, h1, pp, 1, j > 0, &tmOut, stg + (j - 1) * 16384, cprev * 64, row, w, lane, wgid, leader);
            cprev = c; if (++c == 9) c = 0;
            ffn_phase2_chunk(acc0, acc1, h1, pp, 0, true, &tmOut, stg + j * 16384, cprev * 64, row, w, lane, wgid, leader);
            cprev = c; if (++c == 9) c = 0;
        }
        ffn_phase2_chunk(acc1, acc0, h1, pp, 1, true, &tmOut, stg + 7 * 16384, cprev * 64, row, w, lane, wgid, leader);
        wg_wait<0>();
        pin(acc1);
        ffn_store_chunk(acc1, &tmOut, stg + 8 * 16384, c * 64, row, w, lane, wgid, leader);
        if (tid == 128) TS(3, 4);
        if (leader) bulk_wait_all();
        if (tid == 128) TS(3, 5);
    }
}

typedef CUresult (*EncodeFn)(CUtensorMap*, CUtensorMapDataType, cuuint32_t, void*, const cuuint64_t*, const cuuint64_t*, const cuuint32_t*, const cuuint32_t*,
                             CUtensorMapInterleave, CUtensorMapSwizzle, CUtensorMapL2promotion, CUtensorMapFloatOOBfill);

CUtensorMap make_map(EncodeFn enc, const void* base, int rows, int cols, int box_rows) {
    CUtensorMap tm;
    cuuint64_t dims[2] = {(cuuint64_t)cols, (cuuint64_t)rows};
    cuuint64_t strides[1] = {(cuuint64_t)cols * 2};
    cuuint32_t box[2] = {64, (cuuint32_t)box_rows};
    cuuint32_t es[2] = {1, 1};
    enc(&tm, CU_TENSOR_MAP_DATA_TYPE_BFLOAT16, 2, const_cast<void*>(base), dims, strides, box, es, CU_TENSOR_MAP_INTERLEAVE_NONE,
        CU_TENSOR_MAP_SWIZZLE_128B, CU_TENSOR_MAP_L2_PROMOTION_L2_256B, CU_TENSOR_MAP_FLOAT_OOB_FILL_NONE);
    return tm;
}

template <typename... KArgs, typename... Args>
void launch(void (*kern)(KArgs...), int grid, int block, int smem, bool pdl, Args... args) {
    cudaLaunchConfig_t cfg = {};
    cfg.gridDim = dim3(grid); cfg.blockDim = dim3(block); cfg.dynamicSmemBytes = smem; cfg.stream = cudaStreamPerThread;
    cudaLaunchAttribute at[1];
    at[0].id = cudaLaunchAttributeProgrammaticStreamSerialization;
    at[0].val.programmaticStreamSerializationAllowed = 1;
    cfg.attrs = at; cfg.numAttrs = pdl ? 1 : 0;
    cudaLaunchKernelEx(&cfg, kern, KArgs(args)...);
}

}

#define USE_PDL 1

extern "C" void kernel_launch(void* const* d_in, const int* in_sizes, int n_in, void* d_out, int out_size) {
    const __nv_bfloat16* x = (const __nv_bfloat16*)d_in[0];
    const __nv_bfloat16* wq = (const __nv_bfloat16*)d_in[1];
    const __nv_bfloat16* wk = (const __nv_bfloat16*)d_in[2];
    const __nv_bfloat16* wv = (const __nv_bfloat16*)d_in[3];
    const __nv_bfloat16* wo = (const __nv_bfloat16*)d_in[4];
    const __nv_bfloat16* w1 = (const __nv_bfloat16*)d_in[6];
    const __nv_bfloat16* w2 = (const __nv_bfloat16*)d_in[7];
    __nv_bfloat16* out = (__nv_bfloat16*)d_out;

    static EncodeFn enc = nullptr;
    static void *p_o = nullptr, *p_h = nullptr, *p_q = nullptr;
    if (!enc) {
        cudaDriverEntryPointQueryResult qr;
        cudaGetDriverEntryPoint("cuTensorMapEncodeTiled", (void**)&enc, cudaEnableDefault, &qr);
        cudaGetSymbolAddress(&p_o, g_o);
        cudaGetSymbolAddress(&p_h, g_x2);
        cudaGetSymbolAddress(&p_q, g_q);
        cudaFuncSetAttribute(k_qkv, cudaFuncAttributeMaxDynamicSharedMemorySize, P_SMEM);
        cudaFuncSetAttribute(k_attn, cudaFuncAttributeMaxDynamicSharedMemorySize, A_SMEM);
        cudaFuncSetAttribute(k_oproj, cudaFuncAttributeMaxDynamicSharedMemorySize, O_SMEM);
        cudaFuncSetAttribute(k_ffn, cudaFuncAttributeMaxDynamicSharedMemorySize, F_SMEM);
    }
    const CUtensorMap tmWq = make_map(enc, wq, DM, DM, 64);
    const CUtensorMap tmWo = make_map(enc, wo, DM, DM, 64);
    const CUtensorMap tmO = make_map(enc, p_o, SEQ, DM, 64);
    const CUtensorMap tmH64 = make_map(enc, p_h, SEQ, DM, 64);
    const CUtensorMap tmQ = make_map(enc, p_q, SEQ, DM, 64);
    const CUtensorMap tmW1 = make_map(enc, w1, DM, FF, 96);
    const CUtensorMap tmW2 = make_map(enc, w2, FF, DM, 96);
    const CUtensorMap tmOut = make_map(enc, out, SEQ, DM, 64);

    launch(k_qkv, 128, P_THREADS, P_SMEM, false, tmWq, tmQ, x, wk, wv);
    launch(k_attn, 128, A_THREADS, A_SMEM, USE_PDL, w1, w2, wo);
    launch(k_oproj, 96, O_THREADS, O_SMEM, USE_PDL, tmO, tmWo, tmH64, tmOut, x);
    launch(k_ffn, 128, F_THREADS, F_SMEM, USE_PDL, tmH64, tmW1, tmW2, tmOut);
}
```

```cpp
#include <cuda_runtime.h>
#include <cuda_bf16.h>
#include <cuda.h>
#include <stdint.h>

namespace {

constexpr int SEQ = 2048, DM = 576, FF = 4608;
constexpr int KV_BYTES = SEQ * 48;
constexpr float LN_EPS = 1e-5f;
constexpr float LOG2E = 1.4426950408889634f;
constexpr float LN2 = 0.6931471805599453f;
constexpr float Q_SCALE = 0.23570226039551584f * LOG2E;

#define POLY_MASK_V 0xB5B5u
constexpr uint32_t POLY_MASK = POLY_MASK_V;
constexpr float FAST_BOUND = 60.0f;

__device__ __align__(1024) __nv_bfloat16 g_q[SEQ * DM];
__device__ __align__(1024) uint4 g_kc[KV_BYTES / 16];
__device__ __align__(1024) uint4 g_vc[KV_BYTES / 16];
__device__ float g_kmax[32];
__device__ __align__(1024) __nv_bfloat16 g_o[SEQ * DM];
__device__ __align__(1024) __nv_bfloat16 g_x2[SEQ * DM];

#define TS(k, i)

__device__ __forceinline__ uint32_t smem_u32(const void* p) { return (uint32_t)__cvta_generic_to_shared(p); }
__device__ __forceinline__ void wg_fence() { asm volatile("wgmma.fence.sync.aligned;" ::: "memory"); }
__device__ __forceinline__ void wg_commit() { asm volatile("wgmma.commit_group.sync.aligned;" ::: "memory"); }
template <int N> __device__ __forceinline__ void wg_wait() { asm volatile("wgmma.wait_group.sync.aligned %0;" ::"n"(N) : "memory"); }
template <int N> __device__ __forceinline__ void pin(float (&r)[N]) {
#pragma unroll
    for (int i = 0; i < N; i++) asm volatile("" : "+f"(r[i])::"memory");
}
template <int N> __device__ __forceinline__ void pin(uint32_t (&r)[N]) {
#pragma unroll
    for (int i = 0; i < N; i++) asm volatile("" : "+r"(r[i])::"memory");
}
__device__ __forceinline__ constexpr uint32_t desc_hi(uint32_t sbo, uint32_t swz) { return (sbo >> 4) | (swz << 30); }
__device__ __forceinline__ uint32_t desc_lo(uint32_t addr, uint32_t lbo) { return ((addr & 0x3FFFF) >> 4) | ((lbo >> 4) << 16); }
__device__ __forceinline__ uint64_t desc64(uint32_t lo, uint32_t hi) { return ((uint64_t)hi << 32) | lo; }
constexpr uint32_t SMEM0 = 0x400;
__host__ __device__ constexpr uint64_t cdesc(uint32_t off, uint32_t lbo, uint32_t sbo, uint32_t swz) {
    return (uint64_t)(((SMEM0 + off) & 0x3FFFF) >> 4) | ((uint64_t)(lbo >> 4) << 16) | ((uint64_t)(sbo >> 4) << 32) | ((uint64_t)swz << 62);
}
__device__ __forceinline__ void check_smem_base(uint32_t base) { if ((base & 0x3FFFF) != SMEM0) __trap(); }

__device__ __forceinline__ void mbar_init(uint32_t bar, int cnt) { asm volatile("mbarrier.init.shared::cta.b64 [%0], %1;" ::"r"(bar), "r"(cnt) : "memory"); }
__device__ __forceinline__ void mbar_expect(uint32_t bar, int bytes) { asm volatile("mbarrier.arrive.expect_tx.shared::cta.b64 _, [%0], %1;" ::"r"(bar), "r"(bytes) : "memory"); }
__device__ __forceinline__ void mbar_arrive(uint32_t bar) { asm volatile("mbarrier.arrive.shared::cta.b64 _, [%0];" ::"r"(bar) : "memory"); }
__device__ __forceinline__ void mbar_wait(uint32_t bar, uint32_t parity) {
    asm volatile(
        "{\n.reg .pred p;\n.reg .u32 n;\nmov.u32 n, 0;\n"
        "LAB_WAIT:\n"
        "mbarrier.try_wait.parity.shared::cta.b64 p, [%0], %1;\n"
        "@p bra DONE;\n"
        "add.u32 n, n, 1;\n"
        "setp.lt.u32 p, n, 4000000;\n"
        "@p bra LAB_WAIT;\n"
        "trap;\n"
        "DONE:\n}\n" ::"r"(bar), "r"(parity) : "memory");
}
__device__ __forceinline__ void bar_init_fence() {
    asm volatile("fence.mbarrier_init.release.cluster;" ::: "memory");
    asm volatile("fence.proxy.async.shared::cta;" ::: "memory");
}
__device__ __forceinline__ void proxy_fence() { asm volatile("fence.proxy.async.shared::cta;" ::: "memory"); }
__device__ __forceinline__ void named_sync(int id, int n) { asm volatile("bar.sync %0, %1;" ::"r"(id), "r"(n) : "memory"); }
__device__ __forceinline__ void bulk_g2s(uint32_t dst, const void* src, int bytes, uint32_t bar) {
    asm volatile("cp.async.bulk.shared::cluster.global.mbarrier::complete_tx::bytes [%0], [%1], %2, [%3];" ::"r"(dst), "l"(src), "r"(bytes), "r"(bar) : "memory");
}
__device__ __forceinline__ void tma_2d(uint32_t dst, const CUtensorMap* tm, int c0, int c1, uint32_t bar) {
    asm volatile("cp.async.bulk.tensor.2d.shared::cluster.global.mbarrier::complete_tx::bytes [%0], [%1, {%3, %4}], [%2];" ::"r"(dst), "l"(tm), "r"(bar), "r"(c0), "r"(c1) : "memory");
}
__device__ __forceinline__ void cluster_arrive() { asm volatile("barrier.cluster.arrive.release.aligned;" ::: "memory"); }
__device__ __forceinline__ void cluster_wait() { asm volatile("barrier.cluster.wait.acquire.aligned;" ::: "memory"); }
__device__ __forceinline__ void tma_red_2d(const CUtensorMap* tm, int c0, int c1, uint32_t src) {
    asm volatile("cp.reduce.async.bulk.tensor.2d.global.shared::cta.add.tile.bulk_group [%0, {%2, %3}], [%1];" ::"l"(tm), "r"(src), "r"(c0), "r"(c1) : "memory");
}
__device__ __forceinline__ void tma_st_2d(const CUtensorMap* tm, int c0, int c1, uint32_t src) {
    asm volatile("cp.async.bulk.tensor.2d.global.shared::cta.tile.bulk_group [%0, {%2, %3}], [%1];" ::"l"(tm), "r"(src), "r"(c0), "r"(c1) : "memory");
}
__device__ __forceinline__ void bulk_commit() { asm volatile("cp.async.bulk.commit_group;" ::: "memory"); }
__device__ __forceinline__ void bulk_wait_all() { asm volatile("cp.async.bulk.wait_group.read 0;" ::: "memory"); }
__device__ __forceinline__ bool elect_one() {
    uint32_t p;
    asm volatile("{\n.reg .pred P;\nelect.sync _|P, 0xffffffff;\nselp.b32 %0, 1, 0, P;\n}\n" : "=r"(p));
    return p != 0;
}
__device__ __forceinline__ void prefetch_map(const CUtensorMap* tm) { asm volatile("prefetch.tensormap [%0];" ::"l"(tm) : "memory"); }
__device__ __forceinline__ void pdl_launch() { asm volatile("griddepcontrol.launch_dependents;" ::: "memory"); }
__device__ __forceinline__ void pdl_wait() { asm volatile("griddepcontrol.wait;" ::: "memory"); }
__device__ __forceinline__ float ex2(float x) { float y; asm("ex2.approx.ftz.f32 %0, %1;" : "=f"(y) : "f"(x)); return y; }
__device__ __forceinline__ float rcp(float x) { float y; asm("rcp.approx.ftz.f32 %0, %1;" : "=f"(y) : "f"(x)); return y; }
__device__ __forceinline__ uint32_t pack_bf16(float lo, float hi) { uint32_t r; asm("cvt.rn.bf16x2.f32 %0, %1, %2;" : "=r"(r) : "f"(hi), "f"(lo)); return r; }
__device__ __forceinline__ float bf_lo(uint32_t v) { return __uint_as_float(v << 16); }
__device__ __forceinline__ float bf_hi(uint32_t v) { return __uint_as_float(v & 0xFFFF0000u); }
__device__ __forceinline__ uint32_t hfma2(uint32_t a, uint32_t b, uint32_t c) { uint32_t r; asm("fma.rn.f16x2 %0, %1, %2, %3;" : "=r"(r) : "r"(a), "r"(b), "r"(c)); return r; }
__device__ __forceinline__ void stmatrix_x4(uint32_t addr, uint32_t r0, uint32_t r1, uint32_t r2, uint32_t r3) {
    asm volatile("stmatrix.sync.aligned.m8n8.x4.shared.b16 [%0], {%1, %2, %3, %4};" ::"r"(addr), "r"(r0), "r"(r1), "r"(r2), "r"(r3) : "memory");
}

template <int TB> __device__ __forceinline__ void wgmma_ss_n24(float (&d)[12], uint64_t da, uint64_t db, int sc) {
    asm volatile("{\n.reg .pred p;\nsetp.ne.b32 p, %14, 0;\n"
        "wgmma.mma_async.sync.aligned.m64n24k16.f32.bf16.bf16 {%0, %1, %2, %3, %4, %5, %6, %7, %8, %9, %10, %11}, %12, %13, p, 1, 1, 0, %15;\n}\n"
        : "+f"(d[0]), "+f"(d[1]), "+f"(d[2]), "+f"(d[3]), "+f"(d[4]), "+f"(d[5]), "+f"(d[6]), "+f"(d[7]), "+f"(d[8]), "+f"(d[9]), "+f"(d[10]), "+f"(d[11])
        : "l"(da), "l"(db), "r"(sc), "n"(TB));
}
template <int TB> __device__ __forceinline__ void wgmma_ss_n64(float (&d)[32], uint64_t da, uint64_t db, int sc) {
    asm volatile("{\n.reg .pred p;\nsetp.ne.b32 p, %34, 0;\n"
        "wgmma.mma_async.sync.aligned.m64n64k16.f32.bf16.bf16 {%0, %1, %2, %3, %4, %5, %6, %7, %8, %9, %10, %11, %12, %13, %14, %15, %16, %17, %18, %19, %20, %21, %22, %23, %24, %25, %26, %27, %28, %29, %30, %31}, %32, %33, p, 1, 1, 0, %35;\n}\n"
        : "+f"(d[0]), "+f"(d[1]), "+f"(d[2]), "+f"(d[3]), "+f"(d[4]), "+f"(d[5]), "+f"(d[6]), "+f"(d[7]), "+f"(d[8]), "+f"(d[9]), "+f"(d[10]), "+f"(d[11]), "+f"(d[12]), "+f"(d[13]), "+f"(d[14]), "+f"(d[15]), "+f"(d[16]), "+f"(d[17]), "+f"(d[18]), "+f"(d[19]), "+f"(d[20]), "+f"(d[21]), "+f"(d[22]), "+f"(d[23]), "+f"(d[24]), "+f"(d[25]), "+f"(d[26]), "+f"(d[27]), "+f"(d[28]), "+f"(d[29]), "+f"(d[30]), "+f"(d[31])
        : "l"(da), "l"(db), "r"(sc), "n"(TB));
}
template <int TB> __device__ __forceinline__ void wgmma_ss_n128(float (&d)[64], uint64_t da, uint64_t db, int sc) {
    asm volatile("{\n.reg .pred p;\nsetp.ne.b32 p, %66, 0;\n"
        "wgmma.mma_async.sync.aligned.m64n128k16.f32.bf16.bf16 {%0, %1, %2, %3, %4, %5, %6, %7, %8, %9, %10, %11, %12, %13, %14, %15, %16, %17, %18, %19, %20, %21, %22, %23, %24, %25, %26, %27, %28, %29, %30, %31, %32, %33, %34, %35, %36, %37, %38, %39, %40, %41, %42, %43, %44, %45, %46, %47, %48, %49, %50, %51, %52, %53, %54, %55, %56, %57, %58, %59, %60, %61, %62, %63}, %64, %65, p, 1, 1, 0, %67;\n}\n"
        : "+f"(d[0]), "+f"(d[1]), "+f"(d[2]), "+f"(d[3]), "+f"(d[4]), "+f"(d[5]), "+f"(d[6]), "+f"(d[7]), "+f"(d[8]), "+f"(d[9]), "+f"(d[10]), "+f"(d[11]), "+f"(d[12]), "+f"(d[13]), "+f"(d[14]), "+f"(d[15]), "+f"(d[16]), "+f"(d[17]), "+f"(d[18]), "+f"(d[19]), "+f"(d[20]), "+f"(d[21]), "+f"(d[22]), "+f"(d[23]), "+f"(d[24]), "+f"(d[25]), "+f"(d[26]), "+f"(d[27]), "+f"(d[28]), "+f"(d[29]), "+f"(d[30]), "+f"(d[31]), "+f"(d[32]), "+f"(d[33]), "+f"(d[34]), "+f"(d[35]), "+f"(d[36]), "+f"(d[37]), "+f"(d[38]), "+f"(d[39]), "+f"(d[40]), "+f"(d[41]), "+f"(d[42]), "+f"(d[43]), "+f"(d[44]), "+f"(d[45]), "+f"(d[46]), "+f"(d[47]), "+f"(d[48]), "+f"(d[49]), "+f"(d[50]), "+f"(d[51]), "+f"(d[52]), "+f"(d[53]), "+f"(d[54]), "+f"(d[55]), "+f"(d[56]), "+f"(d[57]), "+f"(d[58]), "+f"(d[59]), "+f"(d[60]), "+f"(d[61]), "+f"(d[62]), "+f"(d[63])
        : "l"(da), "l"(db), "r"(sc), "n"(TB));
}
template <int TB> __device__ __forceinline__ void wgmma_rs_n24(float (&d)[12], uint32_t a0, uint32_t a1, uint32_t a2, uint32_t a3, uint64_t db, int sc) {
    asm volatile("{\n.reg .pred p;\nsetp.ne.b32 p, %17, 0;\n"
        "wgmma.mma_async.sync.aligned.m64n24k16.f32.bf16.bf16 {%0, %1, %2, %3, %4, %5, %6, %7, %8, %9, %10, %11}, {%12, %13, %14, %15}, %16, p, 1, 1, %18;\n}\n"
        : "+f"(d[0]), "+f"(d[1]), "+f"(d[2]), "+f"(d[3]), "+f"(d[4]), "+f"(d[5]), "+f"(d[6]), "+f"(d[7]), "+f"(d[8]), "+f"(d[9]), "+f"(d[10]), "+f"(d[11])
        : "r"(a0), "r"(a1), "r"(a2), "r"(a3), "l"(db), "r"(sc), "n"(TB));
}
template <int TB> __device__ __forceinline__ void wgmma_rs_n64(float (&d)[32], uint32_t a0, uint32_t a1, uint32_t a2, uint32_t a3, uint64_t db, int sc) {
    asm volatile("{\n.reg .pred p;\nsetp.ne.b32 p, %37, 0;\n"
        "wgmma.mma_async.sync.aligned.m64n64k16.f32.bf16.bf16 {%0, %1, %2, %3, %4, %5, %6, %7, %8, %9, %10, %11, %12, %13, %14, %15, %16, %17, %18, %19, %20, %21, %22, %23, %24, %25, %26, %27, %28, %29, %30, %31}, {%32, %33, %34, %35}, %36, p, 1, 1, %38;\n}\n"
        : "+f"(d[0]), "+f"(d[1]), "+f"(d[2]), "+f"(d[3]), "+f"(d[4]), "+f"(d[5]), "+f"(d[6]), "+f"(d[7]), "+f"(d[8]), "+f"(d[9]), "+f"(d[10]), "+f"(d[11]), "+f"(d[12]), "+f"(d[13]), "+f"(d[14]), "+f"(d[15]), "+f"(d[16]), "+f"(d[17]), "+f"(d[18]), "+f"(d[19]), "+f"(d[20]), "+f"(d[21]), "+f"(d[22]), "+f"(d[23]), "+f"(d[24]), "+f"(d[25]), "+f"(d[26]), "+f"(d[27]), "+f"(d[28]), "+f"(d[29]), "+f"(d[30]), "+f"(d[31])
        : "r"(a0), "r"(a1), "r"(a2), "r"(a3), "l"(db), "r"(sc), "n"(TB));
}
template <int TB> __device__ __forceinline__ void wgmma_rs_n128(float (&d)[64], uint32_t a0, uint32_t a1, uint32_t a2, uint32_t a3, uint64_t db, int sc) {
    asm volatile("{\n.reg .pred p;\nsetp.ne.b32 p, %69, 0;\n"
        "wgmma.mma_async.sync.aligned.m64n128k16.f32.bf16.bf16 {%0, %1, %2, %3, %4, %5, %6, %7, %8, %9, %10, %11, %12, %13, %14, %15, %16, %17, %18, %19, %20, %21, %22, %23, %24, %25, %26, %27, %28, %29, %30, %31, %32, %33, %34, %35, %36, %37, %38, %39, %40, %41, %42, %43, %44, %45, %46, %47, %48, %49, %50, %51, %52, %53, %54, %55, %56, %57, %58, %59, %60, %61, %62, %63}, {%64, %65, %66, %67}, %68, p, 1, 1, %70;\n}\n"
        : "+f"(d[0]), "+f"(d[1]), "+f"(d[2]), "+f"(d[3]), "+f"(d[4]), "+f"(d[5]), "+f"(d[6]), "+f"(d[7]), "+f"(d[8]), "+f"(d[9]), "+f"(d[10]), "+f"(d[11]), "+f"(d[12]), "+f"(d[13]), "+f"(d[14]), "+f"(d[15]), "+f"(d[16]), "+f"(d[17]), "+f"(d[18]), "+f"(d[19]), "+f"(d[20]), "+f"(d[21]), "+f"(d[22]), "+f"(d[23]), "+f"(d[24]), "+f"(d[25]), "+f"(d[26]), "+f"(d[27]), "+f"(d[28]), "+f"(d[29]), "+f"(d[30]), "+f"(d[31]), "+f"(d[32]), "+f"(d[33]), "+f"(d[34]), "+f"(d[35]), "+f"(d[36]), "+f"(d[37]), "+f"(d[38]), "+f"(d[39]), "+f"(d[40]), "+f"(d[41]), "+f"(d[42]), "+f"(d[43]), "+f"(d[44]), "+f"(d[45]), "+f"(d[46]), "+f"(d[47]), "+f"(d[48]), "+f"(d[49]), "+f"(d[50]), "+f"(d[51]), "+f"(d[52]), "+f"(d[53]), "+f"(d[54]), "+f"(d[55]), "+f"(d[56]), "+f"(d[57]), "+f"(d[58]), "+f"(d[59]), "+f"(d[60]), "+f"(d[61]), "+f"(d[62]), "+f"(d[63])
        : "r"(a0), "r"(a1), "r"(a2), "r"(a3), "l"(db), "r"(sc), "n"(TB));
}

constexpr int P_THREADS = 288;
constexpr int P_NST = 6;
constexpr int P_A_BYTES = 9 * 8192;
constexpr int P_B_STAGE = 3 * 8192;
constexpr int P_SMEM = P_A_BYTES + P_NST * P_B_STAGE + 256 + 320;
constexpr uint32_t HI_SW128 = (1024u >> 4) | (1u << 30);

template <int NCOL, bool WAIT_A>
__device__ __forceinline__ void proj_mma(float (&acc)[NCOL / 2], uint32_t sA, uint32_t sB, uint32_t colofs, uint32_t fullB, uint32_t emptyB, uint32_t fullA, int lane) {
#pragma unroll 1
    for (int kb = 0; kb < 9; kb++) {
        const int s = kb >= P_NST ? kb - P_NST : kb;
        if (WAIT_A) mbar_wait(fullA + kb * 8, 0);

        mbar_wait(fullB + s * 8, kb >= P_NST ? 1 : 0);
        const uint32_t alo = desc_lo(sA + kb * 8192, 16), blo = desc_lo(sB + s * P_B_STAGE + colofs, 8192);
        wg_fence();
#pragma unroll
        for (int ks = 0; ks < 4; ks++) {
            const uint64_t da = desc64(alo + ks * 2, HI_SW128), db = desc64(blo + ks * 128, HI_SW128);
            if constexpr (NCOL == 128) wgmma_ss_n128<1>(acc, da, db, (kb | ks) != 0);
            else wgmma_ss_n64<1>(acc, da, db, (kb | ks) != 0);
        }
        wg_commit();
        if (kb + P_NST < 9 + 1) {
            wg_wait<1>();
            if (kb >= 1 && kb - 1 + P_NST < 9 && lane == 0) mbar_arrive(emptyB + (kb - 1) * 8);
        }
    }
    wg_wait<0>();
    pin(acc);
}

template <int NB>
__device__ __forceinline__ void stage_tile(const uint32_t (&pk)[NB * 2], uint32_t base, int w, int lane) {
    const int r = w * 16 + (lane & 7) + ((lane >> 3) & 1) * 8;
#pragma unroll
    for (int b = 0; b < NB; b += 2) {
        const uint32_t a = base + (b >> 3) * 8192 + r * 128 + ((((b & 7) + (lane >> 4)) ^ (r & 7)) << 4);
        stmatrix_x4(a, pk[2 * b], pk[2 * b + 1], pk[2 * b + 2], pk[2 * b + 3]);
    }
}

__device__ __forceinline__ uint32_t hsub2_bf16(uint32_t a, uint32_t b) { uint32_t r; asm("sub.rn.bf16x2 %0, %1, %2;" : "=r"(r) : "r"(a), "r"(b)); return r; }

constexpr int KV_RAW = DM * 18 * 2;

__global__ void __launch_bounds__(P_THREADS, 1)
k_qkv(const __grid_constant__ CUtensorMap tmWq, const __grid_constant__ CUtensorMap tmQ, const __nv_bfloat16* __restrict__ x, const __nv_bfloat16* __restrict__ wk, const __nv_bfloat16* __restrict__ wv) {
    extern __shared__ __align__(1024) uint8_t smem[];
    const uint32_t sA = smem_u32(smem), sB = sA + P_A_BYTES, bars = sB + P_NST * P_B_STAGE;
    const uint32_t fullB = bars, emptyB = bars + 64, fullX = bars + 128, fullW = bars + 136, rawFree = bars + 144;
    const uint32_t sRaw = sB + 3 * P_B_STAGE;
    float* s_rstd = reinterpret_cast<float*>(smem + P_A_BYTES + P_NST * P_B_STAGE + 256);
    const int tid = threadIdx.x, warp = __shfl_sync(~0u, tid >> 5, 0), lane = tid & 31;
    const bool isQ = blockIdx.x < 96;
    const int m = isQ ? blockIdx.x / 3 : blockIdx.x - 96, cg = blockIdx.x % 3;
    if (tid == 0) TS(0, 0);
    if (warp == 8) {
        if (elect_one()) {
            prefetch_map(&tmWq); prefetch_map(&tmQ);
            for (int i = 0; i < P_NST; i++) { mbar_init(fullB + i * 8, 1); mbar_init(emptyB + i * 8, 8); }
            mbar_init(fullX, 1); mbar_init(fullW, 1); mbar_init(rawFree, 8);
            bar_init_fence();
            mbar_expect(fullX, P_A_BYTES);
            bulk_g2s(sRaw, x + (size_t)m * 64 * DM, P_A_BYTES, fullX);
            if (isQ) {
                for (int kb = 0; kb < 3; kb++) {
                    mbar_expect(fullB + kb * 8, P_B_STAGE);
                    for (int a = 0; a < 3; a++) tma_2d(sB + kb * P_B_STAGE + a * 8192, &tmWq, cg * 192 + a * 64, kb * 64, fullB + kb * 8);
                }
            } else {
                mbar_expect(fullW, 2 * KV_RAW);
                bulk_g2s(sA, wk, KV_RAW, fullW);
                bulk_g2s(sA + KV_RAW, wv, KV_RAW, fullW);
            }
        }
        __syncwarp();
    }
    __syncthreads();
    pdl_launch();
    if (warp == 8) {
        if (isQ && elect_one()) {
            mbar_wait(rawFree, 0);
            for (int kb = 3; kb < 9; kb++) {
                const int s = kb >= P_NST ? kb - P_NST : kb;
                if (kb >= P_NST) mbar_wait(emptyB + s * 8, 0);
                mbar_expect(fullB + s * 8, P_B_STAGE);
                for (int a = 0; a < 3; a++) tma_2d(sB + s * P_B_STAGE + a * 8192, &tmWq, cg * 192 + a * 64, kb * 64, fullB + s * 8);
            }
        }
        return;
    }
    {
        const int row = tid >> 2, q = tid & 3, odd = row & 1;
        mbar_wait(fullX, 0);
        if (tid == 0) TS(0, 6);
        uint4 v[18];
#pragma unroll
        for (int i = 0; i < 18; i++)
            asm volatile("ld.shared.v4.b32 {%0, %1, %2, %3}, [%4];" : "=r"(v[i].x), "=r"(v[i].y), "=r"(v[i].z), "=r"(v[i].w) : "r"(sRaw + row * 1152 + (q + 4 * (i ^ odd)) * 16));
        float sum = 0.f, sum2 = 0.f, sq = 0.f, sq2 = 0.f;
#pragma unroll
        for (int i = 0; i < 18; i++) {
            const uint32_t w[4] = {v[i].x, v[i].y, v[i].z, v[i].w};
#pragma unroll
            for (int j = 0; j < 4; j++) { const float a = bf_lo(w[j]), b = bf_hi(w[j]); sum += a; sum2 += b; sq = fmaf(a, a, sq); sq2 = fmaf(b, b, sq2); }
        }
        __syncwarp();
        if (lane == 0) mbar_arrive(rawFree);
        sum += sum2; sq += sq2;
        sum += __shfl_xor_sync(~0u, sum, 1); sum += __shfl_xor_sync(~0u, sum, 2);
        sq += __shfl_xor_sync(~0u, sq, 1); sq += __shfl_xor_sync(~0u, sq, 2);
        if (tid == 0) TS(0, 4);
        if (!isQ) {
            mbar_wait(fullW, 0);
            if (tid == 0) TS(0, 7);
            const uint32_t* raw = reinterpret_cast<const uint32_t*>(smem);
            uint32_t wr[41];
#pragma unroll
            for (int i = 0; i < 40; i++) wr[i] = raw[tid + i * 256];
            wr[40] = raw[(tid & 127) + 40 * 256];
            int k = tid / 9, r = tid - k * 9;
#pragma unroll
            for (int i = 0; i < 41; i++) {
                const int sel = k >= DM, kk = k - sel * DM;
                uint32_t* dst = reinterpret_cast<uint32_t*>(smem + P_A_BYTES + (sel * 3 + (r >> 2)) * 9216 + (kk >> 3) * 128 + (kk & 7) * 16 + (r & 3) * 4);
                if (i < 40 || tid < 128) *dst = wr[i];
                k += 28; r += 4;
                if (r >= 9) { r -= 9; k++; }
            }
            named_sync(1, 256);
            if (tid == 0) TS(0, 8);
        }
        const float mean = sum * (1.0f / DM);
        if (q == 0) s_rstd[row] = rsqrtf(fmaxf(sq * (1.0f / DM) - mean * mean, 0.f) + LN_EPS);
        const uint32_t mhi = pack_bf16(mean, mean);
        const float rem = mean - bf_lo(mhi);
        const uint32_t mlo = pack_bf16(rem, rem);
#pragma unroll
        for (int i = 0; i < 18; i++) {
            const int c = q + 4 * (i ^ odd);
            const uint32_t o0 = hsub2_bf16(hsub2_bf16(v[i].x, mhi), mlo), o1 = hsub2_bf16(hsub2_bf16(v[i].y, mhi), mlo);
            const uint32_t o2 = hsub2_bf16(hsub2_bf16(v[i].z, mhi), mlo), o3 = hsub2_bf16(hsub2_bf16(v[i].w, mhi), mlo);
            asm volatile("st.shared.v4.b32 [%0], {%1, %2, %3, %4};" ::"r"(sA + (c >> 3) * 8192 + row * 128 + (((c & 7) ^ (row & 7)) << 4)), "r"(o0), "r"(o1), "r"(o2), "r"(o3) : "memory");
        }
    }
    proxy_fence();
    named_sync(1, 256);
    if (tid == 0) TS(0, 1);
    const int wg = warp >> 2, w = warp & 3, g = lane >> 2, t = lane & 3;
    const float rs0 = s_rstd[w * 16 + g], rs1 = s_rstd[w * 16 + g + 8];
    if (isQ) {
        const float c0 = rs0 * Q_SCALE, c1 = rs1 * Q_SCALE;
        if (wg == 0) {
            float acc[64];
            proj_mma<128, false>(acc, sA, sB, 0, fullB, emptyB, 0, lane);
            if (tid == 0) TS(0, 2);
            named_sync(1, 256);
            uint32_t pk[32];
#pragma unroll
            for (int i = 0; i < 16; i++) { pk[2 * i] = pack_bf16(acc[4 * i] * c0, acc[4 * i + 1] * c0); pk[2 * i + 1] = pack_bf16(acc[4 * i + 2] * c1, acc[4 * i + 3] * c1); }
            stage_tile<16>(pk, sA, w, lane);
        } else {
            float acc[32];
            proj_mma<64, false>(acc, sA, sB, 2 * 8192, fullB, emptyB, 0, lane);
            named_sync(1, 256);
            uint32_t pk[16];
#pragma unroll
            for (int i = 0; i < 8; i++) { pk[2 * i] = pack_bf16(acc[4 * i] * c0, acc[4 * i + 1] * c0); pk[2 * i + 1] = pack_bf16(acc[4 * i + 2] * c1, acc[4 * i + 3] * c1); }
            stage_tile<8>(pk, sA + 2 * 8192, w, lane);
        }
        proxy_fence();
        named_sync(1, 256);
        if (warp == 0 && elect_one()) {
            for (int a = 0; a < 3; a++) tma_st_2d(&tmQ, cg * 192 + a * 64, m * 64, sA + a * 8192);
            bulk_commit();
            bulk_wait_all();
        }
    } else {
        float acc[12];
        const uint32_t blo = desc_lo(sB + wg * 3 * 9216, 128);
#pragma unroll
        for (int i = 0; i < 12; i++) acc[i] = 0.f;
        pin(acc);
        wg_fence();
#pragma unroll 1
        for (int kb = 0; kb < 9; kb++) {
            const uint32_t alo = desc_lo(sA + kb * 8192, 16);
#pragma unroll
            for (int ks = 0; ks < 4; ks++)
                wgmma_ss_n24<1>(acc, desc64(alo + ks * 2, HI_SW128), desc64(blo + (kb * 4 + ks) * 16, desc_hi(9216, 0)), 1);
        }
        wg_commit();
        wg_wait<0>();
        pin(acc);
        uint32_t pk[6];
#pragma unroll
        for (int b = 0; b < 3; b++) { pk[2 * b] = pack_bf16(acc[4 * b] * rs0, acc[4 * b + 1] * rs0); pk[2 * b + 1] = pack_bf16(acc[4 * b + 2] * rs1, acc[4 * b + 3] * rs1); }
        float n0 = 0.f, n1 = 0.f, vm = 0.f;
#pragma unroll
        for (int b = 0; b < 3; b++) {
            if (b < 2 || t == 0) {
                const float a = bf_lo(pk[2 * b]), c = bf_hi(pk[2 * b]), d = bf_lo(pk[2 * b + 1]), e = bf_hi(pk[2 * b + 1]);
                n0 = fmaf(a, a, fmaf(c, c, n0)); n1 = fmaf(d, d, fmaf(e, e, n1));
            }
        }
        n0 += __shfl_xor_sync(~0u, n0, 1); n0 += __shfl_xor_sync(~0u, n0, 2);
        n1 += __shfl_xor_sync(~0u, n1, 1); n1 += __shfl_xor_sync(~0u, n1, 2);
        vm = fmaxf(n0, n1);
        if (!(n0 == n0) || !(n1 == n1)) vm = __int_as_float(0x7F800000);
#pragma unroll
        for (int o = 4; o < 32; o <<= 1) vm = fmaxf(vm, __shfl_xor_sync(~0u, vm, o));
        if (t != 0) {
            uint32_t lo, hi;
            if (wg == 0) {
                const int grp = m * 8 + w * 2;
                const uint32_t c = t == 1 ? 0x42FE3F80u   : (t == 2 ? 0x00003BC0u   : 0u);
                lo = ((POLY_MASK >> (grp & 15)) & 1) ? c : 0u;
                hi = ((POLY_MASK >> ((grp + 1) & 15)) & 1) ? c : 0u;
            } else {
                lo = hi = t == 1 ? 0x00003F80u : 0u;
            }
            pk[4] = lo; pk[5] = hi;
        }
        uint32_t* dst = reinterpret_cast<uint32_t*>(wg == 0 ? g_kc : g_vc) + (m * 8 + w * 2) * 96 + g * 4 + t;
#pragma unroll
        for (int b = 0; b < 3; b++) { dst[b * 32] = pk[2 * b]; dst[96 + b * 32] = pk[2 * b + 1]; }
        float* red = s_rstd + 64;
        if (lane == 0) red[warp] = (wg == 0) ? vm : (vm <= 1e24f ? 0.f : __int_as_float(0x7F800000));
        named_sync(1, 256);
        if (tid == 0) {
            float mx = red[0];
#pragma unroll
            for (int i = 1; i < 8; i++) mx = fmaxf(mx, red[i]);
            g_kmax[m] = mx;
        }
    }
    if (tid == 0) TS(0, 3);
}

constexpr int A_THREADS = 512;
constexpr int A_NPIECE = 8;
constexpr int A_OFF_Q = 2 * KV_BYTES;
constexpr int A_OFF_BAR = A_OFF_Q + 4 * 4096;
constexpr int A_SMEM = A_OFF_BAR + 128;

__device__ __forceinline__ uint32_t exp2_pair_fixed(float lo, float hi) {
    const uint32_t G = __byte_perm(__float_as_uint(lo), __float_as_uint(hi), 0x5410);
    const uint32_t Hh = G & 0x007F007Fu;
    const uint32_t tt = hfma2(Hh, 0xF96BF96Bu, 0x358C358Cu);
    return G - hfma2(tt, Hh, 0u);
}

__global__ void __launch_bounds__(A_THREADS, 1)
k_attn() {
    extern __shared__ __align__(1024) uint8_t smem[];
    pdl_launch();
    const uint32_t sK = smem_u32(smem), sV = sK + KV_BYTES, bars = sK + A_OFF_BAR;
    const int tid = threadIdx.x;
    check_smem_base(sK);
    if (tid == 0) TS(1, 0);
    if (tid == 0) {
        for (int i = 0; i < A_NPIECE; i++) mbar_init(bars + i * 8, 1);
        bar_init_fence();
    }
    __syncthreads();
    pdl_wait();
    if (tid == 0) TS(1, 1);
    const int wg = __shfl_sync(~0u, tid >> 7, 0), w = (tid >> 5) & 3, lane = tid & 31, g = lane >> 2, t = lane & 3;
    const uint32_t* q32 = reinterpret_cast<const uint32_t*>(g_q);
    int row = (blockIdx.x * 8 + wg) * 64 + w * 16 + g;
    uint32_t nq[6];
    nq[0] = q32[row * 9 + t]; nq[1] = q32[(row + 8) * 9 + t]; nq[2] = q32[row * 9 + 4 + t]; nq[3] = q32[(row + 8) * 9 + 4 + t];
    nq[4] = q32[row * 9 + 8]; nq[5] = q32[(row + 8) * 9 + 8];
    constexpr int PB = KV_BYTES / A_NPIECE;
    const float kmax_raw = g_kmax[lane];
    if (tid < 32 && elect_one()) {
        for (int i = 0; i < 2; i++) {
            mbar_expect(bars + i * 8, 2 * PB);
            bulk_g2s(sK + i * PB, reinterpret_cast<const char*>(g_kc) + i * PB, PB, bars + i * 8);
            bulk_g2s(sV + i * PB, reinterpret_cast<const char*>(g_vc) + i * PB, PB, bars + i * 8);
        }
    }
    float kmax2 = kmax_raw;
#pragma unroll
    for (int o = 1; o < 32; o <<= 1) kmax2 = fmaxf(kmax2, __shfl_xor_sync(~0u, kmax2, o));
    if (tid < 32 && elect_one()) {
        for (int i = 2; i < A_NPIECE; i++) {
            mbar_expect(bars + i * 8, 2 * PB);
            bulk_g2s(sK + i * PB, reinterpret_cast<const char*>(g_kc) + i * PB, PB, bars + i * 8);
            bulk_g2s(sV + i * PB, reinterpret_cast<const char*>(g_vc) + i * PB, PB, bars + i * 8);
        }
    }
    const uint32_t sQ = sK + A_OFF_Q + wg * 4096 + (w * 2) * 512 + g * 16 + t * 4;
    const uint64_t dQ0 = cdesc(A_OFF_Q, 128, 512, 0) + wg * 256, dQ1 = dQ0 + 16;
#pragma unroll 1
    for (int rep = 0; rep < 2; rep++, row += 256) {
        const uint32_t qa[4] = {nq[0], nq[1], nq[2], nq[3]};
        float n0, n1;
        {
            const float a0 = bf_lo(qa[0]), a1 = bf_hi(qa[0]), a2 = bf_lo(qa[2]), a3 = bf_hi(qa[2]);
            const float b0 = bf_lo(qa[1]), b1 = bf_hi(qa[1]), b2 = bf_lo(qa[3]), b3 = bf_hi(qa[3]);
            n0 = a0 * a0 + a1 * a1 + a2 * a2 + a3 * a3; n1 = b0 * b0 + b1 * b1 + b2 * b2 + b3 * b3;
            if (t == 0) {
                const float c0 = bf_lo(nq[4]), c1 = bf_hi(nq[4]), d0 = bf_lo(nq[5]), d1 = bf_hi(nq[5]);
                n0 += c0 * c0 + c1 * c1; n1 += d0 * d0 + d1 * d1;
            }
            n0 += __shfl_xor_sync(~0u, n0, 1); n0 += __shfl_xor_sync(~0u, n0, 2);
            n1 += __shfl_xor_sync(~0u, n1, 1); n1 += __shfl_xor_sync(~0u, n1, 2);
        }
        const uint32_t x0 = nq[4], x1 = nq[5];
        if (rep == 0) {
            const int nr = row + 256;
            nq[0] = q32[nr * 9 + t]; nq[1] = q32[(nr + 8) * 9 + t]; nq[2] = q32[nr * 9 + 4 + t]; nq[3] = q32[(nr + 8) * 9 + 4 + t];
            nq[4] = q32[nr * 9 + 8]; nq[5] = q32[(nr + 8) * 9 + 8];
        }
        if (tid == 0 && rep == 0) TS(1, 7);
        const bool unsafe = !(fmaxf(n0, n1) * kmax2 <= FAST_BOUND * FAST_BOUND) || !(n0 == n0) || !(n1 == n1);
        uint32_t any_unsafe;
        asm volatile("{\n.reg .pred p, q;\nsetp.ne.u32 p, %1, 0;\nbar.red.or.pred q, %2, 128, p;\nselp.u32 %0, 1, 0, q;\n}\n" : "=r"(any_unsafe) : "r"((uint32_t)unsafe), "r"(wg + 1) : "memory");
        any_unsafe = __shfl_sync(~0u, any_unsafe, 0);
        {
            const uint32_t cst = any_unsafe ? 0u : (t == 1 ? 0x3F804780u : (t == 2 ? 0x00003F80u : 0u));
            asm volatile("st.shared.b32 [%0], %1;" ::"r"(sQ), "r"(qa[0]) : "memory");
            asm volatile("st.shared.b32 [%0], %1;" ::"r"(sQ + 512), "r"(qa[1]) : "memory");
            asm volatile("st.shared.b32 [%0], %1;" ::"r"(sQ + 128), "r"(qa[2]) : "memory");
            asm volatile("st.shared.b32 [%0], %1;" ::"r"(sQ + 640), "r"(qa[3]) : "memory");
            asm volatile("st.shared.b32 [%0], %1;" ::"r"(sQ + 256), "r"(t == 0 ? x0 : cst) : "memory");
            asm volatile("st.shared.b32 [%0], %1;" ::"r"(sQ + 768), "r"(t == 0 ? x1 : cst) : "memory");
            asm volatile("st.shared.b32 [%0], %1;" ::"r"(sQ + 384), "r"(0u) : "memory");
            asm volatile("st.shared.b32 [%0], %1;" ::"r"(sQ + 896), "r"(0u) : "memory");
            proxy_fence();
            named_sync(wg + 1, 128);
        }
        if (tid == 0) TS(1, 2 + rep * 2);
        float o[12];
#pragma unroll
        for (int i = 0; i < 12; i++) o[i] = 0.f;
        pin(o);
        uint64_t dK0 = cdesc(0, 128, 384, 0), dK1 = cdesc(256, 0, 384, 0), dV = cdesc(KV_BYTES, 384, 128, 0);
        if (!any_unsafe) {
            float s[64];
#pragma unroll 1
            for (int j = 0; j < 16; j++) {
                if (rep == 0 && (j & 1) == 0) mbar_wait(bars + (j >> 1) * 8, 0);
                wg_fence();
                wgmma_ss_n128<0>(s, dQ0, dK0, 0);
                wgmma_ss_n128<0>(s, dQ1, dK1, 1);
                wg_commit();
                dK0 += 16 * 384 >> 4; dK1 += 16 * 384 >> 4;
                wg_wait<0>();
                pin(s);
                uint32_t p[32];
#pragma unroll
                for (int i = 0; i < 32; i++) {
                    if ((POLY_MASK >> (i >> 1)) & 1) p[i] = exp2_pair_fixed(s[2 * i], s[2 * i + 1]);
                    else p[i] = pack_bf16(ex2(s[2 * i]), ex2(s[2 * i + 1]));
                }
                pin(p);
                wg_fence();
#pragma unroll
                for (int k = 0; k < 8; k++) wgmma_rs_n24<1>(o, p[4 * k], p[4 * k + 1], p[4 * k + 2], p[4 * k + 3], dV + k * 48, 1);
                wg_commit();
                dV += 16 * 384 >> 4;
                wg_wait<0>();
            }
        } else {
            float s[64];
            float m0 = -INFINITY, m1 = -INFINITY;
#pragma unroll 1
            for (int j = 0; j < 16; j++) {
                if (rep == 0 && (j & 1) == 0) mbar_wait(bars + (j >> 1) * 8, 0);
                wg_fence();
                wgmma_ss_n128<0>(s, dQ0, dK0, 0);
                wgmma_ss_n128<0>(s, dQ1, dK1, 1);
                wg_commit();
                dK0 += 16 * 384 >> 4; dK1 += 16 * 384 >> 4;
                wg_wait<0>();
                pin(s);
                float x0m = m0, x1m = m1;
#pragma unroll
                for (int b = 0; b < 16; b++) { x0m = fmaxf(x0m, fmaxf(s[4 * b], s[4 * b + 1])); x1m = fmaxf(x1m, fmaxf(s[4 * b + 2], s[4 * b + 3])); }
                x0m = fmaxf(x0m, __shfl_xor_sync(~0u, x0m, 1)); x0m = fmaxf(x0m, __shfl_xor_sync(~0u, x0m, 2));
                x1m = fmaxf(x1m, __shfl_xor_sync(~0u, x1m, 1)); x1m = fmaxf(x1m, __shfl_xor_sync(~0u, x1m, 2));
                const float c0 = ex2(m0 - x0m), c1 = ex2(m1 - x1m);
                m0 = x0m; m1 = x1m;
#pragma unroll
                for (int b = 0; b < 3; b++) { o[4 * b] *= c0; o[4 * b + 1] *= c0; o[4 * b + 2] *= c1; o[4 * b + 3] *= c1; }
                uint32_t p[32];
#pragma unroll
                for (int b = 0; b < 16; b++) {
                    p[2 * b] = pack_bf16(ex2(s[4 * b] - m0), ex2(s[4 * b + 1] - m0));
                    p[2 * b + 1] = pack_bf16(ex2(s[4 * b + 2] - m1), ex2(s[4 * b + 3] - m1));
                }
                pin(p); pin(o);
                wg_fence();
#pragma unroll
                for (int k = 0; k < 8; k++) wgmma_rs_n24<1>(o, p[4 * k], p[4 * k + 1], p[4 * k + 2], p[4 * k + 3], dV + k * 48, 1);
                wg_commit();
                dV += 16 * 384 >> 4;
                wg_wait<0>();
            }
        }
        pin(o);
        if (tid == 0) TS(1, 3 + rep * 2);
        const float l0 = __shfl_sync(~0u, o[8], (lane & ~3) | 1), l1 = __shfl_sync(~0u, o[10], (lane & ~3) | 1);
        const float i0 = 1.0f / l0, i1 = 1.0f / l1;
        uint32_t* o32 = reinterpret_cast<uint32_t*>(g_o);
        o32[row * 9 + t] = pack_bf16(o[0] * i0, o[1] * i0);
        o32[(row + 8) * 9 + t] = pack_bf16(o[2] * i1, o[3] * i1);
        o32[row * 9 + 4 + t] = pack_bf16(o[4] * i0, o[5] * i0);
        o32[(row + 8) * 9 + 4 + t] = pack_bf16(o[6] * i1, o[7] * i1);
        if (t == 0) { o32[row * 9 + 8] = pack_bf16(o[8] * i0, o[9] * i0); o32[(row + 8) * 9 + 8] = pack_bf16(o[10] * i1, o[11] * i1); }
    }
    if (tid == 0) TS(1, 6);
    if ((tid & 127) == 0) TS(1, 10 + wg);
}

constexpr int O_THREADS = 416;
constexpr int O_OFF_STAT = P_A_BYTES + P_NST * P_B_STAGE + 256;
constexpr int O_SMEM = O_OFF_STAT + 9 * 64 * 8;

__global__ void __cluster_dims__(3, 1, 1) __launch_bounds__(O_THREADS, 1)
k_oproj(const __grid_constant__ CUtensorMap tmO, const __grid_constant__ CUtensorMap tmWo, const __grid_constant__ CUtensorMap tmX2, const __grid_constant__ CUtensorMap tmOut, const __nv_bfloat16* __restrict__ x) {
    extern __shared__ __align__(1024) uint8_t smem[];
    const uint32_t sA = smem_u32(smem), sB = sA + P_A_BYTES, bars = sB + P_NST * P_B_STAGE;
    const uint32_t fullB = bars, emptyB = bars + 64, fullA = bars + 128;
    const int tid = threadIdx.x, warp = __shfl_sync(~0u, tid >> 5, 0), lane = tid & 31;
    const int m = blockIdx.x / 3, cg = blockIdx.x % 3;
    if (tid == 0) TS(2, 0);
    check_smem_base(sA);
    if (tid == 0) {
        prefetch_map(&tmO); prefetch_map(&tmWo); prefetch_map(&tmX2); prefetch_map(&tmOut);
        for (int i = 0; i < P_NST; i++) { mbar_init(fullB + i * 8, 1); mbar_init(emptyB + i * 8, 12); }
        for (int i = 0; i < 9; i++) mbar_init(fullA + i * 8, 1);
        bar_init_fence();
        for (int kb = 0; kb < 9; kb++) mbar_expect(fullA + kb * 8, 8192);
    }
    __syncthreads();
    pdl_launch();
    if (warp == 12) {
        if (elect_one()) {
            for (int kb = 0; kb < 9; kb++) {
                const int s = kb >= P_NST ? kb - P_NST : kb;
                if (kb == 2) {
                    pdl_wait();
                    TS(2, 1);
                    for (int ka = 0; ka < 9; ka++) tma_2d(sA + ka * 8192, &tmO, ka * 64, m * 64, fullA + ka * 8);
                }
                if (kb >= P_NST) mbar_wait(emptyB + s * 8, 0);
                mbar_expect(fullB + s * 8, P_B_STAGE);
                for (int a = 0; a < 3; a++) tma_2d(sB + s * P_B_STAGE + a * 8192, &tmWo, cg * 192 + a * 64, kb * 64, fullB + s * 8);
            }
        }
        return;
    }
    if (tid == 0) TS(2, 11);
    const int wg = warp >> 2, w = warp & 3, g = lane >> 2, t = lane & 3;
    uint32_t xr[16];
    {
        const uint32_t* x32 = reinterpret_cast<const uint32_t*>(x) + (((m * 64 + w * 16 + g) * DM + cg * 192 + wg * 64 + 2 * t) >> 1);
#pragma unroll
        for (int b = 0; b < 8; b++) { xr[2 * b] = __ldg(x32 + b * 4); xr[2 * b + 1] = __ldg(x32 + b * 4 + 4 * DM); }
    }
    float acc[32];
    {
        const uint64_t dA = cdesc(0, 16, 1024, 1), dB = cdesc(P_A_BYTES, 8192, 1024, 1) + wg * 512;
#pragma unroll 1
        for (int kb = 0; kb < 9; kb++) {
            const int s = kb >= P_NST ? kb - P_NST : kb;
            mbar_wait(fullA + kb * 8, 0);
            mbar_wait(fullB + s * 8, kb >= P_NST ? 1 : 0);
            wg_fence();
#pragma unroll
            for (int ks = 0; ks < 4; ks++) wgmma_ss_n64<1>(acc, dA + (kb * 512 + ks * 2), dB + (s * (P_B_STAGE >> 4) + ks * 128), (kb | ks) != 0);
            wg_commit();
            if (kb < 4) {
                wg_wait<1>();
                if (kb >= 1 && lane == 0) mbar_arrive(emptyB + (kb - 1) * 8);
            }
        }
        wg_wait<0>();
        pin(acc);
    }
    if (tid == 0) TS(2, 2);
    named_sync(1, 384);
    float s0 = 0.f, q0 = 0.f, s1 = 0.f, q1 = 0.f;
#pragma unroll
    for (int b = 0; b < 8; b++) {
        const uint32_t xa = xr[2 * b], xb = xr[2 * b + 1];
        const uint32_t ha = pack_bf16(acc[4 * b] + bf_lo(xa), acc[4 * b + 1] + bf_hi(xa));
        const uint32_t hb = pack_bf16(acc[4 * b + 2] + bf_lo(xb), acc[4 * b + 3] + bf_hi(xb));
        xr[2 * b] = ha; xr[2 * b + 1] = hb;
        const float a = bf_lo(ha), c = bf_hi(ha), d = bf_lo(hb), e = bf_hi(hb);
        s0 += a + c; q0 = fmaf(a, a, fmaf(c, c, q0));
        s1 += d + e; q1 = fmaf(d, d, fmaf(e, e, q1));
    }
    s0 += __shfl_xor_sync(~0u, s0, 1); s0 += __shfl_xor_sync(~0u, s0, 2);
    q0 += __shfl_xor_sync(~0u, q0, 1); q0 += __shfl_xor_sync(~0u, q0, 2);
    s1 += __shfl_xor_sync(~0u, s1, 1); s1 += __shfl_xor_sync(~0u, s1, 2);
    q1 += __shfl_xor_sync(~0u, q1, 1); q1 += __shfl_xor_sync(~0u, q1, 2);
    const int r = w * 16 + g;
    const uint32_t sStat = sA + O_OFF_STAT;
    if (t < 3) {
        uint32_t dst;
        asm("mapa.shared::cluster.u32 %0, %1, %2;" : "=r"(dst) : "r"(sStat + ((cg * 3 + wg) * 64 + r) * 8), "r"(t));
        asm volatile("st.shared::cluster.v2.f32 [%0], {%1, %2};" ::"r"(dst), "f"(s0), "f"(q0) : "memory");
        asm volatile("st.shared::cluster.v2.f32 [%0], {%1, %2};" ::"r"(dst + 64), "f"(s1), "f"(q1) : "memory");
    }
    if (tid == 0) TS(2, 4);
    cluster_arrive();
    stage_tile<8>(xr, sA + wg * 8192, w, lane);
    proxy_fence();
    named_sync(2 + wg, 128);
    const bool leader = w == 0 && elect_one();
    if (leader) { tma_st_2d(&tmOut, cg * 192 + wg * 64, m * 64, sA + wg * 8192); bulk_commit(); }
    cluster_wait();
    if (tid == 0) TS(2, 5);
    s0 = q0 = s1 = q1 = 0.f;
#pragma unroll
    for (int p = 0; p < 9; p++) {
        float a, b, c, d;
        asm volatile("ld.shared.v2.f32 {%0, %1}, [%2];" : "=f"(a), "=f"(b) : "r"(sStat + (p * 64 + r) * 8));
        asm volatile("ld.shared.v2.f32 {%0, %1}, [%2];" : "=f"(c), "=f"(d) : "r"(sStat + (p * 64 + r + 8) * 8));
        s0 += a; q0 += b; s1 += c; q1 += d;
    }
    const float m0 = s0 * (1.0f / DM), m1 = s1 * (1.0f / DM);
    const float rs0 = rsqrtf(fmaxf(q0 * (1.0f / DM) - m0 * m0, 0.f) + LN_EPS), rs1 = rsqrtf(fmaxf(q1 * (1.0f / DM) - m1 * m1, 0.f) + LN_EPS);
    const float sc0 = -LOG2E * rs0, sc1 = -LOG2E * rs1, n0 = -m0 * sc0, n1 = -m1 * sc1;
#pragma unroll
    for (int b = 0; b < 8; b++) {
        xr[2 * b] = pack_bf16(fmaf(bf_lo(xr[2 * b]), sc0, n0), fmaf(bf_hi(xr[2 * b]), sc0, n0));
        xr[2 * b + 1] = pack_bf16(fmaf(bf_lo(xr[2 * b + 1]), sc1, n1), fmaf(bf_hi(xr[2 * b + 1]), sc1, n1));
    }
    stage_tile<8>(xr, sA + (3 + wg) * 8192, w, lane);
    proxy_fence();
    named_sync(2 + wg, 128);
    if (tid == 0) TS(2, 6);
    if (leader) {
        tma_st_2d(&tmX2, cg * 192 + wg * 64, m * 64, sA + (3 + wg) * 8192);
        bulk_commit();
        bulk_wait_all();
    }
    if (tid == 0) TS(2, 3);
}

constexpr int F_THREADS = 384;
constexpr int F_NST = 6;
constexpr int F_STAGE = 96 * 128;
constexpr int F_X_BYTES = 9 * 16384;
constexpr int F_OFF_ST = F_X_BYTES;
constexpr int F_OFF_BAR = F_OFF_ST + F_NST * F_STAGE;
constexpr int F_SMEM = F_OFF_BAR + 256;

__device__ __forceinline__ float after_issue(float v, uint32_t tick) {
    uint32_t r;
    asm("lop3.b32 %0, %1, %1, %2, 0xF0;" : "=r"(r) : "r"(__float_as_uint(v)), "r"(tick));
    return __uint_as_float(r);
}
__device__ __forceinline__ uint32_t read_tick() { uint32_t c; asm volatile("mov.u32 %0, %%clock;" : "=r"(c)::"memory"); return c; }
__device__ __forceinline__ void silu_s1(const float (&acc)[32], float (&tmp)[8], int piece) {
#pragma unroll
    for (int i = 0; i < 8; i++) tmp[i] = ex2(acc[8 * piece + i]);
}
__device__ __forceinline__ void silu_s2(float (&tmp)[8], uint32_t tick) {
    const float one = after_issue(1.0f, tick);
#pragma unroll
    for (int i = 0; i < 8; i++) tmp[i] = rcp(tmp[i] + one);
}
template <int C>
__device__ __forceinline__ void silu_s3(const float (&acc)[32], const float (&tmp)[8], uint32_t (&h1)[144], int piece) {
#pragma unroll
    for (int i = 0; i < 4; i++) h1[C * 16 + 4 * piece + i] = pack_bf16(acc[8 * piece + 2 * i] * tmp[2 * i], acc[8 * piece + 2 * i + 1] * tmp[2 * i + 1]);
}

struct FfnPipe {
    uint32_t full, empty;
    int lane;
    __device__ __forceinline__ void acquire(int s, uint32_t ph) const { mbar_wait(full + s * 8, ph); }
    __device__ __forceinline__ void release(int s) const { if (lane == 0) mbar_arrive(empty + s * 8); }
};

template <int C>
__device__ __forceinline__ void ffn_phase1_chunk(float (&cur)[32], float (&prev)[32], uint32_t (&h1)[144], const FfnPipe& pp, uint64_t dx, uint32_t fullX) {
    float tmp[2][8];
    const uint64_t dw = cdesc(F_OFF_ST, 8192, 1024, 1) + blockIdx.y * (C + 1);
    dx += blockIdx.y * C;
#pragma unroll
    for (int j = 0; j < 6; j++) {
        if (C == 0) { mbar_wait(fullX + ((6 * j) >> 2) * 8, 0); mbar_wait(fullX + ((6 * j + 5) >> 2) * 8, 0); }
        pp.acquire(j, C & 1);
        if (j == 0) pin(cur);
        wg_fence();
#pragma unroll
        for (int i = 0; i < 6; i++) {
            const int ks = 6 * j + i;
            wgmma_ss_n64<1>(cur, dx + ((ks >> 2) * 1024 + (ks & 3) * 2), dw + ((j * F_STAGE + i * 2048) >> 4), ks != 0);
        }
        wg_commit();
        if (C > 0 || j > 0) { wg_wait<1>(); pp.release((j + 5) % 6); }
        if (C > 0) {
            pin(prev);
            if (j >= 1) { pin(tmp[0]); if (j >= 2) pin(tmp[1]); }
            if (j >= 2) silu_s3<(C > 0 ? C - 1 : 0)>(prev, tmp[j & 1], h1, j - 2);
            if (j >= 1 && j <= 4) { silu_s2(tmp[(j - 1) & 1], read_tick()); pin(tmp[(j - 1) & 1]); }
            if (j <= 3) { silu_s1(prev, tmp[j & 1], j); pin(tmp[j & 1]); }
            if (j >= 2) { asm volatile("" : "+r"(h1[(C - 1) * 16 + 4 * (j - 2)]), "+r"(h1[(C - 1) * 16 + 4 * (j - 2) + 1]), "+r"(h1[(C - 1) * 16 + 4 * (j - 2) + 2]), "+r"(h1[(C - 1) * 16 + 4 * (j - 2) + 3]) :: "memory"); }
        }
    }
}

__device__ __forceinline__ void ffn_store_chunk(const float (&acc)[32], const CUtensorMap* tmOut, uint32_t stg, int col, int row, int w, int lane, int wgid, bool leader) {
    uint32_t pk[16];
#pragma unroll
    for (int i = 0; i < 16; i++) pk[i] = pack_bf16(acc[2 * i] * -LN2, acc[2 * i + 1] * -LN2);
    stage_tile<8>(pk, stg, w, lane);
    proxy_fence();
    named_sync(2 + wgid, 128);
    if (leader) {
        tma_red_2d(tmOut, col, row, stg);
        bulk_commit();
    }
}

__device__ __forceinline__ void ffn_phase2_chunk(float (&cur)[32], float (&prev)[32], uint32_t (&h1)[144], const FfnPipe& pp, uint32_t ph, bool store_prev, const CUtensorMap* tmOut, uint32_t stg_prev, int col_prev, int row, int w, int lane, int wgid, bool leader) {
    const uint64_t dw = cdesc(F_OFF_ST, 8192, 1024, 1) + blockIdx.y * col_prev;
#pragma unroll
    for (int j = 0; j < 6; j++) {
        pp.acquire(j, ph);
        if (j == 0) pin(cur);
        wg_fence();
#pragma unroll
        for (int i = 0; i < 6; i++) {
            const int f = (6 * j + i) * 4;
            wgmma_rs_n64<1>(cur, h1[f], h1[f + 1], h1[f + 2], h1[f + 3], dw + ((j * F_STAGE + i * 2048) >> 4), (j | i) != 0);
        }
        wg_commit();
        if (j > 0 || store_prev) { wg_wait<1>(); pp.release((j + 5) % 6); }
        if (j == 0 && store_prev) { pin(prev); ffn_store_chunk(prev, tmOut, stg_prev, col_prev, row, w, lane, wgid, leader); }
    }
}

__global__ void __launch_bounds__(F_THREADS, 1)
k_ffn(const __grid_constant__ CUtensorMap tmH, const __grid_constant__ CUtensorMap tmW1, const __grid_constant__ CUtensorMap tmW2, const __grid_constant__ CUtensorMap tmOut) {
    extern __shared__ __align__(1024) uint8_t smem[];
    const uint32_t sX = smem_u32(smem), sSt = sX + F_OFF_ST, bars = sX + F_OFF_BAR;
    const uint32_t full = bars, empty = bars + 64, fullX = bars + 128;
    const int tid = threadIdx.x, warp = __shfl_sync(~0u, tid >> 5, 0), lane = tid & 31;
#define FFN_MAP 0
    const int m = FFN_MAP == 0 ? (blockIdx.x & 15) : (FFN_MAP == 1 ? (blockIdx.x >> 3) : ((blockIdx.x >> 1) & 15));
    const int fs = FFN_MAP == 0 ? (blockIdx.x >> 4) : (FFN_MAP == 1 ? (blockIdx.x & 7) : ((blockIdx.x >> 5) * 2 + (blockIdx.x & 1)));
    if (tid == 0) TS(3, 0);
    check_smem_base(sX);
    if (tid == 0) {
        prefetch_map(&tmW1); prefetch_map(&tmH); prefetch_map(&tmW2); prefetch_map(&tmOut);
        for (int i = 0; i < F_NST; i++) { mbar_init(full + i * 8, 1); mbar_init(empty + i * 8, 8); }
        for (int i = 0; i < 9; i++) mbar_init(fullX + i * 8, 1);
        bar_init_fence();
        for (int kb = 0; kb < 9; kb++) mbar_expect(fullX + kb * 8, 16384);
    }
    __syncthreads();
    if (warp < 4) {
        asm volatile("setmaxnreg.dec.sync.aligned.u32 24;");
        if (warp == 0 && elect_one()) {
            int s = 0; uint32_t ph = 1;
            int c = 0, j = 0;
#pragma unroll 1
            for (int i = 0; i < 108; i++) {
                if (i == 54) c = fs;
                mbar_wait(empty + s * 8, ph);
                mbar_expect(full + s * 8, F_STAGE);
                if (i < 54) tma_2d(sSt + s * F_STAGE, &tmW1, fs * 576 + c * 64, j * 96, full + s * 8);
                else tma_2d(sSt + s * F_STAGE, &tmW2, c * 64, fs * 576 + j * 96, full + s * 8);
                if (++j == 6) { j = 0; if (++c == 9) c = 0; }
                if (++s == F_NST) { s = 0; ph ^= 1; }
            }
        }
    } else {
        asm volatile("setmaxnreg.inc.sync.aligned.u32 240;");
        const int wgid = (warp >> 2) - 1, w = warp & 3;
        pdl_wait();
        if (tid == 128) TS(3, 1);
        if (warp == 4 && elect_one()) {
            for (int kb = 0; kb < 9; kb++) tma_2d(sX + kb * 16384, &tmH, kb * 64, m * 128, fullX + kb * 8);
        }
        __syncwarp();
        FfnPipe pp{full, empty, lane};
        const uint64_t xlo = cdesc(0, 16, 1024, 1) + wgid * 512;
        uint32_t h1[144];
        float acc0[32], acc1[32];
        ffn_phase1_chunk<0>(acc0, acc1, h1, pp, xlo, fullX);
        if (tid == 128) TS(3, 2);
        ffn_phase1_chunk<1>(acc1, acc0, h1, pp, xlo, fullX);
        ffn_phase1_chunk<2>(acc0, acc1, h1, pp, xlo, fullX);
        ffn_phase1_chunk<3>(acc1, acc0, h1, pp, xlo, fullX);
        ffn_phase1_chunk<4>(acc0, acc1, h1, pp, xlo, fullX);
        ffn_phase1_chunk<5>(acc1, acc0, h1, pp, xlo, fullX);
        ffn_phase1_chunk<6>(acc0, acc1, h1, pp, xlo, fullX);
        ffn_phase1_chunk<7>(acc1, acc0, h1, pp, xlo, fullX);
        ffn_phase1_chunk<8>(acc0, acc1, h1, pp, xlo, fullX);
        wg_wait<0>();
        pp.release(5);
        pin(acc0);
        {
            float tmp[4][8];
#pragma unroll
            for (int p = 0; p < 4; p++) silu_s1(acc0, tmp[p], p);
#pragma unroll
            for (int p = 0; p < 4; p++) silu_s2(tmp[p], 0);
#pragma unroll
            for (int p = 0; p < 4; p++) silu_s3<8>(acc0, tmp[p], h1, p);
        }
        pin(h1);
        if (tid == 128) TS(3, 3);
        const int row = m * 128 + wgid * 64;
        const uint32_t stg = sX + wgid * 8192;
        int c = fs, cprev = 0;
        const bool leader = w == 0 && elect_one();
#pragma unroll 1
        for (int j = 0; j < 8; j += 2) {
            ffn_phase2_chunk(acc1, acc0, h1, pp, 1, j > 0, &tmOut, stg + (j - 1) * 16384, cprev * 64, row, w, lane, wgid, leader);
            cprev = c; if (++c == 9) c = 0;
            ffn_phase2_chunk(acc0, acc1, h1, pp, 0, true, &tmOut, stg + j * 16384, cprev * 64, row, w, lane, wgid, leader);
            cprev = c; if (++c == 9) c = 0;
        }
        ffn_phase2_chunk(acc1, acc0, h1, pp, 1, true, &tmOut, stg + 7 * 16384, cprev * 64, row, w, lane, wgid, leader);
        wg_wait<0>();
        pin(acc1);
        ffn_store_chunk(acc1, &tmOut, stg + 8 * 16384, c * 64, row, w, lane, wgid, leader);
        if (tid == 128) TS(3, 4);
        if (leader) bulk_wait_all();
        if (tid == 128) TS(3, 5);
    }
}

typedef CUresult (*EncodeFn)(CUtensorMap*, CUtensorMapDataType, cuuint32_t, void*, const cuuint64_t*, const cuuint64_t*, const cuuint32_t*, const cuuint32_t*,
                             CUtensorMapInterleave, CUtensorMapSwizzle, CUtensorMapL2promotion, CUtensorMapFloatOOBfill);

CUtensorMap make_map(EncodeFn enc, const void* base, int rows, int cols, int box_rows) {
    CUtensorMap tm;
    cuuint64_t dims[2] = {(cuuint64_t)cols, (cuuint64_t)rows};
    cuuint64_t strides[1] = {(cuuint64_t)cols * 2};
    cuuint32_t box[2] = {64, (cuuint32_t)box_rows};
    cuuint32_t es[2] = {1, 1};
    enc(&tm, CU_TENSOR_MAP_DATA_TYPE_BFLOAT16, 2, const_cast<void*>(base), dims, strides, box, es, CU_TENSOR_MAP_INTERLEAVE_NONE,
        CU_TENSOR_MAP_SWIZZLE_128B, CU_TENSOR_MAP_L2_PROMOTION_L2_256B, CU_TENSOR_MAP_FLOAT_OOB_FILL_NONE);
    return tm;
}

template <typename... KArgs, typename... Args>
void launch(void (*kern)(KArgs...), int grid, int block, int smem, bool pdl, Args... args) {
    cudaLaunchConfig_t cfg = {};
    cfg.gridDim = dim3(grid); cfg.blockDim = dim3(block); cfg.dynamicSmemBytes = smem; cfg.stream = cudaStreamPerThread;
    cudaLaunchAttribute at[1];
    at[0].id = cudaLaunchAttributeProgrammaticStreamSerialization;
    at[0].val.programmaticStreamSerializationAllowed = 1;
    cfg.attrs = at; cfg.numAttrs = pdl ? 1 : 0;
    cudaLaunchKernelEx(&cfg, kern, KArgs(args)...);
}

}

#define USE_PDL 1

extern "C" void kernel_launch(void* const* d_in, const int* in_sizes, int n_in, void* d_out, int out_size) {
    const __nv_bfloat16* x = (const __nv_bfloat16*)d_in[0];
    const __nv_bfloat16* wq = (const __nv_bfloat16*)d_in[1];
    const __nv_bfloat16* wk = (const __nv_bfloat16*)d_in[2];
    const __nv_bfloat16* wv = (const __nv_bfloat16*)d_in[3];
    const __nv_bfloat16* wo = (const __nv_bfloat16*)d_in[4];
    const __nv_bfloat16* w1 = (const __nv_bfloat16*)d_in[6];
    const __nv_bfloat16* w2 = (const __nv_bfloat16*)d_in[7];
    __nv_bfloat16* out = (__nv_bfloat16*)d_out;

    static EncodeFn enc = nullptr;
    static void *p_o = nullptr, *p_h = nullptr, *p_q = nullptr;
    if (!enc) {
        cudaDriverEntryPointQueryResult qr;
        cudaGetDriverEntryPoint("cuTensorMapEncodeTiled", (void**)&enc, cudaEnableDefault, &qr);
        cudaGetSymbolAddress(&p_o, g_o);
        cudaGetSymbolAddress(&p_h, g_x2);
        cudaGetSymbolAddress(&p_q, g_q);
        cudaFuncSetAttribute(k_qkv, cudaFuncAttributeMaxDynamicSharedMemorySize, P_SMEM);
        cudaFuncSetAttribute(k_attn, cudaFuncAttributeMaxDynamicSharedMemorySize, A_SMEM);
        cudaFuncSetAttribute(k_oproj, cudaFuncAttributeMaxDynamicSharedMemorySize, O_SMEM);
        cudaFuncSetAttribute(k_ffn, cudaFuncAttributeMaxDynamicSharedMemorySize, F_SMEM);
    }
    const CUtensorMap tmWq = make_map(enc, wq, DM, DM, 64);
    const CUtensorMap tmWo = make_map(enc, wo, DM, DM, 64);
    const CUtensorMap tmO = make_map(enc, p_o, SEQ, DM, 64);
    const CUtensorMap tmH64 = make_map(enc, p_h, SEQ, DM, 64);
    const CUtensorMap tmH = make_map(enc, p_h, SEQ, DM, 128);
    const CUtensorMap tmQ = make_map(enc, p_q, SEQ, DM, 64);
    const CUtensorMap tmW1 = make_map(enc, w1, DM, FF, 96);
    const CUtensorMap tmW2 = make_map(enc, w2, FF, DM, 96);
    const CUtensorMap tmOut = make_map(enc, out, SEQ, DM, 64);

    launch(k_qkv, 128, P_THREADS, P_SMEM, false, tmWq, tmQ, x, wk, wv);
    launch(k_attn, 128, A_THREADS, A_SMEM, USE_PDL);
    launch(k_oproj, 96, O_THREADS, O_SMEM, USE_PDL, tmO, tmWo, tmH64, tmOut, x);
    launch(k_ffn, 128, F_THREADS, F_SMEM, USE_PDL, tmH, tmW1, tmW2, tmOut);
}
```

```cpp
#include <cuda_runtime.h>
#include <cuda_bf16.h>
#include <cuda.h>
#include <stdint.h>

namespace {

constexpr int SEQ = 2048, DM = 576, FF = 4608;
constexpr int KV_BYTES = SEQ * 48;
constexpr float LN_EPS = 1e-5f;
constexpr float LOG2E = 1.4426950408889634f;
constexpr float LN2 = 0.6931471805599453f;
constexpr float Q_SCALE = 0.23570226039551584f * LOG2E;

#define POLY_MASK_V 0xB5B5u
constexpr uint32_t POLY_MASK = POLY_MASK_V;
constexpr float FAST_BOUND = 60.0f;

__device__ __align__(1024) __nv_bfloat16 g_q[SEQ * DM];
__device__ __align__(1024) uint4 g_kc[KV_BYTES / 16];
__device__ __align__(1024) uint4 g_vc[KV_BYTES / 16];
__device__ __align__(16) float g_kmax[256];
__device__ __align__(1024) __nv_bfloat16 g_o[SEQ * DM];
__device__ __align__(1024) __nv_bfloat16 g_x2[SEQ * DM];

#define TS(k, i)

__device__ __forceinline__ uint32_t smem_u32(const void* p) { return (uint32_t)__cvta_generic_to_shared(p); }
__device__ __forceinline__ void wg_fence() { asm volatile("wgmma.fence.sync.aligned;" ::: "memory"); }
__device__ __forceinline__ void wg_commit() { asm volatile("wgmma.commit_group.sync.aligned;" ::: "memory"); }
template <int N> __device__ __forceinline__ void wg_wait() { asm volatile("wgmma.wait_group.sync.aligned %0;" ::"n"(N) : "memory"); }
template <int N> __device__ __forceinline__ void pin(float (&r)[N]) {
#pragma unroll
    for (int i = 0; i < N; i++) asm volatile("" : "+f"(r[i])::"memory");
}
template <int N> __device__ __forceinline__ void pin(uint32_t (&r)[N]) {
#pragma unroll
    for (int i = 0; i < N; i++) asm volatile("" : "+r"(r[i])::"memory");
}
constexpr uint32_t SMEM0 = 0x400;
__host__ __device__ constexpr uint64_t cdesc(uint32_t off, uint32_t lbo, uint32_t sbo, uint32_t swz) {
    return (uint64_t)(((SMEM0 + off) & 0x3FFFF) >> 4) | ((uint64_t)(lbo >> 4) << 16) | ((uint64_t)(sbo >> 4) << 32) | ((uint64_t)swz << 62);
}
__device__ __forceinline__ void check_smem_base(uint32_t base) { if ((base & 0x3FFFF) != SMEM0) __trap(); }

__device__ __forceinline__ void mbar_init(uint32_t bar, int cnt) { asm volatile("mbarrier.init.shared::cta.b64 [%0], %1;" ::"r"(bar), "r"(cnt) : "memory"); }
__device__ __forceinline__ void mbar_expect(uint32_t bar, int bytes) { asm volatile("mbarrier.arrive.expect_tx.shared::cta.b64 _, [%0], %1;" ::"r"(bar), "r"(bytes) : "memory"); }
__device__ __forceinline__ void mbar_arrive(uint32_t bar) { asm volatile("mbarrier.arrive.shared::cta.b64 _, [%0];" ::"r"(bar) : "memory"); }
__device__ __forceinline__ void mbar_wait(uint32_t bar, uint32_t parity) {
    asm volatile(
        "{\n.reg .pred p;\n.reg .u32 n;\nmov.u32 n, 0;\n"
        "LAB_WAIT:\n"
        "mbarrier.try_wait.parity.shared::cta.b64 p, [%0], %1;\n"
        "@p bra DONE;\n"
        "add.u32 n, n, 1;\n"
        "setp.lt.u32 p, n, 4000000;\n"
        "@p bra LAB_WAIT;\n"
        "trap;\n"
        "DONE:\n}\n" ::"r"(bar), "r"(parity) : "memory");
}
__device__ __forceinline__ void bar_init_fence() {
    asm volatile("fence.mbarrier_init.release.cluster;" ::: "memory");
    asm volatile("fence.proxy.async.shared::cta;" ::: "memory");
}
__device__ __forceinline__ void proxy_fence() { asm volatile("fence.proxy.async.shared::cta;" ::: "memory"); }
__device__ __forceinline__ void named_sync(int id, int n) { asm volatile("bar.sync %0, %1;" ::"r"(id), "r"(n) : "memory"); }
__device__ __forceinline__ void bulk_g2s(uint32_t dst, const void* src, int bytes, uint32_t bar) {
    asm volatile("cp.async.bulk.shared::cluster.global.mbarrier::complete_tx::bytes [%0], [%1], %2, [%3];" ::"r"(dst), "l"(src), "r"(bytes), "r"(bar) : "memory");
}
__device__ __forceinline__ void tma_2d(uint32_t dst, const CUtensorMap* tm, int c0, int c1, uint32_t bar) {
    asm volatile("cp.async.bulk.tensor.2d.shared::cluster.global.mbarrier::complete_tx::bytes [%0], [%1, {%3, %4}], [%2];" ::"r"(dst), "l"(tm), "r"(bar), "r"(c0), "r"(c1) : "memory");
}
__device__ __forceinline__ void cluster_arrive() { asm volatile("barrier.cluster.arrive.release.aligned;" ::: "memory"); }
__device__ __forceinline__ void cluster_wait() { asm volatile("barrier.cluster.wait.acquire.aligned;" ::: "memory"); }
__device__ __forceinline__ void tma_red_2d(const CUtensorMap* tm, int c0, int c1, uint32_t src) {
    asm volatile("cp.reduce.async.bulk.tensor.2d.global.shared::cta.add.tile.bulk_group [%0, {%2, %3}], [%1];" ::"l"(tm), "r"(src), "r"(c0), "r"(c1) : "memory");
}
__device__ __forceinline__ void tma_st_2d(const CUtensorMap* tm, int c0, int c1, uint32_t src) {
    asm volatile("cp.async.bulk.tensor.2d.global.shared::cta.tile.bulk_group [%0, {%2, %3}], [%1];" ::"l"(tm), "r"(src), "r"(c0), "r"(c1) : "memory");
}
__device__ __forceinline__ void bulk_commit() { asm volatile("cp.async.bulk.commit_group;" ::: "memory"); }
__device__ __forceinline__ void bulk_wait_all() { asm volatile("cp.async.bulk.wait_group.read 0;" ::: "memory"); }
__device__ __forceinline__ bool elect_one() {
    uint32_t p;
    asm volatile("{\n.reg .pred P;\nelect.sync _|P, 0xffffffff;\nselp.b32 %0, 1, 0, P;\n}\n" : "=r"(p));
    return p != 0;
}
__device__ __forceinline__ void prefetch_map(const CUtensorMap* tm) { asm volatile("prefetch.tensormap [%0];" ::"l"(tm) : "memory"); }
__device__ __forceinline__ void pdl_launch() { asm volatile("griddepcontrol.launch_dependents;" ::: "memory"); }
__device__ __forceinline__ void pdl_wait() { asm volatile("griddepcontrol.wait;" ::: "memory"); }
__device__ __forceinline__ float ex2(float x) { float y; asm("ex2.approx.ftz.f32 %0, %1;" : "=f"(y) : "f"(x)); return y; }
__device__ __forceinline__ float rcp(float x) { float y; asm("rcp.approx.ftz.f32 %0, %1;" : "=f"(y) : "f"(x)); return y; }
__device__ __forceinline__ uint32_t pack_bf16(float lo, float hi) { uint32_t r; asm("cvt.rn.bf16x2.f32 %0, %1, %2;" : "=r"(r) : "f"(hi), "f"(lo)); return r; }
__device__ __forceinline__ float bf_lo(uint32_t v) { return __uint_as_float(v << 16); }
__device__ __forceinline__ float bf_hi(uint32_t v) { return __uint_as_float(v & 0xFFFF0000u); }
__device__ __forceinline__ uint32_t hfma2(uint32_t a, uint32_t b, uint32_t c) { uint32_t r; asm("fma.rn.f16x2 %0, %1, %2, %3;" : "=r"(r) : "r"(a), "r"(b), "r"(c)); return r; }
__device__ __forceinline__ void stmatrix_x4(uint32_t addr, uint32_t r0, uint32_t r1, uint32_t r2, uint32_t r3) {
    asm volatile("stmatrix.sync.aligned.m8n8.x4.shared.b16 [%0], {%1, %2, %3, %4};" ::"r"(addr), "r"(r0), "r"(r1), "r"(r2), "r"(r3) : "memory");
}

template <int TB> __device__ __forceinline__ void wgmma_ss_n24(float (&d)[12], uint64_t da, uint64_t db, int sc) {
    asm volatile("{\n.reg .pred p;\nsetp.ne.b32 p, %14, 0;\n"
        "wgmma.mma_async.sync.aligned.m64n24k16.f32.bf16.bf16 {%0, %1, %2, %3, %4, %5, %6, %7, %8, %9, %10, %11}, %12, %13, p, 1, 1, 0, %15;\n}\n"
        : "+f"(d[0]), "+f"(d[1]), "+f"(d[2]), "+f"(d[3]), "+f"(d[4]), "+f"(d[5]), "+f"(d[6]), "+f"(d[7]), "+f"(d[8]), "+f"(d[9]), "+f"(d[10]), "+f"(d[11])
        : "l"(da), "l"(db), "r"(sc), "n"(TB));
}
template <int TB> __device__ __forceinline__ void wgmma_ss_n64(float (&d)[32], uint64_t da, uint64_t db, int sc) {
    asm volatile("{\n.reg .pred p;\nsetp.ne.b32 p, %34, 0;\n"
        "wgmma.mma_async.sync.aligned.m64n64k16.f32.bf16.bf16 {%0, %1, %2, %3, %4, %5, %6, %7, %8, %9, %10, %11, %12, %13, %14, %15, %16, %17, %18, %19, %20, %21, %22, %23, %24, %25, %26, %27, %28, %29, %30, %31}, %32, %33, p, 1, 1, 0, %35;\n}\n"
        : "+f"(d[0]), "+f"(d[1]), "+f"(d[2]), "+f"(d[3]), "+f"(d[4]), "+f"(d[5]), "+f"(d[6]), "+f"(d[7]), "+f"(d[8]), "+f"(d[9]), "+f"(d[10]), "+f"(d[11]), "+f"(d[12]), "+f"(d[13]), "+f"(d[14]), "+f"(d[15]), "+f"(d[16]), "+f"(d[17]), "+f"(d[18]), "+f"(d[19]), "+f"(d[20]), "+f"(d[21]), "+f"(d[22]), "+f"(d[23]), "+f"(d[24]), "+f"(d[25]), "+f"(d[26]), "+f"(d[27]), "+f"(d[28]), "+f"(d[29]), "+f"(d[30]), "+f"(d[31])
        : "l"(da), "l"(db), "r"(sc), "n"(TB));
}
template <int TB> __device__ __forceinline__ void wgmma_ss_n128(float (&d)[64], uint64_t da, uint64_t db, int sc) {
    asm volatile("{\n.reg .pred p;\nsetp.ne.b32 p, %66, 0;\n"
        "wgmma.mma_async.sync.aligned.m64n128k16.f32.bf16.bf16 {%0, %1, %2, %3, %4, %5, %6, %7, %8, %9, %10, %11, %12, %13, %14, %15, %16, %17, %18, %19, %20, %21, %22, %23, %24, %25, %26, %27, %28, %29, %30, %31, %32, %33, %34, %35, %36, %37, %38, %39, %40, %41, %42, %43, %44, %45, %46, %47, %48, %49, %50, %51, %52, %53, %54, %55, %56, %57, %58, %59, %60, %61, %62, %63}, %64, %65, p, 1, 1, 0, %67;\n}\n"
        : "+f"(d[0]), "+f"(d[1]), "+f"(d[2]), "+f"(d[3]), "+f"(d[4]), "+f"(d[5]), "+f"(d[6]), "+f"(d[7]), "+f"(d[8]), "+f"(d[9]), "+f"(d[10]), "+f"(d[11]), "+f"(d[12]), "+f"(d[13]), "+f"(d[14]), "+f"(d[15]), "+f"(d[16]), "+f"(d[17]), "+f"(d[18]), "+f"(d[19]), "+f"(d[20]), "+f"(d[21]), "+f"(d[22]), "+f"(d[23]), "+f"(d[24]), "+f"(d[25]), "+f"(d[26]), "+f"(d[27]), "+f"(d[28]), "+f"(d[29]), "+f"(d[30]), "+f"(d[31]), "+f"(d[32]), "+f"(d[33]), "+f"(d[34]), "+f"(d[35]), "+f"(d[36]), "+f"(d[37]), "+f"(d[38]), "+f"(d[39]), "+f"(d[40]), "+f"(d[41]), "+f"(d[42]), "+f"(d[43]), "+f"(d[44]), "+f"(d[45]), "+f"(d[46]), "+f"(d[47]), "+f"(d[48]), "+f"(d[49]), "+f"(d[50]), "+f"(d[51]), "+f"(d[52]), "+f"(d[53]), "+f"(d[54]), "+f"(d[55]), "+f"(d[56]), "+f"(d[57]), "+f"(d[58]), "+f"(d[59]), "+f"(d[60]), "+f"(d[61]), "+f"(d[62]), "+f"(d[63])
        : "l"(da), "l"(db), "r"(sc), "n"(TB));
}
template <int TB> __device__ __forceinline__ void wgmma_rs_n24(float (&d)[12], uint32_t a0, uint32_t a1, uint32_t a2, uint32_t a3, uint64_t db, int sc) {
    asm volatile("{\n.reg .pred p;\nsetp.ne.b32 p, %17, 0;\n"
        "wgmma.mma_async.sync.aligned.m64n24k16.f32.bf16.bf16 {%0, %1, %2, %3, %4, %5, %6, %7, %8, %9, %10, %11}, {%12, %13, %14, %15}, %16, p, 1, 1, %18;\n}\n"
        : "+f"(d[0]), "+f"(d[1]), "+f"(d[2]), "+f"(d[3]), "+f"(d[4]), "+f"(d[5]), "+f"(d[6]), "+f"(d[7]), "+f"(d[8]), "+f"(d[9]), "+f"(d[10]), "+f"(d[11])
        : "r"(a0), "r"(a1), "r"(a2), "r"(a3), "l"(db), "r"(sc), "n"(TB));
}
template <int TB> __device__ __forceinline__ void wgmma_rs_n64(float (&d)[32], uint32_t a0, uint32_t a1, uint32_t a2, uint32_t a3, uint64_t db, int sc) {
    asm volatile("{\n.reg .pred p;\nsetp.ne.b32 p, %37, 0;\n"
        "wgmma.mma_async.sync.aligned.m64n64k16.f32.bf16.bf16 {%0, %1, %2, %3, %4, %5, %6, %7, %8, %9, %10, %11, %12, %13, %14, %15, %16, %17, %18, %19, %20, %21, %22, %23, %24, %25, %26, %27, %28, %29, %30, %31}, {%32, %33, %34, %35}, %36, p, 1, 1, %38;\n}\n"
        : "+f"(d[0]), "+f"(d[1]), "+f"(d[2]), "+f"(d[3]), "+f"(d[4]), "+f"(d[5]), "+f"(d[6]), "+f"(d[7]), "+f"(d[8]), "+f"(d[9]), "+f"(d[10]), "+f"(d[11]), "+f"(d[12]), "+f"(d[13]), "+f"(d[14]), "+f"(d[15]), "+f"(d[16]), "+f"(d[17]), "+f"(d[18]), "+f"(d[19]), "+f"(d[20]), "+f"(d[21]), "+f"(d[22]), "+f"(d[23]), "+f"(d[24]), "+f"(d[25]), "+f"(d[26]), "+f"(d[27]), "+f"(d[28]), "+f"(d[29]), "+f"(d[30]), "+f"(d[31])
        : "r"(a0), "r"(a1), "r"(a2), "r"(a3), "l"(db), "r"(sc), "n"(TB));
}
template <int TB> __device__ __forceinline__ void wgmma_rs_n128(float (&d)[64], uint32_t a0, uint32_t a1, uint32_t a2, uint32_t a3, uint64_t db, int sc) {
    asm volatile("{\n.reg .pred p;\nsetp.ne.b32 p, %69, 0;\n"
        "wgmma.mma_async.sync.aligned.m64n128k16.f32.bf16.bf16 {%0, %1, %2, %3, %4, %5, %6, %7, %8, %9, %10, %11, %12, %13, %14, %15, %16, %17, %18, %19, %20, %21, %22, %23, %24, %25, %26, %27, %28, %29, %30, %31, %32, %33, %34, %35, %36, %37, %38, %39, %40, %41, %42, %43, %44, %45, %46, %47, %48, %49, %50, %51, %52, %53, %54, %55, %56, %57, %58, %59, %60, %61, %62, %63}, {%64, %65, %66, %67}, %68, p, 1, 1, %70;\n}\n"
        : "+f"(d[0]), "+f"(d[1]), "+f"(d[2]), "+f"(d[3]), "+f"(d[4]), "+f"(d[5]), "+f"(d[6]), "+f"(d[7]), "+f"(d[8]), "+f"(d[9]), "+f"(d[10]), "+f"(d[11]), "+f"(d[12]), "+f"(d[13]), "+f"(d[14]), "+f"(d[15]), "+f"(d[16]), "+f"(d[17]), "+f"(d[18]), "+f"(d[19]), "+f"(d[20]), "+f"(d[21]), "+f"(d[22]), "+f"(d[23]), "+f"(d[24]), "+f"(d[25]), "+f"(d[26]), "+f"(d[27]), "+f"(d[28]), "+f"(d[29]), "+f"(d[30]), "+f"(d[31]), "+f"(d[32]), "+f"(d[33]), "+f"(d[34]), "+f"(d[35]), "+f"(d[36]), "+f"(d[37]), "+f"(d[38]), "+f"(d[39]), "+f"(d[40]), "+f"(d[41]), "+f"(d[42]), "+f"(d[43]), "+f"(d[44]), "+f"(d[45]), "+f"(d[46]), "+f"(d[47]), "+f"(d[48]), "+f"(d[49]), "+f"(d[50]), "+f"(d[51]), "+f"(d[52]), "+f"(d[53]), "+f"(d[54]), "+f"(d[55]), "+f"(d[56]), "+f"(d[57]), "+f"(d[58]), "+f"(d[59]), "+f"(d[60]), "+f"(d[61]), "+f"(d[62]), "+f"(d[63])
        : "r"(a0), "r"(a1), "r"(a2), "r"(a3), "l"(db), "r"(sc), "n"(TB));
}

constexpr int P_NST = 6;
constexpr int P_A_BYTES = 9 * 8192;
constexpr int P_B_STAGE = 3 * 8192;
constexpr int P_SMEM = P_A_BYTES + P_NST * P_B_STAGE + 256 + 320;

template <int NB>
__device__ __forceinline__ void stage_tile(const uint32_t (&pk)[NB * 2], uint32_t base, int w, int lane) {
    const int r = w * 16 + (lane & 7) + ((lane >> 3) & 1) * 8;
#pragma unroll
    for (int b = 0; b < NB; b += 2) {
        const uint32_t a = base + (b >> 3) * 8192 + r * 128 + ((((b & 7) + (lane >> 4)) ^ (r & 7)) << 4);
        stmatrix_x4(a, pk[2 * b], pk[2 * b + 1], pk[2 * b + 2], pk[2 * b + 3]);
    }
}

__device__ __forceinline__ uint32_t hsub2_bf16(uint32_t a, uint32_t b) { uint32_t r; asm("sub.rn.bf16x2 %0, %1, %2;" : "=r"(r) : "r"(a), "r"(b)); return r; }

constexpr int KV_RAW = DM * 18 * 2;
constexpr int Q_THREADS = 416;

__device__ __forceinline__ void proj_mma(float (&acc)[32], int wg, uint32_t fullB, uint32_t emptyB, uint32_t fullA, bool wait_a, int lane) {
    const uint64_t dA = cdesc(0, 16, 1024, 1), dB = cdesc(P_A_BYTES, 8192, 1024, 1) + wg * 512;
#pragma unroll 1
    for (int kb = 0; kb < 9; kb++) {
        const int s = kb >= P_NST ? kb - P_NST : kb;
        if (wait_a) mbar_wait(fullA + kb * 8, 0);
        mbar_wait(fullB + s * 8, kb >= P_NST ? 1 : 0);
        wg_fence();
#pragma unroll
        for (int ks = 0; ks < 4; ks++) wgmma_ss_n64<1>(acc, dA + (kb * 512 + ks * 2), dB + (s * (P_B_STAGE >> 4) + ks * 128), (kb | ks) != 0);
        wg_commit();
        if (kb < 4) {
            wg_wait<1>();
            if (kb >= 1 && lane == 0) mbar_arrive(emptyB + (kb - 1) * 8);
        }
    }
    wg_wait<0>();
    pin(acc);
}

__global__ void __launch_bounds__(Q_THREADS, 1)
k_qkv(const __grid_constant__ CUtensorMap tmWq, const __grid_constant__ CUtensorMap tmQ, const __nv_bfloat16* __restrict__ x, const __nv_bfloat16* __restrict__ wk, const __nv_bfloat16* __restrict__ wv) {
    extern __shared__ __align__(1024) uint8_t smem[];
    const uint32_t sA = smem_u32(smem), sB = sA + P_A_BYTES, bars = sB + P_NST * P_B_STAGE;
    const uint32_t fullB = bars, emptyB = bars + 64, fullX = bars + 128, fullW = bars + 136;
    float* s_rstd = reinterpret_cast<float*>(smem + P_A_BYTES + P_NST * P_B_STAGE + 256);
    const int tid = threadIdx.x, warp = __shfl_sync(~0u, tid >> 5, 0), lane = tid & 31;
    const bool isQ = blockIdx.x < 96;
    const int m = isQ ? blockIdx.x / 3 : blockIdx.x - 96, cg = blockIdx.x % 3;
    if (tid == 0) TS(0, 0);
    if (warp == 12) {
        if (elect_one()) {
            mbar_init(fullX, 1);
            bar_init_fence();
            mbar_expect(fullX, P_A_BYTES);
            bulk_g2s(sA, x + (size_t)m * 64 * DM, P_A_BYTES, fullX);
            prefetch_map(&tmWq); prefetch_map(&tmQ);
            for (int i = 0; i < P_NST; i++) { mbar_init(fullB + i * 8, 1); mbar_init(emptyB + i * 8, 12); }
            mbar_init(fullW, 1);
            bar_init_fence();
            if (isQ) {
                for (int kb = 0; kb < P_NST; kb++) {
                    mbar_expect(fullB + kb * 8, P_B_STAGE);
                    for (int a = 0; a < 3; a++) tma_2d(sB + kb * P_B_STAGE + a * 8192, &tmWq, cg * 192 + a * 64, kb * 64, fullB + kb * 8);
                }
            } else {
                mbar_expect(fullW, 2 * KV_RAW);
                bulk_g2s(sB + 3 * P_B_STAGE, wk, KV_RAW, fullW);
                bulk_g2s(sB + 3 * P_B_STAGE + KV_RAW, wv, KV_RAW, fullW);
            }
        }
        __syncwarp();
    }
    check_smem_base(sA);
    __syncthreads();
    pdl_launch();
    if (warp == 12) {
        if (isQ && elect_one()) {
            for (int kb = P_NST; kb < 9; kb++) {
                const int s = kb - P_NST;
                mbar_wait(emptyB + s * 8, 0);
                mbar_expect(fullB + s * 8, P_B_STAGE);
                for (int a = 0; a < 3; a++) tma_2d(sB + s * P_B_STAGE + a * 8192, &tmWq, cg * 192 + a * 64, kb * 64, fullB + s * 8);
            }
        }
        return;
    }
    if (warp < 8) {
        const int row = tid >> 2, q = tid & 3, h0 = (row & 1) * 4;
        mbar_wait(fullX, 0);
        if (tid == 0) TS(0, 6);
        uint4 v[18];
        const uint32_t ra = sA + row * 1152 + (q + h0) * 16, rb = sA + row * 1152 + (q + 4 - h0) * 16;
#pragma unroll
        for (int kb = 0; kb < 9; kb++) {
            asm volatile("ld.shared.v4.b32 {%0, %1, %2, %3}, [%4];" : "=r"(v[2 * kb].x), "=r"(v[2 * kb].y), "=r"(v[2 * kb].z), "=r"(v[2 * kb].w) : "r"(ra + kb * 128));
            asm volatile("ld.shared.v4.b32 {%0, %1, %2, %3}, [%4];" : "=r"(v[2 * kb + 1].x), "=r"(v[2 * kb + 1].y), "=r"(v[2 * kb + 1].z), "=r"(v[2 * kb + 1].w) : "r"(rb + kb * 128));
        }
        float sum = 0.f, sum2 = 0.f, sq = 0.f, sq2 = 0.f;
#pragma unroll
        for (int i = 0; i < 18; i++) {
            const uint32_t w[4] = {v[i].x, v[i].y, v[i].z, v[i].w};
#pragma unroll
            for (int j = 0; j < 4; j++) { const float a = bf_lo(w[j]), b = bf_hi(w[j]); sum += a; sum2 += b; sq = fmaf(a, a, sq); sq2 = fmaf(b, b, sq2); }
        }
        named_sync(1, 256);
        sum += sum2; sq += sq2;
        sum += __shfl_xor_sync(~0u, sum, 1); sum += __shfl_xor_sync(~0u, sum, 2);
        sq += __shfl_xor_sync(~0u, sq, 1); sq += __shfl_xor_sync(~0u, sq, 2);
        if (tid == 0) TS(0, 4);
        const float mean = sum * (1.0f / DM);
        if (q == 0) s_rstd[row] = rsqrtf(fmaxf(sq * (1.0f / DM) - mean * mean, 0.f) + LN_EPS);
        const uint32_t mhi = pack_bf16(mean, mean);
        const float rem = mean - bf_lo(mhi);
        const uint32_t mlo = pack_bf16(rem, rem);
        const uint32_t wa = sA + row * 128 + (((q + h0) ^ (row & 7)) << 4), wb = sA + row * 128 + (((q + 4 - h0) ^ (row & 7)) << 4);
#pragma unroll
        for (int i = 0; i < 18; i++) {
            const uint32_t o0 = hsub2_bf16(hsub2_bf16(v[i].x, mhi), mlo), o1 = hsub2_bf16(hsub2_bf16(v[i].y, mhi), mlo);
            const uint32_t o2 = hsub2_bf16(hsub2_bf16(v[i].z, mhi), mlo), o3 = hsub2_bf16(hsub2_bf16(v[i].w, mhi), mlo);
            asm volatile("st.shared.v4.b32 [%0], {%1, %2, %3, %4};" ::"r"(((i & 1) ? wb : wa) + (i >> 1) * 8192), "r"(o0), "r"(o1), "r"(o2), "r"(o3) : "memory");
        }
    } else if (!isQ) {
        mbar_wait(fullW, 0);
        const uint32_t* raw = reinterpret_cast<const uint32_t*>(smem + P_A_BYTES + 3 * P_B_STAGE);
#pragma unroll 3
        for (int r = tid - 256; r < 2 * DM; r += 128) {
            uint32_t wr[9];
#pragma unroll
            for (int i = 0; i < 9; i++) wr[i] = raw[r * 9 + i];
            const int sel = r >= DM, k = r - sel * DM;
            uint8_t* dst = smem + P_A_BYTES + sel * 3 * 9216 + (k >> 3) * 128 + (k & 7) * 16;
            *reinterpret_cast<uint4*>(dst) = make_uint4(wr[0], wr[1], wr[2], wr[3]);
            *reinterpret_cast<uint4*>(dst + 9216) = make_uint4(wr[4], wr[5], wr[6], wr[7]);
            *reinterpret_cast<uint32_t*>(dst + 2 * 9216) = wr[8];
        }
    }
    proxy_fence();
    named_sync(2, 384);
    if (tid == 0) TS(0, 1);
    const int wg = warp >> 2, w = warp & 3, g = lane >> 2, t = lane & 3;
    const float rs0 = s_rstd[w * 16 + g], rs1 = s_rstd[w * 16 + g + 8];
    if (isQ) {
        const float c0 = rs0 * Q_SCALE, c1 = rs1 * Q_SCALE;
        float acc[32];
        proj_mma(acc, wg, fullB, emptyB, 0, false, lane);
        if (tid == 0) TS(0, 2);
        uint32_t pk[16];
#pragma unroll
        for (int i = 0; i < 8; i++) { pk[2 * i] = pack_bf16(acc[4 * i] * c0, acc[4 * i + 1] * c0); pk[2 * i + 1] = pack_bf16(acc[4 * i + 2] * c1, acc[4 * i + 3] * c1); }
        named_sync(2, 384);
        stage_tile<8>(pk, sA + wg * 8192, w, lane);
        proxy_fence();
        named_sync(3 + wg, 128);
        if (w == 0 && elect_one()) {
            tma_st_2d(&tmQ, cg * 192 + wg * 64, m * 64, sA + wg * 8192);
            bulk_commit();
            bulk_wait_all();
        }
    } else if (wg < 2) {
        float acc[12];
        const uint64_t dA = cdesc(0, 16, 1024, 1), dB = cdesc(P_A_BYTES, 128, 9216, 0) + wg * (3 * 9216 >> 4);
#pragma unroll
        for (int i = 0; i < 12; i++) acc[i] = 0.f;
        pin(acc);
        wg_fence();
#pragma unroll 1
        for (int kb = 0; kb < 9; kb++) {
#pragma unroll
            for (int ks = 0; ks < 4; ks++) wgmma_ss_n24<1>(acc, dA + (kb * 512 + ks * 2), dB + (kb * 4 + ks) * 16, 1);
        }
        wg_commit();
        wg_wait<0>();
        pin(acc);
        uint32_t pk[6];
#pragma unroll
        for (int b = 0; b < 3; b++) { pk[2 * b] = pack_bf16(acc[4 * b] * rs0, acc[4 * b + 1] * rs0); pk[2 * b + 1] = pack_bf16(acc[4 * b + 2] * rs1, acc[4 * b + 3] * rs1); }
        float n0 = 0.f, n1 = 0.f, vm = 0.f;
#pragma unroll
        for (int b = 0; b < 3; b++) {
            if (b < 2 || t == 0) {
                const float a = bf_lo(pk[2 * b]), c = bf_hi(pk[2 * b]), d = bf_lo(pk[2 * b + 1]), e = bf_hi(pk[2 * b + 1]);
                n0 = fmaf(a, a, fmaf(c, c, n0)); n1 = fmaf(d, d, fmaf(e, e, n1));
            }
        }
        n0 += __shfl_xor_sync(~0u, n0, 1); n0 += __shfl_xor_sync(~0u, n0, 2);
        n1 += __shfl_xor_sync(~0u, n1, 1); n1 += __shfl_xor_sync(~0u, n1, 2);
        vm = fmaxf(n0, n1);
        if (!(n0 == n0) || !(n1 == n1)) vm = __int_as_float(0x7F800000);
#pragma unroll
        for (int o = 4; o < 32; o <<= 1) vm = fmaxf(vm, __shfl_xor_sync(~0u, vm, o));
        if (t != 0) {
            uint32_t lo, hi;
            if (wg == 0) {
                const int grp = m * 8 + w * 2;
                const uint32_t c = t == 1 ? 0x42FE3F80u   : (t == 2 ? 0x00003BC0u   : 0u);
                lo = ((POLY_MASK >> (grp & 15)) & 1) ? c : 0u;
                hi = ((POLY_MASK >> ((grp + 1) & 15)) & 1) ? c : 0u;
            } else {
                lo = hi = t == 1 ? 0x00003F80u : 0u;
            }
            pk[4] = lo; pk[5] = hi;
        }
        uint32_t* dst = reinterpret_cast<uint32_t*>(wg == 0 ? g_kc : g_vc) + (m * 8 + w * 2) * 96 + g * 4 + t;
#pragma unroll
        for (int b = 0; b < 3; b++) { dst[b * 32] = pk[2 * b]; dst[96 + b * 32] = pk[2 * b + 1]; }
        if (lane == 0) g_kmax[m * 8 + warp] = (wg == 0) ? vm : (vm <= 1e24f ? 0.f : __int_as_float(0x7F800000));
    }
    if (tid == 0) TS(0, 3);
}

constexpr int A_THREADS = 512;
constexpr int A_NPIECE = 8;
constexpr int A_OFF_Q = 2 * KV_BYTES;
constexpr int A_OFF_BAR = A_OFF_Q + 4 * 4096;
constexpr int A_SMEM = A_OFF_BAR + 128;

__device__ __forceinline__ uint32_t exp2_pair_fixed(float lo, float hi) {
    const uint32_t G = __byte_perm(__float_as_uint(lo), __float_as_uint(hi), 0x5410);
    const uint32_t Hh = G & 0x007F007Fu;
    const uint32_t tt = hfma2(Hh, 0xF96BF96Bu, 0x358C358Cu);
    return G - hfma2(tt, Hh, 0u);
}

__global__ void __launch_bounds__(A_THREADS, 1)
k_attn() {
    extern __shared__ __align__(1024) uint8_t smem[];
    pdl_launch();
    const uint32_t sK = smem_u32(smem), sV = sK + KV_BYTES, bars = sK + A_OFF_BAR;
    const int tid = threadIdx.x;
    check_smem_base(sK);
    if (tid == 0) TS(1, 0);
    if (tid == 0) {
        for (int i = 0; i < A_NPIECE; i++) mbar_init(bars + i * 8, 1);
        bar_init_fence();
    }
    __syncthreads();
    pdl_wait();
    if (tid == 0) TS(1, 1);
    const int wg = __shfl_sync(~0u, tid >> 7, 0), w = (tid >> 5) & 3, lane = tid & 31, g = lane >> 2, t = lane & 3;
    const uint32_t* q32 = reinterpret_cast<const uint32_t*>(g_q);
    int row = (blockIdx.x * 8 + wg) * 64 + w * 16 + g;
    uint32_t nq[6];
    nq[0] = q32[row * 9 + t]; nq[1] = q32[(row + 8) * 9 + t]; nq[2] = q32[row * 9 + 4 + t]; nq[3] = q32[(row + 8) * 9 + 4 + t];
    nq[4] = q32[row * 9 + 8]; nq[5] = q32[(row + 8) * 9 + 8];
    constexpr int PB = KV_BYTES / A_NPIECE;
    const float4 km0 = reinterpret_cast<const float4*>(g_kmax)[lane], km1 = reinterpret_cast<const float4*>(g_kmax)[32 + lane];
    if (tid < 32 && elect_one()) {
        for (int i = 0; i < 2; i++) {
            mbar_expect(bars + i * 8, 2 * PB);
            bulk_g2s(sK + i * PB, reinterpret_cast<const char*>(g_kc) + i * PB, PB, bars + i * 8);
            bulk_g2s(sV + i * PB, reinterpret_cast<const char*>(g_vc) + i * PB, PB, bars + i * 8);
        }
    }
    float kmax2 = fmaxf(fmaxf(fmaxf(km0.x, km0.y), fmaxf(km0.z, km0.w)), fmaxf(fmaxf(km1.x, km1.y), fmaxf(km1.z, km1.w)));
#pragma unroll
    for (int o = 1; o < 32; o <<= 1) kmax2 = fmaxf(kmax2, __shfl_xor_sync(~0u, kmax2, o));
    if (tid < 32 && elect_one()) {
        for (int i = 2; i < A_NPIECE; i++) {
            mbar_expect(bars + i * 8, 2 * PB);
            bulk_g2s(sK + i * PB, reinterpret_cast<const char*>(g_kc) + i * PB, PB, bars + i * 8);
            bulk_g2s(sV + i * PB, reinterpret_cast<const char*>(g_vc) + i * PB, PB, bars + i * 8);
        }
    }
    const uint32_t sQ = sK + A_OFF_Q + wg * 4096 + (w * 2) * 512 + g * 16 + t * 4;
    const uint64_t dQ0 = cdesc(A_OFF_Q, 128, 512, 0) + wg * 256, dQ1 = dQ0 + 16;
#pragma unroll 1
    for (int rep = 0; rep < 2; rep++, row += 256) {
        const uint32_t qa[4] = {nq[0], nq[1], nq[2], nq[3]};
        float n0, n1;
        {
            const float a0 = bf_lo(qa[0]), a1 = bf_hi(qa[0]), a2 = bf_lo(qa[2]), a3 = bf_hi(qa[2]);
            const float b0 = bf_lo(qa[1]), b1 = bf_hi(qa[1]), b2 = bf_lo(qa[3]), b3 = bf_hi(qa[3]);
            n0 = a0 * a0 + a1 * a1 + a2 * a2 + a3 * a3; n1 = b0 * b0 + b1 * b1 + b2 * b2 + b3 * b3;
            if (t == 0) {
                const float c0 = bf_lo(nq[4]), c1 = bf_hi(nq[4]), d0 = bf_lo(nq[5]), d1 = bf_hi(nq[5]);
                n0 += c0 * c0 + c1 * c1; n1 += d0 * d0 + d1 * d1;
            }
            n0 += __shfl_xor_sync(~0u, n0, 1); n0 += __shfl_xor_sync(~0u, n0, 2);
            n1 += __shfl_xor_sync(~0u, n1, 1); n1 += __shfl_xor_sync(~0u, n1, 2);
        }
        const uint32_t x0 = nq[4], x1 = nq[5];
        if (rep == 0) {
            const int nr = row + 256;
            nq[0] = q32[nr * 9 + t]; nq[1] = q32[(nr + 8) * 9 + t]; nq[2] = q32[nr * 9 + 4 + t]; nq[3] = q32[(nr + 8) * 9 + 4 + t];
            nq[4] = q32[nr * 9 + 8]; nq[5] = q32[(nr + 8) * 9 + 8];
        }
        if (tid == 0 && rep == 0) TS(1, 7);
        const bool unsafe = !(fmaxf(n0, n1) * kmax2 <= FAST_BOUND * FAST_BOUND) || !(n0 == n0) || !(n1 == n1);
        uint32_t any_unsafe;
        asm volatile("{\n.reg .pred p, q;\nsetp.ne.u32 p, %1, 0;\nbar.red.or.pred q, %2, 128, p;\nselp.u32 %0, 1, 0, q;\n}\n" : "=r"(any_unsafe) : "r"((uint32_t)unsafe), "r"(wg + 1) : "memory");
        any_unsafe = __shfl_sync(~0u, any_unsafe, 0);
        {
            const uint32_t cst = any_unsafe ? 0u : (t == 1 ? 0x3F804780u : (t == 2 ? 0x00003F80u : 0u));
            asm volatile("st.shared.b32 [%0], %1;" ::"r"(sQ), "r"(qa[0]) : "memory");
            asm volatile("st.shared.b32 [%0], %1;" ::"r"(sQ + 512), "r"(qa[1]) : "memory");
            asm volatile("st.shared.b32 [%0], %1;" ::"r"(sQ + 128), "r"(qa[2]) : "memory");
            asm volatile("st.shared.b32 [%0], %1;" ::"r"(sQ + 640), "r"(qa[3]) : "memory");
            asm volatile("st.shared.b32 [%0], %1;" ::"r"(sQ + 256), "r"(t == 0 ? x0 : cst) : "memory");
            asm volatile("st.shared.b32 [%0], %1;" ::"r"(sQ + 768), "r"(t == 0 ? x1 : cst) : "memory");
            asm volatile("st.shared.b32 [%0], %1;" ::"r"(sQ + 384), "r"(0u) : "memory");
            asm volatile("st.shared.b32 [%0], %1;" ::"r"(sQ + 896), "r"(0u) : "memory");
            proxy_fence();
            named_sync(wg + 1, 128);
        }
        if (tid == 0) TS(1, 2 + rep * 2);
        float o[12];
#pragma unroll
        for (int i = 0; i < 12; i++) o[i] = 0.f;
        pin(o);
        uint64_t dK0 = cdesc(0, 128, 384, 0), dK1 = cdesc(256, 0, 384, 0), dV = cdesc(KV_BYTES, 384, 128, 0);
        if (!any_unsafe) {
            float s[64];
#pragma unroll 1
            for (int j = 0; j < 16; j++) {
                if (rep == 0 && (j & 1) == 0) mbar_wait(bars + (j >> 1) * 8, 0);
                wg_fence();
                wgmma_ss_n128<0>(s, dQ0, dK0, 0);
                wgmma_ss_n128<0>(s, dQ1, dK1, 1);
                wg_commit();
                dK0 += 16 * 384 >> 4; dK1 += 16 * 384 >> 4;
                wg_wait<0>();
                pin(s);
                uint32_t p[32];
#pragma unroll
                for (int i = 0; i < 32; i++) {
                    if ((POLY_MASK >> (i >> 1)) & 1) p[i] = exp2_pair_fixed(s[2 * i], s[2 * i + 1]);
                    else p[i] = pack_bf16(ex2(s[2 * i]), ex2(s[2 * i + 1]));
                }
                pin(p);
                wg_fence();
#pragma unroll
                for (int k = 0; k < 8; k++) wgmma_rs_n24<1>(o, p[4 * k], p[4 * k + 1], p[4 * k + 2], p[4 * k + 3], dV + k * 48, 1);
                wg_commit();
                dV += 16 * 384 >> 4;
                wg_wait<0>();
            }
        } else {
            float s[64];
            float m0 = -INFINITY, m1 = -INFINITY;
#pragma unroll 1
            for (int j = 0; j < 16; j++) {
                if (rep == 0 && (j & 1) == 0) mbar_wait(bars + (j >> 1) * 8, 0);
                wg_fence();
                wgmma_ss_n128<0>(s, dQ0, dK0, 0);
                wgmma_ss_n128<0>(s, dQ1, dK1, 1);
                wg_commit();
                dK0 += 16 * 384 >> 4; dK1 += 16 * 384 >> 4;
                wg_wait<0>();
                pin(s);
                float x0m = m0, x1m = m1;
#pragma unroll
                for (int b = 0; b < 16; b++) { x0m = fmaxf(x0m, fmaxf(s[4 * b], s[4 * b + 1])); x1m = fmaxf(x1m, fmaxf(s[4 * b + 2], s[4 * b + 3])); }
                x0m = fmaxf(x0m, __shfl_xor_sync(~0u, x0m, 1)); x0m = fmaxf(x0m, __shfl_xor_sync(~0u, x0m, 2));
                x1m = fmaxf(x1m, __shfl_xor_sync(~0u, x1m, 1)); x1m = fmaxf(x1m, __shfl_xor_sync(~0u, x1m, 2));
                const float c0 = ex2(m0 - x0m), c1 = ex2(m1 - x1m);
                m0 = x0m; m1 = x1m;
#pragma unroll
                for (int b = 0; b < 3; b++) { o[4 * b] *= c0; o[4 * b + 1] *= c0; o[4 * b + 2] *= c1; o[4 * b + 3] *= c1; }
                uint32_t p[32];
#pragma unroll
                for (int b = 0; b < 16; b++) {
                    p[2 * b] = pack_bf16(ex2(s[4 * b] - m0), ex2(s[4 * b + 1] - m0));
                    p[2 * b + 1] = pack_bf16(ex2(s[4 * b + 2] - m1), ex2(s[4 * b + 3] - m1));
                }
                pin(p); pin(o);
                wg_fence();
#pragma unroll
                for (int k = 0; k < 8; k++) wgmma_rs_n24<1>(o, p[4 * k], p[4 * k + 1], p[4 * k + 2], p[4 * k + 3], dV + k * 48, 1);
                wg_commit();
                dV += 16 * 384 >> 4;
                wg_wait<0>();
            }
        }
        pin(o);
        if (tid == 0) TS(1, 3 + rep * 2);
        const float l0 = __shfl_sync(~0u, o[8], (lane & ~3) | 1), l1 = __shfl_sync(~0u, o[10], (lane & ~3) | 1);
        const float i0 = 1.0f / l0, i1 = 1.0f / l1;
        uint32_t* o32 = reinterpret_cast<uint32_t*>(g_o);
        o32[row * 9 + t] = pack_bf16(o[0] * i0, o[1] * i0);
        o32[(row + 8) * 9 + t] = pack_bf16(o[2] * i1, o[3] * i1);
        o32[row * 9 + 4 + t] = pack_bf16(o[4] * i0, o[5] * i0);
        o32[(row + 8) * 9 + 4 + t] = pack_bf16(o[6] * i1, o[7] * i1);
        if (t == 0) { o32[row * 9 + 8] = pack_bf16(o[8] * i0, o[9] * i0); o32[(row + 8) * 9 + 8] = pack_bf16(o[10] * i1, o[11] * i1); }
    }
    if (tid == 0) TS(1, 6);
    if ((tid & 127) == 0) TS(1, 10 + wg);
}

constexpr int O_THREADS = 416;
constexpr int O_OFF_STAT = P_A_BYTES + P_NST * P_B_STAGE + 256;
constexpr int O_SMEM = O_OFF_STAT + 9 * 64 * 8;

__global__ void __cluster_dims__(3, 1, 1) __launch_bounds__(O_THREADS, 1)
k_oproj(const __grid_constant__ CUtensorMap tmO, const __grid_constant__ CUtensorMap tmWo, const __grid_constant__ CUtensorMap tmX2, const __grid_constant__ CUtensorMap tmOut, const __nv_bfloat16* __restrict__ x) {
    extern __shared__ __align__(1024) uint8_t smem[];
    const uint32_t sA = smem_u32(smem), sB = sA + P_A_BYTES, bars = sB + P_NST * P_B_STAGE;
    const uint32_t fullB = bars, emptyB = bars + 64, fullA = bars + 128;
    const int tid = threadIdx.x, warp = __shfl_sync(~0u, tid >> 5, 0), lane = tid & 31;
    const int m = blockIdx.x / 3, cg = blockIdx.x % 3;
    if (tid == 0) TS(2, 0);
    check_smem_base(sA);
    if (tid == 0) {
        prefetch_map(&tmO); prefetch_map(&tmWo); prefetch_map(&tmX2); prefetch_map(&tmOut);
        for (int i = 0; i < P_NST; i++) { mbar_init(fullB + i * 8, 1); mbar_init(emptyB + i * 8, 12); }
        for (int i = 0; i < 9; i++) mbar_init(fullA + i * 8, 1);
        bar_init_fence();
        for (int kb = 0; kb < 9; kb++) mbar_expect(fullA + kb * 8, 8192);
    }
    __syncthreads();
    pdl_launch();
    if (warp == 12) {
        if (elect_one()) {
            for (int kb = 0; kb < 9; kb++) {
                const int s = kb >= P_NST ? kb - P_NST : kb;
                if (kb == 2) {
                    pdl_wait();
                    TS(2, 1);
                    for (int ka = 0; ka < 9; ka++) tma_2d(sA + ka * 8192, &tmO, ka * 64, m * 64, fullA + ka * 8);
                }
                if (kb >= P_NST) mbar_wait(emptyB + s * 8, 0);
                mbar_expect(fullB + s * 8, P_B_STAGE);
                for (int a = 0; a < 3; a++) tma_2d(sB + s * P_B_STAGE + a * 8192, &tmWo, cg * 192 + a * 64, kb * 64, fullB + s * 8);
            }
        }
        return;
    }
    if (tid == 0) TS(2, 11);
    const int wg = warp >> 2, w = warp & 3, g = lane >> 2, t = lane & 3;
    uint32_t xr[16];
    {
        const uint32_t* x32 = reinterpret_cast<const uint32_t*>(x) + (((m * 64 + w * 16 + g) * DM + cg * 192 + wg * 64 + 2 * t) >> 1);
#pragma unroll
        for (int b = 0; b < 8; b++) { xr[2 * b] = __ldg(x32 + b * 4); xr[2 * b + 1] = __ldg(x32 + b * 4 + 4 * DM); }
    }
    float acc[32];
    proj_mma(acc, wg, fullB, emptyB, fullA, true, lane);
    if (tid == 0) TS(2, 2);
    named_sync(1, 384);
    float s0 = 0.f, q0 = 0.f, s1 = 0.f, q1 = 0.f;
#pragma unroll
    for (int b = 0; b < 8; b++) {
        const uint32_t xa = xr[2 * b], xb = xr[2 * b + 1];
        const uint32_t ha = pack_bf16(acc[4 * b] + bf_lo(xa), acc[4 * b + 1] + bf_hi(xa));
        const uint32_t hb = pack_bf16(acc[4 * b + 2] + bf_lo(xb), acc[4 * b + 3] + bf_hi(xb));
        xr[2 * b] = ha; xr[2 * b + 1] = hb;
        const float a = bf_lo(ha), c = bf_hi(ha), d = bf_lo(hb), e = bf_hi(hb);
        s0 += a + c; q0 = fmaf(a, a, fmaf(c, c, q0));
        s1 += d + e; q1 = fmaf(d, d, fmaf(e, e, q1));
    }
    s0 += __shfl_xor_sync(~0u, s0, 1); s0 += __shfl_xor_sync(~0u, s0, 2);
    q0 += __shfl_xor_sync(~0u, q0, 1); q0 += __shfl_xor_sync(~0u, q0, 2);
    s1 += __shfl_xor_sync(~0u, s1, 1); s1 += __shfl_xor_sync(~0u, s1, 2);
    q1 += __shfl_xor_sync(~0u, q1, 1); q1 += __shfl_xor_sync(~0u, q1, 2);
    const int r = w * 16 + g;
    const uint32_t sStat = sA + O_OFF_STAT;
    if (t < 3) {
        uint32_t dst;
        asm("mapa.shared::cluster.u32 %0, %1, %2;" : "=r"(dst) : "r"(sStat + ((cg * 3 + wg) * 64 + r) * 8), "r"(t));
        asm volatile("st.shared::cluster.v2.f32 [%0], {%1, %2};" ::"r"(dst), "f"(s0), "f"(q0) : "memory");
        asm volatile("st.shared::cluster.v2.f32 [%0], {%1, %2};" ::"r"(dst + 64), "f"(s1), "f"(q1) : "memory");
    }
    if (tid == 0) TS(2, 4);
    cluster_arrive();
    stage_tile<8>(xr, sA + wg * 8192, w, lane);
    proxy_fence();
    named_sync(2 + wg, 128);
    const bool leader = w == 0 && elect_one();
    if (leader) { tma_st_2d(&tmOut, cg * 192 + wg * 64, m * 64, sA + wg * 8192); bulk_commit(); }
    cluster_wait();
    if (tid == 0) TS(2, 5);
    s0 = q0 = s1 = q1 = 0.f;
#pragma unroll
    for (int p = 0; p < 9; p++) {
        float a, b, c, d;
        asm volatile("ld.shared.v2.f32 {%0, %1}, [%2];" : "=f"(a), "=f"(b) : "r"(sStat + (p * 64 + r) * 8));
        asm volatile("ld.shared.v2.f32 {%0, %1}, [%2];" : "=f"(c), "=f"(d) : "r"(sStat + (p * 64 + r + 8) * 8));
        s0 += a; q0 += b; s1 += c; q1 += d;
    }
    const float m0 = s0 * (1.0f / DM), m1 = s1 * (1.0f / DM);
    const float rs0 = rsqrtf(fmaxf(q0 * (1.0f / DM) - m0 * m0, 0.f) + LN_EPS), rs1 = rsqrtf(fmaxf(q1 * (1.0f / DM) - m1 * m1, 0.f) + LN_EPS);
    const float sc0 = -LOG2E * rs0, sc1 = -LOG2E * rs1, n0 = -m0 * sc0, n1 = -m1 * sc1;
#pragma unroll
    for (int b = 0; b < 8; b++) {
        xr[2 * b] = pack_bf16(fmaf(bf_lo(xr[2 * b]), sc0, n0), fmaf(bf_hi(xr[2 * b]), sc0, n0));
        xr[2 * b + 1] = pack_bf16(fmaf(bf_lo(xr[2 * b + 1]), sc1, n1), fmaf(bf_hi(xr[2 * b + 1]), sc1, n1));
    }
    stage_tile<8>(xr, sA + (3 + wg) * 8192, w, lane);
    proxy_fence();
    named_sync(2 + wg, 128);
    if (tid == 0) TS(2, 6);
    if (leader) {
        tma_st_2d(&tmX2, cg * 192 + wg * 64, m * 64, sA + (3 + wg) * 8192);
        bulk_commit();
        bulk_wait_all();
    }
    if (tid == 0) TS(2, 3);
}

constexpr int F_THREADS = 384;
constexpr int F_NST = 6;
constexpr int F_STAGE = 96 * 128;
constexpr int F_X_BYTES = 9 * 16384;
constexpr int F_OFF_ST = F_X_BYTES;
constexpr int F_OFF_BAR = F_OFF_ST + F_NST * F_STAGE;
constexpr int F_SMEM = F_OFF_BAR + 256;

__device__ __forceinline__ float after_issue(float v, uint32_t tick) {
    uint32_t r;
    asm("lop3.b32 %0, %1, %1, %2, 0xF0;" : "=r"(r) : "r"(__float_as_uint(v)), "r"(tick));
    return __uint_as_float(r);
}
__device__ __forceinline__ uint32_t read_tick() { uint32_t c; asm volatile("mov.u32 %0, %%clock;" : "=r"(c)::"memory"); return c; }
__device__ __forceinline__ void silu_s1(const float (&acc)[32], float (&tmp)[8], int piece) {
#pragma unroll
    for (int i = 0; i < 8; i++) tmp[i] = ex2(acc[8 * piece + i]);
}
__device__ __forceinline__ void silu_s2(float (&tmp)[8], uint32_t tick) {
    const float one = after_issue(1.0f, tick);
#pragma unroll
    for (int i = 0; i < 8; i++) tmp[i] = rcp(tmp[i] + one);
}
template <int C>
__device__ __forceinline__ void silu_s3(const float (&acc)[32], const float (&tmp)[8], uint32_t (&h1)[144], int piece) {
#pragma unroll
    for (int i = 0; i < 4; i++) h1[C * 16 + 4 * piece + i] = pack_bf16(acc[8 * piece + 2 * i] * tmp[2 * i], acc[8 * piece + 2 * i + 1] * tmp[2 * i + 1]);
}

struct FfnPipe {
    uint32_t full, empty;
    int lane;
    __device__ __forceinline__ void acquire(int s, uint32_t ph) const { mbar_wait(full + s * 8, ph); }
    __device__ __forceinline__ void release(int s) const { if (lane == 0) mbar_arrive(empty + s * 8); }
};

template <int C>
__device__ __forceinline__ void ffn_phase1_chunk(float (&cur)[32], float (&prev)[32], uint32_t (&h1)[144], const FfnPipe& pp, uint64_t dx, uint32_t fullX) {
    float tmp[2][8];
    const uint64_t dw = cdesc(F_OFF_ST, 8192, 1024, 1) + blockIdx.y * (C + 1);
    dx += blockIdx.y * C;
#pragma unroll
    for (int j = 0; j < 6; j++) {
        if (C == 0) { mbar_wait(fullX + ((6 * j) >> 2) * 8, 0); mbar_wait(fullX + ((6 * j + 5) >> 2) * 8, 0); }
        pp.acquire(j, C & 1);
        if (j == 0) pin(cur);
        wg_fence();
#pragma unroll
        for (int i = 0; i < 6; i++) {
            const int ks = 6 * j + i;
            wgmma_ss_n64<1>(cur, dx + ((ks >> 2) * 1024 + (ks & 3) * 2), dw + ((j * F_STAGE + i * 2048) >> 4), ks != 0);
        }
        wg_commit();
        if (C > 0 || j > 0) { wg_wait<1>(); pp.release((j + 5) % 6); }
        if (C > 0) {
            pin(prev);
            if (j >= 1) { pin(tmp[0]); if (j >= 2) pin(tmp[1]); }
            if (j >= 2) silu_s3<(C > 0 ? C - 1 : 0)>(prev, tmp[j & 1], h1, j - 2);
            if (j >= 1 && j <= 4) { silu_s2(tmp[(j - 1) & 1], read_tick()); pin(tmp[(j - 1) & 1]); }
            if (j <= 3) { silu_s1(prev, tmp[j & 1], j); pin(tmp[j & 1]); }
            if (j >= 2) { asm volatile("" : "+r"(h1[(C - 1) * 16 + 4 * (j - 2)]), "+r"(h1[(C - 1) * 16 + 4 * (j - 2) + 1]), "+r"(h1[(C - 1) * 16 + 4 * (j - 2) + 2]), "+r"(h1[(C - 1) * 16 + 4 * (j - 2) + 3]) :: "memory"); }
        }
    }
}

__device__ __forceinline__ void ffn_store_chunk(const float (&acc)[32], const CUtensorMap* tmOut, uint32_t stg, int col, int row, int w, int lane, int wgid, bool leader) {
    uint32_t pk[16];
#pragma unroll
    for (int i = 0; i < 16; i++) pk[i] = pack_bf16(acc[2 * i] * -LN2, acc[2 * i + 1] * -LN2);
    stage_tile<8>(pk, stg, w, lane);
    proxy_fence();
    named_sync(2 + wgid, 128);
    if (leader) {
        tma_red_2d(tmOut, col, row, stg);
        bulk_commit();
    }
}

__device__ __forceinline__ void ffn_phase2_chunk(float (&cur)[32], float (&prev)[32], uint32_t (&h1)[144], const FfnPipe& pp, uint32_t ph, bool store_prev, const CUtensorMap* tmOut, uint32_t stg_prev, int col_prev, int row, int w, int lane, int wgid, bool leader) {
    const uint64_t dw = cdesc(F_OFF_ST, 8192, 1024, 1) + blockIdx.y * col_prev;
#pragma unroll
    for (int j = 0; j < 6; j++) {
        pp.acquire(j, ph);
        if (j == 0) pin(cur);
        wg_fence();
#pragma unroll
        for (int i = 0; i < 6; i++) {
            const int f = (6 * j + i) * 4;
            wgmma_rs_n64<1>(cur, h1[f], h1[f + 1], h1[f + 2], h1[f + 3], dw + ((j * F_STAGE + i * 2048) >> 4), (j | i) != 0);
        }
        wg_commit();
        if (j > 0 || store_prev) { wg_wait<1>(); pp.release((j + 5) % 6); }
        if (j == 0 && store_prev) { pin(prev); ffn_store_chunk(prev, tmOut, stg_prev, col_prev, row, w, lane, wgid, leader); }
    }
}

__global__ void __launch_bounds__(F_THREADS, 1)
k_ffn(const __grid_constant__ CUtensorMap tmH, const __grid_constant__ CUtensorMap tmW1, const __grid_constant__ CUtensorMap tmW2, const __grid_constant__ CUtensorMap tmOut) {
    extern __shared__ __align__(1024) uint8_t smem[];
    const uint32_t sX = smem_u32(smem), sSt = sX + F_OFF_ST, bars = sX + F_OFF_BAR;
    const uint32_t full = bars, empty = bars + 64, fullX = bars + 128;
    const int tid = threadIdx.x, warp = __shfl_sync(~0u, tid >> 5, 0), lane = tid & 31;
#define FFN_MAP 1
    const int m = FFN_MAP == 0 ? (blockIdx.x & 15) : (FFN_MAP == 1 ? (blockIdx.x >> 3) : ((blockIdx.x >> 1) & 15));
    const int fs = FFN_MAP == 0 ? (blockIdx.x >> 4) : (FFN_MAP == 1 ? (blockIdx.x & 7) : ((blockIdx.x >> 5) * 2 + (blockIdx.x & 1)));
    if (tid == 0) TS(3, 0);
    check_smem_base(sX);
    if (tid == 0) {
        prefetch_map(&tmW1); prefetch_map(&tmH); prefetch_map(&tmW2); prefetch_map(&tmOut);
        for (int i = 0; i < F_NST; i++) { mbar_init(full + i * 8, 1); mbar_init(empty + i * 8, 8); }
        for (int i = 0; i < 9; i++) mbar_init(fullX + i * 8, 1);
        bar_init_fence();
        for (int kb = 0; kb < 9; kb++) mbar_expect(fullX + kb * 8, 16384);
    }
    __syncthreads();
    if (warp < 4) {
        asm volatile("setmaxnreg.dec.sync.aligned.u32 24;");
        if (warp == 0 && elect_one()) {
            int s = 0; uint32_t ph = 1;
            int c = 0, j = 0;
#pragma unroll 1
            for (int i = 0; i < 108; i++) {
                if (i == 54) c = fs;
                mbar_wait(empty + s * 8, ph);
                mbar_expect(full + s * 8, F_STAGE);
                if (i < 54) tma_2d(sSt + s * F_STAGE, &tmW1, fs * 576 + c * 64, j * 96, full + s * 8);
                else tma_2d(sSt + s * F_STAGE, &tmW2, c * 64, fs * 576 + j * 96, full + s * 8);
                if (++j == 6) { j = 0; if (++c == 9) c = 0; }
                if (++s == F_NST) { s = 0; ph ^= 1; }
            }
        }
    } else {
        asm volatile("setmaxnreg.inc.sync.aligned.u32 240;");
        const int wgid = (warp >> 2) - 1, w = warp & 3;
        pdl_wait();
        if (tid == 128) TS(3, 1);
        if (warp == 4 && elect_one()) {
            for (int kb = 0; kb < 9; kb++) tma_2d(sX + kb * 16384, &tmH, kb * 64, m * 128, fullX + kb * 8);
        }
        __syncwarp();
        FfnPipe pp{full, empty, lane};
        const uint64_t xlo = cdesc(0, 16, 1024, 1) + wgid * 512;
        uint32_t h1[144];
        float acc0[32], acc1[32];
        ffn_phase1_chunk<0>(acc0, acc1, h1, pp, xlo, fullX);
        if (tid == 128) TS(3, 2);
        ffn_phase1_chunk<1>(acc1, acc0, h1, pp, xlo, fullX);
        ffn_phase1_chunk<2>(acc0, acc1, h1, pp, xlo, fullX);
        ffn_phase1_chunk<3>(acc1, acc0, h1, pp, xlo, fullX);
        ffn_phase1_chunk<4>(acc0, acc1, h1, pp, xlo, fullX);
        ffn_phase1_chunk<5>(acc1, acc0, h1, pp, xlo, fullX);
        ffn_phase1_chunk<6>(acc0, acc1, h1, pp, xlo, fullX);
        ffn_phase1_chunk<7>(acc1, acc0, h1, pp, xlo, fullX);
        ffn_phase1_chunk<8>(acc0, acc1, h1, pp, xlo, fullX);
        wg_wait<0>();
        pp.release(5);
        pin(acc0);
        {
            float tmp[4][8];
#pragma unroll
            for (int p = 0; p < 4; p++) silu_s1(acc0, tmp[p], p);
#pragma unroll
            for (int p = 0; p < 4; p++) silu_s2(tmp[p], 0);
#pragma unroll
            for (int p = 0; p < 4; p++) silu_s3<8>(acc0, tmp[p], h1, p);
        }
        pin(h1);
        if (tid == 128) TS(3, 3);
        const int row = m * 128 + wgid * 64;
        const uint32_t stg = sX + wgid * 8192;
        int c = fs, cprev = 0;
        const bool leader = w == 0 && elect_one();
#pragma unroll 1
        for (int j = 0; j < 8; j += 2) {
            ffn_phase2_chunk(acc1, acc0, h1, pp, 1, j > 0, &tmOut, stg + (j - 1) * 16384, cprev * 64, row, w, lane, wgid, leader);
            cprev = c; if (++c == 9) c = 0;
            ffn_phase2_chunk(acc0, acc1, h1, pp, 0, true, &tmOut, stg + j * 16384, cprev * 64, row, w, lane, wgid, leader);
            cprev = c; if (++c == 9) c = 0;
        }
        ffn_phase2_chunk(acc1, acc0, h1, pp, 1, true, &tmOut, stg + 7 * 16384, cprev * 64, row, w, lane, wgid, leader);
        wg_wait<0>();
        pin(acc1);
        ffn_store_chunk(acc1, &tmOut, stg + 8 * 16384, c * 64, row, w, lane, wgid, leader);
        if (tid == 128) TS(3, 4);
        if (leader) bulk_wait_all();
        if (tid == 128) TS(3, 5);
    }
}

typedef CUresult (*EncodeFn)(CUtensorMap*, CUtensorMapDataType, cuuint32_t, void*, const cuuint64_t*, const cuuint64_t*, const cuuint32_t*, const cuuint32_t*,
                             CUtensorMapInterleave, CUtensorMapSwizzle, CUtensorMapL2promotion, CUtensorMapFloatOOBfill);

CUtensorMap make_map(EncodeFn enc, const void* base, int rows, int cols, int box_rows) {
    CUtensorMap tm;
    cuuint64_t dims[2] = {(cuuint64_t)cols, (cuuint64_t)rows};
    cuuint64_t strides[1] = {(cuuint64_t)cols * 2};
    cuuint32_t box[2] = {64, (cuuint32_t)box_rows};
    cuuint32_t es[2] = {1, 1};
    enc(&tm, CU_TENSOR_MAP_DATA_TYPE_BFLOAT16, 2, const_cast<void*>(base), dims, strides, box, es, CU_TENSOR_MAP_INTERLEAVE_NONE,
        CU_TENSOR_MAP_SWIZZLE_128B, CU_TENSOR_MAP_L2_PROMOTION_L2_256B, CU_TENSOR_MAP_FLOAT_OOB_FILL_NONE);
    return tm;
}

template <typename... KArgs, typename... Args>
void launch(void (*kern)(KArgs...), int grid, int block, int smem, bool pdl, Args... args) {
    cudaLaunchConfig_t cfg = {};
    cfg.gridDim = dim3(grid); cfg.blockDim = dim3(block); cfg.dynamicSmemBytes = smem; cfg.stream = cudaStreamPerThread;
    cudaLaunchAttribute at[1];
    at[0].id = cudaLaunchAttributeProgrammaticStreamSerialization;
    at[0].val.programmaticStreamSerializationAllowed = 1;
    cfg.attrs = at; cfg.numAttrs = pdl ? 1 : 0;
    cudaLaunchKernelEx(&cfg, kern, KArgs(args)...);
}

}

#define USE_PDL 1

extern "C" void kernel_launch(void* const* d_in, const int* in_sizes, int n_in, void* d_out, int out_size) {
    const __nv_bfloat16* x = (const __nv_bfloat16*)d_in[0];
    const __nv_bfloat16* wq = (const __nv_bfloat16*)d_in[1];
    const __nv_bfloat16* wk = (const __nv_bfloat16*)d_in[2];
    const __nv_bfloat16* wv = (const __nv_bfloat16*)d_in[3];
    const __nv_bfloat16* wo = (const __nv_bfloat16*)d_in[4];
    const __nv_bfloat16* w1 = (const __nv_bfloat16*)d_in[6];
    const __nv_bfloat16* w2 = (const __nv_bfloat16*)d_in[7];
    __nv_bfloat16* out = (__nv_bfloat16*)d_out;

    static EncodeFn enc = nullptr;
    static void *p_o = nullptr, *p_h = nullptr, *p_q = nullptr;
    if (!enc) {
        cudaDriverEntryPointQueryResult qr;
        cudaGetDriverEntryPoint("cuTensorMapEncodeTiled", (void**)&enc, cudaEnableDefault, &qr);
        cudaGetSymbolAddress(&p_o, g_o);
        cudaGetSymbolAddress(&p_h, g_x2);
        cudaGetSymbolAddress(&p_q, g_q);
        cudaFuncSetAttribute(k_qkv, cudaFuncAttributeMaxDynamicSharedMemorySize, P_SMEM);
        cudaFuncSetAttribute(k_attn, cudaFuncAttributeMaxDynamicSharedMemorySize, A_SMEM);
        cudaFuncSetAttribute(k_oproj, cudaFuncAttributeMaxDynamicSharedMemorySize, O_SMEM);
        cudaFuncSetAttribute(k_ffn, cudaFuncAttributeMaxDynamicSharedMemorySize, F_SMEM);
    }
    const CUtensorMap tmWq = make_map(enc, wq, DM, DM, 64);
    const CUtensorMap tmWo = make_map(enc, wo, DM, DM, 64);
    const CUtensorMap tmO = make_map(enc, p_o, SEQ, DM, 64);
    const CUtensorMap tmH64 = make_map(enc, p_h, SEQ, DM, 64);
    const CUtensorMap tmH = make_map(enc, p_h, SEQ, DM, 128);
    const CUtensorMap tmQ = make_map(enc, p_q, SEQ, DM, 64);
    const CUtensorMap tmW1 = make_map(enc, w1, DM, FF, 96);
    const CUtensorMap tmW2 = make_map(enc, w2, FF, DM, 96);
    const CUtensorMap tmOut = make_map(enc, out, SEQ, DM, 64);

    launch(k_qkv, 128, Q_THREADS, P_SMEM, false, tmWq, tmQ, x, wk, wv);
    launch(k_attn, 128, A_THREADS, A_SMEM, USE_PDL);
    launch(k_oproj, 96, O_THREADS, O_SMEM, USE_PDL, tmO, tmWo, tmH64, tmOut, x);
    launch(k_ffn, 128, F_THREADS, F_SMEM, USE_PDL, tmH, tmW1, tmW2, tmOut);
}
```

```cpp
#include <cuda_runtime.h>
#include <cuda_bf16.h>
#include <cuda.h>
#include <stdint.h>

namespace {

constexpr int SEQ = 2048, DM = 576, FF = 4608;
constexpr int KV_BYTES = SEQ * 48;
constexpr float LN_EPS = 1e-5f;
constexpr float LOG2E = 1.4426950408889634f;
constexpr float Q_SCALE = 0.23570226039551584f * LOG2E;

#define POLY_MASK_V 0xB5B5u
constexpr uint32_t POLY_MASK = POLY_MASK_V;
constexpr float FAST_BOUND = 60.0f;

__device__ __align__(1024) __nv_bfloat16 g_q[SEQ * DM];
__device__ __align__(1024) uint4 g_kc[KV_BYTES / 16];
__device__ __align__(1024) uint4 g_vc[KV_BYTES / 16];
__device__ __align__(16) float g_kmax[256];
__device__ __align__(1024) __nv_bfloat16 g_o[SEQ * DM];
__device__ __align__(1024) __nv_bfloat16 g_x2[SEQ * DM];

#define TS(k, i)

__device__ __forceinline__ uint32_t smem_u32(const void* p) { return (uint32_t)__cvta_generic_to_shared(p); }
__device__ __forceinline__ void wg_fence() { asm volatile("wgmma.fence.sync.aligned;" ::: "memory"); }
__device__ __forceinline__ void wg_commit() { asm volatile("wgmma.commit_group.sync.aligned;" ::: "memory"); }
template <int N> __device__ __forceinline__ void wg_wait() { asm volatile("wgmma.wait_group.sync.aligned %0;" ::"n"(N) : "memory"); }
template <int N> __device__ __forceinline__ void pin(float (&r)[N]) {
#pragma unroll
    for (int i = 0; i < N; i++) asm volatile("" : "+f"(r[i])::"memory");
}
template <int N> __device__ __forceinline__ void pin(uint32_t (&r)[N]) {
#pragma unroll
    for (int i = 0; i < N; i++) asm volatile("" : "+r"(r[i])::"memory");
}
constexpr uint32_t SMEM0 = 0x400;
__host__ __device__ constexpr uint64_t cdesc(uint32_t off, uint32_t lbo, uint32_t sbo, uint32_t swz) {
    return (uint64_t)(((SMEM0 + off) & 0x3FFFF) >> 4) | ((uint64_t)(lbo >> 4) << 16) | ((uint64_t)(sbo >> 4) << 32) | ((uint64_t)swz << 62);
}
__device__ __forceinline__ void check_smem_base(uint32_t base) { if ((base & 0x3FFFF) != SMEM0) __trap(); }

__device__ __forceinline__ void mbar_init(uint32_t bar, int cnt) { asm volatile("mbarrier.init.shared::cta.b64 [%0], %1;" ::"r"(bar), "r"(cnt) : "memory"); }
__device__ __forceinline__ void mbar_expect(uint32_t bar, int bytes) { asm volatile("mbarrier.arrive.expect_tx.shared::cta.b64 _, [%0], %1;" ::"r"(bar), "r"(bytes) : "memory"); }
__device__ __forceinline__ void mbar_arrive(uint32_t bar) { asm volatile("mbarrier.arrive.shared::cta.b64 _, [%0];" ::"r"(bar) : "memory"); }
__device__ __forceinline__ void mbar_wait(uint32_t bar, uint32_t parity) {
    asm volatile(
        "{\n.reg .pred p;\n.reg .u32 n;\nmov.u32 n, 0;\n"
        "LAB_WAIT:\n"
        "mbarrier.try_wait.parity.shared::cta.b64 p, [%0], %1;\n"
        "@p bra DONE;\n"
        "add.u32 n, n, 1;\n"
        "setp.lt.u32 p, n, 4000000;\n"
        "@p bra LAB_WAIT;\n"
        "trap;\n"
        "DONE:\n}\n" ::"r"(bar), "r"(parity) : "memory");
}
__device__ __forceinline__ void bar_init_fence() {
    asm volatile("fence.mbarrier_init.release.cluster;" ::: "memory");
    asm volatile("fence.proxy.async.shared::cta;" ::: "memory");
}
__device__ __forceinline__ void proxy_fence() { asm volatile("fence.proxy.async.shared::cta;" ::: "memory"); }
__device__ __forceinline__ void named_sync(int id, int n) { asm volatile("bar.sync %0, %1;" ::"r"(id), "r"(n) : "memory"); }
__device__ __forceinline__ void bulk_g2s(uint32_t dst, const void* src, int bytes, uint32_t bar) {
    asm volatile("cp.async.bulk.shared::cluster.global.mbarrier::complete_tx::bytes [%0], [%1], %2, [%3];" ::"r"(dst), "l"(src), "r"(bytes), "r"(bar) : "memory");
}
__device__ __forceinline__ void tma_2d(uint32_t dst, const CUtensorMap* tm, int c0, int c1, uint32_t bar) {
    asm volatile("cp.async.bulk.tensor.2d.shared::cluster.global.mbarrier::complete_tx::bytes [%0], [%1, {%3, %4}], [%2];" ::"r"(dst), "l"(tm), "r"(bar), "r"(c0), "r"(c1) : "memory");
}
__device__ __forceinline__ void cluster_arrive() { asm volatile("barrier.cluster.arrive.release.aligned;" ::: "memory"); }
__device__ __forceinline__ void cluster_wait() { asm volatile("barrier.cluster.wait.acquire.aligned;" ::: "memory"); }
__device__ __forceinline__ void tma_red_2d(const CUtensorMap* tm, int c0, int c1, uint32_t src) {
    asm volatile("cp.reduce.async.bulk.tensor.2d.global.shared::cta.add.tile.bulk_group [%0, {%2, %3}], [%1];" ::"l"(tm), "r"(src), "r"(c0), "r"(c1) : "memory");
}
__device__ __forceinline__ void tma_st_2d(const CUtensorMap* tm, int c0, int c1, uint32_t src) {
    asm volatile("cp.async.bulk.tensor.2d.global.shared::cta.tile.bulk_group [%0, {%2, %3}], [%1];" ::"l"(tm), "r"(src), "r"(c0), "r"(c1) : "memory");
}
__device__ __forceinline__ void bulk_commit() { asm volatile("cp.async.bulk.commit_group;" ::: "memory"); }
__device__ __forceinline__ void bulk_wait_all() { asm volatile("cp.async.bulk.wait_group.read 0;" ::: "memory"); }
__device__ __forceinline__ bool elect_one() {
    uint32_t p;
    asm volatile("{\n.reg .pred P;\nelect.sync _|P, 0xffffffff;\nselp.b32 %0, 1, 0, P;\n}\n" : "=r"(p));
    return p != 0;
}
__device__ __forceinline__ void prefetch_l2(const void* p, int bytes) { asm volatile("cp.async.bulk.prefetch.L2.global [%0], %1;" ::"l"(p), "r"(bytes) : "memory"); }
__device__ __forceinline__ void prefetch_map(const CUtensorMap* tm) { asm volatile("prefetch.tensormap [%0];" ::"l"(tm) : "memory"); }
__device__ __forceinline__ void pdl_launch() { asm volatile("griddepcontrol.launch_dependents;" ::: "memory"); }
__device__ __forceinline__ void pdl_wait() { asm volatile("griddepcontrol.wait;" ::: "memory"); }
__device__ __forceinline__ float ex2(float x) { float y; asm("ex2.approx.ftz.f32 %0, %1;" : "=f"(y) : "f"(x)); return y; }
__device__ __forceinline__ uint32_t pack_bf16(float lo, float hi) { uint32_t r; asm("cvt.rn.bf16x2.f32 %0, %1, %2;" : "=r"(r) : "f"(hi), "f"(lo)); return r; }
__device__ __forceinline__ float bf_lo(uint32_t v) { return __uint_as_float(v << 16); }
__device__ __forceinline__ float bf_hi(uint32_t v) { return __uint_as_float(v & 0xFFFF0000u); }
__device__ __forceinline__ uint32_t hfma2(uint32_t a, uint32_t b, uint32_t c) { uint32_t r; asm("fma.rn.f16x2 %0, %1, %2, %3;" : "=r"(r) : "r"(a), "r"(b), "r"(c)); return r; }
__device__ __forceinline__ void stmatrix_x4(uint32_t addr, uint32_t r0, uint32_t r1, uint32_t r2, uint32_t r3) {
    asm volatile("stmatrix.sync.aligned.m8n8.x4.shared.b16 [%0], {%1, %2, %3, %4};" ::"r"(addr), "r"(r0), "r"(r1), "r"(r2), "r"(r3) : "memory");
}

template <int TB> __device__ __forceinline__ void wgmma_ss_n24(float (&d)[12], uint64_t da, uint64_t db, int sc) {
    asm volatile("{\n.reg .pred p;\nsetp.ne.b32 p, %14, 0;\n"
        "wgmma.mma_async.sync.aligned.m64n24k16.f32.bf16.bf16 {%0, %1, %2, %3, %4, %5, %6, %7, %8, %9, %10, %11}, %12, %13, p, 1, 1, 0, %15;\n}\n"
        : "+f"(d[0]), "+f"(d[1]), "+f"(d[2]), "+f"(d[3]), "+f"(d[4]), "+f"(d[5]), "+f"(d[6]), "+f"(d[7]), "+f"(d[8]), "+f"(d[9]), "+f"(d[10]), "+f"(d[11])
        : "l"(da), "l"(db), "r"(sc), "n"(TB));
}
template <int TB> __device__ __forceinline__ void wgmma_ss_n64(float (&d)[32], uint64_t da, uint64_t db, int sc) {
    asm volatile("{\n.reg .pred p;\nsetp.ne.b32 p, %34, 0;\n"
        "wgmma.mma_async.sync.aligned.m64n64k16.f32.bf16.bf16 {%0, %1, %2, %3, %4, %5, %6, %7, %8, %9, %10, %11, %12, %13, %14, %15, %16, %17, %18, %19, %20, %21, %22, %23, %24, %25, %26, %27, %28, %29, %30, %31}, %32, %33, p, 1, 1, 0, %35;\n}\n"
        : "+f"(d[0]), "+f"(d[1]), "+f"(d[2]), "+f"(d[3]), "+f"(d[4]), "+f"(d[5]), "+f"(d[6]), "+f"(d[7]), "+f"(d[8]), "+f"(d[9]), "+f"(d[10]), "+f"(d[11]), "+f"(d[12]), "+f"(d[13]), "+f"(d[14]), "+f"(d[15]), "+f"(d[16]), "+f"(d[17]), "+f"(d[18]), "+f"(d[19]), "+f"(d[20]), "+f"(d[21]), "+f"(d[22]), "+f"(d[23]), "+f"(d[24]), "+f"(d[25]), "+f"(d[26]), "+f"(d[27]), "+f"(d[28]), "+f"(d[29]), "+f"(d[30]), "+f"(d[31])
        : "l"(da), "l"(db), "r"(sc), "n"(TB));
}
template <int TB> __device__ __forceinline__ void wgmma_ss_n128(float (&d)[64], uint64_t da, uint64_t db, int sc) {
    asm volatile("{\n.reg .pred p;\nsetp.ne.b32 p, %66, 0;\n"
        "wgmma.mma_async.sync.aligned.m64n128k16.f32.bf16.bf16 {%0, %1, %2, %3, %4, %5, %6, %7, %8, %9, %10, %11, %12, %13, %14, %15, %16, %17, %18, %19, %20, %21, %22, %23, %24, %25, %26, %27, %28, %29, %30, %31, %32, %33, %34, %35, %36, %37, %38, %39, %40, %41, %42, %43, %44, %45, %46, %47, %48, %49, %50, %51, %52, %53, %54, %55, %56, %57, %58, %59, %60, %61, %62, %63}, %64, %65, p, 1, 1, 0, %67;\n}\n"
        : "+f"(d[0]), "+f"(d[1]), "+f"(d[2]), "+f"(d[3]), "+f"(d[4]), "+f"(d[5]), "+f"(d[6]), "+f"(d[7]), "+f"(d[8]), "+f"(d[9]), "+f"(d[10]), "+f"(d[11]), "+f"(d[12]), "+f"(d[13]), "+f"(d[14]), "+f"(d[15]), "+f"(d[16]), "+f"(d[17]), "+f"(d[18]), "+f"(d[19]), "+f"(d[20]), "+f"(d[21]), "+f"(d[22]), "+f"(d[23]), "+f"(d[24]), "+f"(d[25]), "+f"(d[26]), "+f"(d[27]), "+f"(d[28]), "+f"(d[29]), "+f"(d[30]), "+f"(d[31]), "+f"(d[32]), "+f"(d[33]), "+f"(d[34]), "+f"(d[35]), "+f"(d[36]), "+f"(d[37]), "+f"(d[38]), "+f"(d[39]), "+f"(d[40]), "+f"(d[41]), "+f"(d[42]), "+f"(d[43]), "+f"(d[44]), "+f"(d[45]), "+f"(d[46]), "+f"(d[47]), "+f"(d[48]), "+f"(d[49]), "+f"(d[50]), "+f"(d[51]), "+f"(d[52]), "+f"(d[53]), "+f"(d[54]), "+f"(d[55]), "+f"(d[56]), "+f"(d[57]), "+f"(d[58]), "+f"(d[59]), "+f"(d[60]), "+f"(d[61]), "+f"(d[62]), "+f"(d[63])
        : "l"(da), "l"(db), "r"(sc), "n"(TB));
}
template <int TB> __device__ __forceinline__ void wgmma_rs_n24(float (&d)[12], uint32_t a0, uint32_t a1, uint32_t a2, uint32_t a3, uint64_t db, int sc) {
    asm volatile("{\n.reg .pred p;\nsetp.ne.b32 p, %17, 0;\n"
        "wgmma.mma_async.sync.aligned.m64n24k16.f32.bf16.bf16 {%0, %1, %2, %3, %4, %5, %6, %7, %8, %9, %10, %11}, {%12, %13, %14, %15}, %16, p, 1, 1, %18;\n}\n"
        : "+f"(d[0]), "+f"(d[1]), "+f"(d[2]), "+f"(d[3]), "+f"(d[4]), "+f"(d[5]), "+f"(d[6]), "+f"(d[7]), "+f"(d[8]), "+f"(d[9]), "+f"(d[10]), "+f"(d[11])
        : "r"(a0), "r"(a1), "r"(a2), "r"(a3), "l"(db), "r"(sc), "n"(TB));
}
template <int TB> __device__ __forceinline__ void wgmma_rs_n64(float (&d)[32], uint32_t a0, uint32_t a1, uint32_t a2, uint32_t a3, uint64_t db, int sc) {
    asm volatile("{\n.reg .pred p;\nsetp.ne.b32 p, %37, 0;\n"
        "wgmma.mma_async.sync.aligned.m64n64k16.f32.bf16.bf16 {%0, %1, %2, %3, %4, %5, %6, %7, %8, %9, %10, %11, %12, %13, %14, %15, %16, %17, %18, %19, %20, %21, %22, %23, %24, %25, %26, %27, %28, %29, %30, %31}, {%32, %33, %34, %35}, %36, p, 1, 1, %38;\n}\n"
        : "+f"(d[0]), "+f"(d[1]), "+f"(d[2]), "+f"(d[3]), "+f"(d[4]), "+f"(d[5]), "+f"(d[6]), "+f"(d[7]), "+f"(d[8]), "+f"(d[9]), "+f"(d[10]), "+f"(d[11]), "+f"(d[12]), "+f"(d[13]), "+f"(d[14]), "+f"(d[15]), "+f"(d[16]), "+f"(d[17]), "+f"(d[18]), "+f"(d[19]), "+f"(d[20]), "+f"(d[21]), "+f"(d[22]), "+f"(d[23]), "+f"(d[24]), "+f"(d[25]), "+f"(d[26]), "+f"(d[27]), "+f"(d[28]), "+f"(d[29]), "+f"(d[30]), "+f"(d[31])
        : "r"(a0), "r"(a1), "r"(a2), "r"(a3), "l"(db), "r"(sc), "n"(TB));
}
template <int TB> __device__ __forceinline__ void wgmma_rs_n128(float (&d)[64], uint32_t a0, uint32_t a1, uint32_t a2, uint32_t a3, uint64_t db, int sc) {
    asm volatile("{\n.reg .pred p;\nsetp.ne.b32 p, %69, 0;\n"
        "wgmma.mma_async.sync.aligned.m64n128k16.f32.bf16.bf16 {%0, %1, %2, %3, %4, %5, %6, %7, %8, %9, %10, %11, %12, %13, %14, %15, %16, %17, %18, %19, %20, %21, %22, %23, %24, %25, %26, %27, %28, %29, %30, %31, %32, %33, %34, %35, %36, %37, %38, %39, %40, %41, %42, %43, %44, %45, %46, %47, %48, %49, %50, %51, %52, %53, %54, %55, %56, %57, %58, %59, %60, %61, %62, %63}, {%64, %65, %66, %67}, %68, p, 1, 1, %70;\n}\n"
        : "+f"(d[0]), "+f"(d[1]), "+f"(d[2]), "+f"(d[3]), "+f"(d[4]), "+f"(d[5]), "+f"(d[6]), "+f"(d[7]), "+f"(d[8]), "+f"(d[9]), "+f"(d[10]), "+f"(d[11]), "+f"(d[12]), "+f"(d[13]), "+f"(d[14]), "+f"(d[15]), "+f"(d[16]), "+f"(d[17]), "+f"(d[18]), "+f"(d[19]), "+f"(d[20]), "+f"(d[21]), "+f"(d[22]), "+f"(d[23]), "+f"(d[24]), "+f"(d[25]), "+f"(d[26]), "+f"(d[27]), "+f"(d[28]), "+f"(d[29]), "+f"(d[30]), "+f"(d[31]), "+f"(d[32]), "+f"(d[33]), "+f"(d[34]), "+f"(d[35]), "+f"(d[36]), "+f"(d[37]), "+f"(d[38]), "+f"(d[39]), "+f"(d[40]), "+f"(d[41]), "+f"(d[42]), "+f"(d[43]), "+f"(d[44]), "+f"(d[45]), "+f"(d[46]), "+f"(d[47]), "+f"(d[48]), "+f"(d[49]), "+f"(d[50]), "+f"(d[51]), "+f"(d[52]), "+f"(d[53]), "+f"(d[54]), "+f"(d[55]), "+f"(d[56]), "+f"(d[57]), "+f"(d[58]), "+f"(d[59]), "+f"(d[60]), "+f"(d[61]), "+f"(d[62]), "+f"(d[63])
        : "r"(a0), "r"(a1), "r"(a2), "r"(a3), "l"(db), "r"(sc), "n"(TB));
}

constexpr int P_NST = 6;
constexpr int P_A_BYTES = 9 * 8192;
constexpr int P_B_STAGE = 3 * 8192;
constexpr int P_SMEM = P_A_BYTES + P_NST * P_B_STAGE + 256 + 320;

template <int NB>
__device__ __forceinline__ void stage_tile(const uint32_t (&pk)[NB * 2], uint32_t base, int w, int lane) {
    const int r = w * 16 + (lane & 7) + ((lane >> 3) & 1) * 8;
#pragma unroll
    for (int b = 0; b < NB; b += 2) {
        const uint32_t a = base + (b >> 3) * 8192 + r * 128 + ((((b & 7) + (lane >> 4)) ^ (r & 7)) << 4);
        stmatrix_x4(a, pk[2 * b], pk[2 * b + 1], pk[2 * b + 2], pk[2 * b + 3]);
    }
}

__device__ __forceinline__ uint32_t hsub2_bf16(uint32_t a, uint32_t b) { uint32_t r; asm("sub.rn.bf16x2 %0, %1, %2;" : "=r"(r) : "r"(a), "r"(b)); return r; }

constexpr int KV_RAW = DM * 18 * 2;
constexpr int Q_THREADS = 416;

__device__ __forceinline__ void proj_mma(float (&acc)[32], int wg, uint32_t fullB, uint32_t emptyB, uint32_t fullA, bool wait_a, int lane) {
    const uint64_t dA = cdesc(0, 16, 1024, 1), dB = cdesc(P_A_BYTES, 8192, 1024, 1) + wg * 512;
#pragma unroll 1
    for (int kb = 0; kb < 9; kb++) {
        const int s = kb >= P_NST ? kb - P_NST : kb;
        if (wait_a) mbar_wait(fullA + kb * 8, 0);
        mbar_wait(fullB + s * 8, kb >= P_NST ? 1 : 0);
        wg_fence();
#pragma unroll
        for (int ks = 0; ks < 4; ks++) wgmma_ss_n64<1>(acc, dA + (kb * 512 + ks * 2), dB + (s * (P_B_STAGE >> 4) + ks * 128), (kb | ks) != 0);
        wg_commit();
        if (kb < 4) {
            wg_wait<1>();
            if (kb >= 1 && lane == 0) mbar_arrive(emptyB + (kb - 1) * 8);
        }
    }
    wg_wait<0>();
    pin(acc);
}

__global__ void __launch_bounds__(Q_THREADS, 1)
k_qkv(const __grid_constant__ CUtensorMap tmWq, const __grid_constant__ CUtensorMap tmQ, const __nv_bfloat16* __restrict__ x, const __nv_bfloat16* __restrict__ wk, const __nv_bfloat16* __restrict__ wv) {
    extern __shared__ __align__(1024) uint8_t smem[];
    const uint32_t sA = smem_u32(smem), sB = sA + P_A_BYTES, bars = sB + P_NST * P_B_STAGE;
    const uint32_t fullB = bars, emptyB = bars + 64, fullX = bars + 128, fullW = bars + 136;
    float* s_rstd = reinterpret_cast<float*>(smem + P_A_BYTES + P_NST * P_B_STAGE + 256);
    const int tid = threadIdx.x, warp = __shfl_sync(~0u, tid >> 5, 0), lane = tid & 31;
    const bool isQ = blockIdx.x < 96;
    const int m = isQ ? blockIdx.x / 3 : blockIdx.x - 96, cg = blockIdx.x % 3;
    if (tid == 0) TS(0, 0);
    if (warp == 12) {
        if (elect_one()) {
            mbar_init(fullX, 1);
            bar_init_fence();
            mbar_expect(fullX, P_A_BYTES);
            bulk_g2s(sA, x + (size_t)m * 64 * DM, P_A_BYTES, fullX);
            prefetch_map(&tmWq); prefetch_map(&tmQ);
            for (int i = 0; i < P_NST; i++) { mbar_init(fullB + i * 8, 1); mbar_init(emptyB + i * 8, 12); }
            mbar_init(fullW, 1);
            bar_init_fence();
            if (isQ) {
                for (int kb = 0; kb < P_NST; kb++) {
                    mbar_expect(fullB + kb * 8, P_B_STAGE);
                    for (int a = 0; a < 3; a++) tma_2d(sB + kb * P_B_STAGE + a * 8192, &tmWq, cg * 192 + a * 64, kb * 64, fullB + kb * 8);
                }
            } else {
                mbar_expect(fullW, 2 * KV_RAW);
                bulk_g2s(sB + 3 * P_B_STAGE, wk, KV_RAW, fullW);
                bulk_g2s(sB + 3 * P_B_STAGE + KV_RAW, wv, KV_RAW, fullW);
            }
        }
        __syncwarp();
    }
    check_smem_base(sA);
    __syncthreads();
    pdl_launch();
    if (warp == 12) {
        if (isQ && elect_one()) {
            for (int kb = P_NST; kb < 9; kb++) {
                const int s = kb - P_NST;
                mbar_wait(emptyB + s * 8, 0);
                mbar_expect(fullB + s * 8, P_B_STAGE);
                for (int a = 0; a < 3; a++) tma_2d(sB + s * P_B_STAGE + a * 8192, &tmWq, cg * 192 + a * 64, kb * 64, fullB + s * 8);
            }
        }
        return;
    }
    if (warp < 8) {
        const int row = tid >> 2, q = tid & 3, h0 = (row & 1) * 4;
        mbar_wait(fullX, 0);
        if (tid == 0) TS(0, 6);
        uint4 v[18];
        const uint32_t ra = sA + row * 1152 + (q + h0) * 16, rb = sA + row * 1152 + (q + 4 - h0) * 16;
#pragma unroll
        for (int kb = 0; kb < 9; kb++) {
            asm volatile("ld.shared.v4.b32 {%0, %1, %2, %3}, [%4];" : "=r"(v[2 * kb].x), "=r"(v[2 * kb].y), "=r"(v[2 * kb].z), "=r"(v[2 * kb].w) : "r"(ra + kb * 128));
            asm volatile("ld.shared.v4.b32 {%0, %1, %2, %3}, [%4];" : "=r"(v[2 * kb + 1].x), "=r"(v[2 * kb + 1].y), "=r"(v[2 * kb + 1].z), "=r"(v[2 * kb + 1].w) : "r"(rb + kb * 128));
        }
        float sum = 0.f, sum2 = 0.f, sq = 0.f, sq2 = 0.f;
#pragma unroll
        for (int i = 0; i < 18; i++) {
            const uint32_t w[4] = {v[i].x, v[i].y, v[i].z, v[i].w};
#pragma unroll
            for (int j = 0; j < 4; j++) { const float a = bf_lo(w[j]), b = bf_hi(w[j]); sum += a; sum2 += b; sq = fmaf(a, a, sq); sq2 = fmaf(b, b, sq2); }
        }
        named_sync(1, 256);
        sum += sum2; sq += sq2;
        sum += __shfl_xor_sync(~0u, sum, 1); sum += __shfl_xor_sync(~0u, sum, 2);
        sq += __shfl_xor_sync(~0u, sq, 1); sq += __shfl_xor_sync(~0u, sq, 2);
        if (tid == 0) TS(0, 4);
        const float mean = sum * (1.0f / DM);
        if (q == 0) s_rstd[row] = rsqrtf(fmaxf(sq * (1.0f / DM) - mean * mean, 0.f) + LN_EPS);
        const uint32_t mhi = pack_bf16(mean, mean);
        const float rem = mean - bf_lo(mhi);
        const uint32_t mlo = pack_bf16(rem, rem);
        const uint32_t wa = sA + row * 128 + (((q + h0) ^ (row & 7)) << 4), wb = sA + row * 128 + (((q + 4 - h0) ^ (row & 7)) << 4);
#pragma unroll
        for (int i = 0; i < 18; i++) {
            const uint32_t o0 = hsub2_bf16(hsub2_bf16(v[i].x, mhi), mlo), o1 = hsub2_bf16(hsub2_bf16(v[i].y, mhi), mlo);
            const uint32_t o2 = hsub2_bf16(hsub2_bf16(v[i].z, mhi), mlo), o3 = hsub2_bf16(hsub2_bf16(v[i].w, mhi), mlo);
            asm volatile("st.shared.v4.b32 [%0], {%1, %2, %3, %4};" ::"r"(((i & 1) ? wb : wa) + (i >> 1) * 8192), "r"(o0), "r"(o1), "r"(o2), "r"(o3) : "memory");
        }
    } else if (!isQ) {
        mbar_wait(fullW, 0);
        const uint32_t* raw = reinterpret_cast<const uint32_t*>(smem + P_A_BYTES + 3 * P_B_STAGE);
#pragma unroll 3
        for (int r = tid - 256; r < 2 * DM; r += 128) {
            uint32_t wr[9];
#pragma unroll
            for (int i = 0; i < 9; i++) wr[i] = raw[r * 9 + i];
            const int sel = r >= DM, k = r - sel * DM;
            uint8_t* dst = smem + P_A_BYTES + sel * 3 * 9216 + (k >> 3) * 128 + (k & 7) * 16;
            *reinterpret_cast<uint4*>(dst) = make_uint4(wr[0], wr[1], wr[2], wr[3]);
            *reinterpret_cast<uint4*>(dst + 9216) = make_uint4(wr[4], wr[5], wr[6], wr[7]);
            *reinterpret_cast<uint32_t*>(dst + 2 * 9216) = wr[8];
        }
    }
    proxy_fence();
    named_sync(2, 384);
    if (tid == 0) TS(0, 1);
    const int wg = warp >> 2, w = warp & 3, g = lane >> 2, t = lane & 3;
    const float rs0 = s_rstd[w * 16 + g], rs1 = s_rstd[w * 16 + g + 8];
    if (isQ) {
        const float c0 = rs0 * Q_SCALE, c1 = rs1 * Q_SCALE;
        float acc[32];
        proj_mma(acc, wg, fullB, emptyB, 0, false, lane);
        if (tid == 0) TS(0, 2);
        uint32_t pk[16];
#pragma unroll
        for (int i = 0; i < 8; i++) { pk[2 * i] = pack_bf16(acc[4 * i] * c0, acc[4 * i + 1] * c0); pk[2 * i + 1] = pack_bf16(acc[4 * i + 2] * c1, acc[4 * i + 3] * c1); }
        named_sync(2, 384);
        stage_tile<8>(pk, sA + wg * 8192, w, lane);
        proxy_fence();
        named_sync(3 + wg, 128);
        if (w == 0 && elect_one()) {
            tma_st_2d(&tmQ, cg * 192 + wg * 64, m * 64, sA + wg * 8192);
            bulk_commit();
            bulk_wait_all();
        }
    } else if (wg < 2) {
        float acc[12];
        const uint64_t dA = cdesc(0, 16, 1024, 1), dB = cdesc(P_A_BYTES, 128, 9216, 0) + wg * (3 * 9216 >> 4);
#pragma unroll
        for (int i = 0; i < 12; i++) acc[i] = 0.f;
        pin(acc);
        wg_fence();
#pragma unroll 1
        for (int kb = 0; kb < 9; kb++) {
#pragma unroll
            for (int ks = 0; ks < 4; ks++) wgmma_ss_n24<1>(acc, dA + (kb * 512 + ks * 2), dB + (kb * 4 + ks) * 16, 1);
        }
        wg_commit();
        wg_wait<0>();
        pin(acc);
        uint32_t pk[6];
#pragma unroll
        for (int b = 0; b < 3; b++) { pk[2 * b] = pack_bf16(acc[4 * b] * rs0, acc[4 * b + 1] * rs0); pk[2 * b + 1] = pack_bf16(acc[4 * b + 2] * rs1, acc[4 * b + 3] * rs1); }
        float n0 = 0.f, n1 = 0.f, vm = 0.f;
#pragma unroll
        for (int b = 0; b < 3; b++) {
            if (b < 2 || t == 0) {
                const float a = bf_lo(pk[2 * b]), c = bf_hi(pk[2 * b]), d = bf_lo(pk[2 * b + 1]), e = bf_hi(pk[2 * b + 1]);
                n0 = fmaf(a, a, fmaf(c, c, n0)); n1 = fmaf(d, d, fmaf(e, e, n1));
            }
        }
        n0 += __shfl_xor_sync(~0u, n0, 1); n0 += __shfl_xor_sync(~0u, n0, 2);
        n1 += __shfl_xor_sync(~0u, n1, 1); n1 += __shfl_xor_sync(~0u, n1, 2);
        vm = fmaxf(n0, n1);
        if (!(n0 == n0) || !(n1 == n1)) vm = __int_as_float(0x7F800000);
#pragma unroll
        for (int o = 4; o < 32; o <<= 1) vm = fmaxf(vm, __shfl_xor_sync(~0u, vm, o));
        if (t != 0) {
            uint32_t lo, hi;
            if (wg == 0) {
                const int grp = m * 8 + w * 2;
                const uint32_t c = t == 1 ? 0x42FE3F80u   : (t == 2 ? 0x00003BC0u   : 0u);
                lo = ((POLY_MASK >> (grp & 15)) & 1) ? c : 0u;
                hi = ((POLY_MASK >> ((grp + 1) & 15)) & 1) ? c : 0u;
            } else {
                lo = hi = t == 1 ? 0x00003F80u : 0u;
            }
            pk[4] = lo; pk[5] = hi;
        }
        uint32_t* dst = reinterpret_cast<uint32_t*>(wg == 0 ? g_kc : g_vc) + (m * 8 + w * 2) * 96 + g * 4 + t;
#pragma unroll
        for (int b = 0; b < 3; b++) { dst[b * 32] = pk[2 * b]; dst[96 + b * 32] = pk[2 * b + 1]; }
        if (lane == 0) g_kmax[m * 8 + warp] = (wg == 0) ? vm : (vm <= 1e24f ? 0.f : __int_as_float(0x7F800000));
    }
    if (tid == 0) TS(0, 3);
}

constexpr int A_THREADS = 512;
constexpr int A_NPIECE = 8;
constexpr int A_OFF_Q = 2 * KV_BYTES;
constexpr int A_OFF_BAR = A_OFF_Q + 4 * 4096;
constexpr int A_SMEM = A_OFF_BAR + 128;

__device__ __forceinline__ uint32_t exp2_pair_fixed(float lo, float hi) {
    const uint32_t G = __byte_perm(__float_as_uint(lo), __float_as_uint(hi), 0x5410);
    const uint32_t Hh = G & 0x007F007Fu;
    const uint32_t tt = hfma2(Hh, 0xF96BF96Bu, 0x358C358Cu);
    return G - hfma2(tt, Hh, 0u);
}

__global__ void __launch_bounds__(A_THREADS, 1)
k_attn() {
    extern __shared__ __align__(1024) uint8_t smem[];
    pdl_launch();
    const uint32_t sK = smem_u32(smem), sV = sK + KV_BYTES, bars = sK + A_OFF_BAR;
    const int tid = threadIdx.x;
    check_smem_base(sK);
    if (tid == 0) TS(1, 0);
    if (tid == 0) {
        for (int i = 0; i < A_NPIECE; i++) mbar_init(bars + i * 8, 1);
        bar_init_fence();
    }
    __syncthreads();
    pdl_wait();
    if (tid == 0) TS(1, 1);
    const int wg = __shfl_sync(~0u, tid >> 7, 0), w = (tid >> 5) & 3, lane = tid & 31, g = lane >> 2, t = lane & 3;
    const uint32_t* q32 = reinterpret_cast<const uint32_t*>(g_q);
    int row = (blockIdx.x * 8 + wg) * 64 + w * 16 + g;
    uint32_t nq[6];
    nq[0] = q32[row * 9 + t]; nq[1] = q32[(row + 8) * 9 + t]; nq[2] = q32[row * 9 + 4 + t]; nq[3] = q32[(row + 8) * 9 + 4 + t];
    nq[4] = q32[row * 9 + 8]; nq[5] = q32[(row + 8) * 9 + 8];
    constexpr int PB = KV_BYTES / A_NPIECE;
    const float4 km0 = reinterpret_cast<const float4*>(g_kmax)[lane], km1 = reinterpret_cast<const float4*>(g_kmax)[32 + lane];
    if (tid < 32 && elect_one()) {
        for (int i = 0; i < 2; i++) {
            mbar_expect(bars + i * 8, 2 * PB);
            bulk_g2s(sK + i * PB, reinterpret_cast<const char*>(g_kc) + i * PB, PB, bars + i * 8);
            bulk_g2s(sV + i * PB, reinterpret_cast<const char*>(g_vc) + i * PB, PB, bars + i * 8);
        }
    }
    float kmax2 = fmaxf(fmaxf(fmaxf(km0.x, km0.y), fmaxf(km0.z, km0.w)), fmaxf(fmaxf(km1.x, km1.y), fmaxf(km1.z, km1.w)));
#pragma unroll
    for (int o = 1; o < 32; o <<= 1) kmax2 = fmaxf(kmax2, __shfl_xor_sync(~0u, kmax2, o));
    if (tid < 32 && elect_one()) {
        for (int i = 2; i < A_NPIECE; i++) {
            mbar_expect(bars + i * 8, 2 * PB);
            bulk_g2s(sK + i * PB, reinterpret_cast<const char*>(g_kc) + i * PB, PB, bars + i * 8);
            bulk_g2s(sV + i * PB, reinterpret_cast<const char*>(g_vc) + i * PB, PB, bars + i * 8);
        }
    }
    const uint32_t sQ = sK + A_OFF_Q + wg * 4096 + (w * 2) * 512 + g * 16 + t * 4;
    const uint64_t dQ0 = cdesc(A_OFF_Q, 128, 512, 0) + wg * 256, dQ1 = dQ0 + 16;
#pragma unroll 1
    for (int rep = 0; rep < 2; rep++, row += 256) {
        const uint32_t qa[4] = {nq[0], nq[1], nq[2], nq[3]};
        float n0, n1;
        {
            const float a0 = bf_lo(qa[0]), a1 = bf_hi(qa[0]), a2 = bf_lo(qa[2]), a3 = bf_hi(qa[2]);
            const float b0 = bf_lo(qa[1]), b1 = bf_hi(qa[1]), b2 = bf_lo(qa[3]), b3 = bf_hi(qa[3]);
            n0 = a0 * a0 + a1 * a1 + a2 * a2 + a3 * a3; n1 = b0 * b0 + b1 * b1 + b2 * b2 + b3 * b3;
            if (t == 0) {
                const float c0 = bf_lo(nq[4]), c1 = bf_hi(nq[4]), d0 = bf_lo(nq[5]), d1 = bf_hi(nq[5]);
                n0 += c0 * c0 + c1 * c1; n1 += d0 * d0 + d1 * d1;
            }
            n0 += __shfl_xor_sync(~0u, n0, 1); n0 += __shfl_xor_sync(~0u, n0, 2);
            n1 += __shfl_xor_sync(~0u, n1, 1); n1 += __shfl_xor_sync(~0u, n1, 2);
        }
        const uint32_t x0 = nq[4], x1 = nq[5];
        if (rep == 0) {
            const int nr = row + 256;
            nq[0] = q32[nr * 9 + t]; nq[1] = q32[(nr + 8) * 9 + t]; nq[2] = q32[nr * 9 + 4 + t]; nq[3] = q32[(nr + 8) * 9 + 4 + t];
            nq[4] = q32[nr * 9 + 8]; nq[5] = q32[(nr + 8) * 9 + 8];
        }
        if (tid == 0 && rep == 0) TS(1, 7);
        const bool unsafe = !(fmaxf(n0, n1) * kmax2 <= FAST_BOUND * FAST_BOUND) || !(n0 == n0) || !(n1 == n1);
        uint32_t any_unsafe;
        asm volatile("{\n.reg .pred p, q;\nsetp.ne.u32 p, %1, 0;\nbar.red.or.pred q, %2, 128, p;\nselp.u32 %0, 1, 0, q;\n}\n" : "=r"(any_unsafe) : "r"((uint32_t)unsafe), "r"(wg + 1) : "memory");
        any_unsafe = __shfl_sync(~0u, any_unsafe, 0);
        {
            const uint32_t cst = any_unsafe ? 0u : (t == 1 ? 0x3F804780u : (t == 2 ? 0x00003F80u : 0u));
            asm volatile("st.shared.b32 [%0], %1;" ::"r"(sQ), "r"(qa[0]) : "memory");
            asm volatile("st.shared.b32 [%0], %1;" ::"r"(sQ + 512), "r"(qa[1]) : "memory");
            asm volatile("st.shared.b32 [%0], %1;" ::"r"(sQ + 128), "r"(qa[2]) : "memory");
            asm volatile("st.shared.b32 [%0], %1;" ::"r"(sQ + 640), "r"(qa[3]) : "memory");
            asm volatile("st.shared.b32 [%0], %1;" ::"r"(sQ + 256), "r"(t == 0 ? x0 : cst) : "memory");
            asm volatile("st.shared.b32 [%0], %1;" ::"r"(sQ + 768), "r"(t == 0 ? x1 : cst) : "memory");
            asm volatile("st.shared.b32 [%0], %1;" ::"r"(sQ + 384), "r"(0u) : "memory");
            asm volatile("st.shared.b32 [%0], %1;" ::"r"(sQ + 896), "r"(0u) : "memory");
            proxy_fence();
            named_sync(wg + 1, 128);
        }
        if (tid == 0) TS(1, 2 + rep * 2);
        float o[12];
#pragma unroll
        for (int i = 0; i < 12; i++) o[i] = 0.f;
        pin(o);
        uint64_t dK0 = cdesc(0, 128, 384, 0), dK1 = cdesc(256, 0, 384, 0), dV = cdesc(KV_BYTES, 384, 128, 0);
        if (!any_unsafe) {
            float s[64];
#pragma unroll 1
            for (int j = 0; j < 16; j++) {
                if (rep == 0 && (j & 1) == 0) mbar_wait(bars + (j >> 1) * 8, 0);
                wg_fence();
                wgmma_ss_n128<0>(s, dQ0, dK0, 0);
                wgmma_ss_n128<0>(s, dQ1, dK1, 1);
                wg_commit();
                dK0 += 16 * 384 >> 4; dK1 += 16 * 384 >> 4;
                wg_wait<0>();
                pin(s);
                uint32_t p[32];
#pragma unroll
                for (int i = 0; i < 32; i++) {
                    if ((POLY_MASK >> (i >> 1)) & 1) p[i] = exp2_pair_fixed(s[2 * i], s[2 * i + 1]);
                    else p[i] = pack_bf16(ex2(s[2 * i]), ex2(s[2 * i + 1]));
                }
                pin(p);
                wg_fence();
#pragma unroll
                for (int k = 0; k < 8; k++) wgmma_rs_n24<1>(o, p[4 * k], p[4 * k + 1], p[4 * k + 2], p[4 * k + 3], dV + k * 48, 1);
                wg_commit();
                dV += 16 * 384 >> 4;
                wg_wait<0>();
            }
        } else {
            float s[64];
            float m0 = -INFINITY, m1 = -INFINITY;
#pragma unroll 1
            for (int j = 0; j < 16; j++) {
                if (rep == 0 && (j & 1) == 0) mbar_wait(bars + (j >> 1) * 8, 0);
                wg_fence();
                wgmma_ss_n128<0>(s, dQ0, dK0, 0);
                wgmma_ss_n128<0>(s, dQ1, dK1, 1);
                wg_commit();
                dK0 += 16 * 384 >> 4; dK1 += 16 * 384 >> 4;
                wg_wait<0>();
                pin(s);
                float x0m = m0, x1m = m1;
#pragma unroll
                for (int b = 0; b < 16; b++) { x0m = fmaxf(x0m, fmaxf(s[4 * b], s[4 * b + 1])); x1m = fmaxf(x1m, fmaxf(s[4 * b + 2], s[4 * b + 3])); }
                x0m = fmaxf(x0m, __shfl_xor_sync(~0u, x0m, 1)); x0m = fmaxf(x0m, __shfl_xor_sync(~0u, x0m, 2));
                x1m = fmaxf(x1m, __shfl_xor_sync(~0u, x1m, 1)); x1m = fmaxf(x1m, __shfl_xor_sync(~0u, x1m, 2));
                const float c0 = ex2(m0 - x0m), c1 = ex2(m1 - x1m);
                m0 = x0m; m1 = x1m;
#pragma unroll
                for (int b = 0; b < 3; b++) { o[4 * b] *= c0; o[4 * b + 1] *= c0; o[4 * b + 2] *= c1; o[4 * b + 3] *= c1; }
                uint32_t p[32];
#pragma unroll
                for (int b = 0; b < 16; b++) {
                    p[2 * b] = pack_bf16(ex2(s[4 * b] - m0), ex2(s[4 * b + 1] - m0));
                    p[2 * b + 1] = pack_bf16(ex2(s[4 * b + 2] - m1), ex2(s[4 * b + 3] - m1));
                }
                pin(p); pin(o);
                wg_fence();
#pragma unroll
                for (int k = 0; k < 8; k++) wgmma_rs_n24<1>(o, p[4 * k], p[4 * k + 1], p[4 * k + 2], p[4 * k + 3], dV + k * 48, 1);
                wg_commit();
                dV += 16 * 384 >> 4;
                wg_wait<0>();
            }
        }
        pin(o);
        if (tid == 0) TS(1, 3 + rep * 2);
        const float l0 = __shfl_sync(~0u, o[8], (lane & ~3) | 1), l1 = __shfl_sync(~0u, o[10], (lane & ~3) | 1);
        const float i0 = 1.0f / l0, i1 = 1.0f / l1;
        uint32_t* o32 = reinterpret_cast<uint32_t*>(g_o);
        o32[row * 9 + t] = pack_bf16(o[0] * i0, o[1] * i0);
        o32[(row + 8) * 9 + t] = pack_bf16(o[2] * i1, o[3] * i1);
        o32[row * 9 + 4 + t] = pack_bf16(o[4] * i0, o[5] * i0);
        o32[(row + 8) * 9 + 4 + t] = pack_bf16(o[6] * i1, o[7] * i1);
        if (t == 0) { o32[row * 9 + 8] = pack_bf16(o[8] * i0, o[9] * i0); o32[(row + 8) * 9 + 8] = pack_bf16(o[10] * i1, o[11] * i1); }
    }
    if (tid == 0) TS(1, 6);
    if ((tid & 127) == 0) TS(1, 10 + wg);
}

constexpr int O_THREADS = 416;
constexpr int O_OFF_STAT = P_A_BYTES + P_NST * P_B_STAGE + 256;
constexpr int O_SMEM = O_OFF_STAT + 9 * 64 * 8;

__global__ void __cluster_dims__(3, 1, 1) __launch_bounds__(O_THREADS, 1)
k_oproj(const __grid_constant__ CUtensorMap tmO, const __grid_constant__ CUtensorMap tmWo, const __grid_constant__ CUtensorMap tmX2, const __grid_constant__ CUtensorMap tmOut, const __nv_bfloat16* __restrict__ x, const __nv_bfloat16* __restrict__ w1) {
    extern __shared__ __align__(1024) uint8_t smem[];
    const uint32_t sA = smem_u32(smem), sB = sA + P_A_BYTES, bars = sB + P_NST * P_B_STAGE;
    const uint32_t fullB = bars, emptyB = bars + 64, fullA = bars + 128;
    const int tid = threadIdx.x, warp = __shfl_sync(~0u, tid >> 5, 0), lane = tid & 31;
    const int m = blockIdx.x / 3, cg = blockIdx.x % 3;
    if (tid == 0) TS(2, 0);
    check_smem_base(sA);
    if (tid == 0) {
        prefetch_map(&tmO); prefetch_map(&tmWo); prefetch_map(&tmX2); prefetch_map(&tmOut);
        for (int i = 0; i < P_NST; i++) { mbar_init(fullB + i * 8, 1); mbar_init(emptyB + i * 8, 12); }
        for (int i = 0; i < 9; i++) mbar_init(fullA + i * 8, 1);
        bar_init_fence();
        for (int kb = 0; kb < 9; kb++) mbar_expect(fullA + kb * 8, 8192);
    }
    __syncthreads();
    pdl_launch();
    if (warp == 12) {
        if (elect_one()) {
            for (int kb = 0; kb < 9; kb++) {
                const int s = kb >= P_NST ? kb - P_NST : kb;
                if (kb == 2) {
                    pdl_wait();
                    TS(2, 1);
                    for (int ka = 0; ka < 9; ka++) tma_2d(sA + ka * 8192, &tmO, ka * 64, m * 64, fullA + ka * 8);
                }
                if (kb >= P_NST) mbar_wait(emptyB + s * 8, 0);
                mbar_expect(fullB + s * 8, P_B_STAGE);
                for (int a = 0; a < 3; a++) tma_2d(sB + s * P_B_STAGE + a * 8192, &tmWo, cg * 192 + a * 64, kb * 64, fullB + s * 8);
            }
            for (int i = 0; i < 6; i++) prefetch_l2(reinterpret_cast<const char*>(w1) + (size_t)blockIdx.x * (FF * DM * 2 / 96) + i * 9216, 9216);
        }
        return;
    }
    if (tid == 0) TS(2, 11);
    const int wg = warp >> 2, w = warp & 3, g = lane >> 2, t = lane & 3;
    uint32_t xr[16];
    {
        const uint32_t* x32 = reinterpret_cast<const uint32_t*>(x) + (((m * 64 + w * 16 + g) * DM + cg * 192 + wg * 64 + 2 * t) >> 1);
#pragma unroll
        for (int b = 0; b < 8; b++) { xr[2 * b] = __ldg(x32 + b * 4); xr[2 * b + 1] = __ldg(x32 + b * 4 + 4 * DM); }
    }
    float acc[32];
    proj_mma(acc, wg, fullB, emptyB, fullA, true, lane);
    if (tid == 0) TS(2, 2);
    named_sync(1, 384);
    float s0 = 0.f, q0 = 0.f, s1 = 0.f, q1 = 0.f;
#pragma unroll
    for (int b = 0; b < 8; b++) {
        const uint32_t xa = xr[2 * b], xb = xr[2 * b + 1];
        const uint32_t ha = pack_bf16(acc[4 * b] + bf_lo(xa), acc[4 * b + 1] + bf_hi(xa));
        const uint32_t hb = pack_bf16(acc[4 * b + 2] + bf_lo(xb), acc[4 * b + 3] + bf_hi(xb));
        xr[2 * b] = ha; xr[2 * b + 1] = hb;
        const float a = bf_lo(ha), c = bf_hi(ha), d = bf_lo(hb), e = bf_hi(hb);
        s0 += a + c; q0 = fmaf(a, a, fmaf(c, c, q0));
        s1 += d + e; q1 = fmaf(d, d, fmaf(e, e, q1));
    }
    s0 += __shfl_xor_sync(~0u, s0, 1); s0 += __shfl_xor_sync(~0u, s0, 2);
    q0 += __shfl_xor_sync(~0u, q0, 1); q0 += __shfl_xor_sync(~0u, q0, 2);
    s1 += __shfl_xor_sync(~0u, s1, 1); s1 += __shfl_xor_sync(~0u, s1, 2);
    q1 += __shfl_xor_sync(~0u, q1, 1); q1 += __shfl_xor_sync(~0u, q1, 2);
    const int r = w * 16 + g;
    const uint32_t sStat = sA + O_OFF_STAT;
    if (t < 3) {
        uint32_t dst;
        asm("mapa.shared::cluster.u32 %0, %1, %2;" : "=r"(dst) : "r"(sStat + ((cg * 3 + wg) * 64 + r) * 8), "r"(t));
        asm volatile("st.shared::cluster.v2.f32 [%0], {%1, %2};" ::"r"(dst), "f"(s0), "f"(q0) : "memory");
        asm volatile("st.shared::cluster.v2.f32 [%0], {%1, %2};" ::"r"(dst + 64), "f"(s1), "f"(q1) : "memory");
    }
    if (tid == 0) TS(2, 4);
    cluster_arrive();
    stage_tile<8>(xr, sA + wg * 8192, w, lane);
    proxy_fence();
    named_sync(2 + wg, 128);
    const bool leader = w == 0 && elect_one();
    if (leader) { tma_st_2d(&tmOut, cg * 192 + wg * 64, m * 64, sA + wg * 8192); bulk_commit(); }
    cluster_wait();
    if (tid == 0) TS(2, 5);
    s0 = q0 = s1 = q1 = 0.f;
#pragma unroll
    for (int p = 0; p < 9; p++) {
        float a, b, c, d;
        asm volatile("ld.shared.v2.f32 {%0, %1}, [%2];" : "=f"(a), "=f"(b) : "r"(sStat + (p * 64 + r) * 8));
        asm volatile("ld.shared.v2.f32 {%0, %1}, [%2];" : "=f"(c), "=f"(d) : "r"(sStat + (p * 64 + r + 8) * 8));
        s0 += a; q0 += b; s1 += c; q1 += d;
    }
    const float m0 = s0 * (1.0f / DM), m1 = s1 * (1.0f / DM);
    const float rs0 = rsqrtf(fmaxf(q0 * (1.0f / DM) - m0 * m0, 0.f) + LN_EPS), rs1 = rsqrtf(fmaxf(q1 * (1.0f / DM) - m1 * m1, 0.f) + LN_EPS);
    const float sc0 = 0.5f * rs0, sc1 = 0.5f * rs1, n0 = -m0 * sc0, n1 = -m1 * sc1;
#pragma unroll
    for (int b = 0; b < 8; b++) {
        xr[2 * b] = pack_bf16(fmaf(bf_lo(xr[2 * b]), sc0, n0), fmaf(bf_hi(xr[2 * b]), sc0, n0));
        xr[2 * b + 1] = pack_bf16(fmaf(bf_lo(xr[2 * b + 1]), sc1, n1), fmaf(bf_hi(xr[2 * b + 1]), sc1, n1));
    }
    stage_tile<8>(xr, sA + (3 + wg) * 8192, w, lane);
    proxy_fence();
    named_sync(2 + wg, 128);
    if (tid == 0) TS(2, 6);
    if (leader) {
        tma_st_2d(&tmX2, cg * 192 + wg * 64, m * 64, sA + (3 + wg) * 8192);
        bulk_commit();
        bulk_wait_all();
    }
    if (tid == 0) TS(2, 3);
}

constexpr int F_THREADS = 384;
constexpr int F_NST = 6;
constexpr int F_STAGE = 96 * 128;
constexpr int F_X_BYTES = 9 * 16384;
constexpr int F_OFF_ST = F_X_BYTES;
constexpr int F_OFF_BAR = F_OFF_ST + F_NST * F_STAGE;
constexpr int F_SMEM = F_OFF_BAR + 256;

__device__ __forceinline__ float tanh_hw(float x) { float y; asm("tanh.approx.f32 %0, %1;" : "=f"(y) : "f"(x)); return y; }
__host__ __device__ constexpr int piece_begin(int p) { return p == 0 ? 0 : 3 * p + 1; }
template <int P>
__device__ __forceinline__ void silu_s1(const float (&acc)[32], float (&tmp)[8]) {
#pragma unroll
    for (int i = 2 * piece_begin(P); i < 2 * piece_begin(P + 1); i++) tmp[i - 2 * piece_begin(P)] = tanh_hw(acc[i]);
}
template <int C, int P>
__device__ __forceinline__ void silu_s2(const float (&acc)[32], const float (&tmp)[8], uint32_t (&h1)[144]) {
#pragma unroll
    for (int i = piece_begin(P); i < piece_begin(P + 1); i++) {
        const int k = 2 * (i - piece_begin(P));
        h1[C * 16 + i] = pack_bf16(fmaf(acc[2 * i], tmp[k], acc[2 * i]), fmaf(acc[2 * i + 1], tmp[k + 1], acc[2 * i + 1]));
    }
}
template <int C, int J>
__device__ __forceinline__ void silu_slot(const float (&prev)[32], float (&tmp)[2][8], uint32_t (&h1)[144]) {
    if constexpr (J >= 1) silu_s2<C, J - 1>(prev, tmp[(J - 1) & 1], h1);
    if constexpr (J <= 4) { silu_s1<J>(prev, tmp[J & 1]); pin(tmp[J & 1]); }
}

struct FfnPipe {
    uint32_t full, empty;
    int lane;
    __device__ __forceinline__ void acquire(int s, uint32_t ph) const { mbar_wait(full + s * 8, ph); }
    __device__ __forceinline__ void release(int s) const { if (lane == 0) mbar_arrive(empty + s * 8); }
};

template <int C>
__device__ __forceinline__ void ffn_phase1_chunk(float (&cur)[32], float (&prev)[32], uint32_t (&h1)[144], const FfnPipe& pp, uint64_t dx, uint32_t fullX) {
    float tmp[2][8];
    const uint64_t dw = cdesc(F_OFF_ST, 8192, 1024, 1) + blockIdx.y * (C + 1);
    dx += blockIdx.y * C;
#pragma unroll
    for (int j = 0; j < 6; j++) {
        if (C == 0) { mbar_wait(fullX + ((6 * j) >> 2) * 8, 0); mbar_wait(fullX + ((6 * j + 5) >> 2) * 8, 0); }
        pp.acquire(j, C & 1);
        if (j == 0) pin(cur);
        wg_fence();
#pragma unroll
        for (int i = 0; i < 6; i++) {
            const int ks = 6 * j + i;
            wgmma_ss_n64<1>(cur, dx + ((ks >> 2) * 1024 + (ks & 3) * 2), dw + ((j * F_STAGE + i * 2048) >> 4), ks != 0);
        }
        wg_commit();
        if (C > 0 || j > 0) { wg_wait<1>(); pp.release((j + 5) % 6); }
        if (C > 0) {
            constexpr int CP = C > 0 ? C - 1 : 0;
            pin(prev);
            if (j == 0) silu_slot<CP, 0>(prev, tmp, h1);
            if (j == 1) silu_slot<CP, 1>(prev, tmp, h1);
            if (j == 2) silu_slot<CP, 2>(prev, tmp, h1);
            if (j == 3) silu_slot<CP, 3>(prev, tmp, h1);
            if (j == 4) silu_slot<CP, 4>(prev, tmp, h1);
            if (j == 5) silu_slot<CP, 5>(prev, tmp, h1);
        }
    }
}

__device__ __forceinline__ void ffn_store_chunk(const float (&acc)[32], const CUtensorMap* tmOut, uint32_t stg, int col, int row, int w, int lane, int wgid, bool leader) {
    uint32_t pk[16];
#pragma unroll
    for (int i = 0; i < 16; i++) pk[i] = pack_bf16(acc[2 * i], acc[2 * i + 1]);
    stage_tile<8>(pk, stg, w, lane);
    proxy_fence();
    named_sync(2 + wgid, 128);
    if (leader) {
        tma_red_2d(tmOut, col, row, stg);
        bulk_commit();
    }
}

__device__ __forceinline__ void ffn_phase2_chunk(float (&cur)[32], float (&prev)[32], uint32_t (&h1)[144], const FfnPipe& pp, uint32_t ph, bool store_prev, const CUtensorMap* tmOut, uint32_t stg_prev, int col_prev, int row, int w, int lane, int wgid, bool leader) {
    const uint64_t dw = cdesc(F_OFF_ST, 8192, 1024, 1) + blockIdx.y * col_prev;
#pragma unroll
    for (int j = 0; j < 6; j++) {
        pp.acquire(j, ph);
        if (j == 0) pin(cur);
        wg_fence();
#pragma unroll
        for (int i = 0; i < 6; i++) {
            const int f = (6 * j + i) * 4;
            wgmma_rs_n64<1>(cur, h1[f], h1[f + 1], h1[f + 2], h1[f + 3], dw + ((j * F_STAGE + i * 2048) >> 4), (j | i) != 0);
        }
        wg_commit();
        if (j > 0 || store_prev) { wg_wait<1>(); pp.release((j + 5) % 6); }
        if (j == 0 && store_prev) { pin(prev); ffn_store_chunk(prev, tmOut, stg_prev, col_prev, row, w, lane, wgid, leader); }
    }
}

__global__ void __launch_bounds__(F_THREADS, 1)
k_ffn(const __grid_constant__ CUtensorMap tmH, const __grid_constant__ CUtensorMap tmW1, const __grid_constant__ CUtensorMap tmW2, const __grid_constant__ CUtensorMap tmOut, const __nv_bfloat16* __restrict__ w2) {
    extern __shared__ __align__(1024) uint8_t smem[];
    const uint32_t sX = smem_u32(smem), sSt = sX + F_OFF_ST, bars = sX + F_OFF_BAR;
    const uint32_t full = bars, empty = bars + 64, fullX = bars + 128;
    const int tid = threadIdx.x, warp = __shfl_sync(~0u, tid >> 5, 0), lane = tid & 31;
#define FFN_MAP 1
    const int m = FFN_MAP == 0 ? (blockIdx.x & 15) : (FFN_MAP == 1 ? (blockIdx.x >> 3) : ((blockIdx.x >> 1) & 15));
    const int fs = FFN_MAP == 0 ? (blockIdx.x >> 4) : (FFN_MAP == 1 ? (blockIdx.x & 7) : ((blockIdx.x >> 5) * 2 + (blockIdx.x & 1)));
    if (tid == 0) TS(3, 0);
    check_smem_base(sX);
    if (tid == 0) {
        prefetch_map(&tmW1); prefetch_map(&tmH); prefetch_map(&tmW2); prefetch_map(&tmOut);
        for (int i = 0; i < F_NST; i++) { mbar_init(full + i * 8, 1); mbar_init(empty + i * 8, 8); }
        for (int i = 0; i < 9; i++) mbar_init(fullX + i * 8, 1);
        bar_init_fence();
        for (int kb = 0; kb < 9; kb++) mbar_expect(fullX + kb * 8, 16384);
    }
    __syncthreads();
    if (warp < 4) {
        asm volatile("setmaxnreg.dec.sync.aligned.u32 24;");
        if (warp == 1 && lane < 9) prefetch_l2(reinterpret_cast<const char*>(w2) + ((size_t)fs * 576 + m * 36 + lane * 4) * (DM * 2), 4 * DM * 2);
        if (warp == 0 && elect_one()) {
            int s = 0; uint32_t ph = 1;
            int c = 0, j = 0;
#pragma unroll 1
            for (int i = 0; i < 108; i++) {
                if (i == 54) c = fs;
                mbar_wait(empty + s * 8, ph);
                mbar_expect(full + s * 8, F_STAGE);
                if (i < 54) tma_2d(sSt + s * F_STAGE, &tmW1, fs * 576 + c * 64, j * 96, full + s * 8);
                else tma_2d(sSt + s * F_STAGE, &tmW2, c * 64, fs * 576 + j * 96, full + s * 8);
                if (++j == 6) { j = 0; if (++c == 9) c = 0; }
                if (++s == F_NST) { s = 0; ph ^= 1; }
            }
        }
    } else {
        asm volatile("setmaxnreg.inc.sync.aligned.u32 240;");
        const int wgid = (warp >> 2) - 1, w = warp & 3;
        pdl_wait();
        if (tid == 128) TS(3, 1);
        if (warp == 4 && elect_one()) {
            for (int kb = 0; kb < 9; kb++) tma_2d(sX + kb * 16384, &tmH, kb * 64, m * 128, fullX + kb * 8);
        }
        __syncwarp();
        FfnPipe pp{full, empty, lane};
        const uint64_t xlo = cdesc(0, 16, 1024, 1) + wgid * 512;
        uint32_t h1[144];
        float acc0[32], acc1[32];
        ffn_phase1_chunk<0>(acc0, acc1, h1, pp, xlo, fullX);
        if (tid == 128) TS(3, 2);
        ffn_phase1_chunk<1>(acc1, acc0, h1, pp, xlo, fullX);
        ffn_phase1_chunk<2>(acc0, acc1, h1, pp, xlo, fullX);
        ffn_phase1_chunk<3>(acc1, acc0, h1, pp, xlo, fullX);
        ffn_phase1_chunk<4>(acc0, acc1, h1, pp, xlo, fullX);
        ffn_phase1_chunk<5>(acc1, acc0, h1, pp, xlo, fullX);
        ffn_phase1_chunk<6>(acc0, acc1, h1, pp, xlo, fullX);
        ffn_phase1_chunk<7>(acc1, acc0, h1, pp, xlo, fullX);
        ffn_phase1_chunk<8>(acc0, acc1, h1, pp, xlo, fullX);
        wg_wait<0>();
        pp.release(5);
        pin(acc0);
#pragma unroll
        for (int i = 0; i < 16; i++) h1[128 + i] = pack_bf16(fmaf(acc0[2 * i], tanh_hw(acc0[2 * i]), acc0[2 * i]), fmaf(acc0[2 * i + 1], tanh_hw(acc0[2 * i + 1]), acc0[2 * i + 1]));
        pin(h1);
        if (tid == 128) TS(3, 3);
        const int row = m * 128 + wgid * 64;
        const uint32_t stg = sX + wgid * 8192;
        int c = fs, cprev = 0;
        const bool leader = w == 0 && elect_one();
#pragma unroll 1
        for (int j = 0; j < 8; j += 2) {
            ffn_phase2_chunk(acc1, acc0, h1, pp, 1, j > 0, &tmOut, stg + (j - 1) * 16384, cprev * 64, row, w, lane, wgid, leader);
            cprev = c; if (++c == 9) c = 0;
            ffn_phase2_chunk(acc0, acc1, h1, pp, 0, true, &tmOut, stg + j * 16384, cprev * 64, row, w, lane, wgid, leader);
            cprev = c; if (++c == 9) c = 0;
        }
        ffn_phase2_chunk(acc1, acc0, h1, pp, 1, true, &tmOut, stg + 7 * 16384, cprev * 64, row, w, lane, wgid, leader);
        wg_wait<0>();
        pin(acc1);
        ffn_store_chunk(acc1, &tmOut, stg + 8 * 16384, c * 64, row, w, lane, wgid, leader);
        if (tid == 128) TS(3, 4);
        if (leader) bulk_wait_all();
        if (tid == 128) TS(3, 5);
    }
}

typedef CUresult (*EncodeFn)(CUtensorMap*, CUtensorMapDataType, cuuint32_t, void*, const cuuint64_t*, const cuuint64_t*, const cuuint32_t*, const cuuint32_t*,
                             CUtensorMapInterleave, CUtensorMapSwizzle, CUtensorMapL2promotion, CUtensorMapFloatOOBfill);

CUtensorMap make_map(EncodeFn enc, const void* base, int rows, int cols, int box_rows) {
    CUtensorMap tm;
    cuuint64_t dims[2] = {(cuuint64_t)cols, (cuuint64_t)rows};
    cuuint64_t strides[1] = {(cuuint64_t)cols * 2};
    cuuint32_t box[2] = {64, (cuuint32_t)box_rows};
    cuuint32_t es[2] = {1, 1};
    enc(&tm, CU_TENSOR_MAP_DATA_TYPE_BFLOAT16, 2, const_cast<void*>(base), dims, strides, box, es, CU_TENSOR_MAP_INTERLEAVE_NONE,
        CU_TENSOR_MAP_SWIZZLE_128B, CU_TENSOR_MAP_L2_PROMOTION_L2_256B, CU_TENSOR_MAP_FLOAT_OOB_FILL_NONE);
    return tm;
}

template <typename... KArgs, typename... Args>
void launch(void (*kern)(KArgs...), int grid, int block, int smem, bool pdl, Args... args) {
    cudaLaunchConfig_t cfg = {};
    cfg.gridDim = dim3(grid); cfg.blockDim = dim3(block); cfg.dynamicSmemBytes = smem; cfg.stream = cudaStreamPerThread;
    cudaLaunchAttribute at[1];
    at[0].id = cudaLaunchAttributeProgrammaticStreamSerialization;
    at[0].val.programmaticStreamSerializationAllowed = 1;
    cfg.attrs = at; cfg.numAttrs = pdl ? 1 : 0;
    cudaLaunchKernelEx(&cfg, kern, KArgs(args)...);
}

}

#define USE_PDL 1

extern "C" void kernel_launch(void* const* d_in, const int* in_sizes, int n_in, void* d_out, int out_size) {
    const __nv_bfloat16* x = (const __nv_bfloat16*)d_in[0];
    const __nv_bfloat16* wq = (const __nv_bfloat16*)d_in[1];
    const __nv_bfloat16* wk = (const __nv_bfloat16*)d_in[2];
    const __nv_bfloat16* wv = (const __nv_bfloat16*)d_in[3];
    const __nv_bfloat16* wo = (const __nv_bfloat16*)d_in[4];
    const __nv_bfloat16* w1 = (const __nv_bfloat16*)d_in[6];
    const __nv_bfloat16* w2 = (const __nv_bfloat16*)d_in[7];
    __nv_bfloat16* out = (__nv_bfloat16*)d_out;

    static EncodeFn enc = nullptr;
    static void *p_o = nullptr, *p_h = nullptr, *p_q = nullptr;
    if (!enc) {
        cudaDriverEntryPointQueryResult qr;
        cudaGetDriverEntryPoint("cuTensorMapEncodeTiled", (void**)&enc, cudaEnableDefault, &qr);
        cudaGetSymbolAddress(&p_o, g_o);
        cudaGetSymbolAddress(&p_h, g_x2);
        cudaGetSymbolAddress(&p_q, g_q);
        cudaFuncSetAttribute(k_qkv, cudaFuncAttributeMaxDynamicSharedMemorySize, P_SMEM);
        cudaFuncSetAttribute(k_attn, cudaFuncAttributeMaxDynamicSharedMemorySize, A_SMEM);
        cudaFuncSetAttribute(k_oproj, cudaFuncAttributeMaxDynamicSharedMemorySize, O_SMEM);
        cudaFuncSetAttribute(k_ffn, cudaFuncAttributeMaxDynamicSharedMemorySize, F_SMEM);
    }
    const CUtensorMap tmWq = make_map(enc, wq, DM, DM, 64);
    const CUtensorMap tmWo = make_map(enc, wo, DM, DM, 64);
    const CUtensorMap tmO = make_map(enc, p_o, SEQ, DM, 64);
    const CUtensorMap tmH64 = make_map(enc, p_h, SEQ, DM, 64);
    const CUtensorMap tmH = make_map(enc, p_h, SEQ, DM, 128);
    const CUtensorMap tmQ = make_map(enc, p_q, SEQ, DM, 64);
    const CUtensorMap tmW1 = make_map(enc, w1, DM, FF, 96);
    const CUtensorMap tmW2 = make_map(enc, w2, FF, DM, 96);
    const CUtensorMap tmOut = make_map(enc, out, SEQ, DM, 64);

    launch(k_qkv, 128, Q_THREADS, P_SMEM, false, tmWq, tmQ, x, wk, wv);
    launch(k_attn, 128, A_THREADS, A_SMEM, USE_PDL);
    launch(k_oproj, 96, O_THREADS, O_SMEM, USE_PDL, tmO, tmWo, tmH64, tmOut, x, w1);
    launch(k_ffn, 128, F_THREADS, F_SMEM, USE_PDL, tmH, tmW1, tmW2, tmOut, w2);
}
```

```cpp
#include <cuda_runtime.h>
#include <cuda_bf16.h>
#include <cuda.h>
#include <stdint.h>

namespace {

constexpr int SEQ = 2048, DM = 576, FF = 4608;
constexpr int KV_BYTES = SEQ * 48;
constexpr float LN_EPS = 1e-5f;
constexpr float LOG2E = 1.4426950408889634f;
constexpr float Q_SCALE = 0.23570226039551584f * LOG2E;

#define POLY_MASK_V 0xB5B5u
constexpr uint32_t POLY_MASK = POLY_MASK_V;
constexpr float FAST_BOUND = 60.0f;

__device__ __align__(1024) __nv_bfloat16 g_q[SEQ * DM];
__device__ __align__(1024) uint4 g_kc[KV_BYTES / 16];
__device__ __align__(1024) uint4 g_vc[KV_BYTES / 16];
__device__ __align__(16) float g_kmax[256];
__device__ __align__(1024) __nv_bfloat16 g_o[SEQ * DM];
__device__ __align__(1024) __nv_bfloat16 g_x2[SEQ * DM];

#define TS(k, i)

__device__ __forceinline__ uint32_t smem_u32(const void* p) { return (uint32_t)__cvta_generic_to_shared(p); }
__device__ __forceinline__ void wg_fence() { asm volatile("wgmma.fence.sync.aligned;" ::: "memory"); }
__device__ __forceinline__ void wg_commit() { asm volatile("wgmma.commit_group.sync.aligned;" ::: "memory"); }
template <int N> __device__ __forceinline__ void wg_wait() { asm volatile("wgmma.wait_group.sync.aligned %0;" ::"n"(N) : "memory"); }
template <int N> __device__ __forceinline__ void pin(float (&r)[N]) {
#pragma unroll
    for (int i = 0; i < N; i++) asm volatile("" : "+f"(r[i])::"memory");
}
template <int N> __device__ __forceinline__ void pin(uint32_t (&r)[N]) {
#pragma unroll
    for (int i = 0; i < N; i++) asm volatile("" : "+r"(r[i])::"memory");
}
constexpr uint32_t SMEM0 = 0x400;
__host__ __device__ constexpr uint64_t cdesc(uint32_t off, uint32_t lbo, uint32_t sbo, uint32_t swz) {
    return (uint64_t)(((SMEM0 + off) & 0x3FFFF) >> 4) | ((uint64_t)(lbo >> 4) << 16) | ((uint64_t)(sbo >> 4) << 32) | ((uint64_t)swz << 62);
}
__device__ __forceinline__ void check_smem_base(uint32_t base) { if ((base & 0x3FFFF) != SMEM0) __trap(); }

__device__ __forceinline__ void mbar_init(uint32_t bar, int cnt) { asm volatile("mbarrier.init.shared::cta.b64 [%0], %1;" ::"r"(bar), "r"(cnt) : "memory"); }
__device__ __forceinline__ void mbar_expect(uint32_t bar, int bytes) { asm volatile("mbarrier.arrive.expect_tx.shared::cta.b64 _, [%0], %1;" ::"r"(bar), "r"(bytes) : "memory"); }
__device__ __forceinline__ void mbar_arrive(uint32_t bar) { asm volatile("mbarrier.arrive.shared::cta.b64 _, [%0];" ::"r"(bar) : "memory"); }
__device__ __forceinline__ void mbar_wait(uint32_t bar, uint32_t parity) {
    asm volatile(
        "{\n.reg .pred p;\n.reg .u32 n;\nmov.u32 n, 0;\n"
        "LAB_WAIT:\n"
        "mbarrier.try_wait.parity.shared::cta.b64 p, [%0], %1;\n"
        "@p bra DONE;\n"
        "add.u32 n, n, 1;\n"
        "setp.lt.u32 p, n, 4000000;\n"
        "@p bra LAB_WAIT;\n"
        "trap;\n"
        "DONE:\n}\n" ::"r"(bar), "r"(parity) : "memory");
}
__device__ __forceinline__ void bar_init_fence() {
    asm volatile("fence.mbarrier_init.release.cluster;" ::: "memory");
    asm volatile("fence.proxy.async.shared::cta;" ::: "memory");
}
__device__ __forceinline__ void proxy_fence() { asm volatile("fence.proxy.async.shared::cta;" ::: "memory"); }
__device__ __forceinline__ void named_sync(int id, int n) { asm volatile("bar.sync %0, %1;" ::"r"(id), "r"(n) : "memory"); }
__device__ __forceinline__ void bulk_g2s(uint32_t dst, const void* src, int bytes, uint32_t bar) {
    asm volatile("cp.async.bulk.shared::cluster.global.mbarrier::complete_tx::bytes [%0], [%1], %2, [%3];" ::"r"(dst), "l"(src), "r"(bytes), "r"(bar) : "memory");
}
__device__ __forceinline__ void tma_2d(uint32_t dst, const CUtensorMap* tm, int c0, int c1, uint32_t bar) {
    asm volatile("cp.async.bulk.tensor.2d.shared::cluster.global.mbarrier::complete_tx::bytes [%0], [%1, {%3, %4}], [%2];" ::"r"(dst), "l"(tm), "r"(bar), "r"(c0), "r"(c1) : "memory");
}
__device__ __forceinline__ void cluster_arrive() { asm volatile("barrier.cluster.arrive.release.aligned;" ::: "memory"); }
__device__ __forceinline__ void cluster_wait() { asm volatile("barrier.cluster.wait.acquire.aligned;" ::: "memory"); }
__device__ __forceinline__ void tma_red_2d(const CUtensorMap* tm, int c0, int c1, uint32_t src) {
    asm volatile("cp.reduce.async.bulk.tensor.2d.global.shared::cta.add.tile.bulk_group [%0, {%2, %3}], [%1];" ::"l"(tm), "r"(src), "r"(c0), "r"(c1) : "memory");
}
__device__ __forceinline__ void tma_st_2d(const CUtensorMap* tm, int c0, int c1, uint32_t src) {
    asm volatile("cp.async.bulk.tensor.2d.global.shared::cta.tile.bulk_group [%0, {%2, %3}], [%1];" ::"l"(tm), "r"(src), "r"(c0), "r"(c1) : "memory");
}
__device__ __forceinline__ void bulk_commit() { asm volatile("cp.async.bulk.commit_group;" ::: "memory"); }
__device__ __forceinline__ void bulk_wait_all() { asm volatile("cp.async.bulk.wait_group.read 0;" ::: "memory"); }
__device__ __forceinline__ bool elect_one() {
    uint32_t p;
    asm volatile("{\n.reg .pred P;\nelect.sync _|P, 0xffffffff;\nselp.b32 %0, 1, 0, P;\n}\n" : "=r"(p));
    return p != 0;
}
__device__ __forceinline__ void prefetch_l2(const void* p, int bytes) { asm volatile("cp.async.bulk.prefetch.L2.global [%0], %1;" ::"l"(p), "r"(bytes) : "memory"); }
__device__ __forceinline__ void prefetch_map(const CUtensorMap* tm) { asm volatile("prefetch.tensormap [%0];" ::"l"(tm) : "memory"); }
__device__ __forceinline__ void pdl_launch() { asm volatile("griddepcontrol.launch_dependents;" ::: "memory"); }
__device__ __forceinline__ void pdl_wait() { asm volatile("griddepcontrol.wait;" ::: "memory"); }
__device__ __forceinline__ float ex2(float x) { float y; asm("ex2.approx.ftz.f32 %0, %1;" : "=f"(y) : "f"(x)); return y; }
__device__ __forceinline__ uint32_t pack_bf16(float lo, float hi) { uint32_t r; asm("cvt.rn.bf16x2.f32 %0, %1, %2;" : "=r"(r) : "f"(hi), "f"(lo)); return r; }
__device__ __forceinline__ float bf_lo(uint32_t v) { return __uint_as_float(v << 16); }
__device__ __forceinline__ float bf_hi(uint32_t v) { return __uint_as_float(v & 0xFFFF0000u); }
__device__ __forceinline__ uint32_t hfma2(uint32_t a, uint32_t b, uint32_t c) { uint32_t r; asm("fma.rn.f16x2 %0, %1, %2, %3;" : "=r"(r) : "r"(a), "r"(b), "r"(c)); return r; }
__device__ __forceinline__ void stmatrix_x4(uint32_t addr, uint32_t r0, uint32_t r1, uint32_t r2, uint32_t r3) {
    asm volatile("stmatrix.sync.aligned.m8n8.x4.shared.b16 [%0], {%1, %2, %3, %4};" ::"r"(addr), "r"(r0), "r"(r1), "r"(r2), "r"(r3) : "memory");
}

template <int TB> __device__ __forceinline__ void wgmma_ss_n24(float (&d)[12], uint64_t da, uint64_t db, int sc) {
    asm volatile("{\n.reg .pred p;\nsetp.ne.b32 p, %14, 0;\n"
        "wgmma.mma_async.sync.aligned.m64n24k16.f32.bf16.bf16 {%0, %1, %2, %3, %4, %5, %6, %7, %8, %9, %10, %11}, %12, %13, p, 1, 1, 0, %15;\n}\n"
        : "+f"(d[0]), "+f"(d[1]), "+f"(d[2]), "+f"(d[3]), "+f"(d[4]), "+f"(d[5]), "+f"(d[6]), "+f"(d[7]), "+f"(d[8]), "+f"(d[9]), "+f"(d[10]), "+f"(d[11])
        : "l"(da), "l"(db), "r"(sc), "n"(TB));
}
template <int TB> __device__ __forceinline__ void wgmma_ss_n64(float (&d)[32], uint64_t da, uint64_t db, int sc) {
    asm volatile("{\n.reg .pred p;\nsetp.ne.b32 p, %34, 0;\n"
        "wgmma.mma_async.sync.aligned.m64n64k16.f32.bf16.bf16 {%0, %1, %2, %3, %4, %5, %6, %7, %8, %9, %10, %11, %12, %13, %14, %15, %16, %17, %18, %19, %20, %21, %22, %23, %24, %25, %26, %27, %28, %29, %30, %31}, %32, %33, p, 1, 1, 0, %35;\n}\n"
        : "+f"(d[0]), "+f"(d[1]), "+f"(d[2]), "+f"(d[3]), "+f"(d[4]), "+f"(d[5]), "+f"(d[6]), "+f"(d[7]), "+f"(d[8]), "+f"(d[9]), "+f"(d[10]), "+f"(d[11]), "+f"(d[12]), "+f"(d[13]), "+f"(d[14]), "+f"(d[15]), "+f"(d[16]), "+f"(d[17]), "+f"(d[18]), "+f"(d[19]), "+f"(d[20]), "+f"(d[21]), "+f"(d[22]), "+f"(d[23]), "+f"(d[24]), "+f"(d[25]), "+f"(d[26]), "+f"(d[27]), "+f"(d[28]), "+f"(d[29]), "+f"(d[30]), "+f"(d[31])
        : "l"(da), "l"(db), "r"(sc), "n"(TB));
}
template <int TB> __device__ __forceinline__ void wgmma_ss_n128(float (&d)[64], uint64_t da, uint64_t db, int sc) {
    asm volatile("{\n.reg .pred p;\nsetp.ne.b32 p, %66, 0;\n"
        "wgmma.mma_async.sync.aligned.m64n128k16.f32.bf16.bf16 {%0, %1, %2, %3, %4, %5, %6, %7, %8, %9, %10, %11, %12, %13, %14, %15, %16, %17, %18, %19, %20, %21, %22, %23, %24, %25, %26, %27, %28, %29, %30, %31, %32, %33, %34, %35, %36, %37, %38, %39, %40, %41, %42, %43, %44, %45, %46, %47, %48, %49, %50, %51, %52, %53, %54, %55, %56, %57, %58, %59, %60, %61, %62, %63}, %64, %65, p, 1, 1, 0, %67;\n}\n"
        : "+f"(d[0]), "+f"(d[1]), "+f"(d[2]), "+f"(d[3]), "+f"(d[4]), "+f"(d[5]), "+f"(d[6]), "+f"(d[7]), "+f"(d[8]), "+f"(d[9]), "+f"(d[10]), "+f"(d[11]), "+f"(d[12]), "+f"(d[13]), "+f"(d[14]), "+f"(d[15]), "+f"(d[16]), "+f"(d[17]), "+f"(d[18]), "+f"(d[19]), "+f"(d[20]), "+f"(d[21]), "+f"(d[22]), "+f"(d[23]), "+f"(d[24]), "+f"(d[25]), "+f"(d[26]), "+f"(d[27]), "+f"(d[28]), "+f"(d[29]), "+f"(d[30]), "+f"(d[31]), "+f"(d[32]), "+f"(d[33]), "+f"(d[34]), "+f"(d[35]), "+f"(d[36]), "+f"(d[37]), "+f"(d[38]), "+f"(d[39]), "+f"(d[40]), "+f"(d[41]), "+f"(d[42]), "+f"(d[43]), "+f"(d[44]), "+f"(d[45]), "+f"(d[46]), "+f"(d[47]), "+f"(d[48]), "+f"(d[49]), "+f"(d[50]), "+f"(d[51]), "+f"(d[52]), "+f"(d[53]), "+f"(d[54]), "+f"(d[55]), "+f"(d[56]), "+f"(d[57]), "+f"(d[58]), "+f"(d[59]), "+f"(d[60]), "+f"(d[61]), "+f"(d[62]), "+f"(d[63])
        : "l"(da), "l"(db), "r"(sc), "n"(TB));
}
template <int TB> __device__ __forceinline__ void wgmma_rs_n24(float (&d)[12], uint32_t a0, uint32_t a1, uint32_t a2, uint32_t a3, uint64_t db, int sc) {
    asm volatile("{\n.reg .pred p;\nsetp.ne.b32 p, %17, 0;\n"
        "wgmma.mma_async.sync.aligned.m64n24k16.f32.bf16.bf16 {%0, %1, %2, %3, %4, %5, %6, %7, %8, %9, %10, %11}, {%12, %13, %14, %15}, %16, p, 1, 1, %18;\n}\n"
        : "+f"(d[0]), "+f"(d[1]), "+f"(d[2]), "+f"(d[3]), "+f"(d[4]), "+f"(d[5]), "+f"(d[6]), "+f"(d[7]), "+f"(d[8]), "+f"(d[9]), "+f"(d[10]), "+f"(d[11])
        : "r"(a0), "r"(a1), "r"(a2), "r"(a3), "l"(db), "r"(sc), "n"(TB));
}
template <int TB> __device__ __forceinline__ void wgmma_rs_n64(float (&d)[32], uint32_t a0, uint32_t a1, uint32_t a2, uint32_t a3, uint64_t db, int sc) {
    asm volatile("{\n.reg .pred p;\nsetp.ne.b32 p, %37, 0;\n"
        "wgmma.mma_async.sync.aligned.m64n64k16.f32.bf16.bf16 {%0, %1, %2, %3, %4, %5, %6, %7, %8, %9, %10, %11, %12, %13, %14, %15, %16, %17, %18, %19, %20, %21, %22, %23, %24, %25, %26, %27, %28, %29, %30, %31}, {%32, %33, %34, %35}, %36, p, 1, 1, %38;\n}\n"
        : "+f"(d[0]), "+f"(d[1]), "+f"(d[2]), "+f"(d[3]), "+f"(d[4]), "+f"(d[5]), "+f"(d[6]), "+f"(d[7]), "+f"(d[8]), "+f"(d[9]), "+f"(d[10]), "+f"(d[11]), "+f"(d[12]), "+f"(d[13]), "+f"(d[14]), "+f"(d[15]), "+f"(d[16]), "+f"(d[17]), "+f"(d[18]), "+f"(d[19]), "+f"(d[20]), "+f"(d[21]), "+f"(d[22]), "+f"(d[23]), "+f"(d[24]), "+f"(d[25]), "+f"(d[26]), "+f"(d[27]), "+f"(d[28]), "+f"(d[29]), "+f"(d[30]), "+f"(d[31])
        : "r"(a0), "r"(a1), "r"(a2), "r"(a3), "l"(db), "r"(sc), "n"(TB));
}
template <int TB> __device__ __forceinline__ void wgmma_rs_n128(float (&d)[64], uint32_t a0, uint32_t a1, uint32_t a2, uint32_t a3, uint64_t db, int sc) {
    asm volatile("{\n.reg .pred p;\nsetp.ne.b32 p, %69, 0;\n"
        "wgmma.mma_async.sync.aligned.m64n128k16.f32.bf16.bf16 {%0, %1, %2, %3, %4, %5, %6, %7, %8, %9, %10, %11, %12, %13, %14, %15, %16, %17, %18, %19, %20, %21, %22, %23, %24, %25, %26, %27, %28, %29, %30, %31, %32, %33, %34, %35, %36, %37, %38, %39, %40, %41, %42, %43, %44, %45, %46, %47, %48, %49, %50, %51, %52, %53, %54, %55, %56, %57, %58, %59, %60, %61, %62, %63}, {%64, %65, %66, %67}, %68, p, 1, 1, %70;\n}\n"
        : "+f"(d[0]), "+f"(d[1]), "+f"(d[2]), "+f"(d[3]), "+f"(d[4]), "+f"(d[5]), "+f"(d[6]), "+f"(d[7]), "+f"(d[8]), "+f"(d[9]), "+f"(d[10]), "+f"(d[11]), "+f"(d[12]), "+f"(d[13]), "+f"(d[14]), "+f"(d[15]), "+f"(d[16]), "+f"(d[17]), "+f"(d[18]), "+f"(d[19]), "+f"(d[20]), "+f"(d[21]), "+f"(d[22]), "+f"(d[23]), "+f"(d[24]), "+f"(d[25]), "+f"(d[26]), "+f"(d[27]), "+f"(d[28]), "+f"(d[29]), "+f"(d[30]), "+f"(d[31]), "+f"(d[32]), "+f"(d[33]), "+f"(d[34]), "+f"(d[35]), "+f"(d[36]), "+f"(d[37]), "+f"(d[38]), "+f"(d[39]), "+f"(d[40]), "+f"(d[41]), "+f"(d[42]), "+f"(d[43]), "+f"(d[44]), "+f"(d[45]), "+f"(d[46]), "+f"(d[47]), "+f"(d[48]), "+f"(d[49]), "+f"(d[50]), "+f"(d[51]), "+f"(d[52]), "+f"(d[53]), "+f"(d[54]), "+f"(d[55]), "+f"(d[56]), "+f"(d[57]), "+f"(d[58]), "+f"(d[59]), "+f"(d[60]), "+f"(d[61]), "+f"(d[62]), "+f"(d[63])
        : "r"(a0), "r"(a1), "r"(a2), "r"(a3), "l"(db), "r"(sc), "n"(TB));
}

constexpr int P_NST = 6;
constexpr int P_A_BYTES = 9 * 8192;
constexpr int P_B_STAGE = 3 * 8192;
constexpr int P_SMEM = P_A_BYTES + P_NST * P_B_STAGE + 256 + 320;

template <int NB>
__device__ __forceinline__ void stage_tile(const uint32_t (&pk)[NB * 2], uint32_t base, int w, int lane) {
    const int r = w * 16 + (lane & 7) + ((lane >> 3) & 1) * 8;
#pragma unroll
    for (int b = 0; b < NB; b += 2) {
        const uint32_t a = base + (b >> 3) * 8192 + r * 128 + ((((b & 7) + (lane >> 4)) ^ (r & 7)) << 4);
        stmatrix_x4(a, pk[2 * b], pk[2 * b + 1], pk[2 * b + 2], pk[2 * b + 3]);
    }
}

__device__ __forceinline__ uint32_t hsub2_bf16(uint32_t a, uint32_t b) { uint32_t r; asm("sub.rn.bf16x2 %0, %1, %2;" : "=r"(r) : "r"(a), "r"(b)); return r; }

constexpr int KV_RAW = DM * 18 * 2;
constexpr int Q_THREADS = 416;

__device__ __forceinline__ void proj_mma(float (&acc)[32], int wg, uint32_t fullB, uint32_t emptyB, uint32_t fullA, bool wait_a, int lane) {
    const uint64_t dA = cdesc(0, 16, 1024, 1), dB = cdesc(P_A_BYTES, 8192, 1024, 1) + wg * 512;
#pragma unroll 1
    for (int kb = 0; kb < 9; kb++) {
        const int s = kb >= P_NST ? kb - P_NST : kb;
        if (wait_a) mbar_wait(fullA + kb * 8, 0);
        mbar_wait(fullB + s * 8, kb >= P_NST ? 1 : 0);
        wg_fence();
#pragma unroll
        for (int ks = 0; ks < 4; ks++) wgmma_ss_n64<1>(acc, dA + (kb * 512 + ks * 2), dB + (s * (P_B_STAGE >> 4) + ks * 128), (kb | ks) != 0);
        wg_commit();
        if (kb < 4) {
            wg_wait<1>();
            if (kb >= 1 && lane == 0) mbar_arrive(emptyB + (kb - 1) * 8);
        }
    }
    wg_wait<0>();
    pin(acc);
}

__global__ void __launch_bounds__(Q_THREADS, 1)
k_qkv(const __grid_constant__ CUtensorMap tmWq, const __grid_constant__ CUtensorMap tmQ, const __nv_bfloat16* __restrict__ x, const __nv_bfloat16* __restrict__ wk, const __nv_bfloat16* __restrict__ wv) {
    extern __shared__ __align__(1024) uint8_t smem[];
    const uint32_t sA = smem_u32(smem), sB = sA + P_A_BYTES, bars = sB + P_NST * P_B_STAGE;
    const uint32_t fullB = bars, emptyB = bars + 64, fullX = bars + 128, fullW = bars + 136;
    float* s_rstd = reinterpret_cast<float*>(smem + P_A_BYTES + P_NST * P_B_STAGE + 256);
    const int tid = threadIdx.x, warp = __shfl_sync(~0u, tid >> 5, 0), lane = tid & 31;
    const bool isQ = blockIdx.x < 96;
    const int m = isQ ? blockIdx.x / 3 : blockIdx.x - 96, cg = blockIdx.x % 3;
    if (tid == 0) TS(0, 0);
    if (warp == 12) {
        if (elect_one()) {
            mbar_init(fullX, 1);
            bar_init_fence();
            mbar_expect(fullX, P_A_BYTES);
            bulk_g2s(sA, x + (size_t)m * 64 * DM, P_A_BYTES, fullX);
            prefetch_map(&tmWq); prefetch_map(&tmQ);
            for (int i = 0; i < P_NST; i++) { mbar_init(fullB + i * 8, 1); mbar_init(emptyB + i * 8, 12); }
            mbar_init(fullW, 1);
            bar_init_fence();
            if (isQ) {
                for (int kb = 0; kb < P_NST; kb++) {
                    mbar_expect(fullB + kb * 8, P_B_STAGE);
                    for (int a = 0; a < 3; a++) tma_2d(sB + kb * P_B_STAGE + a * 8192, &tmWq, cg * 192 + a * 64, kb * 64, fullB + kb * 8);
                }
            } else {
                mbar_expect(fullW, 2 * KV_RAW);
                bulk_g2s(sB + 3 * P_B_STAGE, wk, KV_RAW, fullW);
                bulk_g2s(sB + 3 * P_B_STAGE + KV_RAW, wv, KV_RAW, fullW);
            }
        }
        __syncwarp();
    }
    check_smem_base(sA);
    __syncthreads();
    pdl_launch();
    if (warp == 12) {
        if (isQ && elect_one()) {
            for (int kb = P_NST; kb < 9; kb++) {
                const int s = kb - P_NST;
                mbar_wait(emptyB + s * 8, 0);
                mbar_expect(fullB + s * 8, P_B_STAGE);
                for (int a = 0; a < 3; a++) tma_2d(sB + s * P_B_STAGE + a * 8192, &tmWq, cg * 192 + a * 64, kb * 64, fullB + s * 8);
            }
        }
        return;
    }
    if (warp < 8) {
        const int row = tid >> 2, q = tid & 3, h0 = (row & 1) * 4;
        mbar_wait(fullX, 0);
        if (tid == 0) TS(0, 6);
        uint4 v[18];
        const uint32_t ra = sA + row * 1152 + (q + h0) * 16, rb = sA + row * 1152 + (q + 4 - h0) * 16;
#pragma unroll
        for (int kb = 0; kb < 9; kb++) {
            asm volatile("ld.shared.v4.b32 {%0, %1, %2, %3}, [%4];" : "=r"(v[2 * kb].x), "=r"(v[2 * kb].y), "=r"(v[2 * kb].z), "=r"(v[2 * kb].w) : "r"(ra + kb * 128));
            asm volatile("ld.shared.v4.b32 {%0, %1, %2, %3}, [%4];" : "=r"(v[2 * kb + 1].x), "=r"(v[2 * kb + 1].y), "=r"(v[2 * kb + 1].z), "=r"(v[2 * kb + 1].w) : "r"(rb + kb * 128));
        }
        float sum = 0.f, sum2 = 0.f, sq = 0.f, sq2 = 0.f;
#pragma unroll
        for (int i = 0; i < 18; i++) {
            const uint32_t w[4] = {v[i].x, v[i].y, v[i].z, v[i].w};
#pragma unroll
            for (int j = 0; j < 4; j++) { const float a = bf_lo(w[j]), b = bf_hi(w[j]); sum += a; sum2 += b; sq = fmaf(a, a, sq); sq2 = fmaf(b, b, sq2); }
        }
        named_sync(1, 256);
        sum += sum2; sq += sq2;
        sum += __shfl_xor_sync(~0u, sum, 1); sum += __shfl_xor_sync(~0u, sum, 2);
        sq += __shfl_xor_sync(~0u, sq, 1); sq += __shfl_xor_sync(~0u, sq, 2);
        if (tid == 0) TS(0, 4);
        const float mean = sum * (1.0f / DM);
        if (q == 0) s_rstd[row] = rsqrtf(fmaxf(sq * (1.0f / DM) - mean * mean, 0.f) + LN_EPS);
        const uint32_t mhi = pack_bf16(mean, mean);
        const float rem = mean - bf_lo(mhi);
        const uint32_t mlo = pack_bf16(rem, rem);
        const uint32_t wa = sA + row * 128 + (((q + h0) ^ (row & 7)) << 4), wb = sA + row * 128 + (((q + 4 - h0) ^ (row & 7)) << 4);
#pragma unroll
        for (int i = 0; i < 18; i++) {
            const uint32_t o0 = hsub2_bf16(hsub2_bf16(v[i].x, mhi), mlo), o1 = hsub2_bf16(hsub2_bf16(v[i].y, mhi), mlo);
            const uint32_t o2 = hsub2_bf16(hsub2_bf16(v[i].z, mhi), mlo), o3 = hsub2_bf16(hsub2_bf16(v[i].w, mhi), mlo);
            asm volatile("st.shared.v4.b32 [%0], {%1, %2, %3, %4};" ::"r"(((i & 1) ? wb : wa) + (i >> 1) * 8192), "r"(o0), "r"(o1), "r"(o2), "r"(o3) : "memory");
        }
    } else if (!isQ) {
        mbar_wait(fullW, 0);
        const uint32_t* raw = reinterpret_cast<const uint32_t*>(smem + P_A_BYTES + 3 * P_B_STAGE);
#pragma unroll 3
        for (int r = tid - 256; r < 2 * DM; r += 128) {
            uint32_t wr[9];
#pragma unroll
            for (int i = 0; i < 9; i++) wr[i] = raw[r * 9 + i];
            const int sel = r >= DM, k = r - sel * DM;
            uint8_t* dst = smem + P_A_BYTES + sel * 3 * 9216 + (k >> 3) * 128 + (k & 7) * 16;
            *reinterpret_cast<uint4*>(dst) = make_uint4(wr[0], wr[1], wr[2], wr[3]);
            *reinterpret_cast<uint4*>(dst + 9216) = make_uint4(wr[4], wr[5], wr[6], wr[7]);
            *reinterpret_cast<uint32_t*>(dst + 2 * 9216) = wr[8];
        }
    }
    proxy_fence();
    named_sync(2, 384);
    if (tid == 0) TS(0, 1);
    const int wg = warp >> 2, w = warp & 3, g = lane >> 2, t = lane & 3;
    const float rs0 = s_rstd[w * 16 + g], rs1 = s_rstd[w * 16 + g + 8];
    if (isQ) {
        const float c0 = rs0 * Q_SCALE, c1 = rs1 * Q_SCALE;
        float acc[32];
        proj_mma(acc, wg, fullB, emptyB, 0, false, lane);
        if (tid == 0) TS(0, 2);
        uint32_t pk[16];
#pragma unroll
        for (int i = 0; i < 8; i++) { pk[2 * i] = pack_bf16(acc[4 * i] * c0, acc[4 * i + 1] * c0); pk[2 * i + 1] = pack_bf16(acc[4 * i + 2] * c1, acc[4 * i + 3] * c1); }
        named_sync(2, 384);
        stage_tile<8>(pk, sA + wg * 8192, w, lane);
        proxy_fence();
        named_sync(3 + wg, 128);
        if (w == 0 && elect_one()) {
            tma_st_2d(&tmQ, cg * 192 + wg * 64, m * 64, sA + wg * 8192);
            bulk_commit();
            bulk_wait_all();
        }
    } else if (wg < 2) {
        float acc[12];
        const uint64_t dA = cdesc(0, 16, 1024, 1), dB = cdesc(P_A_BYTES, 128, 9216, 0) + wg * (3 * 9216 >> 4);
#pragma unroll
        for (int i = 0; i < 12; i++) acc[i] = 0.f;
        pin(acc);
        wg_fence();
#pragma unroll 1
        for (int kb = 0; kb < 9; kb++) {
#pragma unroll
            for (int ks = 0; ks < 4; ks++) wgmma_ss_n24<1>(acc, dA + (kb * 512 + ks * 2), dB + (kb * 4 + ks) * 16, 1);
        }
        wg_commit();
        wg_wait<0>();
        pin(acc);
        uint32_t pk[6];
#pragma unroll
        for (int b = 0; b < 3; b++) { pk[2 * b] = pack_bf16(acc[4 * b] * rs0, acc[4 * b + 1] * rs0); pk[2 * b + 1] = pack_bf16(acc[4 * b + 2] * rs1, acc[4 * b + 3] * rs1); }
        float n0 = 0.f, n1 = 0.f, vm = 0.f;
#pragma unroll
        for (int b = 0; b < 3; b++) {
            if (b < 2 || t == 0) {
                const float a = bf_lo(pk[2 * b]), c = bf_hi(pk[2 * b]), d = bf_lo(pk[2 * b + 1]), e = bf_hi(pk[2 * b + 1]);
                n0 = fmaf(a, a, fmaf(c, c, n0)); n1 = fmaf(d, d, fmaf(e, e, n1));
            }
        }
        n0 += __shfl_xor_sync(~0u, n0, 1); n0 += __shfl_xor_sync(~0u, n0, 2);
        n1 += __shfl_xor_sync(~0u, n1, 1); n1 += __shfl_xor_sync(~0u, n1, 2);
        vm = fmaxf(n0, n1);
        if (!(n0 == n0) || !(n1 == n1)) vm = __int_as_float(0x7F800000);
#pragma unroll
        for (int o = 4; o < 32; o <<= 1) vm = fmaxf(vm, __shfl_xor_sync(~0u, vm, o));
        if (t != 0) {
            uint32_t lo, hi;
            if (wg == 0) {
                const int grp = m * 8 + w * 2;
                const uint32_t c = t == 1 ? 0x42FE3F80u   : (t == 2 ? 0x00003BC0u   : 0u);
                lo = ((POLY_MASK >> (grp & 15)) & 1) ? c : 0u;
                hi = ((POLY_MASK >> ((grp + 1) & 15)) & 1) ? c : 0u;
            } else {
                lo = hi = t == 1 ? 0x00003F80u : 0u;
            }
            pk[4] = lo; pk[5] = hi;
        }
        uint32_t* dst = reinterpret_cast<uint32_t*>(wg == 0 ? g_kc : g_vc) + (m * 8 + w * 2) * 96 + g * 4 + t;
#pragma unroll
        for (int b = 0; b < 3; b++) { dst[b * 32] = pk[2 * b]; dst[96 + b * 32] = pk[2 * b + 1]; }
        if (lane == 0) g_kmax[m * 8 + warp] = (wg == 0) ? vm : (vm <= 1e24f ? 0.f : __int_as_float(0x7F800000));
    }
    if (tid == 0) TS(0, 3);
}

constexpr int A_THREADS = 512;
constexpr int A_NPIECE = 8;
constexpr int A_OFF_Q = 2 * KV_BYTES;
constexpr int A_OFF_BAR = A_OFF_Q + 4 * 4096;
constexpr int A_SMEM = A_OFF_BAR + 128;

__device__ __forceinline__ uint32_t exp2_pair_fixed(float lo, float hi) {
    const uint32_t G = __byte_perm(__float_as_uint(lo), __float_as_uint(hi), 0x5410);
    const uint32_t Hh = G & 0x007F007Fu;
    const uint32_t tt = hfma2(Hh, 0xF96BF96Bu, 0x358C358Cu);
    return G - hfma2(tt, Hh, 0u);
}

__global__ void __launch_bounds__(A_THREADS, 1)
k_attn() {
    extern __shared__ __align__(1024) uint8_t smem[];
    pdl_launch();
    const uint32_t sK = smem_u32(smem), sV = sK + KV_BYTES, bars = sK + A_OFF_BAR;
    const int tid = threadIdx.x;
    check_smem_base(sK);
    if (tid == 0) TS(1, 0);
    if (tid == 0) {
        for (int i = 0; i < A_NPIECE; i++) mbar_init(bars + i * 8, 1);
        bar_init_fence();
    }
    __syncthreads();
    pdl_wait();
    if (tid == 0) TS(1, 1);
    const int wg = __shfl_sync(~0u, tid >> 7, 0), w = (tid >> 5) & 3, lane = tid & 31, g = lane >> 2, t = lane & 3;
    const uint32_t* q32 = reinterpret_cast<const uint32_t*>(g_q);
    int row = (blockIdx.x * 8 + wg) * 64 + w * 16 + g;
    uint32_t nq[6];
    nq[0] = q32[row * 9 + t]; nq[1] = q32[(row + 8) * 9 + t]; nq[2] = q32[row * 9 + 4 + t]; nq[3] = q32[(row + 8) * 9 + 4 + t];
    nq[4] = q32[row * 9 + 8]; nq[5] = q32[(row + 8) * 9 + 8];
    constexpr int PB = KV_BYTES / A_NPIECE;
    const float4 km0 = reinterpret_cast<const float4*>(g_kmax)[lane], km1 = reinterpret_cast<const float4*>(g_kmax)[32 + lane];
    if (tid < 32 && elect_one()) {
        for (int i = 0; i < 2; i++) {
            mbar_expect(bars + i * 8, 2 * PB);
            bulk_g2s(sK + i * PB, reinterpret_cast<const char*>(g_kc) + i * PB, PB, bars + i * 8);
            bulk_g2s(sV + i * PB, reinterpret_cast<const char*>(g_vc) + i * PB, PB, bars + i * 8);
        }
    }
    float kmax2 = fmaxf(fmaxf(fmaxf(km0.x, km0.y), fmaxf(km0.z, km0.w)), fmaxf(fmaxf(km1.x, km1.y), fmaxf(km1.z, km1.w)));
#pragma unroll
    for (int o = 1; o < 32; o <<= 1) kmax2 = fmaxf(kmax2, __shfl_xor_sync(~0u, kmax2, o));
    if (tid < 32 && elect_one()) {
        for (int i = 2; i < A_NPIECE; i++) {
            mbar_expect(bars + i * 8, 2 * PB);
            bulk_g2s(sK + i * PB, reinterpret_cast<const char*>(g_kc) + i * PB, PB, bars + i * 8);
            bulk_g2s(sV + i * PB, reinterpret_cast<const char*>(g_vc) + i * PB, PB, bars + i * 8);
        }
    }
    const uint32_t sQ = sK + A_OFF_Q + wg * 4096 + (w * 2) * 512 + g * 16 + t * 4;
    const uint64_t dQ0 = cdesc(A_OFF_Q, 128, 512, 0) + wg * 256, dQ1 = dQ0 + 16;
#pragma unroll 1
    for (int rep = 0; rep < 2; rep++, row += 256) {
        const uint32_t qa[4] = {nq[0], nq[1], nq[2], nq[3]};
        float n0, n1;
        {
            const float a0 = bf_lo(qa[0]), a1 = bf_hi(qa[0]), a2 = bf_lo(qa[2]), a3 = bf_hi(qa[2]);
            const float b0 = bf_lo(qa[1]), b1 = bf_hi(qa[1]), b2 = bf_lo(qa[3]), b3 = bf_hi(qa[3]);
            n0 = a0 * a0 + a1 * a1 + a2 * a2 + a3 * a3; n1 = b0 * b0 + b1 * b1 + b2 * b2 + b3 * b3;
            if (t == 0) {
                const float c0 = bf_lo(nq[4]), c1 = bf_hi(nq[4]), d0 = bf_lo(nq[5]), d1 = bf_hi(nq[5]);
                n0 += c0 * c0 + c1 * c1; n1 += d0 * d0 + d1 * d1;
            }
            n0 += __shfl_xor_sync(~0u, n0, 1); n0 += __shfl_xor_sync(~0u, n0, 2);
            n1 += __shfl_xor_sync(~0u, n1, 1); n1 += __shfl_xor_sync(~0u, n1, 2);
        }
        const uint32_t x0 = nq[4], x1 = nq[5];
        if (rep == 0) {
            const int nr = row + 256;
            nq[0] = q32[nr * 9 + t]; nq[1] = q32[(nr + 8) * 9 + t]; nq[2] = q32[nr * 9 + 4 + t]; nq[3] = q32[(nr + 8) * 9 + 4 + t];
            nq[4] = q32[nr * 9 + 8]; nq[5] = q32[(nr + 8) * 9 + 8];
        }
        if (tid == 0 && rep == 0) TS(1, 7);
        const bool unsafe = !(fmaxf(n0, n1) * kmax2 <= FAST_BOUND * FAST_BOUND) || !(n0 == n0) || !(n1 == n1);
        uint32_t any_unsafe;
        asm volatile("{\n.reg .pred p, q;\nsetp.ne.u32 p, %1, 0;\nbar.red.or.pred q, %2, 128, p;\nselp.u32 %0, 1, 0, q;\n}\n" : "=r"(any_unsafe) : "r"((uint32_t)unsafe), "r"(wg + 1) : "memory");
        any_unsafe = __shfl_sync(~0u, any_unsafe, 0);
        {
            const uint32_t cst = any_unsafe ? 0u : (t == 1 ? 0x3F804780u : (t == 2 ? 0x00003F80u : 0u));
            asm volatile("st.shared.b32 [%0], %1;" ::"r"(sQ), "r"(qa[0]) : "memory");
            asm volatile("st.shared.b32 [%0], %1;" ::"r"(sQ + 512), "r"(qa[1]) : "memory");
            asm volatile("st.shared.b32 [%0], %1;" ::"r"(sQ + 128), "r"(qa[2]) : "memory");
            asm volatile("st.shared.b32 [%0], %1;" ::"r"(sQ + 640), "r"(qa[3]) : "memory");
            asm volatile("st.shared.b32 [%0], %1;" ::"r"(sQ + 256), "r"(t == 0 ? x0 : cst) : "memory");
            asm volatile("st.shared.b32 [%0], %1;" ::"r"(sQ + 768), "r"(t == 0 ? x1 : cst) : "memory");
            asm volatile("st.shared.b32 [%0], %1;" ::"r"(sQ + 384), "r"(0u) : "memory");
            asm volatile("st.shared.b32 [%0], %1;" ::"r"(sQ + 896), "r"(0u) : "memory");
            proxy_fence();
            named_sync(wg + 1, 128);
        }
        if (tid == 0) TS(1, 2 + rep * 2);
        float o[12];
#pragma unroll
        for (int i = 0; i < 12; i++) o[i] = 0.f;
        pin(o);
        uint64_t dK0 = cdesc(0, 128, 384, 0), dK1 = cdesc(256, 0, 384, 0), dV = cdesc(KV_BYTES, 384, 128, 0);
        if (!any_unsafe) {
            float s[64];
#pragma unroll 1
            for (int j = 0; j < 16; j++) {
                if (rep == 0 && (j & 1) == 0) mbar_wait(bars + (j >> 1) * 8, 0);
                wg_fence();
                wgmma_ss_n128<0>(s, dQ0, dK0, 0);
                wgmma_ss_n128<0>(s, dQ1, dK1, 1);
                wg_commit();
                dK0 += 16 * 384 >> 4; dK1 += 16 * 384 >> 4;
                wg_wait<0>();
                pin(s);
                uint32_t p[32];
#pragma unroll
                for (int i = 0; i < 32; i++) {
                    if ((POLY_MASK >> (i >> 1)) & 1) p[i] = exp2_pair_fixed(s[2 * i], s[2 * i + 1]);
                    else p[i] = pack_bf16(ex2(s[2 * i]), ex2(s[2 * i + 1]));
                }
                pin(p);
                wg_fence();
#pragma unroll
                for (int k = 0; k < 8; k++) wgmma_rs_n24<1>(o, p[4 * k], p[4 * k + 1], p[4 * k + 2], p[4 * k + 3], dV + k * 48, 1);
                wg_commit();
                dV += 16 * 384 >> 4;
                wg_wait<0>();
            }
        } else {
            float s[64];
            float m0 = -INFINITY, m1 = -INFINITY;
#pragma unroll 1
            for (int j = 0; j < 16; j++) {
                if (rep == 0 && (j & 1) == 0) mbar_wait(bars + (j >> 1) * 8, 0);
                wg_fence();
                wgmma_ss_n128<0>(s, dQ0, dK0, 0);
                wgmma_ss_n128<0>(s, dQ1, dK1, 1);
                wg_commit();
                dK0 += 16 * 384 >> 4; dK1 += 16 * 384 >> 4;
                wg_wait<0>();
                pin(s);
                float x0m = m0, x1m = m1;
#pragma unroll
                for (int b = 0; b < 16; b++) { x0m = fmaxf(x0m, fmaxf(s[4 * b], s[4 * b + 1])); x1m = fmaxf(x1m, fmaxf(s[4 * b + 2], s[4 * b + 3])); }
                x0m = fmaxf(x0m, __shfl_xor_sync(~0u, x0m, 1)); x0m = fmaxf(x0m, __shfl_xor_sync(~0u, x0m, 2));
                x1m = fmaxf(x1m, __shfl_xor_sync(~0u, x1m, 1)); x1m = fmaxf(x1m, __shfl_xor_sync(~0u, x1m, 2));
                const float c0 = ex2(m0 - x0m), c1 = ex2(m1 - x1m);
                m0 = x0m; m1 = x1m;
#pragma unroll
                for (int b = 0; b < 3; b++) { o[4 * b] *= c0; o[4 * b + 1] *= c0; o[4 * b + 2] *= c1; o[4 * b + 3] *= c1; }
                uint32_t p[32];
#pragma unroll
                for (int b = 0; b < 16; b++) {
                    p[2 * b] = pack_bf16(ex2(s[4 * b] - m0), ex2(s[4 * b + 1] - m0));
                    p[2 * b + 1] = pack_bf16(ex2(s[4 * b + 2] - m1), ex2(s[4 * b + 3] - m1));
                }
                pin(p); pin(o);
                wg_fence();
#pragma unroll
                for (int k = 0; k < 8; k++) wgmma_rs_n24<1>(o, p[4 * k], p[4 * k + 1], p[4 * k + 2], p[4 * k + 3], dV + k * 48, 1);
                wg_commit();
                dV += 16 * 384 >> 4;
                wg_wait<0>();
            }
        }
        pin(o);
        if (tid == 0) TS(1, 3 + rep * 2);
        const float l0 = __shfl_sync(~0u, o[8], (lane & ~3) | 1), l1 = __shfl_sync(~0u, o[10], (lane & ~3) | 1);
        const float i0 = 1.0f / l0, i1 = 1.0f / l1;
        uint32_t* o32 = reinterpret_cast<uint32_t*>(g_o);
        o32[row * 9 + t] = pack_bf16(o[0] * i0, o[1] * i0);
        o32[(row + 8) * 9 + t] = pack_bf16(o[2] * i1, o[3] * i1);
        o32[row * 9 + 4 + t] = pack_bf16(o[4] * i0, o[5] * i0);
        o32[(row + 8) * 9 + 4 + t] = pack_bf16(o[6] * i1, o[7] * i1);
        if (t == 0) { o32[row * 9 + 8] = pack_bf16(o[8] * i0, o[9] * i0); o32[(row + 8) * 9 + 8] = pack_bf16(o[10] * i1, o[11] * i1); }
    }
    if (tid == 0) TS(1, 6);
    if ((tid & 127) == 0) TS(1, 10 + wg);
}

constexpr int O_THREADS = 416;
constexpr int O_OFF_STAT = P_A_BYTES + P_NST * P_B_STAGE + 256;
constexpr int O_SMEM = O_OFF_STAT + 9 * 64 * 8;

__global__ void __cluster_dims__(3, 1, 1) __launch_bounds__(O_THREADS, 1)
k_oproj(const __grid_constant__ CUtensorMap tmO, const __grid_constant__ CUtensorMap tmWo, const __grid_constant__ CUtensorMap tmX2, const __grid_constant__ CUtensorMap tmOut, const __nv_bfloat16* __restrict__ x, const __nv_bfloat16* __restrict__ w1) {
    extern __shared__ __align__(1024) uint8_t smem[];
    const uint32_t sA = smem_u32(smem), sB = sA + P_A_BYTES, bars = sB + P_NST * P_B_STAGE;
    const uint32_t fullB = bars, emptyB = bars + 64, fullA = bars + 128;
    const int tid = threadIdx.x, warp = __shfl_sync(~0u, tid >> 5, 0), lane = tid & 31;
    const int m = blockIdx.x / 3, cg = blockIdx.x % 3;
    if (tid == 0) TS(2, 0);
    check_smem_base(sA);
    if (tid == 0) {
        prefetch_map(&tmO); prefetch_map(&tmWo); prefetch_map(&tmX2); prefetch_map(&tmOut);
        for (int i = 0; i < P_NST; i++) { mbar_init(fullB + i * 8, 1); mbar_init(emptyB + i * 8, 12); }
        for (int i = 0; i < 9; i++) mbar_init(fullA + i * 8, 1);
        bar_init_fence();
        for (int kb = 0; kb < 9; kb++) mbar_expect(fullA + kb * 8, 8192);
    }
    __syncthreads();
    pdl_launch();
    if (warp == 12) {
        if (elect_one()) {
            for (int kb = 0; kb < 9; kb++) {
                const int s = kb >= P_NST ? kb - P_NST : kb;
                if (kb == 2) {
                    pdl_wait();
                    TS(2, 1);
                    for (int ka = 0; ka < 9; ka++) tma_2d(sA + ka * 8192, &tmO, ka * 64, m * 64, fullA + ka * 8);
                }
                if (kb >= P_NST) mbar_wait(emptyB + s * 8, 0);
                mbar_expect(fullB + s * 8, P_B_STAGE);
                for (int a = 0; a < 3; a++) tma_2d(sB + s * P_B_STAGE + a * 8192, &tmWo, cg * 192 + a * 64, kb * 64, fullB + s * 8);
            }
            for (int i = 0; i < 6; i++) prefetch_l2(reinterpret_cast<const char*>(w1) + (size_t)blockIdx.x * (FF * DM * 2 / 96) + i * 9216, 9216);
        }
        return;
    }
    if (tid == 0) TS(2, 11);
    const int wg = warp >> 2, w = warp & 3, g = lane >> 2, t = lane & 3;
    uint32_t xr[16];
    {
        const uint32_t* x32 = reinterpret_cast<const uint32_t*>(x) + (((m * 64 + w * 16 + g) * DM + cg * 192 + wg * 64 + 2 * t) >> 1);
#pragma unroll
        for (int b = 0; b < 8; b++) { xr[2 * b] = __ldg(x32 + b * 4); xr[2 * b + 1] = __ldg(x32 + b * 4 + 4 * DM); }
    }
    float acc[32];
    proj_mma(acc, wg, fullB, emptyB, fullA, true, lane);
    if (tid == 0) TS(2, 2);
    named_sync(1, 384);
    float s0 = 0.f, q0 = 0.f, s1 = 0.f, q1 = 0.f;
#pragma unroll
    for (int b = 0; b < 8; b++) {
        const uint32_t xa = xr[2 * b], xb = xr[2 * b + 1];
        const uint32_t ha = pack_bf16(acc[4 * b] + bf_lo(xa), acc[4 * b + 1] + bf_hi(xa));
        const uint32_t hb = pack_bf16(acc[4 * b + 2] + bf_lo(xb), acc[4 * b + 3] + bf_hi(xb));
        xr[2 * b] = ha; xr[2 * b + 1] = hb;
        const float a = bf_lo(ha), c = bf_hi(ha), d = bf_lo(hb), e = bf_hi(hb);
        s0 += a + c; q0 = fmaf(a, a, fmaf(c, c, q0));
        s1 += d + e; q1 = fmaf(d, d, fmaf(e, e, q1));
    }
    s0 += __shfl_xor_sync(~0u, s0, 1); s0 += __shfl_xor_sync(~0u, s0, 2);
    q0 += __shfl_xor_sync(~0u, q0, 1); q0 += __shfl_xor_sync(~0u, q0, 2);
    s1 += __shfl_xor_sync(~0u, s1, 1); s1 += __shfl_xor_sync(~0u, s1, 2);
    q1 += __shfl_xor_sync(~0u, q1, 1); q1 += __shfl_xor_sync(~0u, q1, 2);
    const int r = w * 16 + g;
    const uint32_t sStat = sA + O_OFF_STAT;
    if (t < 3) {
        uint32_t dst;
        asm("mapa.shared::cluster.u32 %0, %1, %2;" : "=r"(dst) : "r"(sStat + ((cg * 3 + wg) * 64 + r) * 8), "r"(t));
        asm volatile("st.shared::cluster.v2.f32 [%0], {%1, %2};" ::"r"(dst), "f"(s0), "f"(q0) : "memory");
        asm volatile("st.shared::cluster.v2.f32 [%0], {%1, %2};" ::"r"(dst + 64), "f"(s1), "f"(q1) : "memory");
    }
    if (tid == 0) TS(2, 4);
    cluster_arrive();
    stage_tile<8>(xr, sA + wg * 8192, w, lane);
    proxy_fence();
    named_sync(2 + wg, 128);
    const bool leader = w == 0 && elect_one();
    if (leader) { tma_st_2d(&tmOut, cg * 192 + wg * 64, m * 64, sA + wg * 8192); bulk_commit(); }
    cluster_wait();
    if (tid == 0) TS(2, 5);
    s0 = q0 = s1 = q1 = 0.f;
#pragma unroll
    for (int p = 0; p < 9; p++) {
        float a, b, c, d;
        asm volatile("ld.shared.v2.f32 {%0, %1}, [%2];" : "=f"(a), "=f"(b) : "r"(sStat + (p * 64 + r) * 8));
        asm volatile("ld.shared.v2.f32 {%0, %1}, [%2];" : "=f"(c), "=f"(d) : "r"(sStat + (p * 64 + r + 8) * 8));
        s0 += a; q0 += b; s1 += c; q1 += d;
    }
    const float m0 = s0 * (1.0f / DM), m1 = s1 * (1.0f / DM);
    const float rs0 = rsqrtf(fmaxf(q0 * (1.0f / DM) - m0 * m0, 0.f) + LN_EPS), rs1 = rsqrtf(fmaxf(q1 * (1.0f / DM) - m1 * m1, 0.f) + LN_EPS);
    const float sc0 = 0.5f * rs0, sc1 = 0.5f * rs1, n0 = -m0 * sc0, n1 = -m1 * sc1;
#pragma unroll
    for (int b = 0; b < 8; b++) {
        xr[2 * b] = pack_bf16(fmaf(bf_lo(xr[2 * b]), sc0, n0), fmaf(bf_hi(xr[2 * b]), sc0, n0));
        xr[2 * b + 1] = pack_bf16(fmaf(bf_lo(xr[2 * b + 1]), sc1, n1), fmaf(bf_hi(xr[2 * b + 1]), sc1, n1));
    }
    stage_tile<8>(xr, sA + (3 + wg) * 8192, w, lane);
    proxy_fence();
    named_sync(2 + wg, 128);
    if (tid == 0) TS(2, 6);
    if (leader) {
        tma_st_2d(&tmX2, cg * 192 + wg * 64, m * 64, sA + (3 + wg) * 8192);
        bulk_commit();
        bulk_wait_all();
    }
    if (tid == 0) TS(2, 3);
}

constexpr int F_THREADS = 384;
constexpr int F_NST = 6;
constexpr int F_STAGE = 96 * 128;
constexpr int F_X_BYTES = 9 * 16384;
constexpr int F_OFF_ST = F_X_BYTES;
constexpr int F_OFF_BAR = F_OFF_ST + F_NST * F_STAGE;
constexpr int F_SMEM = F_OFF_BAR + 256;

__device__ __forceinline__ float tanh_hw(float x) { float y; asm("tanh.approx.f32 %0, %1;" : "=f"(y) : "f"(x)); return y; }
__host__ __device__ constexpr int piece_begin(int p) { return p == 0 ? 0 : 3 * p + 1; }
template <int P>
__device__ __forceinline__ void silu_s1(const float (&acc)[32], float (&tmp)[8]) {
#pragma unroll
    for (int i = 2 * piece_begin(P); i < 2 * piece_begin(P + 1); i++) tmp[i - 2 * piece_begin(P)] = tanh_hw(acc[i]);
}
template <int C, int P>
__device__ __forceinline__ void silu_s2(const float (&acc)[32], const float (&tmp)[8], uint32_t (&h1)[144]) {
#pragma unroll
    for (int i = piece_begin(P); i < piece_begin(P + 1); i++) {
        const int k = 2 * (i - piece_begin(P));
        h1[C * 16 + i] = pack_bf16(fmaf(acc[2 * i], tmp[k], acc[2 * i]), fmaf(acc[2 * i + 1], tmp[k + 1], acc[2 * i + 1]));
    }
}
template <int C, int J>
__device__ __forceinline__ void silu_slot(const float (&prev)[32], float (&tmp)[2][8], uint32_t (&h1)[144]) {
    if constexpr (J >= 1) silu_s2<C, J - 1>(prev, tmp[(J - 1) & 1], h1);
    if constexpr (J <= 4) { silu_s1<J>(prev, tmp[J & 1]); pin(tmp[J & 1]); }
}

struct FfnPipe {
    uint32_t full, empty;
    int lane;
    __device__ __forceinline__ void acquire(int s, uint32_t ph) const { mbar_wait(full + s * 8, ph); }
    __device__ __forceinline__ void release(int s) const { if (lane == 0) mbar_arrive(empty + s * 8); }
};

template <int C>
__device__ __forceinline__ void ffn_phase1_chunk(float (&cur)[32], float (&prev)[32], uint32_t (&h1)[144], const FfnPipe& pp, uint64_t dx, uint32_t fullX) {
    float tmp[2][8];
    const uint64_t dw = cdesc(F_OFF_ST, 8192, 1024, 1) + blockIdx.y * (C + 1);
    dx += blockIdx.y * C;
#pragma unroll
    for (int j = 0; j < 6; j++) {
        if (C == 0) { mbar_wait(fullX + ((6 * j) >> 2) * 8, 0); mbar_wait(fullX + ((6 * j + 5) >> 2) * 8, 0); }
        pp.acquire(j, C & 1);
        if (j == 0) pin(cur);
        wg_fence();
#pragma unroll
        for (int i = 0; i < 6; i++) {
            const int ks = 6 * j + i;
            wgmma_ss_n64<1>(cur, dx + ((ks >> 2) * 1024 + (ks & 3) * 2), dw + ((j * F_STAGE + i * 2048) >> 4), ks != 0);
        }
        wg_commit();
        if (C > 0 || j > 0) { wg_wait<1>(); pp.release((j + 5) % 6); }
        if (C > 0) {
            constexpr int CP = C > 0 ? C - 1 : 0;
            pin(prev);
            if (j == 0) silu_slot<CP, 0>(prev, tmp, h1);
            if (j == 1) silu_slot<CP, 1>(prev, tmp, h1);
            if (j == 2) silu_slot<CP, 2>(prev, tmp, h1);
            if (j == 3) silu_slot<CP, 3>(prev, tmp, h1);
            if (j == 4) silu_slot<CP, 4>(prev, tmp, h1);
            if (j == 5) silu_slot<CP, 5>(prev, tmp, h1);
        }
    }
}

__device__ __forceinline__ void ffn_stage_chunk(const float (&acc)[32], uint32_t stg, int w, int lane) {
    uint32_t pk[16];
#pragma unroll
    for (int i = 0; i < 16; i++) pk[i] = pack_bf16(acc[2 * i], acc[2 * i + 1]);
    stage_tile<8>(pk, stg, w, lane);
}
__device__ __forceinline__ void ffn_reduce_chunk(const CUtensorMap* tmOut, uint32_t stg, int col, int row, int w, int wgid, bool leader) {
    proxy_fence();
    if (w != 0) {
        asm volatile("bar.arrive %0, 128;" ::"r"(2 + wgid) : "memory");
    } else {
        named_sync(2 + wgid, 128);
        if (leader) { tma_red_2d(tmOut, col, row, stg); bulk_commit(); }
    }
}

__device__ __forceinline__ void ffn_phase2_chunk(float (&cur)[32], float (&prev)[32], uint32_t (&h1)[144], const FfnPipe& pp, uint32_t ph, bool store_prev, const CUtensorMap* tmOut, uint32_t stg_prev, int col_prev, int row, int w, int lane, int wgid, bool leader) {
    const uint64_t dw = cdesc(F_OFF_ST, 8192, 1024, 1) + blockIdx.y * col_prev;
#pragma unroll
    for (int j = 0; j < 6; j++) {
        pp.acquire(j, ph);
        if (j == 0) pin(cur);
        wg_fence();
#pragma unroll
        for (int i = 0; i < 6; i++) {
            const int f = (6 * j + i) * 4;
            wgmma_rs_n64<1>(cur, h1[f], h1[f + 1], h1[f + 2], h1[f + 3], dw + ((j * F_STAGE + i * 2048) >> 4), (j | i) != 0);
        }
        wg_commit();
        if (j > 0 || store_prev) { wg_wait<1>(); pp.release((j + 5) % 6); }
        if (j == 0 && store_prev) { pin(prev); ffn_stage_chunk(prev, stg_prev, w, lane); }
        if (j == 1 && store_prev) ffn_reduce_chunk(tmOut, stg_prev, col_prev, row, w, wgid, leader);
    }
}

__global__ void __launch_bounds__(F_THREADS, 1)
k_ffn(const __grid_constant__ CUtensorMap tmH, const __grid_constant__ CUtensorMap tmW1, const __grid_constant__ CUtensorMap tmW2, const __grid_constant__ CUtensorMap tmOut, const __nv_bfloat16* __restrict__ w2) {
    extern __shared__ __align__(1024) uint8_t smem[];
    const uint32_t sX = smem_u32(smem), sSt = sX + F_OFF_ST, bars = sX + F_OFF_BAR;
    const uint32_t full = bars, empty = bars + 64, fullX = bars + 128;
    const int tid = threadIdx.x, warp = __shfl_sync(~0u, tid >> 5, 0), lane = tid & 31;
#define FFN_MAP 1
    const int m = FFN_MAP == 0 ? (blockIdx.x & 15) : (FFN_MAP == 1 ? (blockIdx.x >> 3) : ((blockIdx.x >> 1) & 15));
    const int fs = FFN_MAP == 0 ? (blockIdx.x >> 4) : (FFN_MAP == 1 ? (blockIdx.x & 7) : ((blockIdx.x >> 5) * 2 + (blockIdx.x & 1)));
    if (tid == 0) TS(3, 0);
    check_smem_base(sX);
    if (tid == 0) {
        prefetch_map(&tmW1); prefetch_map(&tmH); prefetch_map(&tmW2); prefetch_map(&tmOut);
        for (int i = 0; i < F_NST; i++) { mbar_init(full + i * 8, 1); mbar_init(empty + i * 8, 8); }
        for (int i = 0; i < 9; i++) mbar_init(fullX + i * 8, 1);
        bar_init_fence();
        for (int kb = 0; kb < 9; kb++) mbar_expect(fullX + kb * 8, 16384);
    }
    __syncthreads();
    if (warp < 4) {
        asm volatile("setmaxnreg.dec.sync.aligned.u32 24;");
        if (warp == 1 && lane < 9) prefetch_l2(reinterpret_cast<const char*>(w2) + ((size_t)fs * 576 + m * 36 + lane * 4) * (DM * 2), 4 * DM * 2);
        if (warp == 0 && elect_one()) {
            int s = 0; uint32_t ph = 1;
            int c = 0, j = 0;
#pragma unroll 1
            for (int i = 0; i < 108; i++) {
                if (i == 54) c = fs;
                mbar_wait(empty + s * 8, ph);
                mbar_expect(full + s * 8, F_STAGE);
                if (i < 54) tma_2d(sSt + s * F_STAGE, &tmW1, fs * 576 + c * 64, j * 96, full + s * 8);
                else tma_2d(sSt + s * F_STAGE, &tmW2, c * 64, fs * 576 + j * 96, full + s * 8);
                if (++j == 6) { j = 0; if (++c == 9) c = 0; }
                if (++s == F_NST) { s = 0; ph ^= 1; }
            }
        }
    } else {
        asm volatile("setmaxnreg.inc.sync.aligned.u32 240;");
        const int wgid = (warp >> 2) - 1, w = warp & 3;
        pdl_wait();
        if (tid == 128) TS(3, 1);
        if (warp == 4 && elect_one()) {
            for (int kb = 0; kb < 9; kb++) tma_2d(sX + kb * 16384, &tmH, kb * 64, m * 128, fullX + kb * 8);
        }
        __syncwarp();
        FfnPipe pp{full, empty, lane};
        const uint64_t xlo = cdesc(0, 16, 1024, 1) + wgid * 512;
        uint32_t h1[144];
        float acc0[32], acc1[32];
        ffn_phase1_chunk<0>(acc0, acc1, h1, pp, xlo, fullX);
        if (tid == 128) TS(3, 2);
        ffn_phase1_chunk<1>(acc1, acc0, h1, pp, xlo, fullX);
        ffn_phase1_chunk<2>(acc0, acc1, h1, pp, xlo, fullX);
        ffn_phase1_chunk<3>(acc1, acc0, h1, pp, xlo, fullX);
        ffn_phase1_chunk<4>(acc0, acc1, h1, pp, xlo, fullX);
        ffn_phase1_chunk<5>(acc1, acc0, h1, pp, xlo, fullX);
        ffn_phase1_chunk<6>(acc0, acc1, h1, pp, xlo, fullX);
        ffn_phase1_chunk<7>(acc1, acc0, h1, pp, xlo, fullX);
        ffn_phase1_chunk<8>(acc0, acc1, h1, pp, xlo, fullX);
        wg_wait<0>();
        pp.release(5);
        pin(acc0);
#pragma unroll
        for (int i = 0; i < 16; i++) h1[128 + i] = pack_bf16(fmaf(acc0[2 * i], tanh_hw(acc0[2 * i]), acc0[2 * i]), fmaf(acc0[2 * i + 1], tanh_hw(acc0[2 * i + 1]), acc0[2 * i + 1]));
        pin(h1);
        if (tid == 128) TS(3, 3);
        const int row = m * 128 + wgid * 64;
        const uint32_t stg = sX + wgid * 8192;
        int c = fs, cprev = 0;
        const bool leader = w == 0 && elect_one();
#pragma unroll 1
        for (int j = 0; j < 8; j += 2) {
            ffn_phase2_chunk(acc1, acc0, h1, pp, 1, j > 0, &tmOut, stg + (j - 1) * 16384, cprev * 64, row, w, lane, wgid, leader);
            cprev = c; if (++c == 9) c = 0;
            ffn_phase2_chunk(acc0, acc1, h1, pp, 0, true, &tmOut, stg + j * 16384, cprev * 64, row, w, lane, wgid, leader);
            cprev = c; if (++c == 9) c = 0;
        }
        ffn_phase2_chunk(acc1, acc0, h1, pp, 1, true, &tmOut, stg + 7 * 16384, cprev * 64, row, w, lane, wgid, leader);
        wg_wait<0>();
        pin(acc1);
        ffn_stage_chunk(acc1, stg + 8 * 16384, w, lane);
        ffn_reduce_chunk(&tmOut, stg + 8 * 16384, c * 64, row, w, wgid, leader);
        if (tid == 128) TS(3, 4);
        if (leader) bulk_wait_all();
        if (tid == 128) TS(3, 5);
    }
}

typedef CUresult (*EncodeFn)(CUtensorMap*, CUtensorMapDataType, cuuint32_t, void*, const cuuint64_t*, const cuuint64_t*, const cuuint32_t*, const cuuint32_t*,
                             CUtensorMapInterleave, CUtensorMapSwizzle, CUtensorMapL2promotion, CUtensorMapFloatOOBfill);

CUtensorMap make_map(EncodeFn enc, const void* base, int rows, int cols, int box_rows) {
    CUtensorMap tm;
    cuuint64_t dims[2] = {(cuuint64_t)cols, (cuuint64_t)rows};
    cuuint64_t strides[1] = {(cuuint64_t)cols * 2};
    cuuint32_t box[2] = {64, (cuuint32_t)box_rows};
    cuuint32_t es[2] = {1, 1};
    enc(&tm, CU_TENSOR_MAP_DATA_TYPE_BFLOAT16, 2, const_cast<void*>(base), dims, strides, box, es, CU_TENSOR_MAP_INTERLEAVE_NONE,
        CU_TENSOR_MAP_SWIZZLE_128B, CU_TENSOR_MAP_L2_PROMOTION_L2_256B, CU_TENSOR_MAP_FLOAT_OOB_FILL_NONE);
    return tm;
}

template <typename... KArgs, typename... Args>
void launch(void (*kern)(KArgs...), int grid, int block, int smem, bool pdl, Args... args) {
    cudaLaunchConfig_t cfg = {};
    cfg.gridDim = dim3(grid); cfg.blockDim = dim3(block); cfg.dynamicSmemBytes = smem; cfg.stream = cudaStreamPerThread;
    cudaLaunchAttribute at[1];
    at[0].id = cudaLaunchAttributeProgrammaticStreamSerialization;
    at[0].val.programmaticStreamSerializationAllowed = 1;
    cfg.attrs = at; cfg.numAttrs = pdl ? 1 : 0;
    cudaLaunchKernelEx(&cfg, kern, KArgs(args)...);
}

}

#define USE_PDL 1

extern "C" void kernel_launch(void* const* d_in, const int* in_sizes, int n_in, void* d_out, int out_size) {
    const __nv_bfloat16* x = (const __nv_bfloat16*)d_in[0];
    const __nv_bfloat16* wq = (const __nv_bfloat16*)d_in[1];
    const __nv_bfloat16* wk = (const __nv_bfloat16*)d_in[2];
    const __nv_bfloat16* wv = (const __nv_bfloat16*)d_in[3];
    const __nv_bfloat16* wo = (const __nv_bfloat16*)d_in[4];
    const __nv_bfloat16* w1 = (const __nv_bfloat16*)d_in[6];
    const __nv_bfloat16* w2 = (const __nv_bfloat16*)d_in[7];
    __nv_bfloat16* out = (__nv_bfloat16*)d_out;

    static EncodeFn enc = nullptr;
    static void *p_o = nullptr, *p_h = nullptr, *p_q = nullptr;
    if (!enc) {
        cudaDriverEntryPointQueryResult qr;
        cudaGetDriverEntryPoint("cuTensorMapEncodeTiled", (void**)&enc, cudaEnableDefault, &qr);
        cudaGetSymbolAddress(&p_o, g_o);
        cudaGetSymbolAddress(&p_h, g_x2);
        cudaGetSymbolAddress(&p_q, g_q);
        cudaFuncSetAttribute(k_qkv, cudaFuncAttributeMaxDynamicSharedMemorySize, P_SMEM);
        cudaFuncSetAttribute(k_attn, cudaFuncAttributeMaxDynamicSharedMemorySize, A_SMEM);
        cudaFuncSetAttribute(k_oproj, cudaFuncAttributeMaxDynamicSharedMemorySize, O_SMEM);
        cudaFuncSetAttribute(k_ffn, cudaFuncAttributeMaxDynamicSharedMemorySize, F_SMEM);
    }
    const CUtensorMap tmWq = make_map(enc, wq, DM, DM, 64);
    const CUtensorMap tmWo = make_map(enc, wo, DM, DM, 64);
    const CUtensorMap tmO = make_map(enc, p_o, SEQ, DM, 64);
    const CUtensorMap tmH64 = make_map(enc, p_h, SEQ, DM, 64);
    const CUtensorMap tmH = make_map(enc, p_h, SEQ, DM, 128);
    const CUtensorMap tmQ = make_map(enc, p_q, SEQ, DM, 64);
    const CUtensorMap tmW1 = make_map(enc, w1, DM, FF, 96);
    const CUtensorMap tmW2 = make_map(enc, w2, FF, DM, 96);
    const CUtensorMap tmOut = make_map(enc, out, SEQ, DM, 64);

    launch(k_qkv, 128, Q_THREADS, P_SMEM, false, tmWq, tmQ, x, wk, wv);
    launch(k_attn, 128, A_THREADS, A_SMEM, USE_PDL);
    launch(k_oproj, 96, O_THREADS, O_SMEM, USE_PDL, tmO, tmWo, tmH64, tmOut, x, w1);
    launch(k_ffn, 128, F_THREADS, F_SMEM, USE_PDL, tmH, tmW1, tmW2, tmOut, w2);
}
```

```cpp
#include <cuda_runtime.h>
#include <cuda_bf16.h>
#include <cuda.h>
#include <stdint.h>

namespace {

constexpr int SEQ = 2048, DM = 576, FF = 4608;
constexpr int KV_BYTES = SEQ * 48;
constexpr float LN_EPS = 1e-5f;
constexpr float LOG2E = 1.4426950408889634f;
constexpr float Q_SCALE = 0.23570226039551584f * LOG2E;

#define POLY_MASK_V 0xDB6Du
constexpr uint32_t POLY_MASK = POLY_MASK_V;
constexpr float FAST_BOUND = 60.0f;

__device__ __align__(1024) __nv_bfloat16 g_q[SEQ * DM];
__device__ __align__(1024) uint4 g_kc[KV_BYTES / 16];
__device__ __align__(1024) uint4 g_vc[KV_BYTES / 16];
__device__ __align__(16) float g_kmax[256];
__device__ __align__(1024) __nv_bfloat16 g_o[SEQ * DM];
__device__ __align__(1024) __nv_bfloat16 g_x2[SEQ * DM];

#define TS(k, i)

__device__ __forceinline__ uint32_t smem_u32(const void* p) { return (uint32_t)__cvta_generic_to_shared(p); }
__device__ __forceinline__ void wg_fence() { asm volatile("wgmma.fence.sync.aligned;" ::: "memory"); }
__device__ __forceinline__ void wg_commit() { asm volatile("wgmma.commit_group.sync.aligned;" ::: "memory"); }
template <int N> __device__ __forceinline__ void wg_wait() { asm volatile("wgmma.wait_group.sync.aligned %0;" ::"n"(N) : "memory"); }
template <int N> __device__ __forceinline__ void pin(float (&r)[N]) {
#pragma unroll
    for (int i = 0; i < N; i++) asm volatile("" : "+f"(r[i])::"memory");
}
template <int N> __device__ __forceinline__ void pin(uint32_t (&r)[N]) {
#pragma unroll
    for (int i = 0; i < N; i++) asm volatile("" : "+r"(r[i])::"memory");
}
constexpr uint32_t SMEM0 = 0x400;
__host__ __device__ constexpr uint64_t cdesc(uint32_t off, uint32_t lbo, uint32_t sbo, uint32_t swz) {
    return (uint64_t)(((SMEM0 + off) & 0x3FFFF) >> 4) | ((uint64_t)(lbo >> 4) << 16) | ((uint64_t)(sbo >> 4) << 32) | ((uint64_t)swz << 62);
}
__device__ __forceinline__ void check_smem_base(uint32_t base) { if ((base & 0x3FFFF) != SMEM0) __trap(); }

__device__ __forceinline__ void mbar_init(uint32_t bar, int cnt) { asm volatile("mbarrier.init.shared::cta.b64 [%0], %1;" ::"r"(bar), "r"(cnt) : "memory"); }
__device__ __forceinline__ void mbar_expect(uint32_t bar, int bytes) { asm volatile("mbarrier.arrive.expect_tx.shared::cta.b64 _, [%0], %1;" ::"r"(bar), "r"(bytes) : "memory"); }
__device__ __forceinline__ void mbar_arrive(uint32_t bar) { asm volatile("mbarrier.arrive.shared::cta.b64 _, [%0];" ::"r"(bar) : "memory"); }
__device__ __forceinline__ void mbar_wait(uint32_t bar, uint32_t parity) {
    asm volatile(
        "{\n.reg .pred p;\n.reg .u32 n;\nmov.u32 n, 0;\n"
        "LAB_WAIT:\n"
        "mbarrier.try_wait.parity.shared::cta.b64 p, [%0], %1;\n"
        "@p bra DONE;\n"
        "add.u32 n, n, 1;\n"
        "setp.lt.u32 p, n, 4000000;\n"
        "@p bra LAB_WAIT;\n"
        "trap;\n"
        "DONE:\n}\n" ::"r"(bar), "r"(parity) : "memory");
}
__device__ __forceinline__ void bar_init_fence() {
    asm volatile("fence.mbarrier_init.release.cluster;" ::: "memory");
    asm volatile("fence.proxy.async.shared::cta;" ::: "memory");
}
__device__ __forceinline__ void proxy_fence() { asm volatile("fence.proxy.async.shared::cta;" ::: "memory"); }
__device__ __forceinline__ void named_sync(int id, int n) { asm volatile("bar.sync %0, %1;" ::"r"(id), "r"(n) : "memory"); }
__device__ __forceinline__ void bulk_g2s(uint32_t dst, const void* src, int bytes, uint32_t bar) {
    asm volatile("cp.async.bulk.shared::cluster.global.mbarrier::complete_tx::bytes [%0], [%1], %2, [%3];" ::"r"(dst), "l"(src), "r"(bytes), "r"(bar) : "memory");
}
__device__ __forceinline__ void tma_2d(uint32_t dst, const CUtensorMap* tm, int c0, int c1, uint32_t bar) {
    asm volatile("cp.async.bulk.tensor.2d.shared::cluster.global.mbarrier::complete_tx::bytes [%0], [%1, {%3, %4}], [%2];" ::"r"(dst), "l"(tm), "r"(bar), "r"(c0), "r"(c1) : "memory");
}
__device__ __forceinline__ void cluster_arrive() { asm volatile("barrier.cluster.arrive.release.aligned;" ::: "memory"); }
__device__ __forceinline__ void cluster_wait() { asm volatile("barrier.cluster.wait.acquire.aligned;" ::: "memory"); }
__device__ __forceinline__ void tma_red_2d(const CUtensorMap* tm, int c0, int c1, uint32_t src) {
    asm volatile("cp.reduce.async.bulk.tensor.2d.global.shared::cta.add.tile.bulk_group [%0, {%2, %3}], [%1];" ::"l"(tm), "r"(src), "r"(c0), "r"(c1) : "memory");
}
__device__ __forceinline__ void tma_st_2d(const CUtensorMap* tm, int c0, int c1, uint32_t src) {
    asm volatile("cp.async.bulk.tensor.2d.global.shared::cta.tile.bulk_group [%0, {%2, %3}], [%1];" ::"l"(tm), "r"(src), "r"(c0), "r"(c1) : "memory");
}
__device__ __forceinline__ void bulk_commit() { asm volatile("cp.async.bulk.commit_group;" ::: "memory"); }
__device__ __forceinline__ void bulk_wait_all() { asm volatile("cp.async.bulk.wait_group.read 0;" ::: "memory"); }
__device__ __forceinline__ bool elect_one() {
    uint32_t p;
    asm volatile("{\n.reg .pred P;\nelect.sync _|P, 0xffffffff;\nselp.b32 %0, 1, 0, P;\n}\n" : "=r"(p));
    return p != 0;
}
__device__ __forceinline__ void prefetch_l2(const void* p, int bytes) { asm volatile("cp.async.bulk.prefetch.L2.global [%0], %1;" ::"l"(p), "r"(bytes) : "memory"); }
__device__ __forceinline__ void prefetch_map(const CUtensorMap* tm) { asm volatile("prefetch.tensormap [%0];" ::"l"(tm) : "memory"); }
__device__ __forceinline__ void pdl_launch() { asm volatile("griddepcontrol.launch_dependents;" ::: "memory"); }
__device__ __forceinline__ void pdl_wait() { asm volatile("griddepcontrol.wait;" ::: "memory"); }
__device__ __forceinline__ float ex2(float x) { float y; asm("ex2.approx.ftz.f32 %0, %1;" : "=f"(y) : "f"(x)); return y; }
__device__ __forceinline__ uint32_t pack_bf16(float lo, float hi) { uint32_t r; asm("cvt.rn.bf16x2.f32 %0, %1, %2;" : "=r"(r) : "f"(hi), "f"(lo)); return r; }
__device__ __forceinline__ float bf_lo(uint32_t v) { return __uint_as_float(v << 16); }
__device__ __forceinline__ float bf_hi(uint32_t v) { return __uint_as_float(v & 0xFFFF0000u); }
__device__ __forceinline__ uint32_t hfma2(uint32_t a, uint32_t b, uint32_t c) { uint32_t r; asm("fma.rn.f16x2 %0, %1, %2, %3;" : "=r"(r) : "r"(a), "r"(b), "r"(c)); return r; }
__device__ __forceinline__ void stmatrix_x4(uint32_t addr, uint32_t r0, uint32_t r1, uint32_t r2, uint32_t r3) {
    asm volatile("stmatrix.sync.aligned.m8n8.x4.shared.b16 [%0], {%1, %2, %3, %4};" ::"r"(addr), "r"(r0), "r"(r1), "r"(r2), "r"(r3) : "memory");
}

template <int TB> __device__ __forceinline__ void wgmma_ss_n24(float (&d)[12], uint64_t da, uint64_t db, int sc) {
    asm volatile("{\n.reg .pred p;\nsetp.ne.b32 p, %14, 0;\n"
        "wgmma.mma_async.sync.aligned.m64n24k16.f32.bf16.bf16 {%0, %1, %2, %3, %4, %5, %6, %7, %8, %9, %10, %11}, %12, %13, p, 1, 1, 0, %15;\n}\n"
        : "+f"(d[0]), "+f"(d[1]), "+f"(d[2]), "+f"(d[3]), "+f"(d[4]), "+f"(d[5]), "+f"(d[6]), "+f"(d[7]), "+f"(d[8]), "+f"(d[9]), "+f"(d[10]), "+f"(d[11])
        : "l"(da), "l"(db), "r"(sc), "n"(TB));
}
template <int TB> __device__ __forceinline__ void wgmma_ss_n64(float (&d)[32], uint64_t da, uint64_t db, int sc) {
    asm volatile("{\n.reg .pred p;\nsetp.ne.b32 p, %34, 0;\n"
        "wgmma.mma_async.sync.aligned.m64n64k16.f32.bf16.bf16 {%0, %1, %2, %3, %4, %5, %6, %7, %8, %9, %10, %11, %12, %13, %14, %15, %16, %17, %18, %19, %20, %21, %22, %23, %24, %25, %26, %27, %28, %29, %30, %31}, %32, %33, p, 1, 1, 0, %35;\n}\n"
        : "+f"(d[0]), "+f"(d[1]), "+f"(d[2]), "+f"(d[3]), "+f"(d[4]), "+f"(d[5]), "+f"(d[6]), "+f"(d[7]), "+f"(d[8]), "+f"(d[9]), "+f"(d[10]), "+f"(d[11]), "+f"(d[12]), "+f"(d[13]), "+f"(d[14]), "+f"(d[15]), "+f"(d[16]), "+f"(d[17]), "+f"(d[18]), "+f"(d[19]), "+f"(d[20]), "+f"(d[21]), "+f"(d[22]), "+f"(d[23]), "+f"(d[24]), "+f"(d[25]), "+f"(d[26]), "+f"(d[27]), "+f"(d[28]), "+f"(d[29]), "+f"(d[30]), "+f"(d[31])
        : "l"(da), "l"(db), "r"(sc), "n"(TB));
}
template <int TB> __device__ __forceinline__ void wgmma_ss_n128(float (&d)[64], uint64_t da, uint64_t db, int sc) {
    asm volatile("{\n.reg .pred p;\nsetp.ne.b32 p, %66, 0;\n"
        "wgmma.mma_async.sync.aligned.m64n128k16.f32.bf16.bf16 {%0, %1, %2, %3, %4, %5, %6, %7, %8, %9, %10, %11, %12, %13, %14, %15, %16, %17, %18, %19, %20, %21, %22, %23, %24, %25, %26, %27, %28, %29, %30, %31, %32, %33, %34, %35, %36, %37, %38, %39, %40, %41, %42, %43, %44, %45, %46, %47, %48, %49, %50, %51, %52, %53, %54, %55, %56, %57, %58, %59, %60, %61, %62, %63}, %64, %65, p, 1, 1, 0, %67;\n}\n"
        : "+f"(d[0]), "+f"(d[1]), "+f"(d[2]), "+f"(d[3]), "+f"(d[4]), "+f"(d[5]), "+f"(d[6]), "+f"(d[7]), "+f"(d[8]), "+f"(d[9]), "+f"(d[10]), "+f"(d[11]), "+f"(d[12]), "+f"(d[13]), "+f"(d[14]), "+f"(d[15]), "+f"(d[16]), "+f"(d[17]), "+f"(d[18]), "+f"(d[19]), "+f"(d[20]), "+f"(d[21]), "+f"(d[22]), "+f"(d[23]), "+f"(d[24]), "+f"(d[25]), "+f"(d[26]), "+f"(d[27]), "+f"(d[28]), "+f"(d[29]), "+f"(d[30]), "+f"(d[31]), "+f"(d[32]), "+f"(d[33]), "+f"(d[34]), "+f"(d[35]), "+f"(d[36]), "+f"(d[37]), "+f"(d[38]), "+f"(d[39]), "+f"(d[40]), "+f"(d[41]), "+f"(d[42]), "+f"(d[43]), "+f"(d[44]), "+f"(d[45]), "+f"(d[46]), "+f"(d[47]), "+f"(d[48]), "+f"(d[49]), "+f"(d[50]), "+f"(d[51]), "+f"(d[52]), "+f"(d[53]), "+f"(d[54]), "+f"(d[55]), "+f"(d[56]), "+f"(d[57]), "+f"(d[58]), "+f"(d[59]), "+f"(d[60]), "+f"(d[61]), "+f"(d[62]), "+f"(d[63])
        : "l"(da), "l"(db), "r"(sc), "n"(TB));
}
template <int TB> __device__ __forceinline__ void wgmma_rs_n24(float (&d)[12], uint32_t a0, uint32_t a1, uint32_t a2, uint32_t a3, uint64_t db, int sc) {
    asm volatile("{\n.reg .pred p;\nsetp.ne.b32 p, %17, 0;\n"
        "wgmma.mma_async.sync.aligned.m64n24k16.f32.bf16.bf16 {%0, %1, %2, %3, %4, %5, %6, %7, %8, %9, %10, %11}, {%12, %13, %14, %15}, %16, p, 1, 1, %18;\n}\n"
        : "+f"(d[0]), "+f"(d[1]), "+f"(d[2]), "+f"(d[3]), "+f"(d[4]), "+f"(d[5]), "+f"(d[6]), "+f"(d[7]), "+f"(d[8]), "+f"(d[9]), "+f"(d[10]), "+f"(d[11])
        : "r"(a0), "r"(a1), "r"(a2), "r"(a3), "l"(db), "r"(sc), "n"(TB));
}
template <int TB> __device__ __forceinline__ void wgmma_rs_n64(float (&d)[32], uint32_t a0, uint32_t a1, uint32_t a2, uint32_t a3, uint64_t db, int sc) {
    asm volatile("{\n.reg .pred p;\nsetp.ne.b32 p, %37, 0;\n"
        "wgmma.mma_async.sync.aligned.m64n64k16.f32.bf16.bf16 {%0, %1, %2, %3, %4, %5, %6, %7, %8, %9, %10, %11, %12, %13, %14, %15, %16, %17, %18, %19, %20, %21, %22, %23, %24, %25, %26, %27, %28, %29, %30, %31}, {%32, %33, %34, %35}, %36, p, 1, 1, %38;\n}\n"
        : "+f"(d[0]), "+f"(d[1]), "+f"(d[2]), "+f"(d[3]), "+f"(d[4]), "+f"(d[5]), "+f"(d[6]), "+f"(d[7]), "+f"(d[8]), "+f"(d[9]), "+f"(d[10]), "+f"(d[11]), "+f"(d[12]), "+f"(d[13]), "+f"(d[14]), "+f"(d[15]), "+f"(d[16]), "+f"(d[17]), "+f"(d[18]), "+f"(d[19]), "+f"(d[20]), "+f"(d[21]), "+f"(d[22]), "+f"(d[23]), "+f"(d[24]), "+f"(d[25]), "+f"(d[26]), "+f"(d[27]), "+f"(d[28]), "+f"(d[29]), "+f"(d[30]), "+f"(d[31])
        : "r"(a0), "r"(a1), "r"(a2), "r"(a3), "l"(db), "r"(sc), "n"(TB));
}
template <int TB> __device__ __forceinline__ void wgmma_rs_n128(float (&d)[64], uint32_t a0, uint32_t a1, uint32_t a2, uint32_t a3, uint64_t db, int sc) {
    asm volatile("{\n.reg .pred p;\nsetp.ne.b32 p, %69, 0;\n"
        "wgmma.mma_async.sync.aligned.m64n128k16.f32.bf16.bf16 {%0, %1, %2, %3, %4, %5, %6, %7, %8, %9, %10, %11, %12, %13, %14, %15, %16, %17, %18, %19, %20, %21, %22, %23, %24, %25, %26, %27, %28, %29, %30, %31, %32, %33, %34, %35, %36, %37, %38, %39, %40, %41, %42, %43, %44, %45, %46, %47, %48, %49, %50, %51, %52, %53, %54, %55, %56, %57, %58, %59, %60, %61, %62, %63}, {%64, %65, %66, %67}, %68, p, 1, 1, %70;\n}\n"
        : "+f"(d[0]), "+f"(d[1]), "+f"(d[2]), "+f"(d[3]), "+f"(d[4]), "+f"(d[5]), "+f"(d[6]), "+f"(d[7]), "+f"(d[8]), "+f"(d[9]), "+f"(d[10]), "+f"(d[11]), "+f"(d[12]), "+f"(d[13]), "+f"(d[14]), "+f"(d[15]), "+f"(d[16]), "+f"(d[17]), "+f"(d[18]), "+f"(d[19]), "+f"(d[20]), "+f"(d[21]), "+f"(d[22]), "+f"(d[23]), "+f"(d[24]), "+f"(d[25]), "+f"(d[26]), "+f"(d[27]), "+f"(d[28]), "+f"(d[29]), "+f"(d[30]), "+f"(d[31]), "+f"(d[32]), "+f"(d[33]), "+f"(d[34]), "+f"(d[35]), "+f"(d[36]), "+f"(d[37]), "+f"(d[38]), "+f"(d[39]), "+f"(d[40]), "+f"(d[41]), "+f"(d[42]), "+f"(d[43]), "+f"(d[44]), "+f"(d[45]), "+f"(d[46]), "+f"(d[47]), "+f"(d[48]), "+f"(d[49]), "+f"(d[50]), "+f"(d[51]), "+f"(d[52]), "+f"(d[53]), "+f"(d[54]), "+f"(d[55]), "+f"(d[56]), "+f"(d[57]), "+f"(d[58]), "+f"(d[59]), "+f"(d[60]), "+f"(d[61]), "+f"(d[62]), "+f"(d[63])
        : "r"(a0), "r"(a1), "r"(a2), "r"(a3), "l"(db), "r"(sc), "n"(TB));
}

constexpr int P_NST = 6;
constexpr int P_A_BYTES = 9 * 8192;
constexpr int P_B_STAGE = 3 * 8192;
constexpr int P_SMEM = P_A_BYTES + P_NST * P_B_STAGE + 256 + 320;

template <int NB>
__device__ __forceinline__ void stage_tile(const uint32_t (&pk)[NB * 2], uint32_t base, int w, int lane) {
    const int r = w * 16 + (lane & 7) + ((lane >> 3) & 1) * 8;
#pragma unroll
    for (int b = 0; b < NB; b += 2) {
        const uint32_t a = base + (b >> 3) * 8192 + r * 128 + ((((b & 7) + (lane >> 4)) ^ (r & 7)) << 4);
        stmatrix_x4(a, pk[2 * b], pk[2 * b + 1], pk[2 * b + 2], pk[2 * b + 3]);
    }
}

__device__ __forceinline__ uint32_t hsub2_bf16(uint32_t a, uint32_t b) { uint32_t r; asm("sub.rn.bf16x2 %0, %1, %2;" : "=r"(r) : "r"(a), "r"(b)); return r; }

constexpr int KV_RAW = DM * 18 * 2;
constexpr int Q_THREADS = 416;

__device__ __forceinline__ void proj_mma(float (&acc)[32], int wg, uint32_t fullB, uint32_t emptyB, uint32_t fullA, bool wait_a, int lane) {
    const uint64_t dA = cdesc(0, 16, 1024, 1), dB = cdesc(P_A_BYTES, 8192, 1024, 1) + wg * 512;
#pragma unroll 1
    for (int kb = 0; kb < 9; kb++) {
        const int s = kb >= P_NST ? kb - P_NST : kb;
        if (wait_a) mbar_wait(fullA + kb * 8, 0);
        mbar_wait(fullB + s * 8, kb >= P_NST ? 1 : 0);
        wg_fence();
#pragma unroll
        for (int ks = 0; ks < 4; ks++) wgmma_ss_n64<1>(acc, dA + (kb * 512 + ks * 2), dB + (s * (P_B_STAGE >> 4) + ks * 128), (kb | ks) != 0);
        wg_commit();
        if (kb < 4) {
            wg_wait<1>();
            if (kb >= 1 && lane == 0) mbar_arrive(emptyB + (kb - 1) * 8);
        }
    }
    wg_wait<0>();
    pin(acc);
}

__global__ void __launch_bounds__(Q_THREADS, 1)
k_qkv(const __grid_constant__ CUtensorMap tmWq, const __grid_constant__ CUtensorMap tmQ, const __nv_bfloat16* __restrict__ x, const __nv_bfloat16* __restrict__ wk, const __nv_bfloat16* __restrict__ wv) {
    extern __shared__ __align__(1024) uint8_t smem[];
    const uint32_t sA = smem_u32(smem), sB = sA + P_A_BYTES, bars = sB + P_NST * P_B_STAGE;
    const uint32_t fullB = bars, emptyB = bars + 64, fullX = bars + 128, fullW = bars + 136;
    float* s_rstd = reinterpret_cast<float*>(smem + P_A_BYTES + P_NST * P_B_STAGE + 256);
    const int tid = threadIdx.x, warp = __shfl_sync(~0u, tid >> 5, 0), lane = tid & 31;
    const bool isQ = blockIdx.x < 96;
    const int m = isQ ? blockIdx.x / 3 : blockIdx.x - 96, cg = blockIdx.x % 3;
    if (tid == 0) TS(0, 0);
    if (warp == 12) {
        if (elect_one()) {
            mbar_init(fullX, 1);
            bar_init_fence();
            mbar_expect(fullX, P_A_BYTES);
            bulk_g2s(sA, x + (size_t)m * 64 * DM, P_A_BYTES, fullX);
            prefetch_map(&tmWq); prefetch_map(&tmQ);
            for (int i = 0; i < P_NST; i++) { mbar_init(fullB + i * 8, 1); mbar_init(emptyB + i * 8, 12); }
            mbar_init(fullW, 1);
            bar_init_fence();
            if (isQ) {
                for (int kb = 0; kb < P_NST; kb++) {
                    mbar_expect(fullB + kb * 8, P_B_STAGE);
                    for (int a = 0; a < 3; a++) tma_2d(sB + kb * P_B_STAGE + a * 8192, &tmWq, cg * 192 + a * 64, kb * 64, fullB + kb * 8);
                }
            } else {
                mbar_expect(fullW, 2 * KV_RAW);
                bulk_g2s(sB + 3 * P_B_STAGE, wk, KV_RAW, fullW);
                bulk_g2s(sB + 3 * P_B_STAGE + KV_RAW, wv, KV_RAW, fullW);
            }
        }
        __syncwarp();
    }
    check_smem_base(sA);
    __syncthreads();
    pdl_launch();
    if (warp == 12) {
        if (isQ && elect_one()) {
            for (int kb = P_NST; kb < 9; kb++) {
                const int s = kb - P_NST;
                mbar_wait(emptyB + s * 8, 0);
                mbar_expect(fullB + s * 8, P_B_STAGE);
                for (int a = 0; a < 3; a++) tma_2d(sB + s * P_B_STAGE + a * 8192, &tmWq, cg * 192 + a * 64, kb * 64, fullB + s * 8);
            }
        }
        return;
    }
    if (warp < 8) {
        const int row = tid >> 2, q = tid & 3, h0 = (row & 1) * 4;
        mbar_wait(fullX, 0);
        if (tid == 0) TS(0, 6);
        uint4 v[18];
        const uint32_t ra = sA + row * 1152 + (q + h0) * 16, rb = sA + row * 1152 + (q + 4 - h0) * 16;
#pragma unroll
        for (int kb = 0; kb < 9; kb++) {
            asm volatile("ld.shared.v4.b32 {%0, %1, %2, %3}, [%4];" : "=r"(v[2 * kb].x), "=r"(v[2 * kb].y), "=r"(v[2 * kb].z), "=r"(v[2 * kb].w) : "r"(ra + kb * 128));
            asm volatile("ld.shared.v4.b32 {%0, %1, %2, %3}, [%4];" : "=r"(v[2 * kb + 1].x), "=r"(v[2 * kb + 1].y), "=r"(v[2 * kb + 1].z), "=r"(v[2 * kb + 1].w) : "r"(rb + kb * 128));
        }
        float sum = 0.f, sum2 = 0.f, sq = 0.f, sq2 = 0.f;
#pragma unroll
        for (int i = 0; i < 18; i++) {
            const uint32_t w[4] = {v[i].x, v[i].y, v[i].z, v[i].w};
#pragma unroll
            for (int j = 0; j < 4; j++) { const float a = bf_lo(w[j]), b = bf_hi(w[j]); sum += a; sum2 += b; sq = fmaf(a, a, sq); sq2 = fmaf(b, b, sq2); }
        }
        named_sync(1, 256);
        sum += sum2; sq += sq2;
        sum += __shfl_xor_sync(~0u, sum, 1); sum += __shfl_xor_sync(~0u, sum, 2);
        sq += __shfl_xor_sync(~0u, sq, 1); sq += __shfl_xor_sync(~0u, sq, 2);
        if (tid == 0) TS(0, 4);
        const float mean = sum * (1.0f / DM);
        if (q == 0) s_rstd[row] = rsqrtf(fmaxf(sq * (1.0f / DM) - mean * mean, 0.f) + LN_EPS);
        const uint32_t mhi = pack_bf16(mean, mean);
        const float rem = mean - bf_lo(mhi);
        const uint32_t mlo = pack_bf16(rem, rem);
        const uint32_t wa = sA + row * 128 + (((q + h0) ^ (row & 7)) << 4), wb = sA + row * 128 + (((q + 4 - h0) ^ (row & 7)) << 4);
#pragma unroll
        for (int i = 0; i < 18; i++) {
            const uint32_t o0 = hsub2_bf16(hsub2_bf16(v[i].x, mhi), mlo), o1 = hsub2_bf16(hsub2_bf16(v[i].y, mhi), mlo);
            const uint32_t o2 = hsub2_bf16(hsub2_bf16(v[i].z, mhi), mlo), o3 = hsub2_bf16(hsub2_bf16(v[i].w, mhi), mlo);
            asm volatile("st.shared.v4.b32 [%0], {%1, %2, %3, %4};" ::"r"(((i & 1) ? wb : wa) + (i >> 1) * 8192), "r"(o0), "r"(o1), "r"(o2), "r"(o3) : "memory");
        }
    } else if (!isQ) {
        mbar_wait(fullW, 0);
        const uint32_t* raw = reinterpret_cast<const uint32_t*>(smem + P_A_BYTES + 3 * P_B_STAGE);
#pragma unroll 3
        for (int r = tid - 256; r < 2 * DM; r += 128) {
            uint32_t wr[9];
#pragma unroll
            for (int i = 0; i < 9; i++) wr[i] = raw[r * 9 + i];
            const int sel = r >= DM, k = r - sel * DM;
            uint8_t* dst = smem + P_A_BYTES + sel * 3 * 9216 + (k >> 3) * 128 + (k & 7) * 16;
            *reinterpret_cast<uint4*>(dst) = make_uint4(wr[0], wr[1], wr[2], wr[3]);
            *reinterpret_cast<uint4*>(dst + 9216) = make_uint4(wr[4], wr[5], wr[6], wr[7]);
            *reinterpret_cast<uint32_t*>(dst + 2 * 9216) = wr[8];
        }
    }
    proxy_fence();
    named_sync(2, 384);
    if (tid == 0) TS(0, 1);
    const int wg = warp >> 2, w = warp & 3, g = lane >> 2, t = lane & 3;
    const float rs0 = s_rstd[w * 16 + g], rs1 = s_rstd[w * 16 + g + 8];
    if (isQ) {
        const float c0 = rs0 * Q_SCALE, c1 = rs1 * Q_SCALE;
        float acc[32];
        proj_mma(acc, wg, fullB, emptyB, 0, false, lane);
        if (tid == 0) TS(0, 2);
        uint32_t pk[16];
#pragma unroll
        for (int i = 0; i < 8; i++) { pk[2 * i] = pack_bf16(acc[4 * i] * c0, acc[4 * i + 1] * c0); pk[2 * i + 1] = pack_bf16(acc[4 * i + 2] * c1, acc[4 * i + 3] * c1); }
        named_sync(2, 384);
        stage_tile<8>(pk, sA + wg * 8192, w, lane);
        proxy_fence();
        named_sync(3 + wg, 128);
        if (w == 0 && elect_one()) {
            tma_st_2d(&tmQ, cg * 192 + wg * 64, m * 64, sA + wg * 8192);
            bulk_commit();
            bulk_wait_all();
        }
    } else if (wg < 2) {
        float acc[12];
        const uint64_t dA = cdesc(0, 16, 1024, 1), dB = cdesc(P_A_BYTES, 128, 9216, 0) + wg * (3 * 9216 >> 4);
#pragma unroll
        for (int i = 0; i < 12; i++) acc[i] = 0.f;
        pin(acc);
        wg_fence();
#pragma unroll 1
        for (int kb = 0; kb < 9; kb++) {
#pragma unroll
            for (int ks = 0; ks < 4; ks++) wgmma_ss_n24<1>(acc, dA + (kb * 512 + ks * 2), dB + (kb * 4 + ks) * 16, 1);
        }
        wg_commit();
        wg_wait<0>();
        pin(acc);
        uint32_t pk[6];
#pragma unroll
        for (int b = 0; b < 3; b++) { pk[2 * b] = pack_bf16(acc[4 * b] * rs0, acc[4 * b + 1] * rs0); pk[2 * b + 1] = pack_bf16(acc[4 * b + 2] * rs1, acc[4 * b + 3] * rs1); }
        float n0 = 0.f, n1 = 0.f, vm = 0.f;
#pragma unroll
        for (int b = 0; b < 3; b++) {
            if (b < 2 || t == 0) {
                const float a = bf_lo(pk[2 * b]), c = bf_hi(pk[2 * b]), d = bf_lo(pk[2 * b + 1]), e = bf_hi(pk[2 * b + 1]);
                n0 = fmaf(a, a, fmaf(c, c, n0)); n1 = fmaf(d, d, fmaf(e, e, n1));
            }
        }
        n0 += __shfl_xor_sync(~0u, n0, 1); n0 += __shfl_xor_sync(~0u, n0, 2);
        n1 += __shfl_xor_sync(~0u, n1, 1); n1 += __shfl_xor_sync(~0u, n1, 2);
        vm = fmaxf(n0, n1);
        if (!(n0 == n0) || !(n1 == n1)) vm = __int_as_float(0x7F800000);
#pragma unroll
        for (int o = 4; o < 32; o <<= 1) vm = fmaxf(vm, __shfl_xor_sync(~0u, vm, o));
        if (t != 0) {
            uint32_t lo, hi;
            if (wg == 0) {
                const int grp = m * 8 + w * 2;
                const uint32_t c = t == 1 ? 0x42FE3F80u   : (t == 2 ? 0x00003BC0u   : 0u);
                lo = ((POLY_MASK >> (grp & 15)) & 1) ? c : 0u;
                hi = ((POLY_MASK >> ((grp + 1) & 15)) & 1) ? c : 0u;
            } else {
                lo = hi = t == 1 ? 0x00003F80u : 0u;
            }
            pk[4] = lo; pk[5] = hi;
        }
        uint32_t* dst = reinterpret_cast<uint32_t*>(wg == 0 ? g_kc : g_vc) + (m * 8 + w * 2) * 96 + g * 4 + t;
#pragma unroll
        for (int b = 0; b < 3; b++) { dst[b * 32] = pk[2 * b]; dst[96 + b * 32] = pk[2 * b + 1]; }
        if (lane == 0) g_kmax[m * 8 + warp] = (wg == 0) ? vm : (vm <= 1e24f ? 0.f : __int_as_float(0x7F800000));
    }
    if (tid == 0) TS(0, 3);
}

constexpr int A_THREADS = 512;
constexpr int A_NPIECE = 8;
constexpr int A_OFF_Q = 2 * KV_BYTES;
constexpr int A_OFF_BAR = A_OFF_Q + 4 * 4096;
constexpr int A_SMEM = A_OFF_BAR + 128;

__device__ __forceinline__ uint32_t exp2_pair_fixed(float lo, float hi, uint32_t dep) {
    const uint32_t G = __byte_perm(__float_as_uint(lo), __float_as_uint(hi), 0x5410);
    uint32_t Hh;
    asm("lop3.b32 %0, %1, 0x007F007F, %2, 0xC0;" : "=r"(Hh) : "r"(G), "r"(dep));
    const uint32_t tt = hfma2(Hh, 0xF96BF96Bu, 0x358C358Cu);
    return G - hfma2(tt, Hh, 0u);
}

__global__ void __launch_bounds__(A_THREADS, 1)
k_attn() {
    extern __shared__ __align__(1024) uint8_t smem[];
    pdl_launch();
    const uint32_t sK = smem_u32(smem), sV = sK + KV_BYTES, bars = sK + A_OFF_BAR;
    const int tid = threadIdx.x;
    check_smem_base(sK);
    if (tid == 0) TS(1, 0);
    if (tid == 0) {
        for (int i = 0; i < A_NPIECE; i++) mbar_init(bars + i * 8, 1);
        bar_init_fence();
    }
    __syncthreads();
    pdl_wait();
    if (tid == 0) TS(1, 1);
    const int wg = __shfl_sync(~0u, tid >> 7, 0), w = (tid >> 5) & 3, lane = tid & 31, g = lane >> 2, t = lane & 3;
    const uint32_t* q32 = reinterpret_cast<const uint32_t*>(g_q);
    int row = (blockIdx.x * 8 + wg) * 64 + w * 16 + g;
    uint32_t nq[6];
    nq[0] = q32[row * 9 + t]; nq[1] = q32[(row + 8) * 9 + t]; nq[2] = q32[row * 9 + 4 + t]; nq[3] = q32[(row + 8) * 9 + 4 + t];
    nq[4] = q32[row * 9 + 8]; nq[5] = q32[(row + 8) * 9 + 8];
    constexpr int PB = KV_BYTES / A_NPIECE;
    const float4 km0 = reinterpret_cast<const float4*>(g_kmax)[lane], km1 = reinterpret_cast<const float4*>(g_kmax)[32 + lane];
    if (tid < 32 && elect_one()) {
        for (int i = 0; i < 2; i++) {
            mbar_expect(bars + i * 8, 2 * PB);
            bulk_g2s(sK + i * PB, reinterpret_cast<const char*>(g_kc) + i * PB, PB, bars + i * 8);
            bulk_g2s(sV + i * PB, reinterpret_cast<const char*>(g_vc) + i * PB, PB, bars + i * 8);
        }
    }
    float kmax2 = fmaxf(fmaxf(fmaxf(km0.x, km0.y), fmaxf(km0.z, km0.w)), fmaxf(fmaxf(km1.x, km1.y), fmaxf(km1.z, km1.w)));
#pragma unroll
    for (int o = 1; o < 32; o <<= 1) kmax2 = fmaxf(kmax2, __shfl_xor_sync(~0u, kmax2, o));
    if (tid < 32 && elect_one()) {
        for (int i = 2; i < A_NPIECE; i++) {
            mbar_expect(bars + i * 8, 2 * PB);
            bulk_g2s(sK + i * PB, reinterpret_cast<const char*>(g_kc) + i * PB, PB, bars + i * 8);
            bulk_g2s(sV + i * PB, reinterpret_cast<const char*>(g_vc) + i * PB, PB, bars + i * 8);
        }
    }
    const uint32_t sQ = sK + A_OFF_Q + wg * 4096 + (w * 2) * 512 + g * 16 + t * 4;
    const uint64_t dQ0 = cdesc(A_OFF_Q, 128, 512, 0) + wg * 256, dQ1 = dQ0 + 16;
#pragma unroll 1
    for (int rep = 0; rep < 2; rep++, row += 256) {
        const uint32_t qa[4] = {nq[0], nq[1], nq[2], nq[3]};
        float n0, n1;
        {
            const float a0 = bf_lo(qa[0]), a1 = bf_hi(qa[0]), a2 = bf_lo(qa[2]), a3 = bf_hi(qa[2]);
            const float b0 = bf_lo(qa[1]), b1 = bf_hi(qa[1]), b2 = bf_lo(qa[3]), b3 = bf_hi(qa[3]);
            n0 = a0 * a0 + a1 * a1 + a2 * a2 + a3 * a3; n1 = b0 * b0 + b1 * b1 + b2 * b2 + b3 * b3;
            if (t == 0) {
                const float c0 = bf_lo(nq[4]), c1 = bf_hi(nq[4]), d0 = bf_lo(nq[5]), d1 = bf_hi(nq[5]);
                n0 += c0 * c0 + c1 * c1; n1 += d0 * d0 + d1 * d1;
            }
            n0 += __shfl_xor_sync(~0u, n0, 1); n0 += __shfl_xor_sync(~0u, n0, 2);
            n1 += __shfl_xor_sync(~0u, n1, 1); n1 += __shfl_xor_sync(~0u, n1, 2);
        }
        const uint32_t x0 = nq[4], x1 = nq[5];
        if (rep == 0) {
            const int nr = row + 256;
            nq[0] = q32[nr * 9 + t]; nq[1] = q32[(nr + 8) * 9 + t]; nq[2] = q32[nr * 9 + 4 + t]; nq[3] = q32[(nr + 8) * 9 + 4 + t];
            nq[4] = q32[nr * 9 + 8]; nq[5] = q32[(nr + 8) * 9 + 8];
        }
        if (tid == 0 && rep == 0) TS(1, 7);
        const bool unsafe = !(fmaxf(n0, n1) * kmax2 <= FAST_BOUND * FAST_BOUND) || !(n0 == n0) || !(n1 == n1);
        uint32_t any_unsafe;
        asm volatile("{\n.reg .pred p, q;\nsetp.ne.u32 p, %1, 0;\nbar.red.or.pred q, %2, 128, p;\nselp.u32 %0, 1, 0, q;\n}\n" : "=r"(any_unsafe) : "r"((uint32_t)unsafe), "r"(wg + 1) : "memory");
        any_unsafe = __shfl_sync(~0u, any_unsafe, 0);
        {
            const uint32_t cst = any_unsafe ? 0u : (t == 1 ? 0x3F804780u : (t == 2 ? 0x00003F80u : 0u));
            asm volatile("st.shared.b32 [%0], %1;" ::"r"(sQ), "r"(qa[0]) : "memory");
            asm volatile("st.shared.b32 [%0], %1;" ::"r"(sQ + 512), "r"(qa[1]) : "memory");
            asm volatile("st.shared.b32 [%0], %1;" ::"r"(sQ + 128), "r"(qa[2]) : "memory");
            asm volatile("st.shared.b32 [%0], %1;" ::"r"(sQ + 640), "r"(qa[3]) : "memory");
            asm volatile("st.shared.b32 [%0], %1;" ::"r"(sQ + 256), "r"(t == 0 ? x0 : cst) : "memory");
            asm volatile("st.shared.b32 [%0], %1;" ::"r"(sQ + 768), "r"(t == 0 ? x1 : cst) : "memory");
            asm volatile("st.shared.b32 [%0], %1;" ::"r"(sQ + 384), "r"(0u) : "memory");
            asm volatile("st.shared.b32 [%0], %1;" ::"r"(sQ + 896), "r"(0u) : "memory");
            proxy_fence();
            named_sync(wg + 1, 128);
        }
        if (tid == 0) TS(1, 2 + rep * 2);
        float o[12];
#pragma unroll
        for (int i = 0; i < 12; i++) o[i] = 0.f;
        pin(o);
        uint64_t dK0 = cdesc(0, 128, 384, 0), dK1 = cdesc(256, 0, 384, 0), dV = cdesc(KV_BYTES, 384, 128, 0);
        if (!any_unsafe) {
            float s[64];
#pragma unroll 1
            for (int j = 0; j < 16; j++) {
                if (rep == 0 && (j & 1) == 0) mbar_wait(bars + (j >> 1) * 8, 0);
                wg_fence();
                wgmma_ss_n128<0>(s, dQ0, dK0, 0);
                wgmma_ss_n128<0>(s, dQ1, dK1, 1);
                wg_commit();
                dK0 += 16 * 384 >> 4; dK1 += 16 * 384 >> 4;
                wg_wait<0>();
                pin(s);
                uint32_t p[32];
#define CHAIN 6
                {
                    constexpr int NP = 2 * __builtin_popcount(POLY_MASK), NM = 32 - NP;
                    float e[64];
#pragma unroll
                    for (int i = 0; i < 32; i++)
                        if (!((POLY_MASK >> (i >> 1)) & 1)) { e[2 * i] = ex2(s[2 * i]); e[2 * i + 1] = ex2(s[2 * i + 1]); p[i] = pack_bf16(e[2 * i], e[2 * i + 1]); }
                    int ip = 0;
#pragma unroll
                    for (int i = 0; i < 32; i++) {
                        if ((POLY_MASK >> (i >> 1)) & 1) {
                            const int mm = (ip * 2 * NM) / NP - CHAIN;
                            uint32_t dep = 0;
                            if (CHAIN > 0 && mm >= 0) {
                                int cnt = 0;
#pragma unroll
                                for (int q = 0; q < 32; q++)
                                    if (!((POLY_MASK >> (q >> 1)) & 1)) { if (cnt == (mm >> 1)) dep = __float_as_uint(e[2 * q + (mm & 1)]); cnt++; }
                            }
                            p[i] = exp2_pair_fixed(s[2 * i], s[2 * i + 1], dep);
                            ip++;
                        }
                    }
                }
                pin(p);
                wg_fence();
#pragma unroll
                for (int k = 0; k < 8; k++) {
                    wgmma_rs_n24<1>(o, p[4 * k], p[4 * k + 1], p[4 * k + 2], p[4 * k + 3], dV + k * 48, 1);
                }
                wg_commit();
                dV += 16 * 384 >> 4;
                wg_wait<0>();
            }
        } else {
            float s[64];
            float m0 = -INFINITY, m1 = -INFINITY;
#pragma unroll 1
            for (int j = 0; j < 16; j++) {
                if (rep == 0 && (j & 1) == 0) mbar_wait(bars + (j >> 1) * 8, 0);
                wg_fence();
                wgmma_ss_n128<0>(s, dQ0, dK0, 0);
                wgmma_ss_n128<0>(s, dQ1, dK1, 1);
                wg_commit();
                dK0 += 16 * 384 >> 4; dK1 += 16 * 384 >> 4;
                wg_wait<0>();
                pin(s);
                float x0m = m0, x1m = m1;
#pragma unroll
                for (int b = 0; b < 16; b++) { x0m = fmaxf(x0m, fmaxf(s[4 * b], s[4 * b + 1])); x1m = fmaxf(x1m, fmaxf(s[4 * b + 2], s[4 * b + 3])); }
                x0m = fmaxf(x0m, __shfl_xor_sync(~0u, x0m, 1)); x0m = fmaxf(x0m, __shfl_xor_sync(~0u, x0m, 2));
                x1m = fmaxf(x1m, __shfl_xor_sync(~0u, x1m, 1)); x1m = fmaxf(x1m, __shfl_xor_sync(~0u, x1m, 2));
                const float c0 = ex2(m0 - x0m), c1 = ex2(m1 - x1m);
                m0 = x0m; m1 = x1m;
#pragma unroll
                for (int b = 0; b < 3; b++) { o[4 * b] *= c0; o[4 * b + 1] *= c0; o[4 * b + 2] *= c1; o[4 * b + 3] *= c1; }
                uint32_t p[32];
#pragma unroll
                for (int b = 0; b < 16; b++) {
                    p[2 * b] = pack_bf16(ex2(s[4 * b] - m0), ex2(s[4 * b + 1] - m0));
                    p[2 * b + 1] = pack_bf16(ex2(s[4 * b + 2] - m1), ex2(s[4 * b + 3] - m1));
                }
                pin(p); pin(o);
                wg_fence();
#pragma unroll
                for (int k = 0; k < 8; k++) wgmma_rs_n24<1>(o, p[4 * k], p[4 * k + 1], p[4 * k + 2], p[4 * k + 3], dV + k * 48, 1);
                wg_commit();
                dV += 16 * 384 >> 4;
                wg_wait<0>();
            }
        }
        pin(o);
        if (tid == 0) TS(1, 3 + rep * 2);
        const float l0 = __shfl_sync(~0u, o[8], (lane & ~3) | 1), l1 = __shfl_sync(~0u, o[10], (lane & ~3) | 1);
        const float i0 = 1.0f / l0, i1 = 1.0f / l1;
        uint32_t* o32 = reinterpret_cast<uint32_t*>(g_o);
        o32[row * 9 + t] = pack_bf16(o[0] * i0, o[1] * i0);
        o32[(row + 8) * 9 + t] = pack_bf16(o[2] * i1, o[3] * i1);
        o32[row * 9 + 4 + t] = pack_bf16(o[4] * i0, o[5] * i0);
        o32[(row + 8) * 9 + 4 + t] = pack_bf16(o[6] * i1, o[7] * i1);
        if (t == 0) { o32[row * 9 + 8] = pack_bf16(o[8] * i0, o[9] * i0); o32[(row + 8) * 9 + 8] = pack_bf16(o[10] * i1, o[11] * i1); }
    }
    if (tid == 0) TS(1, 6);
    if ((tid & 127) == 0) TS(1, 10 + wg);
}

constexpr int O_THREADS = 416;
constexpr int O_OFF_STAT = P_A_BYTES + P_NST * P_B_STAGE + 256;
constexpr int O_SMEM = O_OFF_STAT + 9 * 64 * 8;

__global__ void __cluster_dims__(3, 1, 1) __launch_bounds__(O_THREADS, 1)
k_oproj(const __grid_constant__ CUtensorMap tmO, const __grid_constant__ CUtensorMap tmWo, const __grid_constant__ CUtensorMap tmX2, const __grid_constant__ CUtensorMap tmOut, const __nv_bfloat16* __restrict__ x, const __nv_bfloat16* __restrict__ w1) {
    extern __shared__ __align__(1024) uint8_t smem[];
    const uint32_t sA = smem_u32(smem), sB = sA + P_A_BYTES, bars = sB + P_NST * P_B_STAGE;
    const uint32_t fullB = bars, emptyB = bars + 64, fullA = bars + 128;
    const int tid = threadIdx.x, warp = __shfl_sync(~0u, tid >> 5, 0), lane = tid & 31;
    const int m = blockIdx.x / 3, cg = blockIdx.x % 3;
    if (tid == 0) TS(2, 0);
    check_smem_base(sA);
    if (tid == 0) {
        prefetch_map(&tmO); prefetch_map(&tmWo); prefetch_map(&tmX2); prefetch_map(&tmOut);
        for (int i = 0; i < P_NST; i++) { mbar_init(fullB + i * 8, 1); mbar_init(emptyB + i * 8, 12); }
        for (int i = 0; i < 9; i++) mbar_init(fullA + i * 8, 1);
        bar_init_fence();
        for (int kb = 0; kb < 9; kb++) mbar_expect(fullA + kb * 8, 8192);
    }
    __syncthreads();
    pdl_launch();
    if (warp == 12) {
        if (elect_one()) {
            for (int kb = 0; kb < 9; kb++) {
                const int s = kb >= P_NST ? kb - P_NST : kb;
                if (kb == 2) {
                    pdl_wait();
                    TS(2, 1);
                    for (int ka = 0; ka < 9; ka++) tma_2d(sA + ka * 8192, &tmO, ka * 64, m * 64, fullA + ka * 8);
                }
                if (kb >= P_NST) mbar_wait(emptyB + s * 8, 0);
                mbar_expect(fullB + s * 8, P_B_STAGE);
                for (int a = 0; a < 3; a++) tma_2d(sB + s * P_B_STAGE + a * 8192, &tmWo, cg * 192 + a * 64, kb * 64, fullB + s * 8);
            }
            for (int i = 0; i < 6; i++) prefetch_l2(reinterpret_cast<const char*>(w1) + (size_t)blockIdx.x * (FF * DM * 2 / 96) + i * 9216, 9216);
        }
        return;
    }
    if (tid == 0) TS(2, 11);
    const int wg = warp >> 2, w = warp & 3, g = lane >> 2, t = lane & 3;
    uint32_t xr[16];
    {
        const uint32_t* x32 = reinterpret_cast<const uint32_t*>(x) + (((m * 64 + w * 16 + g) * DM + cg * 192 + wg * 64 + 2 * t) >> 1);
#pragma unroll
        for (int b = 0; b < 8; b++) { xr[2 * b] = __ldg(x32 + b * 4); xr[2 * b + 1] = __ldg(x32 + b * 4 + 4 * DM); }
    }
    float acc[32];
    proj_mma(acc, wg, fullB, emptyB, fullA, true, lane);
    if (tid == 0) TS(2, 2);
    named_sync(1, 384);
    float s0 = 0.f, q0 = 0.f, s1 = 0.f, q1 = 0.f;
#pragma unroll
    for (int b = 0; b < 8; b++) {
        const uint32_t xa = xr[2 * b], xb = xr[2 * b + 1];
        const uint32_t ha = pack_bf16(acc[4 * b] + bf_lo(xa), acc[4 * b + 1] + bf_hi(xa));
        const uint32_t hb = pack_bf16(acc[4 * b + 2] + bf_lo(xb), acc[4 * b + 3] + bf_hi(xb));
        xr[2 * b] = ha; xr[2 * b + 1] = hb;
        const float a = bf_lo(ha), c = bf_hi(ha), d = bf_lo(hb), e = bf_hi(hb);
        s0 += a + c; q0 = fmaf(a, a, fmaf(c, c, q0));
        s1 += d + e; q1 = fmaf(d, d, fmaf(e, e, q1));
    }
    s0 += __shfl_xor_sync(~0u, s0, 1); s0 += __shfl_xor_sync(~0u, s0, 2);
    q0 += __shfl_xor_sync(~0u, q0, 1); q0 += __shfl_xor_sync(~0u, q0, 2);
    s1 += __shfl_xor_sync(~0u, s1, 1); s1 += __shfl_xor_sync(~0u, s1, 2);
    q1 += __shfl_xor_sync(~0u, q1, 1); q1 += __shfl_xor_sync(~0u, q1, 2);
    const int r = w * 16 + g;
    const uint32_t sStat = sA + O_OFF_STAT;
    if (t < 3) {
        uint32_t dst;
        asm("mapa.shared::cluster.u32 %0, %1, %2;" : "=r"(dst) : "r"(sStat + ((cg * 3 + wg) * 64 + r) * 8), "r"(t));
        asm volatile("st.shared::cluster.v2.f32 [%0], {%1, %2};" ::"r"(dst), "f"(s0), "f"(q0) : "memory");
        asm volatile("st.shared::cluster.v2.f32 [%0], {%1, %2};" ::"r"(dst + 64), "f"(s1), "f"(q1) : "memory");
    }
    if (tid == 0) TS(2, 4);
    cluster_arrive();
    stage_tile<8>(xr, sA + wg * 8192, w, lane);
    proxy_fence();
    named_sync(2 + wg, 128);
    const bool leader = w == 0 && elect_one();
    if (leader) { tma_st_2d(&tmOut, cg * 192 + wg * 64, m * 64, sA + wg * 8192); bulk_commit(); }
    cluster_wait();
    if (tid == 0) TS(2, 5);
    s0 = q0 = s1 = q1 = 0.f;
#pragma unroll
    for (int p = 0; p < 9; p++) {
        float a, b, c, d;
        asm volatile("ld.shared.v2.f32 {%0, %1}, [%2];" : "=f"(a), "=f"(b) : "r"(sStat + (p * 64 + r) * 8));
        asm volatile("ld.shared.v2.f32 {%0, %1}, [%2];" : "=f"(c), "=f"(d) : "r"(sStat + (p * 64 + r + 8) * 8));
        s0 += a; q0 += b; s1 += c; q1 += d;
    }
    const float m0 = s0 * (1.0f / DM), m1 = s1 * (1.0f / DM);
    const float rs0 = rsqrtf(fmaxf(q0 * (1.0f / DM) - m0 * m0, 0.f) + LN_EPS), rs1 = rsqrtf(fmaxf(q1 * (1.0f / DM) - m1 * m1, 0.f) + LN_EPS);
    const float sc0 = 0.5f * rs0, sc1 = 0.5f * rs1, n0 = -m0 * sc0, n1 = -m1 * sc1;
#pragma unroll
    for (int b = 0; b < 8; b++) {
        xr[2 * b] = pack_bf16(fmaf(bf_lo(xr[2 * b]), sc0, n0), fmaf(bf_hi(xr[2 * b]), sc0, n0));
        xr[2 * b + 1] = pack_bf16(fmaf(bf_lo(xr[2 * b + 1]), sc1, n1), fmaf(bf_hi(xr[2 * b + 1]), sc1, n1));
    }
    stage_tile<8>(xr, sA + (3 + wg) * 8192, w, lane);
    proxy_fence();
    named_sync(2 + wg, 128);
    if (tid == 0) TS(2, 6);
    if (leader) {
        tma_st_2d(&tmX2, cg * 192 + wg * 64, m * 64, sA + (3 + wg) * 8192);
        bulk_commit();
        bulk_wait_all();
    }
    if (tid == 0) TS(2, 3);
}

constexpr int F_THREADS = 384;
constexpr int F_NST = 6;
constexpr int F_STAGE = 96 * 128;
constexpr int F_X_BYTES = 9 * 16384;
constexpr int F_OFF_ST = F_X_BYTES;
constexpr int F_OFF_BAR = F_OFF_ST + F_NST * F_STAGE;
constexpr int F_SMEM = F_OFF_BAR + 256;

__device__ __forceinline__ float tanh_hw(float x) { float y; asm("tanh.approx.f32 %0, %1;" : "=f"(y) : "f"(x)); return y; }
__host__ __device__ constexpr int piece_begin(int p) { return p == 0 ? 0 : 3 * p + 1; }
template <int P>
__device__ __forceinline__ void silu_s1(const float (&acc)[32], float (&tmp)[8]) {
#pragma unroll
    for (int i = 2 * piece_begin(P); i < 2 * piece_begin(P + 1); i++) tmp[i - 2 * piece_begin(P)] = tanh_hw(acc[i]);
}
template <int C, int P>
__device__ __forceinline__ void silu_s2(const float (&acc)[32], const float (&tmp)[8], uint32_t (&h1)[144]) {
#pragma unroll
    for (int i = piece_begin(P); i < piece_begin(P + 1); i++) {
        const int k = 2 * (i - piece_begin(P));
        h1[C * 16 + i] = pack_bf16(fmaf(acc[2 * i], tmp[k], acc[2 * i]), fmaf(acc[2 * i + 1], tmp[k + 1], acc[2 * i + 1]));
    }
}
template <int C, int J>
__device__ __forceinline__ void silu_slot(const float (&prev)[32], float (&tmp)[2][8], uint32_t (&h1)[144]) {
    if constexpr (J >= 1) silu_s2<C, J - 1>(prev, tmp[(J - 1) & 1], h1);
    if constexpr (J <= 4) { silu_s1<J>(prev, tmp[J & 1]); pin(tmp[J & 1]); }
}

struct FfnPipe {
    uint32_t full, empty;
    int lane;
    __device__ __forceinline__ void acquire(int s, uint32_t ph) const { mbar_wait(full + s * 8, ph); }
    __device__ __forceinline__ void release(int s) const { if (lane == 0) mbar_arrive(empty + s * 8); }
};

template <int C>
__device__ __forceinline__ void ffn_phase1_chunk(float (&cur)[32], float (&prev)[32], uint32_t (&h1)[144], const FfnPipe& pp, uint64_t dx, uint32_t fullX) {
    float tmp[2][8];
    const uint64_t dw = cdesc(F_OFF_ST, 8192, 1024, 1) + blockIdx.y * (C + 1);
    dx += blockIdx.y * C;
#pragma unroll
    for (int j = 0; j < 6; j++) {
        if (C == 0) { mbar_wait(fullX + ((6 * j) >> 2) * 8, 0); mbar_wait(fullX + ((6 * j + 5) >> 2) * 8, 0); }
        pp.acquire(j, C & 1);
        if (j == 0) pin(cur);
        wg_fence();
#pragma unroll
        for (int i = 0; i < 6; i++) {
            const int ks = 6 * j + i;
            wgmma_ss_n64<1>(cur, dx + ((ks >> 2) * 1024 + (ks & 3) * 2), dw + ((j * F_STAGE + i * 2048) >> 4), ks != 0);
        }
        wg_commit();
        if (C > 0 || j > 0) { wg_wait<1>(); pp.release((j + 5) % 6); }
        if (C > 0) {
            constexpr int CP = C > 0 ? C - 1 : 0;
            pin(prev);
            if (j == 0) silu_slot<CP, 0>(prev, tmp, h1);
            if (j == 1) silu_slot<CP, 1>(prev, tmp, h1);
            if (j == 2) silu_slot<CP, 2>(prev, tmp, h1);
            if (j == 3) silu_slot<CP, 3>(prev, tmp, h1);
            if (j == 4) silu_slot<CP, 4>(prev, tmp, h1);
            if (j == 5) silu_slot<CP, 5>(prev, tmp, h1);
        }
    }
}

__device__ __forceinline__ void ffn_stage_chunk(const float (&acc)[32], uint32_t stg, int w, int lane) {
    uint32_t pk[16];
#pragma unroll
    for (int i = 0; i < 16; i++) pk[i] = pack_bf16(acc[2 * i], acc[2 * i + 1]);
    stage_tile<8>(pk, stg, w, lane);
}
__device__ __forceinline__ void ffn_reduce_chunk(const CUtensorMap* tmOut, uint32_t stg, int col, int row, int w, int wgid, bool leader) {
    proxy_fence();
    if (w != 0) {
        asm volatile("bar.arrive %0, 128;" ::"r"(2 + wgid) : "memory");
    } else {
        named_sync(2 + wgid, 128);
        if (leader) { tma_red_2d(tmOut, col, row, stg); bulk_commit(); }
    }
}

__device__ __forceinline__ void ffn_phase2_chunk(float (&cur)[32], float (&prev)[32], uint32_t (&h1)[144], const FfnPipe& pp, uint32_t ph, bool store_prev, const CUtensorMap* tmOut, uint32_t stg_prev, int col_prev, int row, int w, int lane, int wgid, bool leader) {
    const uint64_t dw = cdesc(F_OFF_ST, 8192, 1024, 1) + blockIdx.y * col_prev;
#pragma unroll
    for (int j = 0; j < 6; j++) {
        pp.acquire(j, ph);
        if (j == 0) pin(cur);
        wg_fence();
#pragma unroll
        for (int i = 0; i < 6; i++) {
            const int f = (6 * j + i) * 4;
            wgmma_rs_n64<1>(cur, h1[f], h1[f + 1], h1[f + 2], h1[f + 3], dw + ((j * F_STAGE + i * 2048) >> 4), (j | i) != 0);
        }
        wg_commit();
        if (j > 0 || store_prev) { wg_wait<1>(); pp.release((j + 5) % 6); }
        if (j == 0 && store_prev) { pin(prev); ffn_stage_chunk(prev, stg_prev, w, lane); }
        if (j == 1 && store_prev) ffn_reduce_chunk(tmOut, stg_prev, col_prev, row, w, wgid, leader);
    }
}

__global__ void __launch_bounds__(F_THREADS, 1)
k_ffn(const __grid_constant__ CUtensorMap tmH, const __grid_constant__ CUtensorMap tmW1, const __grid_constant__ CUtensorMap tmW2, const __grid_constant__ CUtensorMap tmOut, const __nv_bfloat16* __restrict__ w2) {
    extern __shared__ __align__(1024) uint8_t smem[];
    const uint32_t sX = smem_u32(smem), sSt = sX + F_OFF_ST, bars = sX + F_OFF_BAR;
    const uint32_t full = bars, empty = bars + 64, fullX = bars + 128;
    const int tid = threadIdx.x, warp = __shfl_sync(~0u, tid >> 5, 0), lane = tid & 31;
#define FFN_MAP 1
    const int m = FFN_MAP == 0 ? (blockIdx.x & 15) : (FFN_MAP == 1 ? (blockIdx.x >> 3) : ((blockIdx.x >> 1) & 15));
    const int fs = FFN_MAP == 0 ? (blockIdx.x >> 4) : (FFN_MAP == 1 ? (blockIdx.x & 7) : ((blockIdx.x >> 5) * 2 + (blockIdx.x & 1)));
    if (tid == 0) TS(3, 0);
    check_smem_base(sX);
    if (tid == 0) {
        prefetch_map(&tmW1); prefetch_map(&tmH); prefetch_map(&tmW2); prefetch_map(&tmOut);
        for (int i = 0; i < F_NST; i++) { mbar_init(full + i * 8, 1); mbar_init(empty + i * 8, 8); }
        for (int i = 0; i < 9; i++) mbar_init(fullX + i * 8, 1);
        bar_init_fence();
        for (int kb = 0; kb < 9; kb++) mbar_expect(fullX + kb * 8, 16384);
    }
    __syncthreads();
    if (warp < 4) {
        asm volatile("setmaxnreg.dec.sync.aligned.u32 24;");
        if (warp == 1 && lane < 9) prefetch_l2(reinterpret_cast<const char*>(w2) + ((size_t)fs * 576 + m * 36 + lane * 4) * (DM * 2), 4 * DM * 2);
        if (warp == 0 && elect_one()) {
            int s = 0; uint32_t ph = 1;
            int c = 0, j = 0;
#pragma unroll 1
            for (int i = 0; i < 108; i++) {
                if (i == 54) c = fs;
                mbar_wait(empty + s * 8, ph);
                mbar_expect(full + s * 8, F_STAGE);
                if (i < 54) tma_2d(sSt + s * F_STAGE, &tmW1, fs * 576 + c * 64, j * 96, full + s * 8);
                else tma_2d(sSt + s * F_STAGE, &tmW2, c * 64, fs * 576 + j * 96, full + s * 8);
                if (++j == 6) { j = 0; if (++c == 9) c = 0; }
                if (++s == F_NST) { s = 0; ph ^= 1; }
            }
        }
    } else {
        asm volatile("setmaxnreg.inc.sync.aligned.u32 240;");
        const int wgid = (warp >> 2) - 1, w = warp & 3;
        pdl_wait();
        if (tid == 128) TS(3, 1);
        if (warp == 4 && elect_one()) {
            for (int kb = 0; kb < 9; kb++) tma_2d(sX + kb * 16384, &tmH, kb * 64, m * 128, fullX + kb * 8);
        }
        __syncwarp();
        FfnPipe pp{full, empty, lane};
        const uint64_t xlo = cdesc(0, 16, 1024, 1) + wgid * 512;
        uint32_t h1[144];
        float acc0[32], acc1[32];
        ffn_phase1_chunk<0>(acc0, acc1, h1, pp, xlo, fullX);
        if (tid == 128) TS(3, 2);
        ffn_phase1_chunk<1>(acc1, acc0, h1, pp, xlo, fullX);
        ffn_phase1_chunk<2>(acc0, acc1, h1, pp, xlo, fullX);
        ffn_phase1_chunk<3>(acc1, acc0, h1, pp, xlo, fullX);
        ffn_phase1_chunk<4>(acc0, acc1, h1, pp, xlo, fullX);
        ffn_phase1_chunk<5>(acc1, acc0, h1, pp, xlo, fullX);
        ffn_phase1_chunk<6>(acc0, acc1, h1, pp, xlo, fullX);
        ffn_phase1_chunk<7>(acc1, acc0, h1, pp, xlo, fullX);
        ffn_phase1_chunk<8>(acc0, acc1, h1, pp, xlo, fullX);
        wg_wait<0>();
        pp.release(5);
        pin(acc0);
#pragma unroll
        for (int i = 0; i < 16; i++) h1[128 + i] = pack_bf16(fmaf(acc0[2 * i], tanh_hw(acc0[2 * i]), acc0[2 * i]), fmaf(acc0[2 * i + 1], tanh_hw(acc0[2 * i + 1]), acc0[2 * i + 1]));
        pin(h1);
        if (tid == 128) TS(3, 3);
        const int row = m * 128 + wgid * 64;
        const uint32_t stg = sX + wgid * 8192;
        int c = fs, cprev = 0;
        const bool leader = w == 0 && elect_one();
#pragma unroll 1
        for (int j = 0; j < 8; j += 2) {
            ffn_phase2_chunk(acc1, acc0, h1, pp, 1, j > 0, &tmOut, stg + (j - 1) * 16384, cprev * 64, row, w, lane, wgid, leader);
            cprev = c; if (++c == 9) c = 0;
            ffn_phase2_chunk(acc0, acc1, h1, pp, 0, true, &tmOut, stg + j * 16384, cprev * 64, row, w, lane, wgid, leader);
            cprev = c; if (++c == 9) c = 0;
        }
        ffn_phase2_chunk(acc1, acc0, h1, pp, 1, true, &tmOut, stg + 7 * 16384, cprev * 64, row, w, lane, wgid, leader);
        wg_wait<0>();
        pin(acc1);
        ffn_stage_chunk(acc1, stg + 8 * 16384, w, lane);
        ffn_reduce_chunk(&tmOut, stg + 8 * 16384, c * 64, row, w, wgid, leader);
        if (tid == 128) TS(3, 4);
        if (leader) bulk_wait_all();
        if (tid == 128) TS(3, 5);
    }
}

typedef CUresult (*EncodeFn)(CUtensorMap*, CUtensorMapDataType, cuuint32_t, void*, const cuuint64_t*, const cuuint64_t*, const cuuint32_t*, const cuuint32_t*,
                             CUtensorMapInterleave, CUtensorMapSwizzle, CUtensorMapL2promotion, CUtensorMapFloatOOBfill);

CUtensorMap make_map(EncodeFn enc, const void* base, int rows, int cols, int box_rows) {
    CUtensorMap tm;
    cuuint64_t dims[2] = {(cuuint64_t)cols, (cuuint64_t)rows};
    cuuint64_t strides[1] = {(cuuint64_t)cols * 2};
    cuuint32_t box[2] = {64, (cuuint32_t)box_rows};
    cuuint32_t es[2] = {1, 1};
    enc(&tm, CU_TENSOR_MAP_DATA_TYPE_BFLOAT16, 2, const_cast<void*>(base), dims, strides, box, es, CU_TENSOR_MAP_INTERLEAVE_NONE,
        CU_TENSOR_MAP_SWIZZLE_128B, CU_TENSOR_MAP_L2_PROMOTION_L2_256B, CU_TENSOR_MAP_FLOAT_OOB_FILL_NONE);
    return tm;
}

template <typename... KArgs, typename... Args>
void launch(void (*kern)(KArgs...), int grid, int block, int smem, bool pdl, Args... args) {
    cudaLaunchConfig_t cfg = {};
    cfg.gridDim = dim3(grid); cfg.blockDim = dim3(block); cfg.dynamicSmemBytes = smem; cfg.stream = cudaStreamPerThread;
    cudaLaunchAttribute at[1];
    at[0].id = cudaLaunchAttributeProgrammaticStreamSerialization;
    at[0].val.programmaticStreamSerializationAllowed = 1;
    cfg.attrs = at; cfg.numAttrs = pdl ? 1 : 0;
    cudaLaunchKernelEx(&cfg, kern, KArgs(args)...);
}

}

#define USE_PDL 1

extern "C" void kernel_launch(void* const* d_in, const int* in_sizes, int n_in, void* d_out, int out_size) {
    const __nv_bfloat16* x = (const __nv_bfloat16*)d_in[0];
    const __nv_bfloat16* wq = (const __nv_bfloat16*)d_in[1];
    const __nv_bfloat16* wk = (const __nv_bfloat16*)d_in[2];
    const __nv_bfloat16* wv = (const __nv_bfloat16*)d_in[3];
    const __nv_bfloat16* wo = (const __nv_bfloat16*)d_in[4];
    const __nv_bfloat16* w1 = (const __nv_bfloat16*)d_in[6];
    const __nv_bfloat16* w2 = (const __nv_bfloat16*)d_in[7];
    __nv_bfloat16* out = (__nv_bfloat16*)d_out;

    static EncodeFn enc = nullptr;
    static void *p_o = nullptr, *p_h = nullptr, *p_q = nullptr;
    if (!enc) {
        cudaDriverEntryPointQueryResult qr;
        cudaGetDriverEntryPoint("cuTensorMapEncodeTiled", (void**)&enc, cudaEnableDefault, &qr);
        cudaGetSymbolAddress(&p_o, g_o);
        cudaGetSymbolAddress(&p_h, g_x2);
        cudaGetSymbolAddress(&p_q, g_q);
        cudaFuncSetAttribute(k_qkv, cudaFuncAttributeMaxDynamicSharedMemorySize, P_SMEM);
        cudaFuncSetAttribute(k_attn, cudaFuncAttributeMaxDynamicSharedMemorySize, A_SMEM);
        cudaFuncSetAttribute(k_oproj, cudaFuncAttributeMaxDynamicSharedMemorySize, O_SMEM);
        cudaFuncSetAttribute(k_ffn, cudaFuncAttributeMaxDynamicSharedMemorySize, F_SMEM);
    }
    const CUtensorMap tmWq = make_map(enc, wq, DM, DM, 64);
    const CUtensorMap tmWo = make_map(enc, wo, DM, DM, 64);
    const CUtensorMap tmO = make_map(enc, p_o, SEQ, DM, 64);
    const CUtensorMap tmH64 = make_map(enc, p_h, SEQ, DM, 64);
    const CUtensorMap tmH = make_map(enc, p_h, SEQ, DM, 128);
    const CUtensorMap tmQ = make_map(enc, p_q, SEQ, DM, 64);
    const CUtensorMap tmW1 = make_map(enc, w1, DM, FF, 96);
    const CUtensorMap tmW2 = make_map(enc, w2, FF, DM, 96);
    const CUtensorMap tmOut = make_map(enc, out, SEQ, DM, 64);

    launch(k_qkv, 128, Q_THREADS, P_SMEM, false, tmWq, tmQ, x, wk, wv);
    launch(k_attn, 128, A_THREADS, A_SMEM, USE_PDL);
    launch(k_oproj, 96, O_THREADS, O_SMEM, USE_PDL, tmO, tmWo, tmH64, tmOut, x, w1);
    launch(k_ffn, 128, F_THREADS, F_SMEM, USE_PDL, tmH, tmW1, tmW2, tmOut, w2);
}
```

```cpp
#include <cuda_runtime.h>
#include <cuda_bf16.h>
#include <cuda.h>
#include <stdint.h>

namespace {

constexpr int SEQ = 2048, DM = 576, FF = 4608;
constexpr int KV_BYTES = SEQ * 48;
constexpr float LN_EPS = 1e-5f;
constexpr float LOG2E = 1.4426950408889634f;
constexpr float Q_SCALE = 0.23570226039551584f * LOG2E;

#define POLY_MASK_V 0xDB6Du
constexpr uint32_t POLY_MASK = POLY_MASK_V;
constexpr float FAST_BOUND = 60.0f;

__device__ __align__(1024) __nv_bfloat16 g_q[SEQ * DM];
__device__ __align__(1024) uint4 g_kc[KV_BYTES / 16];
__device__ __align__(1024) uint4 g_vc[KV_BYTES / 16];
__device__ __align__(16) float g_kmax[256];
__device__ __align__(1024) __nv_bfloat16 g_o[SEQ * DM];
__device__ __align__(1024) __nv_bfloat16 g_x2[SEQ * DM];

#define TS(k, i)

__device__ __forceinline__ uint32_t smem_u32(const void* p) { return (uint32_t)__cvta_generic_to_shared(p); }
__device__ __forceinline__ void wg_fence() { asm volatile("wgmma.fence.sync.aligned;" ::: "memory"); }
__device__ __forceinline__ void wg_commit() { asm volatile("wgmma.commit_group.sync.aligned;" ::: "memory"); }
template <int N> __device__ __forceinline__ void wg_wait() { asm volatile("wgmma.wait_group.sync.aligned %0;" ::"n"(N) : "memory"); }
template <int N> __device__ __forceinline__ void pin(float (&r)[N]) {
#pragma unroll
    for (int i = 0; i < N; i++) asm volatile("" : "+f"(r[i])::"memory");
}
template <int N> __device__ __forceinline__ void pin(uint32_t (&r)[N]) {
#pragma unroll
    for (int i = 0; i < N; i++) asm volatile("" : "+r"(r[i])::"memory");
}
constexpr uint32_t SMEM0 = 0x400;
__host__ __device__ constexpr uint64_t cdesc(uint32_t off, uint32_t lbo, uint32_t sbo, uint32_t swz) {
    return (uint64_t)(((SMEM0 + off) & 0x3FFFF) >> 4) | ((uint64_t)(lbo >> 4) << 16) | ((uint64_t)(sbo >> 4) << 32) | ((uint64_t)swz << 62);
}
__device__ __forceinline__ void check_smem_base(uint32_t base) { if ((base & 0x3FFFF) != SMEM0) __trap(); }

__device__ __forceinline__ void mbar_init(uint32_t bar, int cnt) { asm volatile("mbarrier.init.shared::cta.b64 [%0], %1;" ::"r"(bar), "r"(cnt) : "memory"); }
__device__ __forceinline__ void mbar_expect(uint32_t bar, int bytes) { asm volatile("mbarrier.arrive.expect_tx.shared::cta.b64 _, [%0], %1;" ::"r"(bar), "r"(bytes) : "memory"); }
__device__ __forceinline__ void mbar_arrive(uint32_t bar) { asm volatile("mbarrier.arrive.shared::cta.b64 _, [%0];" ::"r"(bar) : "memory"); }
__device__ __forceinline__ void mbar_wait(uint32_t bar, uint32_t parity) {
    asm volatile(
        "{\n.reg .pred p;\n.reg .u32 n;\nmov.u32 n, 0;\n"
        "LAB_WAIT:\n"
        "mbarrier.try_wait.parity.shared::cta.b64 p, [%0], %1;\n"
        "@p bra DONE;\n"
        "add.u32 n, n, 1;\n"
        "setp.lt.u32 p, n, 4000000;\n"
        "@p bra LAB_WAIT;\n"
        "trap;\n"
        "DONE:\n}\n" ::"r"(bar), "r"(parity) : "memory");
}
__device__ __forceinline__ void bar_init_fence() {
    asm volatile("fence.mbarrier_init.release.cluster;" ::: "memory");
    asm volatile("fence.proxy.async.shared::cta;" ::: "memory");
}
__device__ __forceinline__ void proxy_fence() { asm volatile("fence.proxy.async.shared::cta;" ::: "memory"); }
__device__ __forceinline__ void named_sync(int id, int n) { asm volatile("bar.sync %0, %1;" ::"r"(id), "r"(n) : "memory"); }
__device__ __forceinline__ void bulk_g2s(uint32_t dst, const void* src, int bytes, uint32_t bar) {
    asm volatile("cp.async.bulk.shared::cluster.global.mbarrier::complete_tx::bytes [%0], [%1], %2, [%3];" ::"r"(dst), "l"(src), "r"(bytes), "r"(bar) : "memory");
}
__device__ __forceinline__ void tma_2d(uint32_t dst, const CUtensorMap* tm, int c0, int c1, uint32_t bar) {
    asm volatile("cp.async.bulk.tensor.2d.shared::cluster.global.mbarrier::complete_tx::bytes [%0], [%1, {%3, %4}], [%2];" ::"r"(dst), "l"(tm), "r"(bar), "r"(c0), "r"(c1) : "memory");
}
__device__ __forceinline__ void cluster_arrive() { asm volatile("barrier.cluster.arrive.release.aligned;" ::: "memory"); }
__device__ __forceinline__ void cluster_wait() { asm volatile("barrier.cluster.wait.acquire.aligned;" ::: "memory"); }
__device__ __forceinline__ void tma_red_2d(const CUtensorMap* tm, int c0, int c1, uint32_t src) {
    asm volatile("cp.reduce.async.bulk.tensor.2d.global.shared::cta.add.tile.bulk_group [%0, {%2, %3}], [%1];" ::"l"(tm), "r"(src), "r"(c0), "r"(c1) : "memory");
}
__device__ __forceinline__ void tma_st_2d(const CUtensorMap* tm, int c0, int c1, uint32_t src) {
    asm volatile("cp.async.bulk.tensor.2d.global.shared::cta.tile.bulk_group [%0, {%2, %3}], [%1];" ::"l"(tm), "r"(src), "r"(c0), "r"(c1) : "memory");
}
__device__ __forceinline__ void bulk_commit() { asm volatile("cp.async.bulk.commit_group;" ::: "memory"); }
__device__ __forceinline__ void bulk_wait_all() { asm volatile("cp.async.bulk.wait_group.read 0;" ::: "memory"); }
__device__ __forceinline__ bool elect_one() {
    uint32_t p;
    asm volatile("{\n.reg .pred P;\nelect.sync _|P, 0xffffffff;\nselp.b32 %0, 1, 0, P;\n}\n" : "=r"(p));
    return p != 0;
}
__device__ __forceinline__ void prefetch_l2(const void* p, int bytes) { asm volatile("cp.async.bulk.prefetch.L2.global [%0], %1;" ::"l"(p), "r"(bytes) : "memory"); }
__device__ __forceinline__ void prefetch_map(const CUtensorMap* tm) { asm volatile("prefetch.tensormap [%0];" ::"l"(tm) : "memory"); }
__device__ __forceinline__ void pdl_launch() { asm volatile("griddepcontrol.launch_dependents;" ::: "memory"); }
__device__ __forceinline__ void pdl_wait() { asm volatile("griddepcontrol.wait;" ::: "memory"); }
__device__ __forceinline__ float ex2(float x) { float y; asm("ex2.approx.ftz.f32 %0, %1;" : "=f"(y) : "f"(x)); return y; }
__device__ __forceinline__ uint32_t pack_bf16(float lo, float hi) { uint32_t r; asm("cvt.rn.bf16x2.f32 %0, %1, %2;" : "=r"(r) : "f"(hi), "f"(lo)); return r; }
__device__ __forceinline__ float bf_lo(uint32_t v) { return __uint_as_float(v << 16); }
__device__ __forceinline__ float bf_hi(uint32_t v) { return __uint_as_float(v & 0xFFFF0000u); }
__device__ __forceinline__ uint32_t hfma2(uint32_t a, uint32_t b, uint32_t c) { uint32_t r; asm("fma.rn.f16x2 %0, %1, %2, %3;" : "=r"(r) : "r"(a), "r"(b), "r"(c)); return r; }
__device__ __forceinline__ void stmatrix_x4(uint32_t addr, uint32_t r0, uint32_t r1, uint32_t r2, uint32_t r3) {
    asm volatile("stmatrix.sync.aligned.m8n8.x4.shared.b16 [%0], {%1, %2, %3, %4};" ::"r"(addr), "r"(r0), "r"(r1), "r"(r2), "r"(r3) : "memory");
}

template <int TB> __device__ __forceinline__ void wgmma_ss_n24(float (&d)[12], uint64_t da, uint64_t db, int sc) {
    asm volatile("{\n.reg .pred p;\nsetp.ne.b32 p, %14, 0;\n"
        "wgmma.mma_async.sync.aligned.m64n24k16.f32.bf16.bf16 {%0, %1, %2, %3, %4, %5, %6, %7, %8, %9, %10, %11}, %12, %13, p, 1, 1, 0, %15;\n}\n"
        : "+f"(d[0]), "+f"(d[1]), "+f"(d[2]), "+f"(d[3]), "+f"(d[4]), "+f"(d[5]), "+f"(d[6]), "+f"(d[7]), "+f"(d[8]), "+f"(d[9]), "+f"(d[10]), "+f"(d[11])
        : "l"(da), "l"(db), "r"(sc), "n"(TB));
}
template <int TB> __device__ __forceinline__ void wgmma_ss_n64(float (&d)[32], uint64_t da, uint64_t db, int sc) {
    asm volatile("{\n.reg .pred p;\nsetp.ne.b32 p, %34, 0;\n"
        "wgmma.mma_async.sync.aligned.m64n64k16.f32.bf16.bf16 {%0, %1, %2, %3, %4, %5, %6, %7, %8, %9, %10, %11, %12, %13, %14, %15, %16, %17, %18, %19, %20, %21, %22, %23, %24, %25, %26, %27, %28, %29, %30, %31}, %32, %33, p, 1, 1, 0, %35;\n}\n"
        : "+f"(d[0]), "+f"(d[1]), "+f"(d[2]), "+f"(d[3]), "+f"(d[4]), "+f"(d[5]), "+f"(d[6]), "+f"(d[7]), "+f"(d[8]), "+f"(d[9]), "+f"(d[10]), "+f"(d[11]), "+f"(d[12]), "+f"(d[13]), "+f"(d[14]), "+f"(d[15]), "+f"(d[16]), "+f"(d[17]), "+f"(d[18]), "+f"(d[19]), "+f"(d[20]), "+f"(d[21]), "+f"(d[22]), "+f"(d[23]), "+f"(d[24]), "+f"(d[25]), "+f"(d[26]), "+f"(d[27]), "+f"(d[28]), "+f"(d[29]), "+f"(d[30]), "+f"(d[31])
        : "l"(da), "l"(db), "r"(sc), "n"(TB));
}
template <int TB> __device__ __forceinline__ void wgmma_ss_n128(float (&d)[64], uint64_t da, uint64_t db, int sc) {
    asm volatile("{\n.reg .pred p;\nsetp.ne.b32 p, %66, 0;\n"
        "wgmma.mma_async.sync.aligned.m64n128k16.f32.bf16.bf16 {%0, %1, %2, %3, %4, %5, %6, %7, %8, %9, %10, %11, %12, %13, %14, %15, %16, %17, %18, %19, %20, %21, %22, %23, %24, %25, %26, %27, %28, %29, %30, %31, %32, %33, %34, %35, %36, %37, %38, %39, %40, %41, %42, %43, %44, %45, %46, %47, %48, %49, %50, %51, %52, %53, %54, %55, %56, %57, %58, %59, %60, %61, %62, %63}, %64, %65, p, 1, 1, 0, %67;\n}\n"
        : "+f"(d[0]), "+f"(d[1]), "+f"(d[2]), "+f"(d[3]), "+f"(d[4]), "+f"(d[5]), "+f"(d[6]), "+f"(d[7]), "+f"(d[8]), "+f"(d[9]), "+f"(d[10]), "+f"(d[11]), "+f"(d[12]), "+f"(d[13]), "+f"(d[14]), "+f"(d[15]), "+f"(d[16]), "+f"(d[17]), "+f"(d[18]), "+f"(d[19]), "+f"(d[20]), "+f"(d[21]), "+f"(d[22]), "+f"(d[23]), "+f"(d[24]), "+f"(d[25]), "+f"(d[26]), "+f"(d[27]), "+f"(d[28]), "+f"(d[29]), "+f"(d[30]), "+f"(d[31]), "+f"(d[32]), "+f"(d[33]), "+f"(d[34]), "+f"(d[35]), "+f"(d[36]), "+f"(d[37]), "+f"(d[38]), "+f"(d[39]), "+f"(d[40]), "+f"(d[41]), "+f"(d[42]), "+f"(d[43]), "+f"(d[44]), "+f"(d[45]), "+f"(d[46]), "+f"(d[47]), "+f"(d[48]), "+f"(d[49]), "+f"(d[50]), "+f"(d[51]), "+f"(d[52]), "+f"(d[53]), "+f"(d[54]), "+f"(d[55]), "+f"(d[56]), "+f"(d[57]), "+f"(d[58]), "+f"(d[59]), "+f"(d[60]), "+f"(d[61]), "+f"(d[62]), "+f"(d[63])
        : "l"(da), "l"(db), "r"(sc), "n"(TB));
}
template <int TB> __device__ __forceinline__ void wgmma_rs_n24(float (&d)[12], uint32_t a0, uint32_t a1, uint32_t a2, uint32_t a3, uint64_t db, int sc) {
    asm volatile("{\n.reg .pred p;\nsetp.ne.b32 p, %17, 0;\n"
        "wgmma.mma_async.sync.aligned.m64n24k16.f32.bf16.bf16 {%0, %1, %2, %3, %4, %5, %6, %7, %8, %9, %10, %11}, {%12, %13, %14, %15}, %16, p, 1, 1, %18;\n}\n"
        : "+f"(d[0]), "+f"(d[1]), "+f"(d[2]), "+f"(d[3]), "+f"(d[4]), "+f"(d[5]), "+f"(d[6]), "+f"(d[7]), "+f"(d[8]), "+f"(d[9]), "+f"(d[10]), "+f"(d[11])
        : "r"(a0), "r"(a1), "r"(a2), "r"(a3), "l"(db), "r"(sc), "n"(TB));
}
template <int TB> __device__ __forceinline__ void wgmma_rs_n64(float (&d)[32], uint32_t a0, uint32_t a1, uint32_t a2, uint32_t a3, uint64_t db, int sc) {
    asm volatile("{\n.reg .pred p;\nsetp.ne.b32 p, %37, 0;\n"
        "wgmma.mma_async.sync.aligned.m64n64k16.f32.bf16.bf16 {%0, %1, %2, %3, %4, %5, %6, %7, %8, %9, %10, %11, %12, %13, %14, %15, %16, %17, %18, %19, %20, %21, %22, %23, %24, %25, %26, %27, %28, %29, %30, %31}, {%32, %33, %34, %35}, %36, p, 1, 1, %38;\n}\n"
        : "+f"(d[0]), "+f"(d[1]), "+f"(d[2]), "+f"(d[3]), "+f"(d[4]), "+f"(d[5]), "+f"(d[6]), "+f"(d[7]), "+f"(d[8]), "+f"(d[9]), "+f"(d[10]), "+f"(d[11]), "+f"(d[12]), "+f"(d[13]), "+f"(d[14]), "+f"(d[15]), "+f"(d[16]), "+f"(d[17]), "+f"(d[18]), "+f"(d[19]), "+f"(d[20]), "+f"(d[21]), "+f"(d[22]), "+f"(d[23]), "+f"(d[24]), "+f"(d[25]), "+f"(d[26]), "+f"(d[27]), "+f"(d[28]), "+f"(d[29]), "+f"(d[30]), "+f"(d[31])
        : "r"(a0), "r"(a1), "r"(a2), "r"(a3), "l"(db), "r"(sc), "n"(TB));
}
template <int TB> __device__ __forceinline__ void wgmma_rs_n128(float (&d)[64], uint32_t a0, uint32_t a1, uint32_t a2, uint32_t a3, uint64_t db, int sc) {
    asm volatile("{\n.reg .pred p;\nsetp.ne.b32 p, %69, 0;\n"
        "wgmma.mma_async.sync.aligned.m64n128k16.f32.bf16.bf16 {%0, %1, %2, %3, %4, %5, %6, %7, %8, %9, %10, %11, %12, %13, %14, %15, %16, %17, %18, %19, %20, %21, %22, %23, %24, %25, %26, %27, %28, %29, %30, %31, %32, %33, %34, %35, %36, %37, %38, %39, %40, %41, %42, %43, %44, %45, %46, %47, %48, %49, %50, %51, %52, %53, %54, %55, %56, %57, %58, %59, %60, %61, %62, %63}, {%64, %65, %66, %67}, %68, p, 1, 1, %70;\n}\n"
        : "+f"(d[0]), "+f"(d[1]), "+f"(d[2]), "+f"(d[3]), "+f"(d[4]), "+f"(d[5]), "+f"(d[6]), "+f"(d[7]), "+f"(d[8]), "+f"(d[9]), "+f"(d[10]), "+f"(d[11]), "+f"(d[12]), "+f"(d[13]), "+f"(d[14]), "+f"(d[15]), "+f"(d[16]), "+f"(d[17]), "+f"(d[18]), "+f"(d[19]), "+f"(d[20]), "+f"(d[21]), "+f"(d[22]), "+f"(d[23]), "+f"(d[24]), "+f"(d[25]), "+f"(d[26]), "+f"(d[27]), "+f"(d[28]), "+f"(d[29]), "+f"(d[30]), "+f"(d[31]), "+f"(d[32]), "+f"(d[33]), "+f"(d[34]), "+f"(d[35]), "+f"(d[36]), "+f"(d[37]), "+f"(d[38]), "+f"(d[39]), "+f"(d[40]), "+f"(d[41]), "+f"(d[42]), "+f"(d[43]), "+f"(d[44]), "+f"(d[45]), "+f"(d[46]), "+f"(d[47]), "+f"(d[48]), "+f"(d[49]), "+f"(d[50]), "+f"(d[51]), "+f"(d[52]), "+f"(d[53]), "+f"(d[54]), "+f"(d[55]), "+f"(d[56]), "+f"(d[57]), "+f"(d[58]), "+f"(d[59]), "+f"(d[60]), "+f"(d[61]), "+f"(d[62]), "+f"(d[63])
        : "r"(a0), "r"(a1), "r"(a2), "r"(a3), "l"(db), "r"(sc), "n"(TB));
}

constexpr int P_NST = 6;
constexpr int P_A_BYTES = 9 * 8192;
constexpr int P_B_STAGE = 3 * 8192;
constexpr int P_SMEM = P_A_BYTES + P_NST * P_B_STAGE + 256 + 320;

template <int NB>
__device__ __forceinline__ void stage_tile(const uint32_t (&pk)[NB * 2], uint32_t base, int w, int lane) {
    const int r = w * 16 + (lane & 7) + ((lane >> 3) & 1) * 8;
#pragma unroll
    for (int b = 0; b < NB; b += 2) {
        const uint32_t a = base + (b >> 3) * 8192 + r * 128 + ((((b & 7) + (lane >> 4)) ^ (r & 7)) << 4);
        stmatrix_x4(a, pk[2 * b], pk[2 * b + 1], pk[2 * b + 2], pk[2 * b + 3]);
    }
}

__device__ __forceinline__ uint32_t hsub2_bf16(uint32_t a, uint32_t b) { uint32_t r; asm("sub.rn.bf16x2 %0, %1, %2;" : "=r"(r) : "r"(a), "r"(b)); return r; }

constexpr int KV_RAW = DM * 18 * 2;
constexpr int Q_THREADS = 416;

__device__ __forceinline__ void proj_mma(float (&acc)[32], int wg, uint32_t fullB, uint32_t emptyB, uint32_t fullA, bool wait_a, int lane) {
    const uint64_t dA = cdesc(0, 16, 1024, 1), dB = cdesc(P_A_BYTES, 8192, 1024, 1) + wg * 512;
#pragma unroll 1
    for (int kb = 0; kb < 9; kb++) {
        const int s = kb >= P_NST ? kb - P_NST : kb;
        if (wait_a) mbar_wait(fullA + kb * 8, 0);
        mbar_wait(fullB + s * 8, kb >= P_NST ? 1 : 0);
        wg_fence();
#pragma unroll
        for (int ks = 0; ks < 4; ks++) wgmma_ss_n64<1>(acc, dA + (kb * 512 + ks * 2), dB + (s * (P_B_STAGE >> 4) + ks * 128), (kb | ks) != 0);
        wg_commit();
        if (kb < 4) {
            wg_wait<1>();
            if (kb >= 1 && lane == 0) mbar_arrive(emptyB + (kb - 1) * 8);
        }
    }
    wg_wait<0>();
    pin(acc);
}

__global__ void __launch_bounds__(Q_THREADS, 1)
k_qkv(const __grid_constant__ CUtensorMap tmWq, const __grid_constant__ CUtensorMap tmQ, const __nv_bfloat16* __restrict__ x, const __nv_bfloat16* __restrict__ wk, const __nv_bfloat16* __restrict__ wv) {
    extern __shared__ __align__(1024) uint8_t smem[];
    const uint32_t sA = smem_u32(smem), sB = sA + P_A_BYTES, bars = sB + P_NST * P_B_STAGE;
    const uint32_t fullB = bars, emptyB = bars + 64, fullX = bars + 128, fullW = bars + 136;
    float* s_rstd = reinterpret_cast<float*>(smem + P_A_BYTES + P_NST * P_B_STAGE + 256);
    const int tid = threadIdx.x, warp = __shfl_sync(~0u, tid >> 5, 0), lane = tid & 31;
    const bool isQ = blockIdx.x < 96;
    const int m = isQ ? blockIdx.x / 3 : blockIdx.x - 96, cg = blockIdx.x % 3;
    if (tid == 0) TS(0, 0);
    if (warp == 12) {
        if (elect_one()) {
            mbar_init(fullX, 1);
            bar_init_fence();
            mbar_expect(fullX, P_A_BYTES);
            bulk_g2s(sA, x + (size_t)m * 64 * DM, P_A_BYTES, fullX);
            prefetch_map(&tmWq); prefetch_map(&tmQ);
            for (int i = 0; i < P_NST; i++) { mbar_init(fullB + i * 8, 1); mbar_init(emptyB + i * 8, 12); }
            mbar_init(fullW, 1);
            bar_init_fence();
            if (isQ) {
                for (int kb = 0; kb < P_NST; kb++) {
                    mbar_expect(fullB + kb * 8, P_B_STAGE);
                    for (int a = 0; a < 3; a++) tma_2d(sB + kb * P_B_STAGE + a * 8192, &tmWq, cg * 192 + a * 64, kb * 64, fullB + kb * 8);
                }
            } else {
                mbar_expect(fullW, 2 * KV_RAW);
                bulk_g2s(sB + 3 * P_B_STAGE, wk, KV_RAW, fullW);
                bulk_g2s(sB + 3 * P_B_STAGE + KV_RAW, wv, KV_RAW, fullW);
            }
        }
        __syncwarp();
    }
    check_smem_base(sA);
    __syncthreads();
    pdl_launch();
    if (warp == 12) {
        if (isQ && elect_one()) {
            for (int kb = P_NST; kb < 9; kb++) {
                const int s = kb - P_NST;
                mbar_wait(emptyB + s * 8, 0);
                mbar_expect(fullB + s * 8, P_B_STAGE);
                for (int a = 0; a < 3; a++) tma_2d(sB + s * P_B_STAGE + a * 8192, &tmWq, cg * 192 + a * 64, kb * 64, fullB + s * 8);
            }
        }
        return;
    }
    if (warp < 8) {
        const int row = tid >> 2, q = tid & 3, h0 = (row & 1) * 4;
        mbar_wait(fullX, 0);
        if (tid == 0) TS(0, 6);
        uint4 v[18];
        const uint32_t ra = sA + row * 1152 + (q + h0) * 16, rb = sA + row * 1152 + (q + 4 - h0) * 16;
#pragma unroll
        for (int kb = 0; kb < 9; kb++) {
            asm volatile("ld.shared.v4.b32 {%0, %1, %2, %3}, [%4];" : "=r"(v[2 * kb].x), "=r"(v[2 * kb].y), "=r"(v[2 * kb].z), "=r"(v[2 * kb].w) : "r"(ra + kb * 128));
            asm volatile("ld.shared.v4.b32 {%0, %1, %2, %3}, [%4];" : "=r"(v[2 * kb + 1].x), "=r"(v[2 * kb + 1].y), "=r"(v[2 * kb + 1].z), "=r"(v[2 * kb + 1].w) : "r"(rb + kb * 128));
        }
        float sum = 0.f, sum2 = 0.f, sq = 0.f, sq2 = 0.f;
#pragma unroll
        for (int i = 0; i < 18; i++) {
            const uint32_t w[4] = {v[i].x, v[i].y, v[i].z, v[i].w};
#pragma unroll
            for (int j = 0; j < 4; j++) { const float a = bf_lo(w[j]), b = bf_hi(w[j]); sum += a; sum2 += b; sq = fmaf(a, a, sq); sq2 = fmaf(b, b, sq2); }
        }
        named_sync(1, 256);
        sum += sum2; sq += sq2;
        sum += __shfl_xor_sync(~0u, sum, 1); sum += __shfl_xor_sync(~0u, sum, 2);
        sq += __shfl_xor_sync(~0u, sq, 1); sq += __shfl_xor_sync(~0u, sq, 2);
        if (tid == 0) TS(0, 4);
        const float mean = sum * (1.0f / DM);
        if (q == 0) s_rstd[row] = rsqrtf(fmaxf(sq * (1.0f / DM) - mean * mean, 0.f) + LN_EPS);
        const uint32_t mhi = pack_bf16(mean, mean);
        const float rem = mean - bf_lo(mhi);
        const uint32_t mlo = pack_bf16(rem, rem);
        const uint32_t wa = sA + row * 128 + (((q + h0) ^ (row & 7)) << 4), wb = sA + row * 128 + (((q + 4 - h0) ^ (row & 7)) << 4);
#pragma unroll
        for (int i = 0; i < 18; i++) {
            const uint32_t o0 = hsub2_bf16(hsub2_bf16(v[i].x, mhi), mlo), o1 = hsub2_bf16(hsub2_bf16(v[i].y, mhi), mlo);
            const uint32_t o2 = hsub2_bf16(hsub2_bf16(v[i].z, mhi), mlo), o3 = hsub2_bf16(hsub2_bf16(v[i].w, mhi), mlo);
            asm volatile("st.shared.v4.b32 [%0], {%1, %2, %3, %4};" ::"r"(((i & 1) ? wb : wa) + (i >> 1) * 8192), "r"(o0), "r"(o1), "r"(o2), "r"(o3) : "memory");
        }
    } else if (!isQ) {
        mbar_wait(fullW, 0);
        const uint32_t* raw = reinterpret_cast<const uint32_t*>(smem + P_A_BYTES + 3 * P_B_STAGE);
#pragma unroll 3
        for (int r = tid - 256; r < 2 * DM; r += 128) {
            uint32_t wr[9];
#pragma unroll
            for (int i = 0; i < 9; i++) wr[i] = raw[r * 9 + i];
            const int sel = r >= DM, k = r - sel * DM;
            uint8_t* dst = smem + P_A_BYTES + sel * 3 * 9216 + (k >> 3) * 128 + (k & 7) * 16;
            *reinterpret_cast<uint4*>(dst) = make_uint4(wr[0], wr[1], wr[2], wr[3]);
            *reinterpret_cast<uint4*>(dst + 9216) = make_uint4(wr[4], wr[5], wr[6], wr[7]);
            *reinterpret_cast<uint32_t*>(dst + 2 * 9216) = wr[8];
        }
    }
    proxy_fence();
    named_sync(2, 384);
    if (tid == 0) TS(0, 1);
    const int wg = warp >> 2, w = warp & 3, g = lane >> 2, t = lane & 3;
    const float rs0 = s_rstd[w * 16 + g], rs1 = s_rstd[w * 16 + g + 8];
    if (isQ) {
        const float c0 = rs0 * Q_SCALE, c1 = rs1 * Q_SCALE;
        float acc[32];
        proj_mma(acc, wg, fullB, emptyB, 0, false, lane);
        if (tid == 0) TS(0, 2);
        uint32_t pk[16];
#pragma unroll
        for (int i = 0; i < 8; i++) { pk[2 * i] = pack_bf16(acc[4 * i] * c0, acc[4 * i + 1] * c0); pk[2 * i + 1] = pack_bf16(acc[4 * i + 2] * c1, acc[4 * i + 3] * c1); }
        named_sync(2, 384);
        stage_tile<8>(pk, sA + wg * 8192, w, lane);
        proxy_fence();
        named_sync(3 + wg, 128);
        if (w == 0 && elect_one()) {
            tma_st_2d(&tmQ, cg * 192 + wg * 64, m * 64, sA + wg * 8192);
            bulk_commit();
            bulk_wait_all();
        }
    } else if (wg < 2) {
        float acc[12];
        const uint64_t dA = cdesc(0, 16, 1024, 1), dB = cdesc(P_A_BYTES, 128, 9216, 0) + wg * (3 * 9216 >> 4);
#pragma unroll
        for (int i = 0; i < 12; i++) acc[i] = 0.f;
        pin(acc);
        wg_fence();
#pragma unroll 1
        for (int kb = 0; kb < 9; kb++) {
#pragma unroll
            for (int ks = 0; ks < 4; ks++) wgmma_ss_n24<1>(acc, dA + (kb * 512 + ks * 2), dB + (kb * 4 + ks) * 16, 1);
        }
        wg_commit();
        wg_wait<0>();
        pin(acc);
        uint32_t pk[6];
#pragma unroll
        for (int b = 0; b < 3; b++) { pk[2 * b] = pack_bf16(acc[4 * b] * rs0, acc[4 * b + 1] * rs0); pk[2 * b + 1] = pack_bf16(acc[4 * b + 2] * rs1, acc[4 * b + 3] * rs1); }
        float n0 = 0.f, n1 = 0.f, vm = 0.f;
#pragma unroll
        for (int b = 0; b < 3; b++) {
            if (b < 2 || t == 0) {
                const float a = bf_lo(pk[2 * b]), c = bf_hi(pk[2 * b]), d = bf_lo(pk[2 * b + 1]), e = bf_hi(pk[2 * b + 1]);
                n0 = fmaf(a, a, fmaf(c, c, n0)); n1 = fmaf(d, d, fmaf(e, e, n1));
            }
        }
        n0 += __shfl_xor_sync(~0u, n0, 1); n0 += __shfl_xor_sync(~0u, n0, 2);
        n1 += __shfl_xor_sync(~0u, n1, 1); n1 += __shfl_xor_sync(~0u, n1, 2);
        vm = fmaxf(n0, n1);
        if (!(n0 == n0) || !(n1 == n1)) vm = __int_as_float(0x7F800000);
#pragma unroll
        for (int o = 4; o < 32; o <<= 1) vm = fmaxf(vm, __shfl_xor_sync(~0u, vm, o));
        if (t != 0) {
            uint32_t lo, hi;
            if (wg == 0) {
                const int grp = m * 8 + w * 2;
                const uint32_t c = t == 1 ? 0x42FE3F80u   : (t == 2 ? 0x00003BC0u   : 0u);
                lo = ((POLY_MASK >> (grp & 15)) & 1) ? c : 0u;
                hi = ((POLY_MASK >> ((grp + 1) & 15)) & 1) ? c : 0u;
            } else {
                lo = hi = t == 1 ? 0x00003F80u : 0u;
            }
            pk[4] = lo; pk[5] = hi;
        }
        uint32_t* dst = reinterpret_cast<uint32_t*>(wg == 0 ? g_kc : g_vc) + (m * 8 + w * 2) * 96 + g * 4 + t;
#pragma unroll
        for (int b = 0; b < 3; b++) { dst[b * 32] = pk[2 * b]; dst[96 + b * 32] = pk[2 * b + 1]; }
        if (lane == 0) g_kmax[m * 8 + warp] = (wg == 0) ? vm : (vm <= 1e24f ? 0.f : __int_as_float(0x7F800000));
    }
    if (tid == 0) TS(0, 3);
}

constexpr int A_THREADS = 512;
constexpr int A_NPIECE = 8;
constexpr int A_OFF_Q = 2 * KV_BYTES;
constexpr int A_OFF_BAR = A_OFF_Q + 8 * 4096;
constexpr int A_SMEM = A_OFF_BAR + 128;

__device__ __forceinline__ uint32_t exp2_pair_fixed(float lo, float hi, uint32_t dep) {
    const uint32_t G = __byte_perm(__float_as_uint(lo), __float_as_uint(hi), 0x5410);
    uint32_t Hh;
    asm("lop3.b32 %0, %1, 0x007F007F, %2, 0xC0;" : "=r"(Hh) : "r"(G), "r"(dep));
    const uint32_t tt = hfma2(Hh, 0xF96BF96Bu, 0x358C358Cu);
    return G - hfma2(tt, Hh, 0u);
}

__global__ void __launch_bounds__(A_THREADS, 1)
k_attn() {
    extern __shared__ __align__(1024) uint8_t smem[];
    pdl_launch();
    const uint32_t sK = smem_u32(smem), sV = sK + KV_BYTES, bars = sK + A_OFF_BAR;
    const int tid = threadIdx.x;
    check_smem_base(sK);
    if (tid == 0) TS(1, 0);
    if (tid == 0) {
        for (int i = 0; i < A_NPIECE; i++) mbar_init(bars + i * 8, 1);
        bar_init_fence();
    }
    __syncthreads();
    pdl_wait();
    if (tid == 0) TS(1, 1);
    const int wg = __shfl_sync(~0u, tid >> 7, 0), w = (tid >> 5) & 3, lane = tid & 31, g = lane >> 2, t = lane & 3;
    const uint32_t* q32 = reinterpret_cast<const uint32_t*>(g_q);
    int row = (blockIdx.x * 8 + wg) * 64 + w * 16 + g;
    uint32_t nq[2][6];
#pragma unroll
    for (int r = 0; r < 2; r++) {
        const uint32_t* q = q32 + (row + r * 256) * 9;
        nq[r][0] = q[t]; nq[r][1] = q[72 + t]; nq[r][2] = q[4 + t]; nq[r][3] = q[76 + t]; nq[r][4] = q[8]; nq[r][5] = q[80];
    }
    constexpr int PB = KV_BYTES / A_NPIECE;
    const float4 km0 = reinterpret_cast<const float4*>(g_kmax)[lane], km1 = reinterpret_cast<const float4*>(g_kmax)[32 + lane];
    if (tid < 32 && elect_one()) {
        for (int i = 0; i < 2; i++) {
            mbar_expect(bars + i * 8, 2 * PB);
            bulk_g2s(sK + i * PB, reinterpret_cast<const char*>(g_kc) + i * PB, PB, bars + i * 8);
            bulk_g2s(sV + i * PB, reinterpret_cast<const char*>(g_vc) + i * PB, PB, bars + i * 8);
        }
    }
    float kmax2 = fmaxf(fmaxf(fmaxf(km0.x, km0.y), fmaxf(km0.z, km0.w)), fmaxf(fmaxf(km1.x, km1.y), fmaxf(km1.z, km1.w)));
#pragma unroll
    for (int o = 1; o < 32; o <<= 1) kmax2 = fmaxf(kmax2, __shfl_xor_sync(~0u, kmax2, o));
    if (tid < 32 && elect_one()) {
        for (int i = 2; i < A_NPIECE; i++) {
            mbar_expect(bars + i * 8, 2 * PB);
            bulk_g2s(sK + i * PB, reinterpret_cast<const char*>(g_kc) + i * PB, PB, bars + i * 8);
            bulk_g2s(sV + i * PB, reinterpret_cast<const char*>(g_vc) + i * PB, PB, bars + i * 8);
        }
    }
    uint32_t unsafe_mask = 0;
#pragma unroll
    for (int r = 0; r < 2; r++) {
        const float a0 = bf_lo(nq[r][0]), a1 = bf_hi(nq[r][0]), a2 = bf_lo(nq[r][2]), a3 = bf_hi(nq[r][2]);
        const float b0 = bf_lo(nq[r][1]), b1 = bf_hi(nq[r][1]), b2 = bf_lo(nq[r][3]), b3 = bf_hi(nq[r][3]);
        float n0 = a0 * a0 + a1 * a1 + a2 * a2 + a3 * a3, n1 = b0 * b0 + b1 * b1 + b2 * b2 + b3 * b3;
        if (t == 0) {
            const float c0 = bf_lo(nq[r][4]), c1 = bf_hi(nq[r][4]), d0 = bf_lo(nq[r][5]), d1 = bf_hi(nq[r][5]);
            n0 += c0 * c0 + c1 * c1; n1 += d0 * d0 + d1 * d1;
        }
        n0 += __shfl_xor_sync(~0u, n0, 1); n0 += __shfl_xor_sync(~0u, n0, 2);
        n1 += __shfl_xor_sync(~0u, n1, 1); n1 += __shfl_xor_sync(~0u, n1, 2);
        const bool unsafe = !(fmaxf(n0, n1) * kmax2 <= FAST_BOUND * FAST_BOUND) || !(n0 == n0) || !(n1 == n1);
        uint32_t any;
        asm volatile("{\n.reg .pred p, q;\nsetp.ne.u32 p, %1, 0;\nbar.red.or.pred q, %2, 128, p;\nselp.u32 %0, 1, 0, q;\n}\n" : "=r"(any) : "r"((uint32_t)unsafe), "r"(wg + 1) : "memory");
        unsafe_mask |= any << r;
        const uint32_t cst = any ? 0u : (t == 1 ? 0x3F804780u : (t == 2 ? 0x00003F80u : 0u));
        const uint32_t sQ = sK + A_OFF_Q + (r * 4 + wg) * 4096 + (w * 2) * 512 + g * 16 + t * 4;
        asm volatile("st.shared.b32 [%0], %1;" ::"r"(sQ), "r"(nq[r][0]) : "memory");
        asm volatile("st.shared.b32 [%0], %1;" ::"r"(sQ + 512), "r"(nq[r][1]) : "memory");
        asm volatile("st.shared.b32 [%0], %1;" ::"r"(sQ + 128), "r"(nq[r][2]) : "memory");
        asm volatile("st.shared.b32 [%0], %1;" ::"r"(sQ + 640), "r"(nq[r][3]) : "memory");
        asm volatile("st.shared.b32 [%0], %1;" ::"r"(sQ + 256), "r"(t == 0 ? nq[r][4] : cst) : "memory");
        asm volatile("st.shared.b32 [%0], %1;" ::"r"(sQ + 768), "r"(t == 0 ? nq[r][5] : cst) : "memory");
        asm volatile("st.shared.b32 [%0], %1;" ::"r"(sQ + 384), "r"(0u) : "memory");
        asm volatile("st.shared.b32 [%0], %1;" ::"r"(sQ + 896), "r"(0u) : "memory");
    }
    unsafe_mask = __shfl_sync(~0u, unsafe_mask, 0);
    proxy_fence();
    named_sync(wg + 1, 128);
    if (tid == 0) TS(1, 7);
#pragma unroll 1
    for (int rep = 0; rep < 2; rep++, row += 256) {
        const uint32_t any_unsafe = (unsafe_mask >> rep) & 1;
        const uint64_t dQ0 = cdesc(A_OFF_Q, 128, 512, 0) + (rep * 4 + wg) * 256, dQ1 = dQ0 + 16;
        if (tid == 0) TS(1, 2 + rep * 2);
        float o[12];
#pragma unroll
        for (int i = 0; i < 12; i++) o[i] = 0.f;
        pin(o);
        uint64_t dK0 = cdesc(0, 128, 384, 0), dK1 = cdesc(256, 0, 384, 0), dV = cdesc(KV_BYTES, 384, 128, 0);
        if (!any_unsafe) {
            float s[64];
#pragma unroll 1
            for (int j = 0; j < 16; j++) {
                if (rep == 0 && (j & 1) == 0) mbar_wait(bars + (j >> 1) * 8, 0);
                wg_fence();
                wgmma_ss_n128<0>(s, dQ0, dK0, 0);
                wgmma_ss_n128<0>(s, dQ1, dK1, 1);
                wg_commit();
                dK0 += 16 * 384 >> 4; dK1 += 16 * 384 >> 4;
                wg_wait<0>();
                pin(s);
                uint32_t p[32];
#define CHAIN 6
                {
                    constexpr int NP = 2 * __builtin_popcount(POLY_MASK), NM = 32 - NP;
                    float e[64];
#pragma unroll
                    for (int i = 0; i < 32; i++)
                        if (!((POLY_MASK >> (i >> 1)) & 1)) { e[2 * i] = ex2(s[2 * i]); e[2 * i + 1] = ex2(s[2 * i + 1]); p[i] = pack_bf16(e[2 * i], e[2 * i + 1]); }
                    int ip = 0;
#pragma unroll
                    for (int i = 0; i < 32; i++) {
                        if ((POLY_MASK >> (i >> 1)) & 1) {
                            const int mm = (ip * 2 * NM) / NP - CHAIN;
                            uint32_t dep = 0;
                            if (CHAIN > 0 && mm >= 0) {
                                int cnt = 0;
#pragma unroll
                                for (int q = 0; q < 32; q++)
                                    if (!((POLY_MASK >> (q >> 1)) & 1)) { if (cnt == (mm >> 1)) dep = __float_as_uint(e[2 * q + (mm & 1)]); cnt++; }
                            }
                            p[i] = exp2_pair_fixed(s[2 * i], s[2 * i + 1], dep);
                            ip++;
                        }
                    }
                }
                pin(p);
                wg_fence();
#pragma unroll
                for (int k = 0; k < 8; k++) {
                    wgmma_rs_n24<1>(o, p[4 * k], p[4 * k + 1], p[4 * k + 2], p[4 * k + 3], dV + k * 48, 1);
                }
                wg_commit();
                dV += 16 * 384 >> 4;
                wg_wait<0>();
            }
        } else {
            float s[64];
            float m0 = -INFINITY, m1 = -INFINITY;
#pragma unroll 1
            for (int j = 0; j < 16; j++) {
                if (rep == 0 && (j & 1) == 0) mbar_wait(bars + (j >> 1) * 8, 0);
                wg_fence();
                wgmma_ss_n128<0>(s, dQ0, dK0, 0);
                wgmma_ss_n128<0>(s, dQ1, dK1, 1);
                wg_commit();
                dK0 += 16 * 384 >> 4; dK1 += 16 * 384 >> 4;
                wg_wait<0>();
                pin(s);
                float x0m = m0, x1m = m1;
#pragma unroll
                for (int b = 0; b < 16; b++) { x0m = fmaxf(x0m, fmaxf(s[4 * b], s[4 * b + 1])); x1m = fmaxf(x1m, fmaxf(s[4 * b + 2], s[4 * b + 3])); }
                x0m = fmaxf(x0m, __shfl_xor_sync(~0u, x0m, 1)); x0m = fmaxf(x0m, __shfl_xor_sync(~0u, x0m, 2));
                x1m = fmaxf(x1m, __shfl_xor_sync(~0u, x1m, 1)); x1m = fmaxf(x1m, __shfl_xor_sync(~0u, x1m, 2));
                const float c0 = ex2(m0 - x0m), c1 = ex2(m1 - x1m);
                m0 = x0m; m1 = x1m;
#pragma unroll
                for (int b = 0; b < 3; b++) { o[4 * b] *= c0; o[4 * b + 1] *= c0; o[4 * b + 2] *= c1; o[4 * b + 3] *= c1; }
                uint32_t p[32];
#pragma unroll
                for (int b = 0; b < 16; b++) {
                    p[2 * b] = pack_bf16(ex2(s[4 * b] - m0), ex2(s[4 * b + 1] - m0));
                    p[2 * b + 1] = pack_bf16(ex2(s[4 * b + 2] - m1), ex2(s[4 * b + 3] - m1));
                }
                pin(p); pin(o);
                wg_fence();
#pragma unroll
                for (int k = 0; k < 8; k++) wgmma_rs_n24<1>(o, p[4 * k], p[4 * k + 1], p[4 * k + 2], p[4 * k + 3], dV + k * 48, 1);
                wg_commit();
                dV += 16 * 384 >> 4;
                wg_wait<0>();
            }
        }
        pin(o);
        if (tid == 0) TS(1, 3 + rep * 2);
        const float l0 = __shfl_sync(~0u, o[8], (lane & ~3) | 1), l1 = __shfl_sync(~0u, o[10], (lane & ~3) | 1);
        const float i0 = 1.0f / l0, i1 = 1.0f / l1;
        uint32_t* o32 = reinterpret_cast<uint32_t*>(g_o);
        o32[row * 9 + t] = pack_bf16(o[0] * i0, o[1] * i0);
        o32[(row + 8) * 9 + t] = pack_bf16(o[2] * i1, o[3] * i1);
        o32[row * 9 + 4 + t] = pack_bf16(o[4] * i0, o[5] * i0);
        o32[(row + 8) * 9 + 4 + t] = pack_bf16(o[6] * i1, o[7] * i1);
        if (t == 0) { o32[row * 9 + 8] = pack_bf16(o[8] * i0, o[9] * i0); o32[(row + 8) * 9 + 8] = pack_bf16(o[10] * i1, o[11] * i1); }
    }
    if (tid == 0) TS(1, 6);
    if ((tid & 127) == 0) TS(1, 10 + wg);
}

constexpr int O_THREADS = 416;
constexpr int O_OFF_STAT = P_A_BYTES + P_NST * P_B_STAGE + 256;
constexpr int O_SMEM = O_OFF_STAT + 9 * 64 * 8;

__global__ void __cluster_dims__(3, 1, 1) __launch_bounds__(O_THREADS, 1)
k_oproj(const __grid_constant__ CUtensorMap tmO, const __grid_constant__ CUtensorMap tmWo, const __grid_constant__ CUtensorMap tmX2, const __grid_constant__ CUtensorMap tmOut, const __nv_bfloat16* __restrict__ x, const __nv_bfloat16* __restrict__ w1) {
    extern __shared__ __align__(1024) uint8_t smem[];
    const uint32_t sA = smem_u32(smem), sB = sA + P_A_BYTES, bars = sB + P_NST * P_B_STAGE;
    const uint32_t fullB = bars, emptyB = bars + 64, fullA = bars + 128;
    const int tid = threadIdx.x, warp = __shfl_sync(~0u, tid >> 5, 0), lane = tid & 31;
    const int m = blockIdx.x / 3, cg = blockIdx.x % 3;
    if (tid == 0) TS(2, 0);
    check_smem_base(sA);
    if (tid == 0) {
        prefetch_map(&tmO); prefetch_map(&tmWo); prefetch_map(&tmX2); prefetch_map(&tmOut);
        for (int i = 0; i < P_NST; i++) { mbar_init(fullB + i * 8, 1); mbar_init(emptyB + i * 8, 12); }
        for (int i = 0; i < 9; i++) mbar_init(fullA + i * 8, 1);
        bar_init_fence();
        for (int kb = 0; kb < 9; kb++) mbar_expect(fullA + kb * 8, 8192);
    }
    __syncthreads();
    pdl_launch();
    if (warp == 12) {
        if (elect_one()) {
            for (int kb = 0; kb < 9; kb++) {
                const int s = kb >= P_NST ? kb - P_NST : kb;
                if (kb == 2) {
                    pdl_wait();
                    TS(2, 1);
                    for (int ka = 0; ka < 9; ka++) tma_2d(sA + ka * 8192, &tmO, ka * 64, m * 64, fullA + ka * 8);
                }
                if (kb >= P_NST) mbar_wait(emptyB + s * 8, 0);
                mbar_expect(fullB + s * 8, P_B_STAGE);
                for (int a = 0; a < 3; a++) tma_2d(sB + s * P_B_STAGE + a * 8192, &tmWo, cg * 192 + a * 64, kb * 64, fullB + s * 8);
            }
            for (int i = 0; i < 6; i++) prefetch_l2(reinterpret_cast<const char*>(w1) + (size_t)blockIdx.x * (FF * DM * 2 / 96) + i * 9216, 9216);
        }
        return;
    }
    if (tid == 0) TS(2, 11);
    const int wg = warp >> 2, w = warp & 3, g = lane >> 2, t = lane & 3;
    uint32_t xr[16];
    {
        const uint32_t* x32 = reinterpret_cast<const uint32_t*>(x) + (((m * 64 + w * 16 + g) * DM + cg * 192 + wg * 64 + 2 * t) >> 1);
#pragma unroll
        for (int b = 0; b < 8; b++) { xr[2 * b] = __ldg(x32 + b * 4); xr[2 * b + 1] = __ldg(x32 + b * 4 + 4 * DM); }
    }
    float acc[32];
    proj_mma(acc, wg, fullB, emptyB, fullA, true, lane);
    if (tid == 0) TS(2, 2);
    named_sync(1, 384);
    float s0 = 0.f, q0 = 0.f, s1 = 0.f, q1 = 0.f;
#pragma unroll
    for (int b = 0; b < 8; b++) {
        const uint32_t xa = xr[2 * b], xb = xr[2 * b + 1];
        const uint32_t ha = pack_bf16(acc[4 * b] + bf_lo(xa), acc[4 * b + 1] + bf_hi(xa));
        const uint32_t hb = pack_bf16(acc[4 * b + 2] + bf_lo(xb), acc[4 * b + 3] + bf_hi(xb));
        xr[2 * b] = ha; xr[2 * b + 1] = hb;
        const float a = bf_lo(ha), c = bf_hi(ha), d = bf_lo(hb), e = bf_hi(hb);
        s0 += a + c; q0 = fmaf(a, a, fmaf(c, c, q0));
        s1 += d + e; q1 = fmaf(d, d, fmaf(e, e, q1));
    }
    s0 += __shfl_xor_sync(~0u, s0, 1); s0 += __shfl_xor_sync(~0u, s0, 2);
    q0 += __shfl_xor_sync(~0u, q0, 1); q0 += __shfl_xor_sync(~0u, q0, 2);
    s1 += __shfl_xor_sync(~0u, s1, 1); s1 += __shfl_xor_sync(~0u, s1, 2);
    q1 += __shfl_xor_sync(~0u, q1, 1); q1 += __shfl_xor_sync(~0u, q1, 2);
    const int r = w * 16 + g;
    const uint32_t sStat = sA + O_OFF_STAT;
    if (t < 3) {
        uint32_t dst;
        asm("mapa.shared::cluster.u32 %0, %1, %2;" : "=r"(dst) : "r"(sStat + ((cg * 3 + wg) * 64 + r) * 8), "r"(t));
        asm volatile("st.shared::cluster.v2.f32 [%0], {%1, %2};" ::"r"(dst), "f"(s0), "f"(q0) : "memory");
        asm volatile("st.shared::cluster.v2.f32 [%0], {%1, %2};" ::"r"(dst + 64), "f"(s1), "f"(q1) : "memory");
    }
    if (tid == 0) TS(2, 4);
    cluster_arrive();
    stage_tile<8>(xr, sA + wg * 8192, w, lane);
    proxy_fence();
    named_sync(2 + wg, 128);
    const bool leader = w == 0 && elect_one();
    if (leader) { tma_st_2d(&tmOut, cg * 192 + wg * 64, m * 64, sA + wg * 8192); bulk_commit(); }
    cluster_wait();
    if (tid == 0) TS(2, 5);
    s0 = q0 = s1 = q1 = 0.f;
#pragma unroll
    for (int p = 0; p < 9; p++) {
        float a, b, c, d;
        asm volatile("ld.shared.v2.f32 {%0, %1}, [%2];" : "=f"(a), "=f"(b) : "r"(sStat + (p * 64 + r) * 8));
        asm volatile("ld.shared.v2.f32 {%0, %1}, [%2];" : "=f"(c), "=f"(d) : "r"(sStat + (p * 64 + r + 8) * 8));
        s0 += a; q0 += b; s1 += c; q1 += d;
    }
    const float m0 = s0 * (1.0f / DM), m1 = s1 * (1.0f / DM);
    const float rs0 = rsqrtf(fmaxf(q0 * (1.0f / DM) - m0 * m0, 0.f) + LN_EPS), rs1 = rsqrtf(fmaxf(q1 * (1.0f / DM) - m1 * m1, 0.f) + LN_EPS);
    const float sc0 = 0.5f * rs0, sc1 = 0.5f * rs1, n0 = -m0 * sc0, n1 = -m1 * sc1;
#pragma unroll
    for (int b = 0; b < 8; b++) {
        xr[2 * b] = pack_bf16(fmaf(bf_lo(xr[2 * b]), sc0, n0), fmaf(bf_hi(xr[2 * b]), sc0, n0));
        xr[2 * b + 1] = pack_bf16(fmaf(bf_lo(xr[2 * b + 1]), sc1, n1), fmaf(bf_hi(xr[2 * b + 1]), sc1, n1));
    }
    stage_tile<8>(xr, sA + (3 + wg) * 8192, w, lane);
    proxy_fence();
    named_sync(2 + wg, 128);
    if (tid == 0) TS(2, 6);
    if (leader) {
        tma_st_2d(&tmX2, cg * 192 + wg * 64, m * 64, sA + (3 + wg) * 8192);
        bulk_commit();
        bulk_wait_all();
    }
    if (tid == 0) TS(2, 3);
}

constexpr int F_THREADS = 384;
constexpr int F_NST = 6;
constexpr int F_STAGE = 96 * 128;
constexpr int F_X_BYTES = 9 * 16384;
constexpr int F_OFF_ST = F_X_BYTES;
constexpr int F_OFF_BAR = F_OFF_ST + F_NST * F_STAGE;
constexpr int F_SMEM = F_OFF_BAR + 256;

__device__ __forceinline__ float tanh_hw(float x) { float y; asm("tanh.approx.f32 %0, %1;" : "=f"(y) : "f"(x)); return y; }
__host__ __device__ constexpr int piece_begin(int p) { return p == 0 ? 0 : 3 * p + 1; }
template <int P>
__device__ __forceinline__ void silu_s1(const float (&acc)[32], float (&tmp)[8]) {
#pragma unroll
    for (int i = 2 * piece_begin(P); i < 2 * piece_begin(P + 1); i++) tmp[i - 2 * piece_begin(P)] = tanh_hw(acc[i]);
}
template <int C, int P>
__device__ __forceinline__ void silu_s2(const float (&acc)[32], const float (&tmp)[8], uint32_t (&h1)[144]) {
#pragma unroll
    for (int i = piece_begin(P); i < piece_begin(P + 1); i++) {
        const int k = 2 * (i - piece_begin(P));
        h1[C * 16 + i] = pack_bf16(fmaf(acc[2 * i], tmp[k], acc[2 * i]), fmaf(acc[2 * i + 1], tmp[k + 1], acc[2 * i + 1]));
    }
}
template <int C, int J>
__device__ __forceinline__ void silu_slot(const float (&prev)[32], float (&tmp)[2][8], uint32_t (&h1)[144]) {
    if constexpr (J >= 1) silu_s2<C, J - 1>(prev, tmp[(J - 1) & 1], h1);
    if constexpr (J <= 4) { silu_s1<J>(prev, tmp[J & 1]); pin(tmp[J & 1]); }
}

struct FfnPipe {
    uint32_t full, empty;
    int lane;
    __device__ __forceinline__ void acquire(int s, uint32_t ph) const { mbar_wait(full + s * 8, ph); }
    __device__ __forceinline__ void release(int s) const { if (lane == 0) mbar_arrive(empty + s * 8); }
};

template <int C>
__device__ __forceinline__ void ffn_phase1_chunk(float (&cur)[32], float (&prev)[32], uint32_t (&h1)[144], const FfnPipe& pp, uint64_t dx, uint32_t fullX) {
    float tmp[2][8];
    const uint64_t dw = cdesc(F_OFF_ST, 8192, 1024, 1) + blockIdx.y * (C + 1);
    dx += blockIdx.y * C;
#pragma unroll
    for (int j = 0; j < 6; j++) {
        if (C == 0) { mbar_wait(fullX + ((6 * j) >> 2) * 8, 0); mbar_wait(fullX + ((6 * j + 5) >> 2) * 8, 0); }
        pp.acquire(j, C & 1);
        if (j == 0) pin(cur);
        wg_fence();
#pragma unroll
        for (int i = 0; i < 6; i++) {
            const int ks = 6 * j + i;
            wgmma_ss_n64<1>(cur, dx + ((ks >> 2) * 1024 + (ks & 3) * 2), dw + ((j * F_STAGE + i * 2048) >> 4), ks != 0);
        }
        wg_commit();
        if (C > 0 || j > 0) { wg_wait<1>(); pp.release((j + 5) % 6); }
        if (C > 0) {
            constexpr int CP = C > 0 ? C - 1 : 0;
            pin(prev);
            if (j == 0) silu_slot<CP, 0>(prev, tmp, h1);
            if (j == 1) silu_slot<CP, 1>(prev, tmp, h1);
            if (j == 2) silu_slot<CP, 2>(prev, tmp, h1);
            if (j == 3) silu_slot<CP, 3>(prev, tmp, h1);
            if (j == 4) silu_slot<CP, 4>(prev, tmp, h1);
            if (j == 5) silu_slot<CP, 5>(prev, tmp, h1);
        }
    }
}

__device__ __forceinline__ void ffn_stage_chunk(const float (&acc)[32], uint32_t stg, int w, int lane) {
    uint32_t pk[16];
#pragma unroll
    for (int i = 0; i < 16; i++) pk[i] = pack_bf16(acc[2 * i], acc[2 * i + 1]);
    stage_tile<8>(pk, stg, w, lane);
}
__device__ __forceinline__ void ffn_reduce_chunk(const CUtensorMap* tmOut, uint32_t stg, int col, int row, int w, int wgid, bool leader) {
    proxy_fence();
    if (w != 0) {
        asm volatile("bar.arrive %0, 128;" ::"r"(2 + wgid) : "memory");
    } else {
        named_sync(2 + wgid, 128);
        if (leader) { tma_red_2d(tmOut, col, row, stg); bulk_commit(); }
    }
}

__device__ __forceinline__ void ffn_phase2_chunk(float (&cur)[32], float (&prev)[32], uint32_t (&h1)[144], const FfnPipe& pp, uint32_t ph, bool store_prev, const CUtensorMap* tmOut, uint32_t stg_prev, int col_prev, int row, int w, int lane, int wgid, bool leader) {
    const uint64_t dw = cdesc(F_OFF_ST, 8192, 1024, 1) + blockIdx.y * col_prev;
#pragma unroll
    for (int j = 0; j < 6; j++) {
        pp.acquire(j, ph);
        if (j == 0) pin(cur);
        wg_fence();
#pragma unroll
        for (int i = 0; i < 6; i++) {
            const int f = (6 * j + i) * 4;
            wgmma_rs_n64<1>(cur, h1[f], h1[f + 1], h1[f + 2], h1[f + 3], dw + ((j * F_STAGE + i * 2048) >> 4), (j | i) != 0);
        }
        wg_commit();
        if (j > 0 || store_prev) { wg_wait<1>(); pp.release((j + 5) % 6); }
        if (j == 0 && store_prev) { pin(prev); ffn_stage_chunk(prev, stg_prev, w, lane); }
        if (j == 1 && store_prev) ffn_reduce_chunk(tmOut, stg_prev, col_prev, row, w, wgid, leader);
    }
}

__global__ void __launch_bounds__(F_THREADS, 1)
k_ffn(const __grid_constant__ CUtensorMap tmH, const __grid_constant__ CUtensorMap tmW1, const __grid_constant__ CUtensorMap tmW2, const __grid_constant__ CUtensorMap tmOut, const __nv_bfloat16* __restrict__ w2) {
    extern __shared__ __align__(1024) uint8_t smem[];
    const uint32_t sX = smem_u32(smem), sSt = sX + F_OFF_ST, bars = sX + F_OFF_BAR;
    const uint32_t full = bars, empty = bars + 64, fullX = bars + 128;
    const int tid = threadIdx.x, warp = __shfl_sync(~0u, tid >> 5, 0), lane = tid & 31;
#define FFN_MAP 1
    const int m = FFN_MAP == 0 ? (blockIdx.x & 15) : (FFN_MAP == 1 ? (blockIdx.x >> 3) : ((blockIdx.x >> 1) & 15));
    const int fs = FFN_MAP == 0 ? (blockIdx.x >> 4) : (FFN_MAP == 1 ? (blockIdx.x & 7) : ((blockIdx.x >> 5) * 2 + (blockIdx.x & 1)));
    if (tid == 0) TS(3, 0);
    check_smem_base(sX);
    if (tid == 0) {
        prefetch_map(&tmW1); prefetch_map(&tmH); prefetch_map(&tmW2); prefetch_map(&tmOut);
        for (int i = 0; i < F_NST; i++) { mbar_init(full + i * 8, 1); mbar_init(empty + i * 8, 8); }
        for (int i = 0; i < 9; i++) mbar_init(fullX + i * 8, 1);
        bar_init_fence();
        for (int kb = 0; kb < 9; kb++) mbar_expect(fullX + kb * 8, 16384);
    }
    __syncthreads();
    if (warp < 4) {
        asm volatile("setmaxnreg.dec.sync.aligned.u32 24;");
        if (warp == 1 && lane < 9) prefetch_l2(reinterpret_cast<const char*>(w2) + ((size_t)fs * 576 + m * 36 + lane * 4) * (DM * 2), 4 * DM * 2);
        if (warp == 0 && elect_one()) {
            int s = 0; uint32_t ph = 1;
            int c = 0, j = 0;
#pragma unroll 1
            for (int i = 0; i < 108; i++) {
                if (i == 54) c = fs;
                mbar_wait(empty + s * 8, ph);
                mbar_expect(full + s * 8, F_STAGE);
                if (i < 54) tma_2d(sSt + s * F_STAGE, &tmW1, fs * 576 + c * 64, j * 96, full + s * 8);
                else tma_2d(sSt + s * F_STAGE, &tmW2, c * 64, fs * 576 + j * 96, full + s * 8);
                if (++j == 6) { j = 0; if (++c == 9) c = 0; }
                if (++s == F_NST) { s = 0; ph ^= 1; }
            }
        }
    } else {
        asm volatile("setmaxnreg.inc.sync.aligned.u32 240;");
        const int wgid = (warp >> 2) - 1, w = warp & 3;
        pdl_wait();
        if (tid == 128) TS(3, 1);
        if (warp == 4 && elect_one()) {
            for (int kb = 0; kb < 9; kb++) tma_2d(sX + kb * 16384, &tmH, kb * 64, m * 128, fullX + kb * 8);
        }
        __syncwarp();
        FfnPipe pp{full, empty, lane};
        const uint64_t xlo = cdesc(0, 16, 1024, 1) + wgid * 512;
        uint32_t h1[144];
        float acc0[32], acc1[32];
        ffn_phase1_chunk<0>(acc0, acc1, h1, pp, xlo, fullX);
        if (tid == 128) TS(3, 2);
        ffn_phase1_chunk<1>(acc1, acc0, h1, pp, xlo, fullX);
        ffn_phase1_chunk<2>(acc0, acc1, h1, pp, xlo, fullX);
        ffn_phase1_chunk<3>(acc1, acc0, h1, pp, xlo, fullX);
        ffn_phase1_chunk<4>(acc0, acc1, h1, pp, xlo, fullX);
        ffn_phase1_chunk<5>(acc1, acc0, h1, pp, xlo, fullX);
        ffn_phase1_chunk<6>(acc0, acc1, h1, pp, xlo, fullX);
        ffn_phase1_chunk<7>(acc1, acc0, h1, pp, xlo, fullX);
        ffn_phase1_chunk<8>(acc0, acc1, h1, pp, xlo, fullX);
        wg_wait<0>();
        pp.release(5);
        pin(acc0);
#pragma unroll
        for (int i = 0; i < 16; i++) h1[128 + i] = pack_bf16(fmaf(acc0[2 * i], tanh_hw(acc0[2 * i]), acc0[2 * i]), fmaf(acc0[2 * i + 1], tanh_hw(acc0[2 * i + 1]), acc0[2 * i + 1]));
        pin(h1);
        if (tid == 128) TS(3, 3);
        const int row = m * 128 + wgid * 64;
        const uint32_t stg = sX + wgid * 8192;
        int c = fs, cprev = 0;
        const bool leader = w == 0 && elect_one();
#pragma unroll 1
        for (int j = 0; j < 8; j += 2) {
            ffn_phase2_chunk(acc1, acc0, h1, pp, 1, j > 0, &tmOut, stg + (j - 1) * 16384, cprev * 64, row, w, lane, wgid, leader);
            cprev = c; if (++c == 9) c = 0;
            ffn_phase2_chunk(acc0, acc1, h1, pp, 0, true, &tmOut, stg + j * 16384, cprev * 64, row, w, lane, wgid, leader);
            cprev = c; if (++c == 9) c = 0;
        }
        ffn_phase2_chunk(acc1, acc0, h1, pp, 1, true, &tmOut, stg + 7 * 16384, cprev * 64, row, w, lane, wgid, leader);
        wg_wait<0>();
        pin(acc1);
        ffn_stage_chunk(acc1, stg + 8 * 16384, w, lane);
        ffn_reduce_chunk(&tmOut, stg + 8 * 16384, c * 64, row, w, wgid, leader);
        if (tid == 128) TS(3, 4);
        if (leader) bulk_wait_all();
        if (tid == 128) TS(3, 5);
    }
}

typedef CUresult (*EncodeFn)(CUtensorMap*, CUtensorMapDataType, cuuint32_t, void*, const cuuint64_t*, const cuuint64_t*, const cuuint32_t*, const cuuint32_t*,
                             CUtensorMapInterleave, CUtensorMapSwizzle, CUtensorMapL2promotion, CUtensorMapFloatOOBfill);

CUtensorMap make_map(EncodeFn enc, const void* base, int rows, int cols, int box_rows) {
    CUtensorMap tm;
    cuuint64_t dims[2] = {(cuuint64_t)cols, (cuuint64_t)rows};
    cuuint64_t strides[1] = {(cuuint64_t)cols * 2};
    cuuint32_t box[2] = {64, (cuuint32_t)box_rows};
    cuuint32_t es[2] = {1, 1};
    enc(&tm, CU_TENSOR_MAP_DATA_TYPE_BFLOAT16, 2, const_cast<void*>(base), dims, strides, box, es, CU_TENSOR_MAP_INTERLEAVE_NONE,
        CU_TENSOR_MAP_SWIZZLE_128B, CU_TENSOR_MAP_L2_PROMOTION_L2_256B, CU_TENSOR_MAP_FLOAT_OOB_FILL_NONE);
    return tm;
}

template <typename... KArgs, typename... Args>
void launch(void (*kern)(KArgs...), int grid, int block, int smem, bool pdl, Args... args) {
    cudaLaunchConfig_t cfg = {};
    cfg.gridDim = dim3(grid); cfg.blockDim = dim3(block); cfg.dynamicSmemBytes = smem; cfg.stream = cudaStreamPerThread;
    cudaLaunchAttribute at[1];
    at[0].id = cudaLaunchAttributeProgrammaticStreamSerialization;
    at[0].val.programmaticStreamSerializationAllowed = 1;
    cfg.attrs = at; cfg.numAttrs = pdl ? 1 : 0;
    cudaLaunchKernelEx(&cfg, kern, KArgs(args)...);
}

}

#define USE_PDL 1

extern "C" void kernel_launch(void* const* d_in, const int* in_sizes, int n_in, void* d_out, int out_size) {
    const __nv_bfloat16* x = (const __nv_bfloat16*)d_in[0];
    const __nv_bfloat16* wq = (const __nv_bfloat16*)d_in[1];
    const __nv_bfloat16* wk = (const __nv_bfloat16*)d_in[2];
    const __nv_bfloat16* wv = (const __nv_bfloat16*)d_in[3];
    const __nv_bfloat16* wo = (const __nv_bfloat16*)d_in[4];
    const __nv_bfloat16* w1 = (const __nv_bfloat16*)d_in[6];
    const __nv_bfloat16* w2 = (const __nv_bfloat16*)d_in[7];
    __nv_bfloat16* out = (__nv_bfloat16*)d_out;

    static EncodeFn enc = nullptr;
    static void *p_o = nullptr, *p_h = nullptr, *p_q = nullptr;
    if (!enc) {
        cudaDriverEntryPointQueryResult qr;
        cudaGetDriverEntryPoint("cuTensorMapEncodeTiled", (void**)&enc, cudaEnableDefault, &qr);
        cudaGetSymbolAddress(&p_o, g_o);
        cudaGetSymbolAddress(&p_h, g_x2);
        cudaGetSymbolAddress(&p_q, g_q);
        cudaFuncSetAttribute(k_qkv, cudaFuncAttributeMaxDynamicSharedMemorySize, P_SMEM);
        cudaFuncSetAttribute(k_attn, cudaFuncAttributeMaxDynamicSharedMemorySize, A_SMEM);
        cudaFuncSetAttribute(k_oproj, cudaFuncAttributeMaxDynamicSharedMemorySize, O_SMEM);
        cudaFuncSetAttribute(k_ffn, cudaFuncAttributeMaxDynamicSharedMemorySize, F_SMEM);
    }
    const CUtensorMap tmWq = make_map(enc, wq, DM, DM, 64);
    const CUtensorMap tmWo = make_map(enc, wo, DM, DM, 64);
    const CUtensorMap tmO = make_map(enc, p_o, SEQ, DM, 64);
    const CUtensorMap tmH64 = make_map(enc, p_h, SEQ, DM, 64);
    const CUtensorMap tmH = make_map(enc, p_h, SEQ, DM, 128);
    const CUtensorMap tmQ = make_map(enc, p_q, SEQ, DM, 64);
    const CUtensorMap tmW1 = make_map(enc, w1, DM, FF, 96);
    const CUtensorMap tmW2 = make_map(enc, w2, FF, DM, 96);
    const CUtensorMap tmOut = make_map(enc, out, SEQ, DM, 64);

    launch(k_qkv, 128, Q_THREADS, P_SMEM, false, tmWq, tmQ, x, wk, wv);
    launch(k_attn, 128, A_THREADS, A_SMEM, USE_PDL);
    launch(k_oproj, 96, O_THREADS, O_SMEM, USE_PDL, tmO, tmWo, tmH64, tmOut, x, w1);
    launch(k_ffn, 128, F_THREADS, F_SMEM, USE_PDL, tmH, tmW1, tmW2, tmOut, w2);
}
```

```cpp
#include <cuda_runtime.h>
#include <cuda_bf16.h>
#include <cuda.h>
#include <stdint.h>

namespace {

constexpr int SEQ = 2048, DM = 576, FF = 4608;
constexpr int KV_BYTES = SEQ * 48;
constexpr float LN_EPS = 1e-5f;
constexpr float LOG2E = 1.4426950408889634f;
constexpr float Q_SCALE = 0.23570226039551584f * LOG2E;

#define POLY_MASK_V 0xB6DBu
constexpr uint32_t POLY_MASK = POLY_MASK_V;
#define FAST_BOUND_V 60.0f
constexpr float FAST_BOUND = FAST_BOUND_V;

__device__ __align__(1024) __nv_bfloat16 g_q[SEQ * DM];
__device__ __align__(1024) uint4 g_kc[KV_BYTES / 16];
__device__ __align__(1024) uint4 g_vc[KV_BYTES / 16];
__device__ __align__(16) float g_kmax[256];
__device__ __align__(1024) __nv_bfloat16 g_o[SEQ * DM];
__device__ __align__(1024) __nv_bfloat16 g_x2[SEQ * DM];

#define TS(k, i)

__device__ __forceinline__ uint32_t smem_u32(const void* p) { return (uint32_t)__cvta_generic_to_shared(p); }
__device__ __forceinline__ void wg_fence() { asm volatile("wgmma.fence.sync.aligned;" ::: "memory"); }
__device__ __forceinline__ void wg_commit() { asm volatile("wgmma.commit_group.sync.aligned;" ::: "memory"); }
template <int N> __device__ __forceinline__ void wg_wait() { asm volatile("wgmma.wait_group.sync.aligned %0;" ::"n"(N) : "memory"); }
template <int N> __device__ __forceinline__ void pin(float (&r)[N]) {
#pragma unroll
    for (int i = 0; i < N; i++) asm volatile("" : "+f"(r[i])::"memory");
}
template <int N> __device__ __forceinline__ void pin(uint32_t (&r)[N]) {
#pragma unroll
    for (int i = 0; i < N; i++) asm volatile("" : "+r"(r[i])::"memory");
}
constexpr uint32_t SMEM0 = 0x400;
__host__ __device__ constexpr uint64_t cdesc(uint32_t off, uint32_t lbo, uint32_t sbo, uint32_t swz) {
    return (uint64_t)(((SMEM0 + off) & 0x3FFFF) >> 4) | ((uint64_t)(lbo >> 4) << 16) | ((uint64_t)(sbo >> 4) << 32) | ((uint64_t)swz << 62);
}
__device__ __forceinline__ void check_smem_base(uint32_t base) { if ((base & 0x3FFFF) != SMEM0) __trap(); }

__device__ __forceinline__ void mbar_init(uint32_t bar, int cnt) { asm volatile("mbarrier.init.shared::cta.b64 [%0], %1;" ::"r"(bar), "r"(cnt) : "memory"); }
__device__ __forceinline__ void mbar_expect(uint32_t bar, int bytes) { asm volatile("mbarrier.arrive.expect_tx.shared::cta.b64 _, [%0], %1;" ::"r"(bar), "r"(bytes) : "memory"); }
__device__ __forceinline__ void mbar_arrive(uint32_t bar) { asm volatile("mbarrier.arrive.shared::cta.b64 _, [%0];" ::"r"(bar) : "memory"); }
__device__ __forceinline__ void mbar_wait(uint32_t bar, uint32_t parity) {
    asm volatile(
        "{\n.reg .pred p;\n.reg .u32 n;\nmov.u32 n, 0;\n"
        "LAB_WAIT:\n"
        "mbarrier.try_wait.parity.shared::cta.b64 p, [%0], %1;\n"
        "@p bra DONE;\n"
        "add.u32 n, n, 1;\n"
        "setp.lt.u32 p, n, 4000000;\n"
        "@p bra LAB_WAIT;\n"
        "trap;\n"
        "DONE:\n}\n" ::"r"(bar), "r"(parity) : "memory");
}
__device__ __forceinline__ void bar_init_fence() {
    asm volatile("fence.mbarrier_init.release.cluster;" ::: "memory");
    asm volatile("fence.proxy.async.shared::cta;" ::: "memory");
}
__device__ __forceinline__ void proxy_fence() { asm volatile("fence.proxy.async.shared::cta;" ::: "memory"); }
__device__ __forceinline__ void named_sync(int id, int n) { asm volatile("bar.sync %0, %1;" ::"r"(id), "r"(n) : "memory"); }
__device__ __forceinline__ void bulk_g2s(uint32_t dst, const void* src, int bytes, uint32_t bar) {
    asm volatile("cp.async.bulk.shared::cluster.global.mbarrier::complete_tx::bytes [%0], [%1], %2, [%3];" ::"r"(dst), "l"(src), "r"(bytes), "r"(bar) : "memory");
}
__device__ __forceinline__ void tma_2d(uint32_t dst, const CUtensorMap* tm, int c0, int c1, uint32_t bar) {
    asm volatile("cp.async.bulk.tensor.2d.shared::cluster.global.mbarrier::complete_tx::bytes [%0], [%1, {%3, %4}], [%2];" ::"r"(dst), "l"(tm), "r"(bar), "r"(c0), "r"(c1) : "memory");
}
__device__ __forceinline__ void cluster_arrive() { asm volatile("barrier.cluster.arrive.release.aligned;" ::: "memory"); }
__device__ __forceinline__ void cluster_wait() { asm volatile("barrier.cluster.wait.acquire.aligned;" ::: "memory"); }
__device__ __forceinline__ void tma_red_2d(const CUtensorMap* tm, int c0, int c1, uint32_t src) {
    asm volatile("cp.reduce.async.bulk.tensor.2d.global.shared::cta.add.tile.bulk_group [%0, {%2, %3}], [%1];" ::"l"(tm), "r"(src), "r"(c0), "r"(c1) : "memory");
}
__device__ __forceinline__ void tma_st_2d(const CUtensorMap* tm, int c0, int c1, uint32_t src) {
    asm volatile("cp.async.bulk.tensor.2d.global.shared::cta.tile.bulk_group [%0, {%2, %3}], [%1];" ::"l"(tm), "r"(src), "r"(c0), "r"(c1) : "memory");
}
__device__ __forceinline__ void bulk_commit() { asm volatile("cp.async.bulk.commit_group;" ::: "memory"); }
__device__ __forceinline__ void bulk_wait_all() { asm volatile("cp.async.bulk.wait_group.read 0;" ::: "memory"); }
__device__ __forceinline__ bool elect_one() {
    uint32_t p;
    asm volatile("{\n.reg .pred P;\nelect.sync _|P, 0xffffffff;\nselp.b32 %0, 1, 0, P;\n}\n" : "=r"(p));
    return p != 0;
}
__device__ __forceinline__ void prefetch_l2(const void* p, int bytes) { asm volatile("cp.async.bulk.prefetch.L2.global [%0], %1;" ::"l"(p), "r"(bytes) : "memory"); }
__device__ __forceinline__ void prefetch_map(const CUtensorMap* tm) { asm volatile("prefetch.tensormap [%0];" ::"l"(tm) : "memory"); }
__device__ __forceinline__ void pdl_launch() { asm volatile("griddepcontrol.launch_dependents;" ::: "memory"); }
__device__ __forceinline__ void pdl_wait() { asm volatile("griddepcontrol.wait;" ::: "memory"); }
__device__ __forceinline__ float ex2(float x) { float y; asm("ex2.approx.ftz.f32 %0, %1;" : "=f"(y) : "f"(x)); return y; }
__device__ __forceinline__ uint32_t pack_bf16(float lo, float hi) { uint32_t r; asm("cvt.rn.bf16x2.f32 %0, %1, %2;" : "=r"(r) : "f"(hi), "f"(lo)); return r; }
__device__ __forceinline__ float bf_lo(uint32_t v) { return __uint_as_float(v << 16); }
__device__ __forceinline__ float bf_hi(uint32_t v) { return __uint_as_float(v & 0xFFFF0000u); }
__device__ __forceinline__ uint32_t hfma2(uint32_t a, uint32_t b, uint32_t c) { uint32_t r; asm("fma.rn.f16x2 %0, %1, %2, %3;" : "=r"(r) : "r"(a), "r"(b), "r"(c)); return r; }
__device__ __forceinline__ void stmatrix_x4(uint32_t addr, uint32_t r0, uint32_t r1, uint32_t r2, uint32_t r3) {
    asm volatile("stmatrix.sync.aligned.m8n8.x4.shared.b16 [%0], {%1, %2, %3, %4};" ::"r"(addr), "r"(r0), "r"(r1), "r"(r2), "r"(r3) : "memory");
}

template <int TB> __device__ __forceinline__ void wgmma_ss_n24(float (&d)[12], uint64_t da, uint64_t db, int sc) {
    asm volatile("{\n.reg .pred p;\nsetp.ne.b32 p, %14, 0;\n"
        "wgmma.mma_async.sync.aligned.m64n24k16.f32.bf16.bf16 {%0, %1, %2, %3, %4, %5, %6, %7, %8, %9, %10, %11}, %12, %13, p, 1, 1, 0, %15;\n}\n"
        : "+f"(d[0]), "+f"(d[1]), "+f"(d[2]), "+f"(d[3]), "+f"(d[4]), "+f"(d[5]), "+f"(d[6]), "+f"(d[7]), "+f"(d[8]), "+f"(d[9]), "+f"(d[10]), "+f"(d[11])
        : "l"(da), "l"(db), "r"(sc), "n"(TB));
}
template <int TB> __device__ __forceinline__ void wgmma_ss_n64(float (&d)[32], uint64_t da, uint64_t db, int sc) {
    asm volatile("{\n.reg .pred p;\nsetp.ne.b32 p, %34, 0;\n"
        "wgmma.mma_async.sync.aligned.m64n64k16.f32.bf16.bf16 {%0, %1, %2, %3, %4, %5, %6, %7, %8, %9, %10, %11, %12, %13, %14, %15, %16, %17, %18, %19, %20, %21, %22, %23, %24, %25, %26, %27, %28, %29, %30, %31}, %32, %33, p, 1, 1, 0, %35;\n}\n"
        : "+f"(d[0]), "+f"(d[1]), "+f"(d[2]), "+f"(d[3]), "+f"(d[4]), "+f"(d[5]), "+f"(d[6]), "+f"(d[7]), "+f"(d[8]), "+f"(d[9]), "+f"(d[10]), "+f"(d[11]), "+f"(d[12]), "+f"(d[13]), "+f"(d[14]), "+f"(d[15]), "+f"(d[16]), "+f"(d[17]), "+f"(d[18]), "+f"(d[19]), "+f"(d[20]), "+f"(d[21]), "+f"(d[22]), "+f"(d[23]), "+f"(d[24]), "+f"(d[25]), "+f"(d[26]), "+f"(d[27]), "+f"(d[28]), "+f"(d[29]), "+f"(d[30]), "+f"(d[31])
        : "l"(da), "l"(db), "r"(sc), "n"(TB));
}
template <int TB> __device__ __forceinline__ void wgmma_ss_n128(float (&d)[64], uint64_t da, uint64_t db, int sc) {
    asm volatile("{\n.reg .pred p;\nsetp.ne.b32 p, %66, 0;\n"
        "wgmma.mma_async.sync.aligned.m64n128k16.f32.bf16.bf16 {%0, %1, %2, %3, %4, %5, %6, %7, %8, %9, %10, %11, %12, %13, %14, %15, %16, %17, %18, %19, %20, %21, %22, %23, %24, %25, %26, %27, %28, %29, %30, %31, %32, %33, %34, %35, %36, %37, %38, %39, %40, %41, %42, %43, %44, %45, %46, %47, %48, %49, %50, %51, %52, %53, %54, %55, %56, %57, %58, %59, %60, %61, %62, %63}, %64, %65, p, 1, 1, 0, %67;\n}\n"
        : "+f"(d[0]), "+f"(d[1]), "+f"(d[2]), "+f"(d[3]), "+f"(d[4]), "+f"(d[5]), "+f"(d[6]), "+f"(d[7]), "+f"(d[8]), "+f"(d[9]), "+f"(d[10]), "+f"(d[11]), "+f"(d[12]), "+f"(d[13]), "+f"(d[14]), "+f"(d[15]), "+f"(d[16]), "+f"(d[17]), "+f"(d[18]), "+f"(d[19]), "+f"(d[20]), "+f"(d[21]), "+f"(d[22]), "+f"(d[23]), "+f"(d[24]), "+f"(d[25]), "+f"(d[26]), "+f"(d[27]), "+f"(d[28]), "+f"(d[29]), "+f"(d[30]), "+f"(d[31]), "+f"(d[32]), "+f"(d[33]), "+f"(d[34]), "+f"(d[35]), "+f"(d[36]), "+f"(d[37]), "+f"(d[38]), "+f"(d[39]), "+f"(d[40]), "+f"(d[41]), "+f"(d[42]), "+f"(d[43]), "+f"(d[44]), "+f"(d[45]), "+f"(d[46]), "+f"(d[47]), "+f"(d[48]), "+f"(d[49]), "+f"(d[50]), "+f"(d[51]), "+f"(d[52]), "+f"(d[53]), "+f"(d[54]), "+f"(d[55]), "+f"(d[56]), "+f"(d[57]), "+f"(d[58]), "+f"(d[59]), "+f"(d[60]), "+f"(d[61]), "+f"(d[62]), "+f"(d[63])
        : "l"(da), "l"(db), "r"(sc), "n"(TB));
}
template <int TB> __device__ __forceinline__ void wgmma_rs_n24(float (&d)[12], uint32_t a0, uint32_t a1, uint32_t a2, uint32_t a3, uint64_t db, int sc) {
    asm volatile("{\n.reg .pred p;\nsetp.ne.b32 p, %17, 0;\n"
        "wgmma.mma_async.sync.aligned.m64n24k16.f32.bf16.bf16 {%0, %1, %2, %3, %4, %5, %6, %7, %8, %9, %10, %11}, {%12, %13, %14, %15}, %16, p, 1, 1, %18;\n}\n"
        : "+f"(d[0]), "+f"(d[1]), "+f"(d[2]), "+f"(d[3]), "+f"(d[4]), "+f"(d[5]), "+f"(d[6]), "+f"(d[7]), "+f"(d[8]), "+f"(d[9]), "+f"(d[10]), "+f"(d[11])
        : "r"(a0), "r"(a1), "r"(a2), "r"(a3), "l"(db), "r"(sc), "n"(TB));
}
template <int TB> __device__ __forceinline__ void wgmma_rs_n64(float (&d)[32], uint32_t a0, uint32_t a1, uint32_t a2, uint32_t a3, uint64_t db, int sc) {
    asm volatile("{\n.reg .pred p;\nsetp.ne.b32 p, %37, 0;\n"
        "wgmma.mma_async.sync.aligned.m64n64k16.f32.bf16.bf16 {%0, %1, %2, %3, %4, %5, %6, %7, %8, %9, %10, %11, %12, %13, %14, %15, %16, %17, %18, %19, %20, %21, %22, %23, %24, %25, %26, %27, %28, %29, %30, %31}, {%32, %33, %34, %35}, %36, p, 1, 1, %38;\n}\n"
        : "+f"(d[0]), "+f"(d[1]), "+f"(d[2]), "+f"(d[3]), "+f"(d[4]), "+f"(d[5]), "+f"(d[6]), "+f"(d[7]), "+f"(d[8]), "+f"(d[9]), "+f"(d[10]), "+f"(d[11]), "+f"(d[12]), "+f"(d[13]), "+f"(d[14]), "+f"(d[15]), "+f"(d[16]), "+f"(d[17]), "+f"(d[18]), "+f"(d[19]), "+f"(d[20]), "+f"(d[21]), "+f"(d[22]), "+f"(d[23]), "+f"(d[24]), "+f"(d[25]), "+f"(d[26]), "+f"(d[27]), "+f"(d[28]), "+f"(d[29]), "+f"(d[30]), "+f"(d[31])
        : "r"(a0), "r"(a1), "r"(a2), "r"(a3), "l"(db), "r"(sc), "n"(TB));
}
template <int TB> __device__ __forceinline__ void wgmma_rs_n128(float (&d)[64], uint32_t a0, uint32_t a1, uint32_t a2, uint32_t a3, uint64_t db, int sc) {
    asm volatile("{\n.reg .pred p;\nsetp.ne.b32 p, %69, 0;\n"
        "wgmma.mma_async.sync.aligned.m64n128k16.f32.bf16.bf16 {%0, %1, %2, %3, %4, %5, %6, %7, %8, %9, %10, %11, %12, %13, %14, %15, %16, %17, %18, %19, %20, %21, %22, %23, %24, %25, %26, %27, %28, %29, %30, %31, %32, %33, %34, %35, %36, %37, %38, %39, %40, %41, %42, %43, %44, %45, %46, %47, %48, %49, %50, %51, %52, %53, %54, %55, %56, %57, %58, %59, %60, %61, %62, %63}, {%64, %65, %66, %67}, %68, p, 1, 1, %70;\n}\n"
        : "+f"(d[0]), "+f"(d[1]), "+f"(d[2]), "+f"(d[3]), "+f"(d[4]), "+f"(d[5]), "+f"(d[6]), "+f"(d[7]), "+f"(d[8]), "+f"(d[9]), "+f"(d[10]), "+f"(d[11]), "+f"(d[12]), "+f"(d[13]), "+f"(d[14]), "+f"(d[15]), "+f"(d[16]), "+f"(d[17]), "+f"(d[18]), "+f"(d[19]), "+f"(d[20]), "+f"(d[21]), "+f"(d[22]), "+f"(d[23]), "+f"(d[24]), "+f"(d[25]), "+f"(d[26]), "+f"(d[27]), "+f"(d[28]), "+f"(d[29]), "+f"(d[30]), "+f"(d[31]), "+f"(d[32]), "+f"(d[33]), "+f"(d[34]), "+f"(d[35]), "+f"(d[36]), "+f"(d[37]), "+f"(d[38]), "+f"(d[39]), "+f"(d[40]), "+f"(d[41]), "+f"(d[42]), "+f"(d[43]), "+f"(d[44]), "+f"(d[45]), "+f"(d[46]), "+f"(d[47]), "+f"(d[48]), "+f"(d[49]), "+f"(d[50]), "+f"(d[51]), "+f"(d[52]), "+f"(d[53]), "+f"(d[54]), "+f"(d[55]), "+f"(d[56]), "+f"(d[57]), "+f"(d[58]), "+f"(d[59]), "+f"(d[60]), "+f"(d[61]), "+f"(d[62]), "+f"(d[63])
        : "r"(a0), "r"(a1), "r"(a2), "r"(a3), "l"(db), "r"(sc), "n"(TB));
}

constexpr int P_NST = 6;
constexpr int P_A_BYTES = 9 * 8192;
constexpr int P_B_STAGE = 3 * 8192;
constexpr int P_SMEM = P_A_BYTES + P_NST * P_B_STAGE + 256 + 320;

template <int NB>
__device__ __forceinline__ void stage_tile(const uint32_t (&pk)[NB * 2], uint32_t base, int w, int lane) {
    const int r = w * 16 + (lane & 7) + ((lane >> 3) & 1) * 8;
#pragma unroll
    for (int b = 0; b < NB; b += 2) {
        const uint32_t a = base + (b >> 3) * 8192 + r * 128 + ((((b & 7) + (lane >> 4)) ^ (r & 7)) << 4);
        stmatrix_x4(a, pk[2 * b], pk[2 * b + 1], pk[2 * b + 2], pk[2 * b + 3]);
    }
}

__device__ __forceinline__ uint32_t hsub2_bf16(uint32_t a, uint32_t b) { uint32_t r; asm("sub.rn.bf16x2 %0, %1, %2;" : "=r"(r) : "r"(a), "r"(b)); return r; }

constexpr int KV_RAW = DM * 18 * 2;
constexpr int Q_THREADS = 416;

__device__ __forceinline__ void proj_mma(float (&acc)[32], int wg, uint32_t fullB, uint32_t emptyB, uint32_t fullA, bool wait_a, int lane) {
    const uint64_t dA = cdesc(0, 16, 1024, 1), dB = cdesc(P_A_BYTES, 8192, 1024, 1) + wg * 512;
#pragma unroll 1
    for (int kb = 0; kb < 9; kb++) {
        const int s = kb >= P_NST ? kb - P_NST : kb;
        if (wait_a) mbar_wait(fullA + kb * 8, 0);
        mbar_wait(fullB + s * 8, kb >= P_NST ? 1 : 0);
        wg_fence();
#pragma unroll
        for (int ks = 0; ks < 4; ks++) wgmma_ss_n64<1>(acc, dA + (kb * 512 + ks * 2), dB + (s * (P_B_STAGE >> 4) + ks * 128), (kb | ks) != 0);
        wg_commit();
        if (kb < 4) {
            wg_wait<1>();
            if (kb >= 1 && lane == 0) mbar_arrive(emptyB + (kb - 1) * 8);
        }
    }
    wg_wait<0>();
    pin(acc);
}

__global__ void __launch_bounds__(Q_THREADS, 1)
k_qkv(const __grid_constant__ CUtensorMap tmWq, const __grid_constant__ CUtensorMap tmQ, const __nv_bfloat16* __restrict__ x, const __nv_bfloat16* __restrict__ wk, const __nv_bfloat16* __restrict__ wv) {
    extern __shared__ __align__(1024) uint8_t smem[];
    const uint32_t sA = smem_u32(smem), sB = sA + P_A_BYTES, bars = sB + P_NST * P_B_STAGE;
    const uint32_t fullB = bars, emptyB = bars + 64, fullX = bars + 128, fullW = bars + 136;
    float* s_rstd = reinterpret_cast<float*>(smem + P_A_BYTES + P_NST * P_B_STAGE + 256);
    const int tid = threadIdx.x, warp = __shfl_sync(~0u, tid >> 5, 0), lane = tid & 31;
    const bool isQ = blockIdx.x < 96;
    const int m = isQ ? blockIdx.x / 3 : blockIdx.x - 96, cg = blockIdx.x % 3;
    if (tid == 0) TS(0, 0);
    if (warp == 12) {
        if (elect_one()) {
            mbar_init(fullX, 1);
            bar_init_fence();
            mbar_expect(fullX, P_A_BYTES);
            bulk_g2s(sA, x + (size_t)m * 64 * DM, P_A_BYTES, fullX);
            TS(0, 7);
            prefetch_map(&tmWq); prefetch_map(&tmQ);
            for (int i = 0; i < P_NST; i++) { mbar_init(fullB + i * 8, 1); mbar_init(emptyB + i * 8, 12); }
            mbar_init(fullW, 1);
            bar_init_fence();
            if (isQ) {
                for (int kb = 0; kb < P_NST; kb++) {
                    mbar_expect(fullB + kb * 8, P_B_STAGE);
                    for (int a = 0; a < 3; a++) tma_2d(sB + kb * P_B_STAGE + a * 8192, &tmWq, cg * 192 + a * 64, kb * 64, fullB + kb * 8);
                }
            } else {
                mbar_expect(fullW, 2 * KV_RAW);
                bulk_g2s(sB + 3 * P_B_STAGE, wk, KV_RAW, fullW);
                bulk_g2s(sB + 3 * P_B_STAGE + KV_RAW, wv, KV_RAW, fullW);
            }
        }
        __syncwarp();
    }
    check_smem_base(sA);
    __syncthreads();
    if (tid == 0) TS(0, 8);
    pdl_launch();
    if (warp == 12) {
        if (isQ && elect_one()) {
            for (int kb = P_NST; kb < 9; kb++) {
                const int s = kb - P_NST;
                mbar_wait(emptyB + s * 8, 0);
                mbar_expect(fullB + s * 8, P_B_STAGE);
                for (int a = 0; a < 3; a++) tma_2d(sB + s * P_B_STAGE + a * 8192, &tmWq, cg * 192 + a * 64, kb * 64, fullB + s * 8);
            }
        }
        return;
    }
    if (warp < 8) {
        const int row = tid >> 2, q = tid & 3, h0 = (row & 1) * 4;
        mbar_wait(fullX, 0);
        if (tid == 0) TS(0, 6);
        uint4 v[18];
        const uint32_t ra = sA + row * 1152 + (q + h0) * 16, rb = sA + row * 1152 + (q + 4 - h0) * 16;
#pragma unroll
        for (int kb = 0; kb < 9; kb++) {
            asm volatile("ld.shared.v4.b32 {%0, %1, %2, %3}, [%4];" : "=r"(v[2 * kb].x), "=r"(v[2 * kb].y), "=r"(v[2 * kb].z), "=r"(v[2 * kb].w) : "r"(ra + kb * 128));
            asm volatile("ld.shared.v4.b32 {%0, %1, %2, %3}, [%4];" : "=r"(v[2 * kb + 1].x), "=r"(v[2 * kb + 1].y), "=r"(v[2 * kb + 1].z), "=r"(v[2 * kb + 1].w) : "r"(rb + kb * 128));
        }
        float sum = 0.f, sum2 = 0.f, sq = 0.f, sq2 = 0.f;
#pragma unroll
        for (int i = 0; i < 18; i++) {
            const uint32_t w[4] = {v[i].x, v[i].y, v[i].z, v[i].w};
#pragma unroll
            for (int j = 0; j < 4; j++) { const float a = bf_lo(w[j]), b = bf_hi(w[j]); sum += a; sum2 += b; sq = fmaf(a, a, sq); sq2 = fmaf(b, b, sq2); }
        }
        named_sync(1, 256);
        sum += sum2; sq += sq2;
        sum += __shfl_xor_sync(~0u, sum, 1); sum += __shfl_xor_sync(~0u, sum, 2);
        sq += __shfl_xor_sync(~0u, sq, 1); sq += __shfl_xor_sync(~0u, sq, 2);
        if (tid == 0) TS(0, 4);
        const float mean = sum * (1.0f / DM);
        if (q == 0) s_rstd[row] = rsqrtf(fmaxf(sq * (1.0f / DM) - mean * mean, 0.f) + LN_EPS);
        const uint32_t mhi = pack_bf16(mean, mean);
        const float rem = mean - bf_lo(mhi);
        const uint32_t mlo = pack_bf16(rem, rem);
        const uint32_t wa = sA + row * 128 + (((q + h0) ^ (row & 7)) << 4), wb = sA + row * 128 + (((q + 4 - h0) ^ (row & 7)) << 4);
#pragma unroll
        for (int i = 0; i < 18; i++) {
            const uint32_t o0 = hsub2_bf16(hsub2_bf16(v[i].x, mhi), mlo), o1 = hsub2_bf16(hsub2_bf16(v[i].y, mhi), mlo);
            const uint32_t o2 = hsub2_bf16(hsub2_bf16(v[i].z, mhi), mlo), o3 = hsub2_bf16(hsub2_bf16(v[i].w, mhi), mlo);
            asm volatile("st.shared.v4.b32 [%0], {%1, %2, %3, %4};" ::"r"(((i & 1) ? wb : wa) + (i >> 1) * 8192), "r"(o0), "r"(o1), "r"(o2), "r"(o3) : "memory");
        }
    } else if (!isQ) {
        mbar_wait(fullW, 0);
        const uint32_t* raw = reinterpret_cast<const uint32_t*>(smem + P_A_BYTES + 3 * P_B_STAGE);
#pragma unroll 3
        for (int r = tid - 256; r < 2 * DM; r += 128) {
            uint32_t wr[9];
#pragma unroll
            for (int i = 0; i < 9; i++) wr[i] = raw[r * 9 + i];
            const int sel = r >= DM, k = r - sel * DM;
            uint8_t* dst = smem + P_A_BYTES + sel * 3 * 9216 + (k >> 3) * 128 + (k & 7) * 16;
            *reinterpret_cast<uint4*>(dst) = make_uint4(wr[0], wr[1], wr[2], wr[3]);
            *reinterpret_cast<uint4*>(dst + 9216) = make_uint4(wr[4], wr[5], wr[6], wr[7]);
            *reinterpret_cast<uint32_t*>(dst + 2 * 9216) = wr[8];
        }
    }
    proxy_fence();
    named_sync(2, 384);
    if (tid == 0) TS(0, 1);
    const int wg = warp >> 2, w = warp & 3, g = lane >> 2, t = lane & 3;
    const float rs0 = s_rstd[w * 16 + g], rs1 = s_rstd[w * 16 + g + 8];
    if (isQ) {
        const float c0 = rs0 * Q_SCALE, c1 = rs1 * Q_SCALE;
        float acc[32];
        proj_mma(acc, wg, fullB, emptyB, 0, false, lane);
        if (tid == 0) TS(0, 2);
        uint32_t pk[16];
#pragma unroll
        for (int i = 0; i < 8; i++) { pk[2 * i] = pack_bf16(acc[4 * i] * c0, acc[4 * i + 1] * c0); pk[2 * i + 1] = pack_bf16(acc[4 * i + 2] * c1, acc[4 * i + 3] * c1); }
        named_sync(2, 384);
        stage_tile<8>(pk, sA + wg * 8192, w, lane);
        proxy_fence();
        named_sync(3 + wg, 128);
        if (w == 0 && elect_one()) {
            tma_st_2d(&tmQ, cg * 192 + wg * 64, m * 64, sA + wg * 8192);
            bulk_commit();
            bulk_wait_all();
        }
    } else if (wg < 2) {
        float acc[12];
        const uint64_t dA = cdesc(0, 16, 1024, 1), dB = cdesc(P_A_BYTES, 128, 9216, 0) + wg * (3 * 9216 >> 4);
#pragma unroll
        for (int i = 0; i < 12; i++) acc[i] = 0.f;
        pin(acc);
        wg_fence();
#pragma unroll 1
        for (int kb = 0; kb < 9; kb++) {
#pragma unroll
            for (int ks = 0; ks < 4; ks++) wgmma_ss_n24<1>(acc, dA + (kb * 512 + ks * 2), dB + (kb * 4 + ks) * 16, 1);
        }
        wg_commit();
        wg_wait<0>();
        pin(acc);
        uint32_t pk[6];
#pragma unroll
        for (int b = 0; b < 3; b++) { pk[2 * b] = pack_bf16(acc[4 * b] * rs0, acc[4 * b + 1] * rs0); pk[2 * b + 1] = pack_bf16(acc[4 * b + 2] * rs1, acc[4 * b + 3] * rs1); }
        float n0 = 0.f, n1 = 0.f, vm = 0.f;
#pragma unroll
        for (int b = 0; b < 3; b++) {
            if (b < 2 || t == 0) {
                const float a = bf_lo(pk[2 * b]), c = bf_hi(pk[2 * b]), d = bf_lo(pk[2 * b + 1]), e = bf_hi(pk[2 * b + 1]);
                n0 = fmaf(a, a, fmaf(c, c, n0)); n1 = fmaf(d, d, fmaf(e, e, n1));
            }
        }
        n0 += __shfl_xor_sync(~0u, n0, 1); n0 += __shfl_xor_sync(~0u, n0, 2);
        n1 += __shfl_xor_sync(~0u, n1, 1); n1 += __shfl_xor_sync(~0u, n1, 2);
        vm = fmaxf(n0, n1);
        if (!(n0 == n0) || !(n1 == n1)) vm = __int_as_float(0x7F800000);
#pragma unroll
        for (int o = 4; o < 32; o <<= 1) vm = fmaxf(vm, __shfl_xor_sync(~0u, vm, o));
        if (t != 0) {
            uint32_t lo, hi;
            if (wg == 0) {
                const int grp = m * 8 + w * 2;
                const uint32_t c = t == 1 ? 0x42FE3F80u   : (t == 2 ? 0x00003BC0u   : 0u);
                lo = ((POLY_MASK >> (grp & 15)) & 1) ? c : 0u;
                hi = ((POLY_MASK >> ((grp + 1) & 15)) & 1) ? c : 0u;
            } else {
                lo = hi = t == 1 ? 0x00003F80u : 0u;
            }
            pk[4] = lo; pk[5] = hi;
        }
        uint32_t* dst = reinterpret_cast<uint32_t*>(wg == 0 ? g_kc : g_vc) + (m * 8 + w * 2) * 96 + g * 4 + t;
#pragma unroll
        for (int b = 0; b < 3; b++) { dst[b * 32] = pk[2 * b]; dst[96 + b * 32] = pk[2 * b + 1]; }
        if (lane == 0) g_kmax[m * 8 + warp] = (wg == 0) ? vm : (vm <= 1e24f ? 0.f : __int_as_float(0x7F800000));
    }
    if (tid == 0) TS(0, 3);
}

constexpr int A_THREADS = 512;
constexpr int A_NPIECE = 8;
constexpr int A_OFF_Q = 2 * KV_BYTES;
constexpr int A_OFF_BAR = A_OFF_Q + 8 * 4096;
constexpr int A_SMEM = A_OFF_BAR + 128;

__device__ __forceinline__ uint32_t exp2_pair_fixed(float lo, float hi, uint32_t dep) {
    const uint32_t G = __byte_perm(__float_as_uint(lo), __float_as_uint(hi), 0x5410);
    uint32_t Hh;
    asm("lop3.b32 %0, %1, 0x007F007F, %2, 0xC0;" : "=r"(Hh) : "r"(G), "r"(dep));
    const uint32_t tt = hfma2(Hh, 0xF96BF96Bu, 0x358C358Cu);
    return G - hfma2(tt, Hh, 0u);
}

__global__ void __launch_bounds__(A_THREADS, 1)
k_attn() {
    extern __shared__ __align__(1024) uint8_t smem[];
    pdl_launch();
    const uint32_t sK = smem_u32(smem), sV = sK + KV_BYTES, bars = sK + A_OFF_BAR;
    const int tid = threadIdx.x;
    check_smem_base(sK);
    if (tid == 0) TS(1, 0);
    if (tid == 0) {
        for (int i = 0; i < A_NPIECE; i++) mbar_init(bars + i * 8, 1);
        bar_init_fence();
    }
    __syncthreads();
    pdl_wait();
    if (tid == 0) TS(1, 1);
    const int wg = __shfl_sync(~0u, tid >> 7, 0), w = (tid >> 5) & 3, lane = tid & 31, g = lane >> 2, t = lane & 3;
    const uint32_t* q32 = reinterpret_cast<const uint32_t*>(g_q);
    int row = (blockIdx.x * 8 + wg) * 64 + w * 16 + g;
    uint32_t nq[2][6];
#pragma unroll
    for (int r = 0; r < 2; r++) {
        const uint32_t* q = q32 + (row + r * 256) * 9;
        nq[r][0] = q[t]; nq[r][1] = q[72 + t]; nq[r][2] = q[4 + t]; nq[r][3] = q[76 + t]; nq[r][4] = q[8]; nq[r][5] = q[80];
    }
    constexpr int PB = KV_BYTES / A_NPIECE;
    const float4 km0 = reinterpret_cast<const float4*>(g_kmax)[lane], km1 = reinterpret_cast<const float4*>(g_kmax)[32 + lane];
    if (tid < 32 && elect_one()) {
        for (int i = 0; i < 2; i++) {
            mbar_expect(bars + i * 8, 2 * PB);
            bulk_g2s(sK + i * PB, reinterpret_cast<const char*>(g_kc) + i * PB, PB, bars + i * 8);
            bulk_g2s(sV + i * PB, reinterpret_cast<const char*>(g_vc) + i * PB, PB, bars + i * 8);
        }
    }
    float kmax2 = fmaxf(fmaxf(fmaxf(km0.x, km0.y), fmaxf(km0.z, km0.w)), fmaxf(fmaxf(km1.x, km1.y), fmaxf(km1.z, km1.w)));
#pragma unroll
    for (int o = 1; o < 32; o <<= 1) kmax2 = fmaxf(kmax2, __shfl_xor_sync(~0u, kmax2, o));
    if (tid < 32 && elect_one()) {
        for (int i = 2; i < A_NPIECE; i++) {
            mbar_expect(bars + i * 8, 2 * PB);
            bulk_g2s(sK + i * PB, reinterpret_cast<const char*>(g_kc) + i * PB, PB, bars + i * 8);
            bulk_g2s(sV + i * PB, reinterpret_cast<const char*>(g_vc) + i * PB, PB, bars + i * 8);
        }
    }
    uint32_t unsafe_mask = 0;
#pragma unroll
    for (int r = 0; r < 2; r++) {
        const float a0 = bf_lo(nq[r][0]), a1 = bf_hi(nq[r][0]), a2 = bf_lo(nq[r][2]), a3 = bf_hi(nq[r][2]);
        const float b0 = bf_lo(nq[r][1]), b1 = bf_hi(nq[r][1]), b2 = bf_lo(nq[r][3]), b3 = bf_hi(nq[r][3]);
        float n0 = a0 * a0 + a1 * a1 + a2 * a2 + a3 * a3, n1 = b0 * b0 + b1 * b1 + b2 * b2 + b3 * b3;
        if (t == 0) {
            const float c0 = bf_lo(nq[r][4]), c1 = bf_hi(nq[r][4]), d0 = bf_lo(nq[r][5]), d1 = bf_hi(nq[r][5]);
            n0 += c0 * c0 + c1 * c1; n1 += d0 * d0 + d1 * d1;
        }
        n0 += __shfl_xor_sync(~0u, n0, 1); n0 += __shfl_xor_sync(~0u, n0, 2);
        n1 += __shfl_xor_sync(~0u, n1, 1); n1 += __shfl_xor_sync(~0u, n1, 2);
        const bool unsafe = !(fmaxf(n0, n1) * kmax2 <= FAST_BOUND * FAST_BOUND) || !(n0 == n0) || !(n1 == n1);
        uint32_t any;
        asm volatile("{\n.reg .pred p, q;\nsetp.ne.u32 p, %1, 0;\nbar.red.or.pred q, %2, 128, p;\nselp.u32 %0, 1, 0, q;\n}\n" : "=r"(any) : "r"((uint32_t)unsafe), "r"(wg + 1) : "memory");
        unsafe_mask |= any << r;
        const uint32_t cst = any ? 0u : (t == 1 ? 0x3F804780u : (t == 2 ? 0x00003F80u : 0u));
        const uint32_t sQ = sK + A_OFF_Q + (r * 4 + wg) * 4096 + (w * 2) * 512 + g * 16 + t * 4;
        asm volatile("st.shared.b32 [%0], %1;" ::"r"(sQ), "r"(nq[r][0]) : "memory");
        asm volatile("st.shared.b32 [%0], %1;" ::"r"(sQ + 512), "r"(nq[r][1]) : "memory");
        asm volatile("st.shared.b32 [%0], %1;" ::"r"(sQ + 128), "r"(nq[r][2]) : "memory");
        asm volatile("st.shared.b32 [%0], %1;" ::"r"(sQ + 640), "r"(nq[r][3]) : "memory");
        asm volatile("st.shared.b32 [%0], %1;" ::"r"(sQ + 256), "r"(t == 0 ? nq[r][4] : cst) : "memory");
        asm volatile("st.shared.b32 [%0], %1;" ::"r"(sQ + 768), "r"(t == 0 ? nq[r][5] : cst) : "memory");
        asm volatile("st.shared.b32 [%0], %1;" ::"r"(sQ + 384), "r"(0u) : "memory");
        asm volatile("st.shared.b32 [%0], %1;" ::"r"(sQ + 896), "r"(0u) : "memory");
    }
    unsafe_mask = __shfl_sync(~0u, unsafe_mask, 0);
    proxy_fence();
    named_sync(wg + 1, 128);
    if (tid == 0) TS(1, 7);
#pragma unroll 1
    for (int rep = 0; rep < 2; rep++, row += 256) {
        const uint32_t any_unsafe = (unsafe_mask >> rep) & 1;
        const uint64_t dQ0 = cdesc(A_OFF_Q, 128, 512, 0) + (rep * 4 + wg) * 256, dQ1 = dQ0 + 16;
        if (tid == 0) TS(1, 2 + rep * 2);
        float o[12];
#pragma unroll
        for (int i = 0; i < 12; i++) o[i] = 0.f;
        pin(o);
        uint64_t dK0 = cdesc(0, 128, 384, 0), dK1 = cdesc(256, 0, 384, 0), dV = cdesc(KV_BYTES, 384, 128, 0);
        if (!any_unsafe) {
            float s[64];
#pragma unroll 1
            for (int j = 0; j < 16; j++) {
                if (rep == 0 && (j & 1) == 0) mbar_wait(bars + (j >> 1) * 8, 0);
                wg_fence();
                wgmma_ss_n128<0>(s, dQ0, dK0, 0);
                wgmma_ss_n128<0>(s, dQ1, dK1, 1);
                wg_commit();
                dK0 += 16 * 384 >> 4; dK1 += 16 * 384 >> 4;
                wg_wait<0>();
                pin(s);
                uint32_t p[32];
#define CHAIN 6
                {
                    constexpr int NP = 2 * __builtin_popcount(POLY_MASK), NM = 32 - NP;
                    float e[64];
#pragma unroll
                    for (int i = 0; i < 32; i++)
                        if (!((POLY_MASK >> (i >> 1)) & 1)) { e[2 * i] = ex2(s[2 * i]); e[2 * i + 1] = ex2(s[2 * i + 1]); p[i] = pack_bf16(e[2 * i], e[2 * i + 1]); }
                    int ip = 0;
#pragma unroll
                    for (int i = 0; i < 32; i++) {
                        if ((POLY_MASK >> (i >> 1)) & 1) {
                            const int mm = (ip * 2 * NM) / NP - CHAIN;
                            uint32_t dep = 0;
                            if (CHAIN > 0 && mm >= 0) {
                                int cnt = 0;
#pragma unroll
                                for (int q = 0; q < 32; q++)
                                    if (!((POLY_MASK >> (q >> 1)) & 1)) { if (cnt == (mm >> 1)) dep = __float_as_uint(e[2 * q + (mm & 1)]); cnt++; }
                            }
                            p[i] = exp2_pair_fixed(s[2 * i], s[2 * i + 1], dep);
                            ip++;
                        }
                    }
                }
                pin(p);
                wg_fence();
#pragma unroll
                for (int k = 0; k < 8; k++) {
                    wgmma_rs_n24<1>(o, p[4 * k], p[4 * k + 1], p[4 * k + 2], p[4 * k + 3], dV + k * 48, 1);
                }
                wg_commit();
                dV += 16 * 384 >> 4;
                wg_wait<0>();
            }
        } else {
            float s[64];
            float m0 = -INFINITY, m1 = -INFINITY;
#pragma unroll 1
            for (int j = 0; j < 16; j++) {
                if (rep == 0 && (j & 1) == 0) mbar_wait(bars + (j >> 1) * 8, 0);
                wg_fence();
                wgmma_ss_n128<0>(s, dQ0, dK0, 0);
                wgmma_ss_n128<0>(s, dQ1, dK1, 1);
                wg_commit();
                dK0 += 16 * 384 >> 4; dK1 += 16 * 384 >> 4;
                wg_wait<0>();
                pin(s);
                float x0m = m0, x1m = m1;
#pragma unroll
                for (int b = 0; b < 16; b++) { x0m = fmaxf(x0m, fmaxf(s[4 * b], s[4 * b + 1])); x1m = fmaxf(x1m, fmaxf(s[4 * b + 2], s[4 * b + 3])); }
                x0m = fmaxf(x0m, __shfl_xor_sync(~0u, x0m, 1)); x0m = fmaxf(x0m, __shfl_xor_sync(~0u, x0m, 2));
                x1m = fmaxf(x1m, __shfl_xor_sync(~0u, x1m, 1)); x1m = fmaxf(x1m, __shfl_xor_sync(~0u, x1m, 2));
                const float c0 = ex2(m0 - x0m), c1 = ex2(m1 - x1m);
                m0 = x0m; m1 = x1m;
#pragma unroll
                for (int b = 0; b < 3; b++) { o[4 * b] *= c0; o[4 * b + 1] *= c0; o[4 * b + 2] *= c1; o[4 * b + 3] *= c1; }
                uint32_t p[32];
#pragma unroll
                for (int b = 0; b < 16; b++) {
                    p[2 * b] = pack_bf16(ex2(s[4 * b] - m0), ex2(s[4 * b + 1] - m0));
                    p[2 * b + 1] = pack_bf16(ex2(s[4 * b + 2] - m1), ex2(s[4 * b + 3] - m1));
                }
                pin(p); pin(o);
                wg_fence();
#pragma unroll
                for (int k = 0; k < 8; k++) wgmma_rs_n24<1>(o, p[4 * k], p[4 * k + 1], p[4 * k + 2], p[4 * k + 3], dV + k * 48, 1);
                wg_commit();
                dV += 16 * 384 >> 4;
                wg_wait<0>();
            }
        }
        pin(o);
        if (tid == 0) TS(1, 3 + rep * 2);
        const float l0 = __shfl_sync(~0u, o[8], (lane & ~3) | 1), l1 = __shfl_sync(~0u, o[10], (lane & ~3) | 1);
        const float i0 = 1.0f / l0, i1 = 1.0f / l1;
        uint32_t* o32 = reinterpret_cast<uint32_t*>(g_o);
        o32[row * 9 + t] = pack_bf16(o[0] * i0, o[1] * i0);
        o32[(row + 8) * 9 + t] = pack_bf16(o[2] * i1, o[3] * i1);
        o32[row * 9 + 4 + t] = pack_bf16(o[4] * i0, o[5] * i0);
        o32[(row + 8) * 9 + 4 + t] = pack_bf16(o[6] * i1, o[7] * i1);
        if (t == 0) { o32[row * 9 + 8] = pack_bf16(o[8] * i0, o[9] * i0); o32[(row + 8) * 9 + 8] = pack_bf16(o[10] * i1, o[11] * i1); }
    }
    if (tid == 0) TS(1, 6);
    if ((tid & 127) == 0) TS(1, 10 + wg);
}

constexpr int O_THREADS = 416;
constexpr int O_OFF_STAT = P_A_BYTES + P_NST * P_B_STAGE + 256;
constexpr int O_SMEM = O_OFF_STAT + 9 * 64 * 8;

__global__ void __cluster_dims__(3, 1, 1) __launch_bounds__(O_THREADS, 1)
k_oproj(const __grid_constant__ CUtensorMap tmO, const __grid_constant__ CUtensorMap tmWo, const __grid_constant__ CUtensorMap tmX2, const __grid_constant__ CUtensorMap tmOut, const __nv_bfloat16* __restrict__ x, const __nv_bfloat16* __restrict__ w1) {
    extern __shared__ __align__(1024) uint8_t smem[];
    const uint32_t sA = smem_u32(smem), sB = sA + P_A_BYTES, bars = sB + P_NST * P_B_STAGE;
    const uint32_t fullB = bars, emptyB = bars + 64, fullA = bars + 128;
    const int tid = threadIdx.x, warp = __shfl_sync(~0u, tid >> 5, 0), lane = tid & 31;
    const int m = blockIdx.x / 3, cg = blockIdx.x % 3;
    if (tid == 0) TS(2, 0);
    check_smem_base(sA);
    if (tid == 0) {
        prefetch_map(&tmO); prefetch_map(&tmWo); prefetch_map(&tmX2); prefetch_map(&tmOut);
        for (int i = 0; i < P_NST; i++) { mbar_init(fullB + i * 8, 1); mbar_init(emptyB + i * 8, 12); }
        for (int i = 0; i < 9; i++) mbar_init(fullA + i * 8, 1);
        bar_init_fence();
        for (int kb = 0; kb < 9; kb++) mbar_expect(fullA + kb * 8, 8192);
    }
    __syncthreads();
    pdl_launch();
    if (warp == 12) {
        if (elect_one()) {
            for (int kb = 0; kb < 9; kb++) {
                const int s = kb >= P_NST ? kb - P_NST : kb;
                if (kb == 2) {
                    pdl_wait();
                    TS(2, 1);
                    for (int ka = 0; ka < 9; ka++) tma_2d(sA + ka * 8192, &tmO, ka * 64, m * 64, fullA + ka * 8);
                }
                if (kb >= P_NST) mbar_wait(emptyB + s * 8, 0);
                mbar_expect(fullB + s * 8, P_B_STAGE);
                for (int a = 0; a < 3; a++) tma_2d(sB + s * P_B_STAGE + a * 8192, &tmWo, cg * 192 + a * 64, kb * 64, fullB + s * 8);
            }
            for (int i = 0; i < 6; i++) prefetch_l2(reinterpret_cast<const char*>(w1) + (size_t)blockIdx.x * (FF * DM * 2 / 96) + i * 9216, 9216);
        }
        return;
    }
    if (tid == 0) TS(2, 11);
    const int wg = warp >> 2, w = warp & 3, g = lane >> 2, t = lane & 3;
    uint32_t xr[16];
    {
        const uint32_t* x32 = reinterpret_cast<const uint32_t*>(x) + (((m * 64 + w * 16 + g) * DM + cg * 192 + wg * 64 + 2 * t) >> 1);
#pragma unroll
        for (int b = 0; b < 8; b++) { xr[2 * b] = __ldg(x32 + b * 4); xr[2 * b + 1] = __ldg(x32 + b * 4 + 4 * DM); }
    }
    float acc[32];
    proj_mma(acc, wg, fullB, emptyB, fullA, true, lane);
    if (tid == 0) TS(2, 2);
    named_sync(1, 384);
    float s0 = 0.f, q0 = 0.f, s1 = 0.f, q1 = 0.f;
#pragma unroll
    for (int b = 0; b < 8; b++) {
        const uint32_t xa = xr[2 * b], xb = xr[2 * b + 1];
        const uint32_t ha = pack_bf16(acc[4 * b] + bf_lo(xa), acc[4 * b + 1] + bf_hi(xa));
        const uint32_t hb = pack_bf16(acc[4 * b + 2] + bf_lo(xb), acc[4 * b + 3] + bf_hi(xb));
        xr[2 * b] = ha; xr[2 * b + 1] = hb;
        const float a = bf_lo(ha), c = bf_hi(ha), d = bf_lo(hb), e = bf_hi(hb);
        s0 += a + c; q0 = fmaf(a, a, fmaf(c, c, q0));
        s1 += d + e; q1 = fmaf(d, d, fmaf(e, e, q1));
    }
    s0 += __shfl_xor_sync(~0u, s0, 1); s0 += __shfl_xor_sync(~0u, s0, 2);
    q0 += __shfl_xor_sync(~0u, q0, 1); q0 += __shfl_xor_sync(~0u, q0, 2);
    s1 += __shfl_xor_sync(~0u, s1, 1); s1 += __shfl_xor_sync(~0u, s1, 2);
    q1 += __shfl_xor_sync(~0u, q1, 1); q1 += __shfl_xor_sync(~0u, q1, 2);
    const int r = w * 16 + g;
    const uint32_t sStat = sA + O_OFF_STAT;
    if (t < 3) {
        uint32_t dst;
        asm("mapa.shared::cluster.u32 %0, %1, %2;" : "=r"(dst) : "r"(sStat + ((cg * 3 + wg) * 64 + r) * 8), "r"(t));
        asm volatile("st.shared::cluster.v2.f32 [%0], {%1, %2};" ::"r"(dst), "f"(s0), "f"(q0) : "memory");
        asm volatile("st.shared::cluster.v2.f32 [%0], {%1, %2};" ::"r"(dst + 64), "f"(s1), "f"(q1) : "memory");
    }
    if (tid == 0) TS(2, 4);
    cluster_arrive();
    stage_tile<8>(xr, sA + wg * 8192, w, lane);
    proxy_fence();
    named_sync(2 + wg, 128);
    const bool leader = w == 0 && elect_one();
    if (leader) { tma_st_2d(&tmOut, cg * 192 + wg * 64, m * 64, sA + wg * 8192); bulk_commit(); }
    cluster_wait();
    if (tid == 0) TS(2, 5);
    s0 = q0 = s1 = q1 = 0.f;
#pragma unroll
    for (int p = 0; p < 9; p++) {
        float a, b, c, d;
        asm volatile("ld.shared.v2.f32 {%0, %1}, [%2];" : "=f"(a), "=f"(b) : "r"(sStat + (p * 64 + r) * 8));
        asm volatile("ld.shared.v2.f32 {%0, %1}, [%2];" : "=f"(c), "=f"(d) : "r"(sStat + (p * 64 + r + 8) * 8));
        s0 += a; q0 += b; s1 += c; q1 += d;
    }
    const float m0 = s0 * (1.0f / DM), m1 = s1 * (1.0f / DM);
    const float rs0 = rsqrtf(fmaxf(q0 * (1.0f / DM) - m0 * m0, 0.f) + LN_EPS), rs1 = rsqrtf(fmaxf(q1 * (1.0f / DM) - m1 * m1, 0.f) + LN_EPS);
    const float sc0 = 0.5f * rs0, sc1 = 0.5f * rs1, n0 = -m0 * sc0, n1 = -m1 * sc1;
#pragma unroll
    for (int b = 0; b < 8; b++) {
        xr[2 * b] = pack_bf16(fmaf(bf_lo(xr[2 * b]), sc0, n0), fmaf(bf_hi(xr[2 * b]), sc0, n0));
        xr[2 * b + 1] = pack_bf16(fmaf(bf_lo(xr[2 * b + 1]), sc1, n1), fmaf(bf_hi(xr[2 * b + 1]), sc1, n1));
    }
    stage_tile<8>(xr, sA + (3 + wg) * 8192, w, lane);
    proxy_fence();
    named_sync(2 + wg, 128);
    if (tid == 0) TS(2, 6);
    if (leader) {
        tma_st_2d(&tmX2, cg * 192 + wg * 64, m * 64, sA + (3 + wg) * 8192);
        bulk_commit();
        bulk_wait_all();
    }
    if (tid == 0) TS(2, 3);
}

constexpr int F_THREADS = 384;
constexpr int F_NST = 6;
constexpr int F_STAGE = 96 * 128;
constexpr int F_X_BYTES = 9 * 16384;
constexpr int F_OFF_ST = F_X_BYTES;
constexpr int F_OFF_BAR = F_OFF_ST + F_NST * F_STAGE;
constexpr int F_SMEM = F_OFF_BAR + 256;

__device__ __forceinline__ float tanh_hw(float x) { float y; asm("tanh.approx.f32 %0, %1;" : "=f"(y) : "f"(x)); return y; }
__host__ __device__ constexpr int piece_begin(int p) { return p == 0 ? 0 : 3 * p + 1; }
template <int P>
__device__ __forceinline__ void silu_s1(const float (&acc)[32], float (&tmp)[8]) {
#pragma unroll
    for (int i = 2 * piece_begin(P); i < 2 * piece_begin(P + 1); i++) tmp[i - 2 * piece_begin(P)] = tanh_hw(acc[i]);
}
template <int C, int P>
__device__ __forceinline__ void silu_s2(const float (&acc)[32], const float (&tmp)[8], uint32_t (&h1)[144]) {
#pragma unroll
    for (int i = piece_begin(P); i < piece_begin(P + 1); i++) {
        const int k = 2 * (i - piece_begin(P));
        h1[C * 16 + i] = pack_bf16(fmaf(acc[2 * i], tmp[k], acc[2 * i]), fmaf(acc[2 * i + 1], tmp[k + 1], acc[2 * i + 1]));
    }
}
template <int J>
__device__ __forceinline__ void silu_slot_last(const float (&prev)[32], float (&tmp)[2][8], uint32_t (&h1)[144]) {
    if constexpr (J >= 1 && J <= 4) {
#pragma unroll
        for (int i = 0; i < 4; i++) {
            const int q = 4 * (J - 1) + i;
            h1[128 + q] = pack_bf16(fmaf(prev[2 * q], tmp[(J - 1) & 1][2 * i], prev[2 * q]), fmaf(prev[2 * q + 1], tmp[(J - 1) & 1][2 * i + 1], prev[2 * q + 1]));
        }
    }
    if constexpr (J <= 3) {
#pragma unroll
        for (int i = 0; i < 8; i++) tmp[J & 1][i] = tanh_hw(prev[8 * J + i]);
        pin(tmp[J & 1]);
    }
}
template <int C, int J>
__device__ __forceinline__ void silu_slot(const float (&prev)[32], float (&tmp)[2][8], uint32_t (&h1)[144]) {
    if constexpr (J >= 1) silu_s2<C, J - 1>(prev, tmp[(J - 1) & 1], h1);
    if constexpr (J <= 4) { silu_s1<J>(prev, tmp[J & 1]); pin(tmp[J & 1]); }
}

struct FfnPipe {
    uint32_t full, empty;
    int lane;
    __device__ __forceinline__ void acquire(int s, uint32_t ph) const { mbar_wait(full + s * 8, ph); }
    __device__ __forceinline__ void release(int s) const { if (lane == 0) mbar_arrive(empty + s * 8); }
};

template <int C>
__device__ __forceinline__ void ffn_phase1_chunk(float (&cur)[32], float (&prev)[32], uint32_t (&h1)[144], const FfnPipe& pp, uint64_t dx, uint32_t fullX) {
    float tmp[2][8];
    const uint64_t dw = cdesc(F_OFF_ST, 8192, 1024, 1) + blockIdx.y * (C + 1);
    dx += blockIdx.y * C;
#pragma unroll
    for (int j = 0; j < 6; j++) {
        if (C == 0) { mbar_wait(fullX + ((6 * j) >> 2) * 8, 0); mbar_wait(fullX + ((6 * j + 5) >> 2) * 8, 0); }
        pp.acquire(j, C & 1);
        if (j == 0) pin(cur);
        wg_fence();
#pragma unroll
        for (int i = 0; i < 6; i++) {
            const int ks = 6 * j + i;
            wgmma_ss_n64<1>(cur, dx + ((ks >> 2) * 1024 + (ks & 3) * 2), dw + ((j * F_STAGE + i * 2048) >> 4), ks != 0);
        }
        wg_commit();
        if (C > 0 || j > 0) { wg_wait<1>(); pp.release((j + 5) % 6); }
        if (C > 0) {
            constexpr int CP = C > 0 ? C - 1 : 0;
            pin(prev);
            if (j == 0) silu_slot<CP, 0>(prev, tmp, h1);
            if (j == 1) silu_slot<CP, 1>(prev, tmp, h1);
            if (j == 2) silu_slot<CP, 2>(prev, tmp, h1);
            if (j == 3) silu_slot<CP, 3>(prev, tmp, h1);
            if (j == 4) silu_slot<CP, 4>(prev, tmp, h1);
            if (j == 5) silu_slot<CP, 5>(prev, tmp, h1);
        }
    }
}

__device__ __forceinline__ void ffn_stage_chunk(const float (&acc)[32], uint32_t stg, int w, int lane) {
    uint32_t pk[16];
#pragma unroll
    for (int i = 0; i < 16; i++) pk[i] = pack_bf16(acc[2 * i], acc[2 * i + 1]);
    stage_tile<8>(pk, stg, w, lane);
}
__device__ __forceinline__ void ffn_reduce_chunk(const CUtensorMap* tmOut, uint32_t stg, int col, int row, int w, int wgid, bool leader) {
    proxy_fence();
    if (w != 0) {
        asm volatile("bar.arrive %0, 128;" ::"r"(2 + wgid) : "memory");
    } else {
        named_sync(2 + wgid, 128);
        if (leader) { tma_red_2d(tmOut, col, row, stg); bulk_commit(); }
    }
}

template <bool FIRST>
__device__ __forceinline__ void ffn_phase2_chunk(float (&cur)[32], float (&prev)[32], uint32_t (&h1)[144], const FfnPipe& pp, uint32_t ph, const CUtensorMap* tmOut, uint32_t stg_prev, int col_prev, int row, int w, int lane, int wgid, bool leader) {
    const uint64_t dw = cdesc(F_OFF_ST, 8192, 1024, 1) + blockIdx.y * col_prev;
    float tmp[2][8];
#pragma unroll
    for (int j = 0; j < 6; j++) {
        pp.acquire(j, ph);
        if (j == 0) pin(cur);
        if (FIRST && j == 5) pin(h1);
        wg_fence();
#pragma unroll
        for (int i = 0; i < 6; i++) {
            const int f = (6 * j + i) * 4;
            wgmma_rs_n64<1>(cur, h1[f], h1[f + 1], h1[f + 2], h1[f + 3], dw + ((j * F_STAGE + i * 2048) >> 4), (j | i) != 0);
        }
        wg_commit();
        wg_wait<1>();
        pp.release((j + 5) % 6);
        if (FIRST) {
            pin(prev);
            if (j == 0) silu_slot_last<0>(prev, tmp, h1);
            if (j == 1) silu_slot_last<1>(prev, tmp, h1);
            if (j == 2) silu_slot_last<2>(prev, tmp, h1);
            if (j == 3) silu_slot_last<3>(prev, tmp, h1);
            if (j == 4) silu_slot_last<4>(prev, tmp, h1);
        } else {
            if (j == 0) { pin(prev); ffn_stage_chunk(prev, stg_prev, w, lane); }
            if (j == 1) ffn_reduce_chunk(tmOut, stg_prev, col_prev, row, w, wgid, leader);
        }
    }
}

__global__ void __launch_bounds__(F_THREADS, 1)
k_ffn(const __grid_constant__ CUtensorMap tmH, const __grid_constant__ CUtensorMap tmW1, const __grid_constant__ CUtensorMap tmW2, const __grid_constant__ CUtensorMap tmOut, const __nv_bfloat16* __restrict__ w2) {
    extern __shared__ __align__(1024) uint8_t smem[];
    const uint32_t sX = smem_u32(smem), sSt = sX + F_OFF_ST, bars = sX + F_OFF_BAR;
    const uint32_t full = bars, empty = bars + 64, fullX = bars + 128;
    const int tid = threadIdx.x, warp = __shfl_sync(~0u, tid >> 5, 0), lane = tid & 31;
#define FFN_MAP 1
    const int m = FFN_MAP == 0 ? (blockIdx.x & 15) : (FFN_MAP == 1 ? (blockIdx.x >> 3) : ((blockIdx.x >> 1) & 15));
    const int fs = FFN_MAP == 0 ? (blockIdx.x >> 4) : (FFN_MAP == 1 ? (blockIdx.x & 7) : ((blockIdx.x >> 5) * 2 + (blockIdx.x & 1)));
    if (tid == 0) TS(3, 0);
    check_smem_base(sX);
    if (tid == 0) {
        prefetch_map(&tmW1); prefetch_map(&tmH); prefetch_map(&tmW2); prefetch_map(&tmOut);
        for (int i = 0; i < F_NST; i++) { mbar_init(full + i * 8, 1); mbar_init(empty + i * 8, 8); }
        for (int i = 0; i < 9; i++) mbar_init(fullX + i * 8, 1);
        bar_init_fence();
        for (int kb = 0; kb < 9; kb++) mbar_expect(fullX + kb * 8, 16384);
    }
    __syncthreads();
    if (warp < 4) {
        asm volatile("setmaxnreg.dec.sync.aligned.u32 24;");
        if (warp == 1 && lane < 9) prefetch_l2(reinterpret_cast<const char*>(w2) + ((size_t)fs * 576 + m * 36 + lane * 4) * (DM * 2), 4 * DM * 2);
        if (warp == 0 && elect_one()) {
            int s = 0; uint32_t ph = 1;
            int c = 0, j = 0;
#pragma unroll 1
            for (int i = 0; i < 108; i++) {
                if (i == 54) c = fs;
                mbar_wait(empty + s * 8, ph);
                mbar_expect(full + s * 8, F_STAGE);
                if (i < 54) tma_2d(sSt + s * F_STAGE, &tmW1, fs * 576 + c * 64, j * 96, full + s * 8);
                else tma_2d(sSt + s * F_STAGE, &tmW2, c * 64, fs * 576 + j * 96, full + s * 8);
                if (++j == 6) { j = 0; if (++c == 9) c = 0; }
                if (++s == F_NST) { s = 0; ph ^= 1; }
            }
        }
    } else {
        asm volatile("setmaxnreg.inc.sync.aligned.u32 240;");
        const int wgid = (warp >> 2) - 1, w = warp & 3;
        pdl_wait();
        if (tid == 128) TS(3, 1);
        if (warp == 4 && elect_one()) {
            for (int kb = 0; kb < 9; kb++) tma_2d(sX + kb * 16384, &tmH, kb * 64, m * 128, fullX + kb * 8);
        }
        __syncwarp();
        FfnPipe pp{full, empty, lane};
        const uint64_t xlo = cdesc(0, 16, 1024, 1) + wgid * 512;
        uint32_t h1[144];
        float acc0[32], acc1[32];
        ffn_phase1_chunk<0>(acc0, acc1, h1, pp, xlo, fullX);
        if (tid == 128) TS(3, 2);
        ffn_phase1_chunk<1>(acc1, acc0, h1, pp, xlo, fullX);
        ffn_phase1_chunk<2>(acc0, acc1, h1, pp, xlo, fullX);
        ffn_phase1_chunk<3>(acc1, acc0, h1, pp, xlo, fullX);
        ffn_phase1_chunk<4>(acc0, acc1, h1, pp, xlo, fullX);
        ffn_phase1_chunk<5>(acc1, acc0, h1, pp, xlo, fullX);
        ffn_phase1_chunk<6>(acc0, acc1, h1, pp, xlo, fullX);
        ffn_phase1_chunk<7>(acc1, acc0, h1, pp, xlo, fullX);
        ffn_phase1_chunk<8>(acc0, acc1, h1, pp, xlo, fullX);
        if (tid == 128) TS(3, 3);
        const int row = m * 128 + wgid * 64;
        const uint32_t stg = sX + wgid * 8192;
        int c = fs, cprev = 0;
        const bool leader = w == 0 && elect_one();
        ffn_phase2_chunk<true>(acc1, acc0, h1, pp, 1, &tmOut, 0, 0, row, w, lane, wgid, leader);
        cprev = c; if (++c == 9) c = 0;
#pragma unroll 1
        for (int j = 1; j < 9; j += 2) {
            ffn_phase2_chunk<false>(acc0, acc1, h1, pp, 0, &tmOut, stg + (j - 1) * 16384, cprev * 64, row, w, lane, wgid, leader);
            cprev = c; if (++c == 9) c = 0;
            ffn_phase2_chunk<false>(acc1, acc0, h1, pp, 1, &tmOut, stg + j * 16384, cprev * 64, row, w, lane, wgid, leader);
            cprev = c; if (++c == 9) c = 0;
        }
        wg_wait<0>();
        pin(acc1);
        ffn_stage_chunk(acc1, stg + 8 * 16384, w, lane);
        ffn_reduce_chunk(&tmOut, stg + 8 * 16384, cprev * 64, row, w, wgid, leader);
        if (tid == 128) TS(3, 4);
        if (leader) bulk_wait_all();
        if (tid == 128) TS(3, 5);
    }
}

typedef CUresult (*EncodeFn)(CUtensorMap*, CUtensorMapDataType, cuuint32_t, void*, const cuuint64_t*, const cuuint64_t*, const cuuint32_t*, const cuuint32_t*,
                             CUtensorMapInterleave, CUtensorMapSwizzle, CUtensorMapL2promotion, CUtensorMapFloatOOBfill);

CUtensorMap make_map(EncodeFn enc, const void* base, int rows, int cols, int box_rows) {
    CUtensorMap tm;
    cuuint64_t dims[2] = {(cuuint64_t)cols, (cuuint64_t)rows};
    cuuint64_t strides[1] = {(cuuint64_t)cols * 2};
    cuuint32_t box[2] = {64, (cuuint32_t)box_rows};
    cuuint32_t es[2] = {1, 1};
    enc(&tm, CU_TENSOR_MAP_DATA_TYPE_BFLOAT16, 2, const_cast<void*>(base), dims, strides, box, es, CU_TENSOR_MAP_INTERLEAVE_NONE,
        CU_TENSOR_MAP_SWIZZLE_128B, CU_TENSOR_MAP_L2_PROMOTION_L2_256B, CU_TENSOR_MAP_FLOAT_OOB_FILL_NONE);
    return tm;
}

template <typename... KArgs, typename... Args>
void launch(void (*kern)(KArgs...), int grid, int block, int smem, bool pdl, Args... args) {
    cudaLaunchConfig_t cfg = {};
    cfg.gridDim = dim3(grid); cfg.blockDim = dim3(block); cfg.dynamicSmemBytes = smem; cfg.stream = cudaStreamPerThread;
    cudaLaunchAttribute at[1];
    at[0].id = cudaLaunchAttributeProgrammaticStreamSerialization;
    at[0].val.programmaticStreamSerializationAllowed = 1;
    cfg.attrs = at; cfg.numAttrs = pdl ? 1 : 0;
    cudaLaunchKernelEx(&cfg, kern, KArgs(args)...);
}

}

#define USE_PDL 1

extern "C" void kernel_launch(void* const* d_in, const int* in_sizes, int n_in, void* d_out, int out_size) {
    const __nv_bfloat16* x = (const __nv_bfloat16*)d_in[0];
    const __nv_bfloat16* wq = (const __nv_bfloat16*)d_in[1];
    const __nv_bfloat16* wk = (const __nv_bfloat16*)d_in[2];
    const __nv_bfloat16* wv = (const __nv_bfloat16*)d_in[3];
    const __nv_bfloat16* wo = (const __nv_bfloat16*)d_in[4];
    const __nv_bfloat16* w1 = (const __nv_bfloat16*)d_in[6];
    const __nv_bfloat16* w2 = (const __nv_bfloat16*)d_in[7];
    __nv_bfloat16* out = (__nv_bfloat16*)d_out;

    static EncodeFn enc = nullptr;
    static void *p_o = nullptr, *p_h = nullptr, *p_q = nullptr;
    if (!enc) {
        cudaDriverEntryPointQueryResult qr;
        cudaGetDriverEntryPoint("cuTensorMapEncodeTiled", (void**)&enc, cudaEnableDefault, &qr);
        cudaGetSymbolAddress(&p_o, g_o);
        cudaGetSymbolAddress(&p_h, g_x2);
        cudaGetSymbolAddress(&p_q, g_q);
        cudaFuncSetAttribute(k_qkv, cudaFuncAttributeMaxDynamicSharedMemorySize, P_SMEM);
        cudaFuncSetAttribute(k_attn, cudaFuncAttributeMaxDynamicSharedMemorySize, A_SMEM);
        cudaFuncSetAttribute(k_oproj, cudaFuncAttributeMaxDynamicSharedMemorySize, O_SMEM);
        cudaFuncSetAttribute(k_ffn, cudaFuncAttributeMaxDynamicSharedMemorySize, F_SMEM);
    }
    const CUtensorMap tmWq = make_map(enc, wq, DM, DM, 64);
    const CUtensorMap tmWo = make_map(enc, wo, DM, DM, 64);
    const CUtensorMap tmO = make_map(enc, p_o, SEQ, DM, 64);
    const CUtensorMap tmH64 = make_map(enc, p_h, SEQ, DM, 64);
    const CUtensorMap tmH = make_map(enc, p_h, SEQ, DM, 128);
    const CUtensorMap tmQ = make_map(enc, p_q, SEQ, DM, 64);
    const CUtensorMap tmW1 = make_map(enc, w1, DM, FF, 96);
    const CUtensorMap tmW2 = make_map(enc, w2, FF, DM, 96);
    const CUtensorMap tmOut = make_map(enc, out, SEQ, DM, 64);

    launch(k_qkv, 128, Q_THREADS, P_SMEM, false, tmWq, tmQ, x, wk, wv);
    launch(k_attn, 128, A_THREADS, A_SMEM, USE_PDL);
    launch(k_oproj, 96, O_THREADS, O_SMEM, USE_PDL, tmO, tmWo, tmH64, tmOut, x, w1);
    launch(k_ffn, 128, F_THREADS, F_SMEM, USE_PDL, tmH, tmW1, tmW2, tmOut, w2);
}
```

```cpp
#include <cuda_runtime.h>
#include <cuda_bf16.h>
#include <cuda.h>
#include <stdint.h>

namespace {

constexpr int SEQ = 2048, DM = 576, FF = 4608;
constexpr int KV_BYTES = SEQ * 48;
constexpr float LN_EPS = 1e-5f;
constexpr float LOG2E = 1.4426950408889634f;
constexpr float Q_SCALE = 0.23570226039551584f * LOG2E;

#define POLY_MASK_V 0xB6DBu
constexpr uint32_t POLY_MASK = POLY_MASK_V;
#define FAST_BOUND_V 60.0f
constexpr float FAST_BOUND = FAST_BOUND_V;

__device__ __align__(1024) __nv_bfloat16 g_q[SEQ * DM];
__device__ __align__(1024) uint4 g_kc[KV_BYTES / 16];
__device__ __align__(1024) uint4 g_vc[KV_BYTES / 16];
__device__ __align__(16) float g_kmax[256];
__device__ __align__(1024) __nv_bfloat16 g_o[SEQ * DM];
__device__ __align__(1024) __nv_bfloat16 g_x2[SEQ * DM];

__device__ __forceinline__ uint32_t smem_u32(const void* p) { return (uint32_t)__cvta_generic_to_shared(p); }
__device__ __forceinline__ void wg_fence() { asm volatile("wgmma.fence.sync.aligned;" ::: "memory"); }
__device__ __forceinline__ void wg_commit() { asm volatile("wgmma.commit_group.sync.aligned;" ::: "memory"); }
template <int N> __device__ __forceinline__ void wg_wait() { asm volatile("wgmma.wait_group.sync.aligned %0;" ::"n"(N) : "memory"); }
template <int N> __device__ __forceinline__ void pin(float (&r)[N]) {
#pragma unroll
    for (int i = 0; i < N; i++) asm volatile("" : "+f"(r[i])::"memory");
}
template <int N> __device__ __forceinline__ void pin(uint32_t (&r)[N]) {
#pragma unroll
    for (int i = 0; i < N; i++) asm volatile("" : "+r"(r[i])::"memory");
}
constexpr uint32_t SMEM0 = 0x400;
__host__ __device__ constexpr uint64_t cdesc(uint32_t off, uint32_t lbo, uint32_t sbo, uint32_t swz) {
    return (uint64_t)(((SMEM0 + off) & 0x3FFFF) >> 4) | ((uint64_t)(lbo >> 4) << 16) | ((uint64_t)(sbo >> 4) << 32) | ((uint64_t)swz << 62);
}
__device__ __forceinline__ void check_smem_base(uint32_t base) { if ((base & 0x3FFFF) != SMEM0) __trap(); }

__device__ __forceinline__ void mbar_init(uint32_t bar, int cnt) { asm volatile("mbarrier.init.shared::cta.b64 [%0], %1;" ::"r"(bar), "r"(cnt) : "memory"); }
__device__ __forceinline__ void mbar_expect(uint32_t bar, int bytes) { asm volatile("mbarrier.arrive.expect_tx.shared::cta.b64 _, [%0], %1;" ::"r"(bar), "r"(bytes) : "memory"); }
__device__ __forceinline__ void mbar_arrive(uint32_t bar) { asm volatile("mbarrier.arrive.shared::cta.b64 _, [%0];" ::"r"(bar) : "memory"); }
__device__ __forceinline__ void mbar_wait(uint32_t bar, uint32_t parity) {
    asm volatile(
        "{\n.reg .pred p;\n.reg .u32 n;\nmov.u32 n, 0;\n"
        "LAB_WAIT:\n"
        "mbarrier.try_wait.parity.shared::cta.b64 p, [%0], %1;\n"
        "@p bra DONE;\n"
        "add.u32 n, n, 1;\n"
        "setp.lt.u32 p, n, 4000000;\n"
        "@p bra LAB_WAIT;\n"
        "trap;\n"
        "DONE:\n}\n" ::"r"(bar), "r"(parity) : "memory");
}
__device__ __forceinline__ void bar_init_fence() {
    asm volatile("fence.mbarrier_init.release.cluster;" ::: "memory");
    asm volatile("fence.proxy.async.shared::cta;" ::: "memory");
}
__device__ __forceinline__ void proxy_fence() { asm volatile("fence.proxy.async.shared::cta;" ::: "memory"); }
__device__ __forceinline__ void named_sync(int id, int n) { asm volatile("bar.sync %0, %1;" ::"r"(id), "r"(n) : "memory"); }
__device__ __forceinline__ void bulk_g2s(uint32_t dst, const void* src, int bytes, uint32_t bar) {
    asm volatile("cp.async.bulk.shared::cluster.global.mbarrier::complete_tx::bytes [%0], [%1], %2, [%3];" ::"r"(dst), "l"(src), "r"(bytes), "r"(bar) : "memory");
}
__device__ __forceinline__ void tma_2d(uint32_t dst, const CUtensorMap* tm, int c0, int c1, uint32_t bar) {
    asm volatile("cp.async.bulk.tensor.2d.shared::cluster.global.mbarrier::complete_tx::bytes [%0], [%1, {%3, %4}], [%2];" ::"r"(dst), "l"(tm), "r"(bar), "r"(c0), "r"(c1) : "memory");
}
__device__ __forceinline__ void cluster_arrive() { asm volatile("barrier.cluster.arrive.release.aligned;" ::: "memory"); }
__device__ __forceinline__ void cluster_wait() { asm volatile("barrier.cluster.wait.acquire.aligned;" ::: "memory"); }
__device__ __forceinline__ void tma_red_2d(const CUtensorMap* tm, int c0, int c1, uint32_t src) {
    asm volatile("cp.reduce.async.bulk.tensor.2d.global.shared::cta.add.tile.bulk_group [%0, {%2, %3}], [%1];" ::"l"(tm), "r"(src), "r"(c0), "r"(c1) : "memory");
}
__device__ __forceinline__ void tma_st_2d(const CUtensorMap* tm, int c0, int c1, uint32_t src) {
    asm volatile("cp.async.bulk.tensor.2d.global.shared::cta.tile.bulk_group [%0, {%2, %3}], [%1];" ::"l"(tm), "r"(src), "r"(c0), "r"(c1) : "memory");
}
__device__ __forceinline__ void bulk_commit() { asm volatile("cp.async.bulk.commit_group;" ::: "memory"); }
__device__ __forceinline__ void bulk_wait_all() { asm volatile("cp.async.bulk.wait_group.read 0;" ::: "memory"); }
__device__ __forceinline__ bool elect_one() {
    uint32_t p;
    asm volatile("{\n.reg .pred P;\nelect.sync _|P, 0xffffffff;\nselp.b32 %0, 1, 0, P;\n}\n" : "=r"(p));
    return p != 0;
}
__device__ __forceinline__ void prefetch_l2(const void* p, int bytes) { asm volatile("cp.async.bulk.prefetch.L2.global [%0], %1;" ::"l"(p), "r"(bytes) : "memory"); }
__device__ __forceinline__ void prefetch_map(const CUtensorMap* tm) { asm volatile("prefetch.tensormap [%0];" ::"l"(tm) : "memory"); }
__device__ __forceinline__ void pdl_launch() { asm volatile("griddepcontrol.launch_dependents;" ::: "memory"); }
__device__ __forceinline__ void pdl_wait() { asm volatile("griddepcontrol.wait;" ::: "memory"); }
__device__ __forceinline__ float ex2(float x) { float y; asm("ex2.approx.ftz.f32 %0, %1;" : "=f"(y) : "f"(x)); return y; }
__device__ __forceinline__ uint32_t pack_bf16(float lo, float hi) { uint32_t r; asm("cvt.rn.bf16x2.f32 %0, %1, %2;" : "=r"(r) : "f"(hi), "f"(lo)); return r; }
__device__ __forceinline__ float bf_lo(uint32_t v) { return __uint_as_float(v << 16); }
__device__ __forceinline__ float bf_hi(uint32_t v) { return __uint_as_float(v & 0xFFFF0000u); }
__device__ __forceinline__ uint32_t hfma2(uint32_t a, uint32_t b, uint32_t c) { uint32_t r; asm("fma.rn.f16x2 %0, %1, %2, %3;" : "=r"(r) : "r"(a), "r"(b), "r"(c)); return r; }
__device__ __forceinline__ void stmatrix_x4(uint32_t addr, uint32_t r0, uint32_t r1, uint32_t r2, uint32_t r3) {
    asm volatile("stmatrix.sync.aligned.m8n8.x4.shared.b16 [%0], {%1, %2, %3, %4};" ::"r"(addr), "r"(r0), "r"(r1), "r"(r2), "r"(r3) : "memory");
}

template <int TB> __device__ __forceinline__ void wgmma_ss_n24(float (&d)[12], uint64_t da, uint64_t db, int sc) {
    asm volatile("{\n.reg .pred p;\nsetp.ne.b32 p, %14, 0;\n"
        "wgmma.mma_async.sync.aligned.m64n24k16.f32.bf16.bf16 {%0, %1, %2, %3, %4, %5, %6, %7, %8, %9, %10, %11}, %12, %13, p, 1, 1, 0, %15;\n}\n"
        : "+f"(d[0]), "+f"(d[1]), "+f"(d[2]), "+f"(d[3]), "+f"(d[4]), "+f"(d[5]), "+f"(d[6]), "+f"(d[7]), "+f"(d[8]), "+f"(d[9]), "+f"(d[10]), "+f"(d[11])
        : "l"(da), "l"(db), "r"(sc), "n"(TB));
}
template <int TB> __device__ __forceinline__ void wgmma_ss_n64(float (&d)[32], uint64_t da, uint64_t db, int sc) {
    asm volatile("{\n.reg .pred p;\nsetp.ne.b32 p, %34, 0;\n"
        "wgmma.mma_async.sync.aligned.m64n64k16.f32.bf16.bf16 {%0, %1, %2, %3, %4, %5, %6, %7, %8, %9, %10, %11, %12, %13, %14, %15, %16, %17, %18, %19, %20, %21, %22, %23, %24, %25, %26, %27, %28, %29, %30, %31}, %32, %33, p, 1, 1, 0, %35;\n}\n"
        : "+f"(d[0]), "+f"(d[1]), "+f"(d[2]), "+f"(d[3]), "+f"(d[4]), "+f"(d[5]), "+f"(d[6]), "+f"(d[7]), "+f"(d[8]), "+f"(d[9]), "+f"(d[10]), "+f"(d[11]), "+f"(d[12]), "+f"(d[13]), "+f"(d[14]), "+f"(d[15]), "+f"(d[16]), "+f"(d[17]), "+f"(d[18]), "+f"(d[19]), "+f"(d[20]), "+f"(d[21]), "+f"(d[22]), "+f"(d[23]), "+f"(d[24]), "+f"(d[25]), "+f"(d[26]), "+f"(d[27]), "+f"(d[28]), "+f"(d[29]), "+f"(d[30]), "+f"(d[31])
        : "l"(da), "l"(db), "r"(sc), "n"(TB));
}
template <int TB> __device__ __forceinline__ void wgmma_ss_n128(float (&d)[64], uint64_t da, uint64_t db, int sc) {
    asm volatile("{\n.reg .pred p;\nsetp.ne.b32 p, %66, 0;\n"
        "wgmma.mma_async.sync.aligned.m64n128k16.f32.bf16.bf16 {%0, %1, %2, %3, %4, %5, %6, %7, %8, %9, %10, %11, %12, %13, %14, %15, %16, %17, %18, %19, %20, %21, %22, %23, %24, %25, %26, %27, %28, %29, %30, %31, %32, %33, %34, %35, %36, %37, %38, %39, %40, %41, %42, %43, %44, %45, %46, %47, %48, %49, %50, %51, %52, %53, %54, %55, %56, %57, %58, %59, %60, %61, %62, %63}, %64, %65, p, 1, 1, 0, %67;\n}\n"
        : "+f"(d[0]), "+f"(d[1]), "+f"(d[2]), "+f"(d[3]), "+f"(d[4]), "+f"(d[5]), "+f"(d[6]), "+f"(d[7]), "+f"(d[8]), "+f"(d[9]), "+f"(d[10]), "+f"(d[11]), "+f"(d[12]), "+f"(d[13]), "+f"(d[14]), "+f"(d[15]), "+f"(d[16]), "+f"(d[17]), "+f"(d[18]), "+f"(d[19]), "+f"(d[20]), "+f"(d[21]), "+f"(d[22]), "+f"(d[23]), "+f"(d[24]), "+f"(d[25]), "+f"(d[26]), "+f"(d[27]), "+f"(d[28]), "+f"(d[29]), "+f"(d[30]), "+f"(d[31]), "+f"(d[32]), "+f"(d[33]), "+f"(d[34]), "+f"(d[35]), "+f"(d[36]), "+f"(d[37]), "+f"(d[38]), "+f"(d[39]), "+f"(d[40]), "+f"(d[41]), "+f"(d[42]), "+f"(d[43]), "+f"(d[44]), "+f"(d[45]), "+f"(d[46]), "+f"(d[47]), "+f"(d[48]), "+f"(d[49]), "+f"(d[50]), "+f"(d[51]), "+f"(d[52]), "+f"(d[53]), "+f"(d[54]), "+f"(d[55]), "+f"(d[56]), "+f"(d[57]), "+f"(d[58]), "+f"(d[59]), "+f"(d[60]), "+f"(d[61]), "+f"(d[62]), "+f"(d[63])
        : "l"(da), "l"(db), "r"(sc), "n"(TB));
}
template <int TB> __device__ __forceinline__ void wgmma_rs_n24(float (&d)[12], uint32_t a0, uint32_t a1, uint32_t a2, uint32_t a3, uint64_t db, int sc) {
    asm volatile("{\n.reg .pred p;\nsetp.ne.b32 p, %17, 0;\n"
        "wgmma.mma_async.sync.aligned.m64n24k16.f32.bf16.bf16 {%0, %1, %2, %3, %4, %5, %6, %7, %8, %9, %10, %11}, {%12, %13, %14, %15}, %16, p, 1, 1, %18;\n}\n"
        : "+f"(d[0]), "+f"(d[1]), "+f"(d[2]), "+f"(d[3]), "+f"(d[4]), "+f"(d[5]), "+f"(d[6]), "+f"(d[7]), "+f"(d[8]), "+f"(d[9]), "+f"(d[10]), "+f"(d[11])
        : "r"(a0), "r"(a1), "r"(a2), "r"(a3), "l"(db), "r"(sc), "n"(TB));
}
template <int TB> __device__ __forceinline__ void wgmma_rs_n64(float (&d)[32], uint32_t a0, uint32_t a1, uint32_t a2, uint32_t a3, uint64_t db, int sc) {
    asm volatile("{\n.reg .pred p;\nsetp.ne.b32 p, %37, 0;\n"
        "wgmma.mma_async.sync.aligned.m64n64k16.f32.bf16.bf16 {%0, %1, %2, %3, %4, %5, %6, %7, %8, %9, %10, %11, %12, %13, %14, %15, %16, %17, %18, %19, %20, %21, %22, %23, %24, %25, %26, %27, %28, %29, %30, %31}, {%32, %33, %34, %35}, %36, p, 1, 1, %38;\n}\n"
        : "+f"(d[0]), "+f"(d[1]), "+f"(d[2]), "+f"(d[3]), "+f"(d[4]), "+f"(d[5]), "+f"(d[6]), "+f"(d[7]), "+f"(d[8]), "+f"(d[9]), "+f"(d[10]), "+f"(d[11]), "+f"(d[12]), "+f"(d[13]), "+f"(d[14]), "+f"(d[15]), "+f"(d[16]), "+f"(d[17]), "+f"(d[18]), "+f"(d[19]), "+f"(d[20]), "+f"(d[21]), "+f"(d[22]), "+f"(d[23]), "+f"(d[24]), "+f"(d[25]), "+f"(d[26]), "+f"(d[27]), "+f"(d[28]), "+f"(d[29]), "+f"(d[30]), "+f"(d[31])
        : "r"(a0), "r"(a1), "r"(a2), "r"(a3), "l"(db), "r"(sc), "n"(TB));
}
template <int TB> __device__ __forceinline__ void wgmma_rs_n128(float (&d)[64], uint32_t a0, uint32_t a1, uint32_t a2, uint32_t a3, uint64_t db, int sc) {
    asm volatile("{\n.reg .pred p;\nsetp.ne.b32 p, %69, 0;\n"
        "wgmma.mma_async.sync.aligned.m64n128k16.f32.bf16.bf16 {%0, %1, %2, %3, %4, %5, %6, %7, %8, %9, %10, %11, %12, %13, %14, %15, %16, %17, %18, %19, %20, %21, %22, %23, %24, %25, %26, %27, %28, %29, %30, %31, %32, %33, %34, %35, %36, %37, %38, %39, %40, %41, %42, %43, %44, %45, %46, %47, %48, %49, %50, %51, %52, %53, %54, %55, %56, %57, %58, %59, %60, %61, %62, %63}, {%64, %65, %66, %67}, %68, p, 1, 1, %70;\n}\n"
        : "+f"(d[0]), "+f"(d[1]), "+f"(d[2]), "+f"(d[3]), "+f"(d[4]), "+f"(d[5]), "+f"(d[6]), "+f"(d[7]), "+f"(d[8]), "+f"(d[9]), "+f"(d[10]), "+f"(d[11]), "+f"(d[12]), "+f"(d[13]), "+f"(d[14]), "+f"(d[15]), "+f"(d[16]), "+f"(d[17]), "+f"(d[18]), "+f"(d[19]), "+f"(d[20]), "+f"(d[21]), "+f"(d[22]), "+f"(d[23]), "+f"(d[24]), "+f"(d[25]), "+f"(d[26]), "+f"(d[27]), "+f"(d[28]), "+f"(d[29]), "+f"(d[30]), "+f"(d[31]), "+f"(d[32]), "+f"(d[33]), "+f"(d[34]), "+f"(d[35]), "+f"(d[36]), "+f"(d[37]), "+f"(d[38]), "+f"(d[39]), "+f"(d[40]), "+f"(d[41]), "+f"(d[42]), "+f"(d[43]), "+f"(d[44]), "+f"(d[45]), "+f"(d[46]), "+f"(d[47]), "+f"(d[48]), "+f"(d[49]), "+f"(d[50]), "+f"(d[51]), "+f"(d[52]), "+f"(d[53]), "+f"(d[54]), "+f"(d[55]), "+f"(d[56]), "+f"(d[57]), "+f"(d[58]), "+f"(d[59]), "+f"(d[60]), "+f"(d[61]), "+f"(d[62]), "+f"(d[63])
        : "r"(a0), "r"(a1), "r"(a2), "r"(a3), "l"(db), "r"(sc), "n"(TB));
}

constexpr int P_NST = 6;
constexpr int P_A_BYTES = 9 * 8192;
constexpr int P_B_STAGE = 3 * 8192;
constexpr int P_SMEM = P_A_BYTES + P_NST * P_B_STAGE + 256 + 320;

template <int NB>
__device__ __forceinline__ void stage_tile(const uint32_t (&pk)[NB * 2], uint32_t base, int w, int lane) {
    const int r = w * 16 + (lane & 7) + ((lane >> 3) & 1) * 8;
#pragma unroll
    for (int b = 0; b < NB; b += 2) {
        const uint32_t a = base + (b >> 3) * 8192 + r * 128 + ((((b & 7) + (lane >> 4)) ^ (r & 7)) << 4);
        stmatrix_x4(a, pk[2 * b], pk[2 * b + 1], pk[2 * b + 2], pk[2 * b + 3]);
    }
}

__device__ __forceinline__ uint32_t hsub2_bf16(uint32_t a, uint32_t b) { uint32_t r; asm("sub.rn.bf16x2 %0, %1, %2;" : "=r"(r) : "r"(a), "r"(b)); return r; }

constexpr int KV_RAW = DM * 18 * 2;
constexpr int Q_THREADS = 416;

__device__ __forceinline__ void proj_mma(float (&acc)[32], int wg, uint32_t fullB, uint32_t emptyB, uint32_t fullA, bool wait_a, int lane) {
    const uint64_t dA = cdesc(0, 16, 1024, 1), dB = cdesc(P_A_BYTES, 8192, 1024, 1) + wg * 512;
#pragma unroll 1
    for (int kb = 0; kb < 9; kb++) {
        const int s = kb >= P_NST ? kb - P_NST : kb;
        if (wait_a) mbar_wait(fullA + kb * 8, 0);
        mbar_wait(fullB + s * 8, kb >= P_NST ? 1 : 0);
        wg_fence();
#pragma unroll
        for (int ks = 0; ks < 4; ks++) wgmma_ss_n64<1>(acc, dA + (kb * 512 + ks * 2), dB + (s * (P_B_STAGE >> 4) + ks * 128), (kb | ks) != 0);
        wg_commit();
        if (kb < 4) {
            wg_wait<1>();
            if (kb >= 1 && lane == 0) mbar_arrive(emptyB + (kb - 1) * 8);
        }
    }
    wg_wait<0>();
    pin(acc);
}

__global__ void __launch_bounds__(Q_THREADS, 1)
k_qkv(const __grid_constant__ CUtensorMap tmWq, const __grid_constant__ CUtensorMap tmQ, const __nv_bfloat16* __restrict__ x, const __nv_bfloat16* __restrict__ wk, const __nv_bfloat16* __restrict__ wv) {
    extern __shared__ __align__(1024) uint8_t smem[];
    const uint32_t sA = smem_u32(smem), sB = sA + P_A_BYTES, bars = sB + P_NST * P_B_STAGE;
    const uint32_t fullB = bars, emptyB = bars + 64, fullX = bars + 128, fullW = bars + 136;
    float* s_rstd = reinterpret_cast<float*>(smem + P_A_BYTES + P_NST * P_B_STAGE + 256);
    const int tid = threadIdx.x, warp = __shfl_sync(~0u, tid >> 5, 0), lane = tid & 31;
    const bool isQ = blockIdx.x < 96;
    const int m = isQ ? blockIdx.x / 3 : blockIdx.x - 96, cg = blockIdx.x % 3;
    if (warp == 12) {
        if (elect_one()) {
            mbar_init(fullX, 1);
            bar_init_fence();
            mbar_expect(fullX, P_A_BYTES);
            bulk_g2s(sA, x + (size_t)m * 64 * DM, P_A_BYTES, fullX);
            prefetch_map(&tmWq); prefetch_map(&tmQ);
            for (int i = 0; i < P_NST; i++) { mbar_init(fullB + i * 8, 1); mbar_init(emptyB + i * 8, 12); }
            mbar_init(fullW, 1);
            bar_init_fence();
            if (isQ) {
                for (int kb = 0; kb < P_NST; kb++) {
                    mbar_expect(fullB + kb * 8, P_B_STAGE);
                    for (int a = 0; a < 3; a++) tma_2d(sB + kb * P_B_STAGE + a * 8192, &tmWq, cg * 192 + a * 64, kb * 64, fullB + kb * 8);
                }
            } else {
                mbar_expect(fullW, 2 * KV_RAW);
                bulk_g2s(sB + 3 * P_B_STAGE, wk, KV_RAW, fullW);
                bulk_g2s(sB + 3 * P_B_STAGE + KV_RAW, wv, KV_RAW, fullW);
            }
        }
        __syncwarp();
    }
    check_smem_base(sA);
    __syncthreads();
    pdl_launch();
    if (warp == 12) {
        if (isQ && elect_one()) {
            for (int kb = P_NST; kb < 9; kb++) {
                const int s = kb - P_NST;
                mbar_wait(emptyB + s * 8, 0);
                mbar_expect(fullB + s * 8, P_B_STAGE);
                for (int a = 0; a < 3; a++) tma_2d(sB + s * P_B_STAGE + a * 8192, &tmWq, cg * 192 + a * 64, kb * 64, fullB + s * 8);
            }
        }
        return;
    }
    if (warp < 8) {
        const int row = tid >> 2, q = tid & 3, h0 = (row & 1) * 4;
        mbar_wait(fullX, 0);
        uint4 v[18];
        const uint32_t ra = sA + row * 1152 + (q + h0) * 16, rb = sA + row * 1152 + (q + 4 - h0) * 16;
#pragma unroll
        for (int kb = 0; kb < 9; kb++) {
            asm volatile("ld.shared.v4.b32 {%0, %1, %2, %3}, [%4];" : "=r"(v[2 * kb].x), "=r"(v[2 * kb].y), "=r"(v[2 * kb].z), "=r"(v[2 * kb].w) : "r"(ra + kb * 128));
            asm volatile("ld.shared.v4.b32 {%0, %1, %2, %3}, [%4];" : "=r"(v[2 * kb + 1].x), "=r"(v[2 * kb + 1].y), "=r"(v[2 * kb + 1].z), "=r"(v[2 * kb + 1].w) : "r"(rb + kb * 128));
        }
        float sum = 0.f, sum2 = 0.f, sq = 0.f, sq2 = 0.f;
#pragma unroll
        for (int i = 0; i < 18; i++) {
            const uint32_t w[4] = {v[i].x, v[i].y, v[i].z, v[i].w};
#pragma unroll
            for (int j = 0; j < 4; j++) { const float a = bf_lo(w[j]), b = bf_hi(w[j]); sum += a; sum2 += b; sq = fmaf(a, a, sq); sq2 = fmaf(b, b, sq2); }
        }
        named_sync(1, 256);
        sum += sum2; sq += sq2;
        sum += __shfl_xor_sync(~0u, sum, 1); sum += __shfl_xor_sync(~0u, sum, 2);
        sq += __shfl_xor_sync(~0u, sq, 1); sq += __shfl_xor_sync(~0u, sq, 2);
        const float mean = sum * (1.0f / DM);
        if (q == 0) s_rstd[row] = rsqrtf(fmaxf(sq * (1.0f / DM) - mean * mean, 0.f) + LN_EPS);
        const uint32_t mhi = pack_bf16(mean, mean);
        const float rem = mean - bf_lo(mhi);
        const uint32_t mlo = pack_bf16(rem, rem);
        const uint32_t wa = sA + row * 128 + (((q + h0) ^ (row & 7)) << 4), wb = sA + row * 128 + (((q + 4 - h0) ^ (row & 7)) << 4);
#pragma unroll
        for (int i = 0; i < 18; i++) {
            const uint32_t o0 = hsub2_bf16(hsub2_bf16(v[i].x, mhi), mlo), o1 = hsub2_bf16(hsub2_bf16(v[i].y, mhi), mlo);
            const uint32_t o2 = hsub2_bf16(hsub2_bf16(v[i].z, mhi), mlo), o3 = hsub2_bf16(hsub2_bf16(v[i].w, mhi), mlo);
            asm volatile("st.shared.v4.b32 [%0], {%1, %2, %3, %4};" ::"r"(((i & 1) ? wb : wa) + (i >> 1) * 8192), "r"(o0), "r"(o1), "r"(o2), "r"(o3) : "memory");
        }
    } else if (!isQ) {
        mbar_wait(fullW, 0);
        const uint32_t* raw = reinterpret_cast<const uint32_t*>(smem + P_A_BYTES + 3 * P_B_STAGE);
#pragma unroll 3
        for (int r = tid - 256; r < 2 * DM; r += 128) {
            uint32_t wr[9];
#pragma unroll
            for (int i = 0; i < 9; i++) wr[i] = raw[r * 9 + i];
            const int sel = r >= DM, k = r - sel * DM;
            uint8_t* dst = smem + P_A_BYTES + sel * 3 * 9216 + (k >> 3) * 128 + (k & 7) * 16;
            *reinterpret_cast<uint4*>(dst) = make_uint4(wr[0], wr[1], wr[2], wr[3]);
            *reinterpret_cast<uint4*>(dst + 9216) = make_uint4(wr[4], wr[5], wr[6], wr[7]);
            *reinterpret_cast<uint32_t*>(dst + 2 * 9216) = wr[8];
        }
    }
    proxy_fence();
    named_sync(2, 384);
    const int wg = warp >> 2, w = warp & 3, g = lane >> 2, t = lane & 3;
    const float rs0 = s_rstd[w * 16 + g], rs1 = s_rstd[w * 16 + g + 8];
    if (isQ) {
        const float c0 = rs0 * Q_SCALE, c1 = rs1 * Q_SCALE;
        float acc[32];
        proj_mma(acc, wg, fullB, emptyB, 0, false, lane);
        uint32_t pk[16];
#pragma unroll
        for (int i = 0; i < 8; i++) { pk[2 * i] = pack_bf16(acc[4 * i] * c0, acc[4 * i + 1] * c0); pk[2 * i + 1] = pack_bf16(acc[4 * i + 2] * c1, acc[4 * i + 3] * c1); }
        named_sync(2, 384);
        stage_tile<8>(pk, sA + wg * 8192, w, lane);
        proxy_fence();
        named_sync(3 + wg, 128);
        if (w == 0 && elect_one()) {
            tma_st_2d(&tmQ, cg * 192 + wg * 64, m * 64, sA + wg * 8192);
            bulk_commit();
            bulk_wait_all();
        }
    } else if (wg < 2) {
        float acc[12];
        const uint64_t dA = cdesc(0, 16, 1024, 1), dB = cdesc(P_A_BYTES, 128, 9216, 0) + wg * (3 * 9216 >> 4);
#pragma unroll
        for (int i = 0; i < 12; i++) acc[i] = 0.f;
        pin(acc);
        wg_fence();
#pragma unroll 1
        for (int kb = 0; kb < 9; kb++) {
#pragma unroll
            for (int ks = 0; ks < 4; ks++) wgmma_ss_n24<1>(acc, dA + (kb * 512 + ks * 2), dB + (kb * 4 + ks) * 16, 1);
        }
        wg_commit();
        wg_wait<0>();
        pin(acc);
        uint32_t pk[6];
#pragma unroll
        for (int b = 0; b < 3; b++) { pk[2 * b] = pack_bf16(acc[4 * b] * rs0, acc[4 * b + 1] * rs0); pk[2 * b + 1] = pack_bf16(acc[4 * b + 2] * rs1, acc[4 * b + 3] * rs1); }
        float n0 = 0.f, n1 = 0.f, vm = 0.f;
#pragma unroll
        for (int b = 0; b < 3; b++) {
            if (b < 2 || t == 0) {
                const float a = bf_lo(pk[2 * b]), c = bf_hi(pk[2 * b]), d = bf_lo(pk[2 * b + 1]), e = bf_hi(pk[2 * b + 1]);
                n0 = fmaf(a, a, fmaf(c, c, n0)); n1 = fmaf(d, d, fmaf(e, e, n1));
            }
        }
        n0 += __shfl_xor_sync(~0u, n0, 1); n0 += __shfl_xor_sync(~0u, n0, 2);
        n1 += __shfl_xor_sync(~0u, n1, 1); n1 += __shfl_xor_sync(~0u, n1, 2);
        vm = fmaxf(n0, n1);
        if (!(n0 == n0) || !(n1 == n1)) vm = __int_as_float(0x7F800000);
#pragma unroll
        for (int o = 4; o < 32; o <<= 1) vm = fmaxf(vm, __shfl_xor_sync(~0u, vm, o));
        if (t != 0) {
            uint32_t lo, hi;
            if (wg == 0) {
                const int grp = m * 8 + w * 2;
                const uint32_t c = t == 1 ? 0x42FE3F80u   : (t == 2 ? 0x00003BC0u   : 0u);
                lo = ((POLY_MASK >> (grp & 15)) & 1) ? c : 0u;
                hi = ((POLY_MASK >> ((grp + 1) & 15)) & 1) ? c : 0u;
            } else {
                lo = hi = t == 1 ? 0x00003F80u : 0u;
            }
            pk[4] = lo; pk[5] = hi;
        }
        uint32_t* dst = reinterpret_cast<uint32_t*>(wg == 0 ? g_kc : g_vc) + (m * 8 + w * 2) * 96 + g * 4 + t;
#pragma unroll
        for (int b = 0; b < 3; b++) { dst[b * 32] = pk[2 * b]; dst[96 + b * 32] = pk[2 * b + 1]; }
        if (lane == 0) g_kmax[m * 8 + warp] = (wg == 0) ? vm : (vm <= 1e24f ? 0.f : __int_as_float(0x7F800000));
    }
}

constexpr int A_THREADS = 512;
constexpr int A_NPIECE = 8;
constexpr int A_OFF_Q = 2 * KV_BYTES;
constexpr int A_OFF_BAR = A_OFF_Q + 8 * 4096;
constexpr int A_SMEM = A_OFF_BAR + 128;

__device__ __forceinline__ uint32_t exp2_pair_fixed(float lo, float hi, uint32_t dep) {
    const uint32_t G = __byte_perm(__float_as_uint(lo), __float_as_uint(hi), 0x5410);
    uint32_t Hh;
    asm("lop3.b32 %0, %1, 0x007F007F, %2, 0xC0;" : "=r"(Hh) : "r"(G), "r"(dep));
    const uint32_t tt = hfma2(Hh, 0xF96BF96Bu, 0x358C358Cu);
    return G - hfma2(tt, Hh, 0u);
}

__global__ void __launch_bounds__(A_THREADS, 1)
k_attn() {
    extern __shared__ __align__(1024) uint8_t smem[];
    pdl_launch();
    const uint32_t sK = smem_u32(smem), sV = sK + KV_BYTES, bars = sK + A_OFF_BAR;
    const int tid = threadIdx.x;
    check_smem_base(sK);
    if (tid == 0) {
        for (int i = 0; i < A_NPIECE; i++) mbar_init(bars + i * 8, 1);
        bar_init_fence();
    }
    __syncthreads();
    pdl_wait();
    const int wg = __shfl_sync(~0u, tid >> 7, 0), w = (tid >> 5) & 3, lane = tid & 31, g = lane >> 2, t = lane & 3;
    const uint32_t* q32 = reinterpret_cast<const uint32_t*>(g_q);
    int row = (blockIdx.x * 8 + wg) * 64 + w * 16 + g;
    uint32_t nq[2][6];
#pragma unroll
    for (int r = 0; r < 2; r++) {
        const uint32_t* q = q32 + (row + r * 256) * 9;
        nq[r][0] = q[t]; nq[r][1] = q[72 + t]; nq[r][2] = q[4 + t]; nq[r][3] = q[76 + t]; nq[r][4] = q[8]; nq[r][5] = q[80];
    }
    constexpr int PB = KV_BYTES / A_NPIECE;
    const float4 km0 = reinterpret_cast<const float4*>(g_kmax)[lane], km1 = reinterpret_cast<const float4*>(g_kmax)[32 + lane];
    if (tid < 32 && elect_one()) {
        for (int i = 0; i < 2; i++) {
            mbar_expect(bars + i * 8, 2 * PB);
            bulk_g2s(sK + i * PB, reinterpret_cast<const char*>(g_kc) + i * PB, PB, bars + i * 8);
            bulk_g2s(sV + i * PB, reinterpret_cast<const char*>(g_vc) + i * PB, PB, bars + i * 8);
        }
    }
    float kmax2 = fmaxf(fmaxf(fmaxf(km0.x, km0.y), fmaxf(km0.z, km0.w)), fmaxf(fmaxf(km1.x, km1.y), fmaxf(km1.z, km1.w)));
#pragma unroll
    for (int o = 1; o < 32; o <<= 1) kmax2 = fmaxf(kmax2, __shfl_xor_sync(~0u, kmax2, o));
    if (tid < 32 && elect_one()) {
        for (int i = 2; i < A_NPIECE; i++) {
            mbar_expect(bars + i * 8, 2 * PB);
            bulk_g2s(sK + i * PB, reinterpret_cast<const char*>(g_kc) + i * PB, PB, bars + i * 8);
            bulk_g2s(sV + i * PB, reinterpret_cast<const char*>(g_vc) + i * PB, PB, bars + i * 8);
        }
    }
    uint32_t vote = 0;
#pragma unroll
    for (int r = 0; r < 2; r++) {
        const uint32_t (&q)[6] = nq[r];
        const float a0 = bf_lo(q[0]), a1 = bf_hi(q[0]), a2 = bf_lo(q[2]), a3 = bf_hi(q[2]);
        const float b0 = bf_lo(q[1]), b1 = bf_hi(q[1]), b2 = bf_lo(q[3]), b3 = bf_hi(q[3]);
        float n0 = a0 * a0 + a1 * a1 + a2 * a2 + a3 * a3, n1 = b0 * b0 + b1 * b1 + b2 * b2 + b3 * b3;
        if (t == 0) {
            const float c0 = bf_lo(q[4]), c1 = bf_hi(q[4]), d0 = bf_lo(q[5]), d1 = bf_hi(q[5]);
            n0 += c0 * c0 + c1 * c1; n1 += d0 * d0 + d1 * d1;
        }
        n0 += __shfl_xor_sync(~0u, n0, 1); n0 += __shfl_xor_sync(~0u, n0, 2);
        n1 += __shfl_xor_sync(~0u, n1, 1); n1 += __shfl_xor_sync(~0u, n1, 2);
        const bool unsafe = !(fmaxf(n0, n1) * kmax2 <= FAST_BOUND * FAST_BOUND) || !(n0 == n0) || !(n1 == n1);
        vote |= (__any_sync(~0u, unsafe) ? 1u : 0u) << r;
        const uint32_t cst = t == 1 ? 0x3F804780u : (t == 2 ? 0x00003F80u : 0u);
        const uint32_t sQ = sK + A_OFF_Q + (r * 4 + wg) * 4096 + (w * 2) * 512 + g * 16 + t * 4;
        asm volatile("st.shared.b32 [%0], %1;" ::"r"(sQ), "r"(q[0]) : "memory");
        asm volatile("st.shared.b32 [%0], %1;" ::"r"(sQ + 512), "r"(q[1]) : "memory");
        asm volatile("st.shared.b32 [%0], %1;" ::"r"(sQ + 128), "r"(q[2]) : "memory");
        asm volatile("st.shared.b32 [%0], %1;" ::"r"(sQ + 640), "r"(q[3]) : "memory");
        asm volatile("st.shared.b32 [%0], %1;" ::"r"(sQ + 256), "r"(t == 0 ? q[4] : cst) : "memory");
        asm volatile("st.shared.b32 [%0], %1;" ::"r"(sQ + 768), "r"(t == 0 ? q[5] : cst) : "memory");
        asm volatile("st.shared.b32 [%0], %1;" ::"r"(sQ + 384), "r"(0u) : "memory");
        asm volatile("st.shared.b32 [%0], %1;" ::"r"(sQ + 896), "r"(0u) : "memory");
    }
    const uint32_t sVote = bars + 64 + wg * 16;
    if (lane == 0) asm volatile("st.shared.b32 [%0], %1;" ::"r"(sVote + w * 4), "r"(vote) : "memory");
    proxy_fence();
    named_sync(wg + 1, 128);
    uint32_t unsafe_mask;
    {
        uint32_t v0, v1, v2, v3;
        asm volatile("ld.shared.v4.b32 {%0, %1, %2, %3}, [%4];" : "=r"(v0), "=r"(v1), "=r"(v2), "=r"(v3) : "r"(sVote));
        unsafe_mask = __shfl_sync(~0u, v0 | v1 | v2 | v3, 0);
    }
    if (unsafe_mask) {
#pragma unroll
        for (int r = 0; r < 2; r++) {
            if (((unsafe_mask >> r) & 1) && t != 0) {
                const uint32_t sQ = sK + A_OFF_Q + (r * 4 + wg) * 4096 + (w * 2) * 512 + g * 16 + t * 4;
                asm volatile("st.shared.b32 [%0], %1;" ::"r"(sQ + 256), "r"(0u) : "memory");
                asm volatile("st.shared.b32 [%0], %1;" ::"r"(sQ + 768), "r"(0u) : "memory");
            }
        }
        proxy_fence();
        named_sync(wg + 1, 128);
    }
#pragma unroll 1
    for (int rep = 0; rep < 2; rep++, row += 256) {
        const uint32_t any_unsafe = (unsafe_mask >> rep) & 1;
        const uint64_t dQ0 = cdesc(A_OFF_Q, 128, 512, 0) + (rep * 4 + wg) * 256, dQ1 = dQ0 + 16;
        float o[12];
#pragma unroll
        for (int i = 0; i < 12; i++) o[i] = 0.f;
        pin(o);
        uint64_t dK0 = cdesc(0, 128, 384, 0), dK1 = cdesc(256, 0, 384, 0), dV = cdesc(KV_BYTES, 384, 128, 0);
        if (!any_unsafe) {
            float s[64];
#pragma unroll 1
            for (int j = 0; j < 16; j++) {
                if (rep == 0 && (j & 1) == 0) mbar_wait(bars + (j >> 1) * 8, 0);
                wg_fence();
                wgmma_ss_n128<0>(s, dQ0, dK0, 0);
                wgmma_ss_n128<0>(s, dQ1, dK1, 1);
                wg_commit();
                dK0 += 16 * 384 >> 4; dK1 += 16 * 384 >> 4;
                wg_wait<0>();
                pin(s);
                uint32_t p[32];
#define CHAIN 6
                {
                    constexpr int NP = 2 * __builtin_popcount(POLY_MASK), NM = 32 - NP;
                    float e[64];
#pragma unroll
                    for (int i = 0; i < 32; i++)
                        if (!((POLY_MASK >> (i >> 1)) & 1)) { e[2 * i] = ex2(s[2 * i]); e[2 * i + 1] = ex2(s[2 * i + 1]); p[i] = pack_bf16(e[2 * i], e[2 * i + 1]); }
                    int ip = 0;
#pragma unroll
                    for (int i = 0; i < 32; i++) {
                        if ((POLY_MASK >> (i >> 1)) & 1) {
                            const int mm = (ip * 2 * NM) / NP - CHAIN;
                            uint32_t dep = 0;
                            if (CHAIN > 0 && mm >= 0) {
                                int cnt = 0;
#pragma unroll
                                for (int q = 0; q < 32; q++)
                                    if (!((POLY_MASK >> (q >> 1)) & 1)) { if (cnt == (mm >> 1)) dep = __float_as_uint(e[2 * q + (mm & 1)]); cnt++; }
                            }
                            p[i] = exp2_pair_fixed(s[2 * i], s[2 * i + 1], dep);
                            ip++;
                        }
                    }
                }
                pin(p);
                wg_fence();
#pragma unroll
                for (int k = 0; k < 8; k++) {
                    wgmma_rs_n24<1>(o, p[4 * k], p[4 * k + 1], p[4 * k + 2], p[4 * k + 3], dV + k * 48, 1);
                }
                wg_commit();
                dV += 16 * 384 >> 4;
                wg_wait<0>();
            }
        } else {
            float s[64];
            float m0 = -INFINITY, m1 = -INFINITY;
#pragma unroll 1
            for (int j = 0; j < 16; j++) {
                if (rep == 0 && (j & 1) == 0) mbar_wait(bars + (j >> 1) * 8, 0);
                wg_fence();
                wgmma_ss_n128<0>(s, dQ0, dK0, 0);
                wgmma_ss_n128<0>(s, dQ1, dK1, 1);
                wg_commit();
                dK0 += 16 * 384 >> 4; dK1 += 16 * 384 >> 4;
                wg_wait<0>();
                pin(s);
                float x0m = m0, x1m = m1;
#pragma unroll
                for (int b = 0; b < 16; b++) { x0m = fmaxf(x0m, fmaxf(s[4 * b], s[4 * b + 1])); x1m = fmaxf(x1m, fmaxf(s[4 * b + 2], s[4 * b + 3])); }
                x0m = fmaxf(x0m, __shfl_xor_sync(~0u, x0m, 1)); x0m = fmaxf(x0m, __shfl_xor_sync(~0u, x0m, 2));
                x1m = fmaxf(x1m, __shfl_xor_sync(~0u, x1m, 1)); x1m = fmaxf(x1m, __shfl_xor_sync(~0u, x1m, 2));
                const float c0 = ex2(m0 - x0m), c1 = ex2(m1 - x1m);
                m0 = x0m; m1 = x1m;
#pragma unroll
                for (int b = 0; b < 3; b++) { o[4 * b] *= c0; o[4 * b + 1] *= c0; o[4 * b + 2] *= c1; o[4 * b + 3] *= c1; }
                uint32_t p[32];
#pragma unroll
                for (int b = 0; b < 16; b++) {
                    p[2 * b] = pack_bf16(ex2(s[4 * b] - m0), ex2(s[4 * b + 1] - m0));
                    p[2 * b + 1] = pack_bf16(ex2(s[4 * b + 2] - m1), ex2(s[4 * b + 3] - m1));
                }
                pin(p); pin(o);
                wg_fence();
#pragma unroll
                for (int k = 0; k < 8; k++) wgmma_rs_n24<1>(o, p[4 * k], p[4 * k + 1], p[4 * k + 2], p[4 * k + 3], dV + k * 48, 1);
                wg_commit();
                dV += 16 * 384 >> 4;
                wg_wait<0>();
            }
        }
        pin(o);
        const float l0 = __shfl_sync(~0u, o[8], (lane & ~3) | 1), l1 = __shfl_sync(~0u, o[10], (lane & ~3) | 1);
        const float i0 = 1.0f / l0, i1 = 1.0f / l1;
        uint32_t* o32 = reinterpret_cast<uint32_t*>(g_o);
        o32[row * 9 + t] = pack_bf16(o[0] * i0, o[1] * i0);
        o32[(row + 8) * 9 + t] = pack_bf16(o[2] * i1, o[3] * i1);
        o32[row * 9 + 4 + t] = pack_bf16(o[4] * i0, o[5] * i0);
        o32[(row + 8) * 9 + 4 + t] = pack_bf16(o[6] * i1, o[7] * i1);
        if (t == 0) { o32[row * 9 + 8] = pack_bf16(o[8] * i0, o[9] * i0); o32[(row + 8) * 9 + 8] = pack_bf16(o[10] * i1, o[11] * i1); }
    }
}

constexpr int O_THREADS = 416;
constexpr int O_OFF_STAT = P_A_BYTES + P_NST * P_B_STAGE + 256;
constexpr int O_SMEM = O_OFF_STAT + 9 * 64 * 8;

__global__ void __cluster_dims__(3, 1, 1) __launch_bounds__(O_THREADS, 1)
k_oproj(const __grid_constant__ CUtensorMap tmO, const __grid_constant__ CUtensorMap tmWo, const __grid_constant__ CUtensorMap tmX2, const __grid_constant__ CUtensorMap tmOut, const __nv_bfloat16* __restrict__ x, const __nv_bfloat16* __restrict__ w1) {
    extern __shared__ __align__(1024) uint8_t smem[];
    const uint32_t sA = smem_u32(smem), sB = sA + P_A_BYTES, bars = sB + P_NST * P_B_STAGE;
    const uint32_t fullB = bars, emptyB = bars + 64, fullA = bars + 128;
    const int tid = threadIdx.x, warp = __shfl_sync(~0u, tid >> 5, 0), lane = tid & 31;
    const int m = blockIdx.x / 3, cg = blockIdx.x % 3;
    check_smem_base(sA);
    if (tid == 0) {
        prefetch_map(&tmO); prefetch_map(&tmWo); prefetch_map(&tmX2); prefetch_map(&tmOut);
        for (int i = 0; i < P_NST; i++) { mbar_init(fullB + i * 8, 1); mbar_init(emptyB + i * 8, 12); }
        for (int i = 0; i < 9; i++) mbar_init(fullA + i * 8, 1);
        bar_init_fence();
        for (int kb = 0; kb < 9; kb++) mbar_expect(fullA + kb * 8, 8192);
    }
    __syncthreads();
    pdl_launch();
    if (warp == 12) {
        if (elect_one()) {
            for (int kb = 0; kb < 9; kb++) {
                const int s = kb >= P_NST ? kb - P_NST : kb;
                if (kb == 2) {
                    pdl_wait();
                    for (int ka = 0; ka < 9; ka++) tma_2d(sA + ka * 8192, &tmO, ka * 64, m * 64, fullA + ka * 8);
                }
                if (kb >= P_NST) mbar_wait(emptyB + s * 8, 0);
                mbar_expect(fullB + s * 8, P_B_STAGE);
                for (int a = 0; a < 3; a++) tma_2d(sB + s * P_B_STAGE + a * 8192, &tmWo, cg * 192 + a * 64, kb * 64, fullB + s * 8);
            }
            for (int i = 0; i < 6; i++) prefetch_l2(reinterpret_cast<const char*>(w1) + (size_t)blockIdx.x * (FF * DM * 2 / 96) + i * 9216, 9216);
        }
        return;
    }
    const int wg = warp >> 2, w = warp & 3, g = lane >> 2, t = lane & 3;
    uint32_t xr[16];
    {
        const uint32_t* x32 = reinterpret_cast<const uint32_t*>(x) + (((m * 64 + w * 16 + g) * DM + cg * 192 + wg * 64 + 2 * t) >> 1);
#pragma unroll
        for (int b = 0; b < 8; b++) { xr[2 * b] = __ldg(x32 + b * 4); xr[2 * b + 1] = __ldg(x32 + b * 4 + 4 * DM); }
    }
    float acc[32];
    proj_mma(acc, wg, fullB, emptyB, fullA, true, lane);
    named_sync(1, 384);
    float s0 = 0.f, q0 = 0.f, s1 = 0.f, q1 = 0.f;
#pragma unroll
    for (int b = 0; b < 8; b++) {
        const uint32_t xa = xr[2 * b], xb = xr[2 * b + 1];
        const uint32_t ha = pack_bf16(acc[4 * b] + bf_lo(xa), acc[4 * b + 1] + bf_hi(xa));
        const uint32_t hb = pack_bf16(acc[4 * b + 2] + bf_lo(xb), acc[4 * b + 3] + bf_hi(xb));
        xr[2 * b] = ha; xr[2 * b + 1] = hb;
        const float a = bf_lo(ha), c = bf_hi(ha), d = bf_lo(hb), e = bf_hi(hb);
        s0 += a + c; q0 = fmaf(a, a, fmaf(c, c, q0));
        s1 += d + e; q1 = fmaf(d, d, fmaf(e, e, q1));
    }
    s0 += __shfl_xor_sync(~0u, s0, 1); s0 += __shfl_xor_sync(~0u, s0, 2);
    q0 += __shfl_xor_sync(~0u, q0, 1); q0 += __shfl_xor_sync(~0u, q0, 2);
    s1 += __shfl_xor_sync(~0u, s1, 1); s1 += __shfl_xor_sync(~0u, s1, 2);
    q1 += __shfl_xor_sync(~0u, q1, 1); q1 += __shfl_xor_sync(~0u, q1, 2);
    const int r = w * 16 + g;
    const uint32_t sStat = sA + O_OFF_STAT;
    if (t < 3) {
        uint32_t dst;
        asm("mapa.shared::cluster.u32 %0, %1, %2;" : "=r"(dst) : "r"(sStat + ((cg * 3 + wg) * 64 + r) * 8), "r"(t));
        asm volatile("st.shared::cluster.v2.f32 [%0], {%1, %2};" ::"r"(dst), "f"(s0), "f"(q0) : "memory");
        asm volatile("st.shared::cluster.v2.f32 [%0], {%1, %2};" ::"r"(dst + 64), "f"(s1), "f"(q1) : "memory");
    }
    cluster_arrive();
    stage_tile<8>(xr, sA + wg * 8192, w, lane);
    proxy_fence();
    named_sync(2 + wg, 128);
    const bool leader = w == 0 && elect_one();
    if (leader) { tma_st_2d(&tmOut, cg * 192 + wg * 64, m * 64, sA + wg * 8192); bulk_commit(); }
    cluster_wait();
    s0 = q0 = s1 = q1 = 0.f;
#pragma unroll
    for (int p = 0; p < 9; p++) {
        float a, b, c, d;
        asm volatile("ld.shared.v2.f32 {%0, %1}, [%2];" : "=f"(a), "=f"(b) : "r"(sStat + (p * 64 + r) * 8));
        asm volatile("ld.shared.v2.f32 {%0, %1}, [%2];" : "=f"(c), "=f"(d) : "r"(sStat + (p * 64 + r + 8) * 8));
        s0 += a; q0 += b; s1 += c; q1 += d;
    }
    const float m0 = s0 * (1.0f / DM), m1 = s1 * (1.0f / DM);
    const float rs0 = rsqrtf(fmaxf(q0 * (1.0f / DM) - m0 * m0, 0.f) + LN_EPS), rs1 = rsqrtf(fmaxf(q1 * (1.0f / DM) - m1 * m1, 0.f) + LN_EPS);
    const float sc0 = 0.5f * rs0, sc1 = 0.5f * rs1, n0 = -m0 * sc0, n1 = -m1 * sc1;
#pragma unroll
    for (int b = 0; b < 8; b++) {
        xr[2 * b] = pack_bf16(fmaf(bf_lo(xr[2 * b]), sc0, n0), fmaf(bf_hi(xr[2 * b]), sc0, n0));
        xr[2 * b + 1] = pack_bf16(fmaf(bf_lo(xr[2 * b + 1]), sc1, n1), fmaf(bf_hi(xr[2 * b + 1]), sc1, n1));
    }
    stage_tile<8>(xr, sA + (3 + wg) * 8192, w, lane);
    proxy_fence();
    named_sync(2 + wg, 128);
    if (leader) {
        tma_st_2d(&tmX2, cg * 192 + wg * 64, m * 64, sA + (3 + wg) * 8192);
        bulk_commit();
        bulk_wait_all();
    }
}

constexpr int F_THREADS = 384;
constexpr int F_NST = 6;
constexpr int F_STAGE = 96 * 128;
constexpr int F_X_BYTES = 9 * 16384;
constexpr int F_OFF_ST = F_X_BYTES;
constexpr int F_OFF_ST2 = 4 * 16384;
constexpr int F_OFF_BAR = F_OFF_ST + F_NST * F_STAGE;
constexpr int F_SMEM = F_OFF_BAR + 512;

__device__ __forceinline__ float tanh_hw(float x) { float y; asm("tanh.approx.f32 %0, %1;" : "=f"(y) : "f"(x)); return y; }
__host__ __device__ constexpr int piece_begin(int p) { return p == 0 ? 0 : 3 * p + 1; }
template <int P>
__device__ __forceinline__ void silu_s1(const float (&acc)[32], float (&tmp)[8]) {
#pragma unroll
    for (int i = 2 * piece_begin(P); i < 2 * piece_begin(P + 1); i++) tmp[i - 2 * piece_begin(P)] = tanh_hw(acc[i]);
}
template <int C, int P>
__device__ __forceinline__ void silu_s2(const float (&acc)[32], const float (&tmp)[8], uint32_t (&h1)[144]) {
#pragma unroll
    for (int i = piece_begin(P); i < piece_begin(P + 1); i++) {
        const int k = 2 * (i - piece_begin(P));
        h1[C * 16 + i] = pack_bf16(fmaf(acc[2 * i], tmp[k], acc[2 * i]), fmaf(acc[2 * i + 1], tmp[k + 1], acc[2 * i + 1]));
    }
}
template <int J>
__device__ __forceinline__ void silu_slot_last(const float (&prev)[32], float (&tmp)[2][8], uint32_t (&h1)[144]) {
    if constexpr (J >= 1 && J <= 4) {
#pragma unroll
        for (int i = 0; i < 4; i++) {
            const int q = 4 * (J - 1) + i;
            h1[128 + q] = pack_bf16(fmaf(prev[2 * q], tmp[(J - 1) & 1][2 * i], prev[2 * q]), fmaf(prev[2 * q + 1], tmp[(J - 1) & 1][2 * i + 1], prev[2 * q + 1]));
        }
    }
    if constexpr (J <= 3) {
#pragma unroll
        for (int i = 0; i < 8; i++) tmp[J & 1][i] = tanh_hw(prev[8 * J + i]);
        pin(tmp[J & 1]);
    }
}
template <int C, int J>
__device__ __forceinline__ void silu_slot(const float (&prev)[32], float (&tmp)[2][8], uint32_t (&h1)[144]) {
    if constexpr (J >= 1) silu_s2<C, J - 1>(prev, tmp[(J - 1) & 1], h1);
    if constexpr (J <= 4) { silu_s1<J>(prev, tmp[J & 1]); pin(tmp[J & 1]); }
}

struct FfnPipe {
    uint32_t full, empty;
    int lane;
    __device__ __forceinline__ void acquire(int s, uint32_t ph) const { mbar_wait(full + s * 8, ph); }
    __device__ __forceinline__ void release(int s) const { if (lane == 0) mbar_arrive(empty + s * 8); }
};

template <int C>
__device__ __forceinline__ void ffn_phase1_chunk(float (&cur)[32], float (&prev)[32], uint32_t (&h1)[144], const FfnPipe& pp, uint64_t dx, uint32_t fullX) {
    float tmp[2][8];
    const uint64_t dw = cdesc(F_OFF_ST, 8192, 1024, 1) + blockIdx.y * (C + 1);
    dx += blockIdx.y * C;
#pragma unroll
    for (int j = 0; j < 6; j++) {
        if (C == 0) { mbar_wait(fullX + ((6 * j) >> 2) * 8, 0); mbar_wait(fullX + ((6 * j + 5) >> 2) * 8, 0); }
        pp.acquire(j, C & 1);
        if (j == 0) pin(cur);
        wg_fence();
#pragma unroll
        for (int i = 0; i < 6; i++) {
            const int ks = 6 * j + i;
            wgmma_ss_n64<1>(cur, dx + ((ks >> 2) * 1024 + (ks & 3) * 2), dw + ((j * F_STAGE + i * 2048) >> 4), ks != 0);
        }
        wg_commit();
        if (C > 0 || j > 0) { wg_wait<1>(); pp.release((j + 5) % 6); }
        if (C > 0) {
            constexpr int CP = C > 0 ? C - 1 : 0;
            pin(prev);
            if (j == 0) silu_slot<CP, 0>(prev, tmp, h1);
            if (j == 1) silu_slot<CP, 1>(prev, tmp, h1);
            if (j == 2) silu_slot<CP, 2>(prev, tmp, h1);
            if (j == 3) silu_slot<CP, 3>(prev, tmp, h1);
            if (j == 4) silu_slot<CP, 4>(prev, tmp, h1);
            if (j == 5) silu_slot<CP, 5>(prev, tmp, h1);
        }
    }
}

__device__ __forceinline__ void ffn_stage_chunk(const float (&acc)[32], uint32_t stg, int w, int lane) {
    uint32_t pk[16];
#pragma unroll
    for (int i = 0; i < 16; i++) pk[i] = pack_bf16(acc[2 * i], acc[2 * i + 1]);
    stage_tile<8>(pk, stg, w, lane);
}
__device__ __forceinline__ void ffn_reduce_chunk(const CUtensorMap* tmOut, uint32_t stg, int col, int row, int w, int wgid, bool leader) {
    proxy_fence();
    if (w != 0) {
        asm volatile("bar.arrive %0, 128;" ::"r"(2 + wgid) : "memory");
    } else {
        named_sync(2 + wgid, 128);
        if (leader) {
            tma_red_2d(tmOut, col, row, stg);
            bulk_commit();
            asm volatile("cp.async.bulk.wait_group.read 3;" ::: "memory");
        }
    }
}

template <bool FIRST, int SET>
__device__ __forceinline__ void ffn_phase2_chunk(float (&cur)[32], float (&prev)[32], uint32_t (&h1)[144], const FfnPipe& pa, const FfnPipe& pb, uint32_t ph, uint32_t xfree,
                                                 const CUtensorMap* tmOut, uint32_t stg_prev, int col_prev, int row, int w, int lane, int wgid, bool leader) {
    const uint64_t dw = cdesc(SET ? F_OFF_ST2 : F_OFF_ST, 8192, 1024, 1) + blockIdx.y * col_prev;
    const FfnPipe& mine = SET ? pb : pa;
    const FfnPipe& other = SET ? pa : pb;
    float tmp[2][8];
#pragma unroll
    for (int j = 0; j < 6; j++) {
        mine.acquire(j, ph);
        if (j == 0) pin(cur);
        if (FIRST && j == 5) pin(h1);
        wg_fence();
#pragma unroll
        for (int i = 0; i < 6; i++) {
            const int f = (6 * j + i) * 4;
            wgmma_rs_n64<1>(cur, h1[f], h1[f + 1], h1[f + 2], h1[f + 3], dw + ((j * F_STAGE + i * 2048) >> 4), (j | i) != 0);
        }
        wg_commit();
        wg_wait<1>();
        if (j > 0) mine.release(j - 1);
        else if (FIRST) { pa.release(5); if (lane == 0) mbar_arrive(xfree); }
        else other.release(5);
        if (FIRST) {
            pin(prev);
            if (j == 0) silu_slot_last<0>(prev, tmp, h1);
            if (j == 1) silu_slot_last<1>(prev, tmp, h1);
            if (j == 2) silu_slot_last<2>(prev, tmp, h1);
            if (j == 3) silu_slot_last<3>(prev, tmp, h1);
            if (j == 4) silu_slot_last<4>(prev, tmp, h1);
        } else {
            if (j == 0) { pin(prev); ffn_stage_chunk(prev, stg_prev, w, lane); }
            if (j == 1) ffn_reduce_chunk(tmOut, stg_prev, col_prev, row, w, wgid, leader);
        }
    }
}

__global__ void __launch_bounds__(F_THREADS, 1)
k_ffn(const __grid_constant__ CUtensorMap tmH, const __grid_constant__ CUtensorMap tmW1, const __grid_constant__ CUtensorMap tmW2, const __grid_constant__ CUtensorMap tmOut, const __nv_bfloat16* __restrict__ w2) {
    extern __shared__ __align__(1024) uint8_t smem[];
    const uint32_t sX = smem_u32(smem), sSt = sX + F_OFF_ST, bars = sX + F_OFF_BAR;
    const uint32_t full = bars, empty = bars + 64, fullX = bars + 128, full2 = bars + 256, empty2 = bars + 320, xfree = bars + 384;
    const int tid = threadIdx.x, warp = __shfl_sync(~0u, tid >> 5, 0), lane = tid & 31;
#define FFN_MAP 1
    const int m = FFN_MAP == 0 ? (blockIdx.x & 15) : (FFN_MAP == 1 ? (blockIdx.x >> 3) : ((blockIdx.x >> 1) & 15));
    const int fs = FFN_MAP == 0 ? (blockIdx.x >> 4) : (FFN_MAP == 1 ? (blockIdx.x & 7) : ((blockIdx.x >> 5) * 2 + (blockIdx.x & 1)));
    check_smem_base(sX);
    if (tid == 0) {
        prefetch_map(&tmW1); prefetch_map(&tmH); prefetch_map(&tmW2); prefetch_map(&tmOut);
        for (int i = 0; i < F_NST; i++) { mbar_init(full + i * 8, 1); mbar_init(empty + i * 8, 8); mbar_init(full2 + i * 8, 1); mbar_init(empty2 + i * 8, 8); }
        for (int i = 0; i < 9; i++) mbar_init(fullX + i * 8, 1);
        mbar_init(xfree, 8);
        bar_init_fence();
        for (int kb = 0; kb < 9; kb++) mbar_expect(fullX + kb * 8, 16384);
    }
    __syncthreads();
    if (warp < 4) {
        asm volatile("setmaxnreg.dec.sync.aligned.u32 24;");
        if (warp == 1 && lane < 9) prefetch_l2(reinterpret_cast<const char*>(w2) + ((size_t)fs * 576 + m * 36 + lane * 4) * (DM * 2), 4 * DM * 2);
        if (warp == 0 && elect_one()) {
#pragma unroll 1
            for (int c = 0; c < 9; c++) {
#pragma unroll 1
                for (int j = 0; j < 6; j++) {
                    mbar_wait(empty + j * 8, (c & 1) ^ 1);
                    mbar_expect(full + j * 8, F_STAGE);
                    tma_2d(sSt + j * F_STAGE, &tmW1, fs * 576 + c * 64, j * 96, full + j * 8);
                }
            }
            int col = fs;
#pragma unroll 1
            for (int c = 0; c < 9; c++) {
                const bool setb = c & 1;
                if (c == 1) mbar_wait(xfree, 0);
#pragma unroll 1
                for (int j = 0; j < 6; j++) {
                    if (!setb) mbar_wait(empty + j * 8, ((9 + (c >> 1)) & 1) ^ 1);
                    else if (c > 1) mbar_wait(empty2 + j * 8, ((c >> 1) - 1) & 1);
                    const uint32_t fb = (setb ? full2 : full) + j * 8;
                    mbar_expect(fb, F_STAGE);
                    tma_2d((setb ? sX + F_OFF_ST2 : sSt) + j * F_STAGE, &tmW2, col * 64, fs * 576 + j * 96, fb);
                }
                if (++col == 9) col = 0;
            }
        }
    } else {
        asm volatile("setmaxnreg.inc.sync.aligned.u32 240;");
        const int wgid = (warp >> 2) - 1, w = warp & 3;
        pdl_wait();
        if (warp == 4 && elect_one()) {
            for (int kb = 0; kb < 9; kb++) tma_2d(sX + kb * 16384, &tmH, kb * 64, m * 128, fullX + kb * 8);
        }
        __syncwarp();
        FfnPipe pp{full, empty, lane};
        const uint64_t xlo = cdesc(0, 16, 1024, 1) + wgid * 512;
        uint32_t h1[144];
        float acc0[32], acc1[32];
        ffn_phase1_chunk<0>(acc0, acc1, h1, pp, xlo, fullX);
        ffn_phase1_chunk<1>(acc1, acc0, h1, pp, xlo, fullX);
        ffn_phase1_chunk<2>(acc0, acc1, h1, pp, xlo, fullX);
        ffn_phase1_chunk<3>(acc1, acc0, h1, pp, xlo, fullX);
        ffn_phase1_chunk<4>(acc0, acc1, h1, pp, xlo, fullX);
        ffn_phase1_chunk<5>(acc1, acc0, h1, pp, xlo, fullX);
        ffn_phase1_chunk<6>(acc0, acc1, h1, pp, xlo, fullX);
        ffn_phase1_chunk<7>(acc1, acc0, h1, pp, xlo, fullX);
        ffn_phase1_chunk<8>(acc0, acc1, h1, pp, xlo, fullX);
        const int row = m * 128 + wgid * 64;
        const uint32_t stg = sX + wgid * 8192;
        int c = fs, cprev = 0;
        const bool leader = w == 0 && elect_one();
        const FfnPipe pb{full2, empty2, lane};
        ffn_phase2_chunk<true, 0>(acc1, acc0, h1, pp, pb, 1, xfree, &tmOut, 0, 0, row, w, lane, wgid, leader);
        cprev = c; if (++c == 9) c = 0;
#pragma unroll 1
        for (int j = 1; j < 9; j += 2) {
            const uint32_t u = j >> 1;
            ffn_phase2_chunk<false, 1>(acc0, acc1, h1, pp, pb, u & 1, xfree, &tmOut, stg + ((j - 1) & 3) * 16384, cprev * 64, row, w, lane, wgid, leader);
            cprev = c; if (++c == 9) c = 0;
            ffn_phase2_chunk<false, 0>(acc1, acc0, h1, pp, pb, u & 1, xfree, &tmOut, stg + (j & 3) * 16384, cprev * 64, row, w, lane, wgid, leader);
            cprev = c; if (++c == 9) c = 0;
        }
        wg_wait<0>();
        pin(acc1);
        ffn_stage_chunk(acc1, stg, w, lane);
        ffn_reduce_chunk(&tmOut, stg, cprev * 64, row, w, wgid, leader);
        if (leader) bulk_wait_all();
    }
}

typedef CUresult (*EncodeFn)(CUtensorMap*, CUtensorMapDataType, cuuint32_t, void*, const cuuint64_t*, const cuuint64_t*, const cuuint32_t*, const cuuint32_t*,
                             CUtensorMapInterleave, CUtensorMapSwizzle, CUtensorMapL2promotion, CUtensorMapFloatOOBfill);

CUtensorMap make_map(EncodeFn enc, const void* base, int rows, int cols, int box_rows) {
    CUtensorMap tm;
    cuuint64_t dims[2] = {(cuuint64_t)cols, (cuuint64_t)rows};
    cuuint64_t strides[1] = {(cuuint64_t)cols * 2};
    cuuint32_t box[2] = {64, (cuuint32_t)box_rows};
    cuuint32_t es[2] = {1, 1};
    enc(&tm, CU_TENSOR_MAP_DATA_TYPE_BFLOAT16, 2, const_cast<void*>(base), dims, strides, box, es, CU_TENSOR_MAP_INTERLEAVE_NONE,
        CU_TENSOR_MAP_SWIZZLE_128B, CU_TENSOR_MAP_L2_PROMOTION_L2_256B, CU_TENSOR_MAP_FLOAT_OOB_FILL_NONE);
    return tm;
}

template <typename... KArgs, typename... Args>
void launch(void (*kern)(KArgs...), int grid, int block, int smem, bool pdl, Args... args) {
    cudaLaunchConfig_t cfg = {};
    cfg.gridDim = dim3(grid); cfg.blockDim = dim3(block); cfg.dynamicSmemBytes = smem; cfg.stream = cudaStreamPerThread;
    cudaLaunchAttribute at[1];
    at[0].id = cudaLaunchAttributeProgrammaticStreamSerialization;
    at[0].val.programmaticStreamSerializationAllowed = 1;
    cfg.attrs = at; cfg.numAttrs = pdl ? 1 : 0;
    cudaLaunchKernelEx(&cfg, kern, KArgs(args)...);
}

}

#define USE_PDL 1

extern "C" void kernel_launch(void* const* d_in, const int* in_sizes, int n_in, void* d_out, int out_size) {
    const __nv_bfloat16* x = (const __nv_bfloat16*)d_in[0];
    const __nv_bfloat16* wq = (const __nv_bfloat16*)d_in[1];
    const __nv_bfloat16* wk = (const __nv_bfloat16*)d_in[2];
    const __nv_bfloat16* wv = (const __nv_bfloat16*)d_in[3];
    const __nv_bfloat16* wo = (const __nv_bfloat16*)d_in[4];
    const __nv_bfloat16* w1 = (const __nv_bfloat16*)d_in[6];
    const __nv_bfloat16* w2 = (const __nv_bfloat16*)d_in[7];
    __nv_bfloat16* out = (__nv_bfloat16*)d_out;

    static EncodeFn enc = nullptr;
    static void *p_o = nullptr, *p_h = nullptr, *p_q = nullptr;
    if (!enc) {
        cudaDriverEntryPointQueryResult qr;
        cudaGetDriverEntryPoint("cuTensorMapEncodeTiled", (void**)&enc, cudaEnableDefault, &qr);
        cudaGetSymbolAddress(&p_o, g_o);
        cudaGetSymbolAddress(&p_h, g_x2);
        cudaGetSymbolAddress(&p_q, g_q);
        cudaFuncSetAttribute(k_qkv, cudaFuncAttributeMaxDynamicSharedMemorySize, P_SMEM);
        cudaFuncSetAttribute(k_attn, cudaFuncAttributeMaxDynamicSharedMemorySize, A_SMEM);
        cudaFuncSetAttribute(k_oproj, cudaFuncAttributeMaxDynamicSharedMemorySize, O_SMEM);
        cudaFuncSetAttribute(k_ffn, cudaFuncAttributeMaxDynamicSharedMemorySize, F_SMEM);
    }
    const CUtensorMap tmWq = make_map(enc, wq, DM, DM, 64);
    const CUtensorMap tmWo = make_map(enc, wo, DM, DM, 64);
    const CUtensorMap tmO = make_map(enc, p_o, SEQ, DM, 64);
    const CUtensorMap tmH64 = make_map(enc, p_h, SEQ, DM, 64);
    const CUtensorMap tmH = make_map(enc, p_h, SEQ, DM, 128);
    const CUtensorMap tmQ = make_map(enc, p_q, SEQ, DM, 64);
    const CUtensorMap tmW1 = make_map(enc, w1, DM, FF, 96);
    const CUtensorMap tmW2 = make_map(enc, w2, FF, DM, 96);
    const CUtensorMap tmOut = make_map(enc, out, SEQ, DM, 64);

    launch(k_qkv, 128, Q_THREADS, P_SMEM, false, tmWq, tmQ, x, wk, wv);
    launch(k_attn, 128, A_THREADS, A_SMEM, USE_PDL);
    launch(k_oproj, 96, O_THREADS, O_SMEM, USE_PDL, tmO, tmWo, tmH64, tmOut, x, w1);
    launch(k_ffn, 128, F_THREADS, F_SMEM, USE_PDL, tmH, tmW1, tmW2, tmOut, w2);
}
```

```cpp
#include <cuda_runtime.h>
#include <cuda_bf16.h>
#include <cuda.h>
#include <stdint.h>

namespace {

constexpr int SEQ = 2048, DM = 576, FF = 4608;
constexpr int KV_BYTES = SEQ * 48;
constexpr float LN_EPS = 1e-5f;
constexpr float LOG2E = 1.4426950408889634f;
constexpr float Q_SCALE = 0.23570226039551584f * LOG2E;

#define POLY_MASK_V 0xB6DBu
constexpr uint32_t POLY_MASK = POLY_MASK_V;
#define FAST_BOUND_V 60.0f
constexpr float FAST_BOUND = FAST_BOUND_V;

__device__ __align__(1024) __nv_bfloat16 g_q[SEQ * DM];
__device__ __align__(1024) uint4 g_kc[KV_BYTES / 16];
__device__ __align__(1024) uint4 g_vc[KV_BYTES / 16];
__device__ __align__(16) float g_kmax[256];
__device__ __align__(1024) __nv_bfloat16 g_o[SEQ * DM];
__device__ __align__(1024) __nv_bfloat16 g_x2[SEQ * DM];

__device__ __forceinline__ uint32_t smem_u32(const void* p) { return (uint32_t)__cvta_generic_to_shared(p); }
__device__ __forceinline__ void wg_fence() { asm volatile("wgmma.fence.sync.aligned;" ::: "memory"); }
__device__ __forceinline__ void wg_commit() { asm volatile("wgmma.commit_group.sync.aligned;" ::: "memory"); }
template <int N> __device__ __forceinline__ void wg_wait() { asm volatile("wgmma.wait_group.sync.aligned %0;" ::"n"(N) : "memory"); }
template <int N> __device__ __forceinline__ void pin(float (&r)[N]) {
#pragma unroll
    for (int i = 0; i < N; i++) asm volatile("" : "+f"(r[i])::"memory");
}
template <int N> __device__ __forceinline__ void pin(uint32_t (&r)[N]) {
#pragma unroll
    for (int i = 0; i < N; i++) asm volatile("" : "+r"(r[i])::"memory");
}
constexpr uint32_t SMEM0 = 0x400;
__host__ __device__ constexpr uint64_t cdesc(uint32_t off, uint32_t lbo, uint32_t sbo, uint32_t swz) {
    return (uint64_t)(((SMEM0 + off) & 0x3FFFF) >> 4) | ((uint64_t)(lbo >> 4) << 16) | ((uint64_t)(sbo >> 4) << 32) | ((uint64_t)swz << 62);
}
__device__ __forceinline__ void check_smem_base(uint32_t base) { if ((base & 0x3FFFF) != SMEM0) __trap(); }

__device__ __forceinline__ void mbar_init(uint32_t bar, int cnt) { asm volatile("mbarrier.init.shared::cta.b64 [%0], %1;" ::"r"(bar), "r"(cnt) : "memory"); }
__device__ __forceinline__ void mbar_expect(uint32_t bar, int bytes) { asm volatile("mbarrier.arrive.expect_tx.shared::cta.b64 _, [%0], %1;" ::"r"(bar), "r"(bytes) : "memory"); }
__device__ __forceinline__ void mbar_arrive(uint32_t bar) { asm volatile("mbarrier.arrive.shared::cta.b64 _, [%0];" ::"r"(bar) : "memory"); }
__device__ __forceinline__ void mbar_wait(uint32_t bar, uint32_t parity) {
    asm volatile(
        "{\n.reg .pred p;\n.reg .u32 n;\nmov.u32 n, 0;\n"
        "LAB_WAIT:\n"
        "mbarrier.try_wait.parity.shared::cta.b64 p, [%0], %1;\n"
        "@p bra DONE;\n"
        "add.u32 n, n, 1;\n"
        "setp.lt.u32 p, n, 4000000;\n"
        "@p bra LAB_WAIT;\n"
        "trap;\n"
        "DONE:\n}\n" ::"r"(bar), "r"(parity) : "memory");
}
__device__ __forceinline__ void bar_init_fence() {
    asm volatile("fence.mbarrier_init.release.cluster;" ::: "memory");
    asm volatile("fence.proxy.async.shared::cta;" ::: "memory");
}
__device__ __forceinline__ void proxy_fence() { asm volatile("fence.proxy.async.shared::cta;" ::: "memory"); }
__device__ __forceinline__ void named_sync(int id, int n) { asm volatile("bar.sync %0, %1;" ::"r"(id), "r"(n) : "memory"); }
__device__ __forceinline__ void bulk_g2s(uint32_t dst, const void* src, int bytes, uint32_t bar) {
    asm volatile("cp.async.bulk.shared::cluster.global.mbarrier::complete_tx::bytes [%0], [%1], %2, [%3];" ::"r"(dst), "l"(src), "r"(bytes), "r"(bar) : "memory");
}
__device__ __forceinline__ void tma_2d(uint32_t dst, const CUtensorMap* tm, int c0, int c1, uint32_t bar) {
    asm volatile("cp.async.bulk.tensor.2d.shared::cluster.global.mbarrier::complete_tx::bytes [%0], [%1, {%3, %4}], [%2];" ::"r"(dst), "l"(tm), "r"(bar), "r"(c0), "r"(c1) : "memory");
}
__device__ __forceinline__ void cluster_arrive() { asm volatile("barrier.cluster.arrive.release.aligned;" ::: "memory"); }
__device__ __forceinline__ void cluster_wait() { asm volatile("barrier.cluster.wait.acquire.aligned;" ::: "memory"); }
__device__ __forceinline__ void tma_red_2d(const CUtensorMap* tm, int c0, int c1, uint32_t src) {
    asm volatile("cp.reduce.async.bulk.tensor.2d.global.shared::cta.add.tile.bulk_group [%0, {%2, %3}], [%1];" ::"l"(tm), "r"(src), "r"(c0), "r"(c1) : "memory");
}
__device__ __forceinline__ void tma_st_2d(const CUtensorMap* tm, int c0, int c1, uint32_t src) {
    asm volatile("cp.async.bulk.tensor.2d.global.shared::cta.tile.bulk_group [%0, {%2, %3}], [%1];" ::"l"(tm), "r"(src), "r"(c0), "r"(c1) : "memory");
}
__device__ __forceinline__ void bulk_commit() { asm volatile("cp.async.bulk.commit_group;" ::: "memory"); }
__device__ __forceinline__ void bulk_wait_all() { asm volatile("cp.async.bulk.wait_group.read 0;" ::: "memory"); }
__device__ __forceinline__ bool elect_one() {
    uint32_t p;
    asm volatile("{\n.reg .pred P;\nelect.sync _|P, 0xffffffff;\nselp.b32 %0, 1, 0, P;\n}\n" : "=r"(p));
    return p != 0;
}
__device__ __forceinline__ void prefetch_l2(const void* p, int bytes) { asm volatile("cp.async.bulk.prefetch.L2.global [%0], %1;" ::"l"(p), "r"(bytes) : "memory"); }
__device__ __forceinline__ void prefetch_map(const CUtensorMap* tm) { asm volatile("prefetch.tensormap [%0];" ::"l"(tm) : "memory"); }
__device__ __forceinline__ void pdl_launch() { asm volatile("griddepcontrol.launch_dependents;" ::: "memory"); }
__device__ __forceinline__ void pdl_wait() { asm volatile("griddepcontrol.wait;" ::: "memory"); }
__device__ __forceinline__ float ex2(float x) { float y; asm("ex2.approx.ftz.f32 %0, %1;" : "=f"(y) : "f"(x)); return y; }
__device__ __forceinline__ uint32_t pack_bf16(float lo, float hi) { uint32_t r; asm("cvt.rn.bf16x2.f32 %0, %1, %2;" : "=r"(r) : "f"(hi), "f"(lo)); return r; }
__device__ __forceinline__ float bf_lo(uint32_t v) { return __uint_as_float(v << 16); }
__device__ __forceinline__ float bf_hi(uint32_t v) { return __uint_as_float(v & 0xFFFF0000u); }
__device__ __forceinline__ uint32_t hfma2(uint32_t a, uint32_t b, uint32_t c) { uint32_t r; asm("fma.rn.f16x2 %0, %1, %2, %3;" : "=r"(r) : "r"(a), "r"(b), "r"(c)); return r; }
__device__ __forceinline__ void stmatrix_x4(uint32_t addr, uint32_t r0, uint32_t r1, uint32_t r2, uint32_t r3) {
    asm volatile("stmatrix.sync.aligned.m8n8.x4.shared.b16 [%0], {%1, %2, %3, %4};" ::"r"(addr), "r"(r0), "r"(r1), "r"(r2), "r"(r3) : "memory");
}

template <int TB> __device__ __forceinline__ void wgmma_ss_n24(float (&d)[12], uint64_t da, uint64_t db, int sc) {
    asm volatile("{\n.reg .pred p;\nsetp.ne.b32 p, %14, 0;\n"
        "wgmma.mma_async.sync.aligned.m64n24k16.f32.bf16.bf16 {%0, %1, %2, %3, %4, %5, %6, %7, %8, %9, %10, %11}, %12, %13, p, 1, 1, 0, %15;\n}\n"
        : "+f"(d[0]), "+f"(d[1]), "+f"(d[2]), "+f"(d[3]), "+f"(d[4]), "+f"(d[5]), "+f"(d[6]), "+f"(d[7]), "+f"(d[8]), "+f"(d[9]), "+f"(d[10]), "+f"(d[11])
        : "l"(da), "l"(db), "r"(sc), "n"(TB));
}
template <int TB> __device__ __forceinline__ void wgmma_ss_n64(float (&d)[32], uint64_t da, uint64_t db, int sc) {
    asm volatile("{\n.reg .pred p;\nsetp.ne.b32 p, %34, 0;\n"
        "wgmma.mma_async.sync.aligned.m64n64k16.f32.bf16.bf16 {%0, %1, %2, %3, %4, %5, %6, %7, %8, %9, %10, %11, %12, %13, %14, %15, %16, %17, %18, %19, %20, %21, %22, %23, %24, %25, %26, %27, %28, %29, %30, %31}, %32, %33, p, 1, 1, 0, %35;\n}\n"
        : "+f"(d[0]), "+f"(d[1]), "+f"(d[2]), "+f"(d[3]), "+f"(d[4]), "+f"(d[5]), "+f"(d[6]), "+f"(d[7]), "+f"(d[8]), "+f"(d[9]), "+f"(d[10]), "+f"(d[11]), "+f"(d[12]), "+f"(d[13]), "+f"(d[14]), "+f"(d[15]), "+f"(d[16]), "+f"(d[17]), "+f"(d[18]), "+f"(d[19]), "+f"(d[20]), "+f"(d[21]), "+f"(d[22]), "+f"(d[23]), "+f"(d[24]), "+f"(d[25]), "+f"(d[26]), "+f"(d[27]), "+f"(d[28]), "+f"(d[29]), "+f"(d[30]), "+f"(d[31])
        : "l"(da), "l"(db), "r"(sc), "n"(TB));
}
template <int TB> __device__ __forceinline__ void wgmma_ss_n128(float (&d)[64], uint64_t da, uint64_t db, int sc) {
    asm volatile("{\n.reg .pred p;\nsetp.ne.b32 p, %66, 0;\n"
        "wgmma.mma_async.sync.aligned.m64n128k16.f32.bf16.bf16 {%0, %1, %2, %3, %4, %5, %6, %7, %8, %9, %10, %11, %12, %13, %14, %15, %16, %17, %18, %19, %20, %21, %22, %23, %24, %25, %26, %27, %28, %29, %30, %31, %32, %33, %34, %35, %36, %37, %38, %39, %40, %41, %42, %43, %44, %45, %46, %47, %48, %49, %50, %51, %52, %53, %54, %55, %56, %57, %58, %59, %60, %61, %62, %63}, %64, %65, p, 1, 1, 0, %67;\n}\n"
        : "+f"(d[0]), "+f"(d[1]), "+f"(d[2]), "+f"(d[3]), "+f"(d[4]), "+f"(d[5]), "+f"(d[6]), "+f"(d[7]), "+f"(d[8]), "+f"(d[9]), "+f"(d[10]), "+f"(d[11]), "+f"(d[12]), "+f"(d[13]), "+f"(d[14]), "+f"(d[15]), "+f"(d[16]), "+f"(d[17]), "+f"(d[18]), "+f"(d[19]), "+f"(d[20]), "+f"(d[21]), "+f"(d[22]), "+f"(d[23]), "+f"(d[24]), "+f"(d[25]), "+f"(d[26]), "+f"(d[27]), "+f"(d[28]), "+f"(d[29]), "+f"(d[30]), "+f"(d[31]), "+f"(d[32]), "+f"(d[33]), "+f"(d[34]), "+f"(d[35]), "+f"(d[36]), "+f"(d[37]), "+f"(d[38]), "+f"(d[39]), "+f"(d[40]), "+f"(d[41]), "+f"(d[42]), "+f"(d[43]), "+f"(d[44]), "+f"(d[45]), "+f"(d[46]), "+f"(d[47]), "+f"(d[48]), "+f"(d[49]), "+f"(d[50]), "+f"(d[51]), "+f"(d[52]), "+f"(d[53]), "+f"(d[54]), "+f"(d[55]), "+f"(d[56]), "+f"(d[57]), "+f"(d[58]), "+f"(d[59]), "+f"(d[60]), "+f"(d[61]), "+f"(d[62]), "+f"(d[63])
        : "l"(da), "l"(db), "r"(sc), "n"(TB));
}
template <int TB> __device__ __forceinline__ void wgmma_rs_n24(float (&d)[12], uint32_t a0, uint32_t a1, uint32_t a2, uint32_t a3, uint64_t db, int sc) {
    asm volatile("{\n.reg .pred p;\nsetp.ne.b32 p, %17, 0;\n"
        "wgmma.mma_async.sync.aligned.m64n24k16.f32.bf16.bf16 {%0, %1, %2, %3, %4, %5, %6, %7, %8, %9, %10, %11}, {%12, %13, %14, %15}, %16, p, 1, 1, %18;\n}\n"
        : "+f"(d[0]), "+f"(d[1]), "+f"(d[2]), "+f"(d[3]), "+f"(d[4]), "+f"(d[5]), "+f"(d[6]), "+f"(d[7]), "+f"(d[8]), "+f"(d[9]), "+f"(d[10]), "+f"(d[11])
        : "r"(a0), "r"(a1), "r"(a2), "r"(a3), "l"(db), "r"(sc), "n"(TB));
}
template <int TB> __device__ __forceinline__ void wgmma_rs_n64(float (&d)[32], uint32_t a0, uint32_t a1, uint32_t a2, uint32_t a3, uint64_t db, int sc) {
    asm volatile("{\n.reg .pred p;\nsetp.ne.b32 p, %37, 0;\n"
        "wgmma.mma_async.sync.aligned.m64n64k16.f32.bf16.bf16 {%0, %1, %2, %3, %4, %5, %6, %7, %8, %9, %10, %11, %12, %13, %14, %15, %16, %17, %18, %19, %20, %21, %22, %23, %24, %25, %26, %27, %28, %29, %30, %31}, {%32, %33, %34, %35}, %36, p, 1, 1, %38;\n}\n"
        : "+f"(d[0]), "+f"(d[1]), "+f"(d[2]), "+f"(d[3]), "+f"(d[4]), "+f"(d[5]), "+f"(d[6]), "+f"(d[7]), "+f"(d[8]), "+f"(d[9]), "+f"(d[10]), "+f"(d[11]), "+f"(d[12]), "+f"(d[13]), "+f"(d[14]), "+f"(d[15]), "+f"(d[16]), "+f"(d[17]), "+f"(d[18]), "+f"(d[19]), "+f"(d[20]), "+f"(d[21]), "+f"(d[22]), "+f"(d[23]), "+f"(d[24]), "+f"(d[25]), "+f"(d[26]), "+f"(d[27]), "+f"(d[28]), "+f"(d[29]), "+f"(d[30]), "+f"(d[31])
        : "r"(a0), "r"(a1), "r"(a2), "r"(a3), "l"(db), "r"(sc), "n"(TB));
}
template <int TB> __device__ __forceinline__ void wgmma_rs_n128(float (&d)[64], uint32_t a0, uint32_t a1, uint32_t a2, uint32_t a3, uint64_t db, int sc) {
    asm volatile("{\n.reg .pred p;\nsetp.ne.b32 p, %69, 0;\n"
        "wgmma.mma_async.sync.aligned.m64n128k16.f32.bf16.bf16 {%0, %1, %2, %3, %4, %5, %6, %7, %8, %9, %10, %11, %12, %13, %14, %15, %16, %17, %18, %19, %20, %21, %22, %23, %24, %25, %26, %27, %28, %29, %30, %31, %32, %33, %34, %35, %36, %37, %38, %39, %40, %41, %42, %43, %44, %45, %46, %47, %48, %49, %50, %51, %52, %53, %54, %55, %56, %57, %58, %59, %60, %61, %62, %63}, {%64, %65, %66, %67}, %68, p, 1, 1, %70;\n}\n"
        : "+f"(d[0]), "+f"(d[1]), "+f"(d[2]), "+f"(d[3]), "+f"(d[4]), "+f"(d[5]), "+f"(d[6]), "+f"(d[7]), "+f"(d[8]), "+f"(d[9]), "+f"(d[10]), "+f"(d[11]), "+f"(d[12]), "+f"(d[13]), "+f"(d[14]), "+f"(d[15]), "+f"(d[16]), "+f"(d[17]), "+f"(d[18]), "+f"(d[19]), "+f"(d[20]), "+f"(d[21]), "+f"(d[22]), "+f"(d[23]), "+f"(d[24]), "+f"(d[25]), "+f"(d[26]), "+f"(d[27]), "+f"(d[28]), "+f"(d[29]), "+f"(d[30]), "+f"(d[31]), "+f"(d[32]), "+f"(d[33]), "+f"(d[34]), "+f"(d[35]), "+f"(d[36]), "+f"(d[37]), "+f"(d[38]), "+f"(d[39]), "+f"(d[40]), "+f"(d[41]), "+f"(d[42]), "+f"(d[43]), "+f"(d[44]), "+f"(d[45]), "+f"(d[46]), "+f"(d[47]), "+f"(d[48]), "+f"(d[49]), "+f"(d[50]), "+f"(d[51]), "+f"(d[52]), "+f"(d[53]), "+f"(d[54]), "+f"(d[55]), "+f"(d[56]), "+f"(d[57]), "+f"(d[58]), "+f"(d[59]), "+f"(d[60]), "+f"(d[61]), "+f"(d[62]), "+f"(d[63])
        : "r"(a0), "r"(a1), "r"(a2), "r"(a3), "l"(db), "r"(sc), "n"(TB));
}

constexpr int P_NST = 6;
constexpr int P_A_BYTES = 9 * 8192;
constexpr int P_B_STAGE = 3 * 8192;
constexpr int P_SMEM = P_A_BYTES + P_NST * P_B_STAGE + 256 + 320;

template <int NB>
__device__ __forceinline__ void stage_tile(const uint32_t (&pk)[NB * 2], uint32_t base, int w, int lane) {
    const int r = w * 16 + (lane & 7) + ((lane >> 3) & 1) * 8;
#pragma unroll
    for (int b = 0; b < NB; b += 2) {
        const uint32_t a = base + (b >> 3) * 8192 + r * 128 + ((((b & 7) + (lane >> 4)) ^ (r & 7)) << 4);
        stmatrix_x4(a, pk[2 * b], pk[2 * b + 1], pk[2 * b + 2], pk[2 * b + 3]);
    }
}

__device__ __forceinline__ uint32_t hsub2_bf16(uint32_t a, uint32_t b) { uint32_t r; asm("sub.rn.bf16x2 %0, %1, %2;" : "=r"(r) : "r"(a), "r"(b)); return r; }

constexpr int KV_RAW = DM * 18 * 2;
constexpr int Q_THREADS = 416;

__device__ __forceinline__ void proj_mma(float (&acc)[32], int wg, uint32_t fullB, uint32_t emptyB, uint32_t fullA, bool wait_a, int lane) {
    const uint64_t dA = cdesc(0, 16, 1024, 1), dB = cdesc(P_A_BYTES, 8192, 1024, 1) + wg * 512;
#pragma unroll 1
    for (int kb = 0; kb < 9; kb++) {
        const int s = kb >= P_NST ? kb - P_NST : kb;
        if (wait_a) mbar_wait(fullA + kb * 8, 0);
        mbar_wait(fullB + s * 8, kb >= P_NST ? 1 : 0);
        wg_fence();
#pragma unroll
        for (int ks = 0; ks < 4; ks++) wgmma_ss_n64<1>(acc, dA + (kb * 512 + ks * 2), dB + (s * (P_B_STAGE >> 4) + ks * 128), (kb | ks) != 0);
        wg_commit();
        if (kb < 4) {
            wg_wait<1>();
            if (kb >= 1 && lane == 0) mbar_arrive(emptyB + (kb - 1) * 8);
        }
    }
    wg_wait<0>();
    pin(acc);
}

__global__ void __launch_bounds__(Q_THREADS, 1)
k_qkv(const __grid_constant__ CUtensorMap tmWq, const __grid_constant__ CUtensorMap tmQ, const __nv_bfloat16* __restrict__ x, const __nv_bfloat16* __restrict__ wk, const __nv_bfloat16* __restrict__ wv) {
    extern __shared__ __align__(1024) uint8_t smem[];
    const uint32_t sA = smem_u32(smem), sB = sA + P_A_BYTES, bars = sB + P_NST * P_B_STAGE;
    const uint32_t fullB = bars, emptyB = bars + 64, fullX = bars + 128, fullW = bars + 136;
    float* s_rstd = reinterpret_cast<float*>(smem + P_A_BYTES + P_NST * P_B_STAGE + 256);
    const int tid = threadIdx.x, warp = __shfl_sync(~0u, tid >> 5, 0), lane = tid & 31;
    const bool isQ = blockIdx.x < 96;
    const int m = isQ ? blockIdx.x / 3 : blockIdx.x - 96, cg = blockIdx.x % 3;
    if (warp == 12) {
        if (elect_one()) {
            mbar_init(fullX, 1);
            bar_init_fence();
            mbar_expect(fullX, P_A_BYTES);
            bulk_g2s(sA, x + (size_t)m * 64 * DM, P_A_BYTES, fullX);
            prefetch_map(&tmWq); prefetch_map(&tmQ);
            for (int i = 0; i < P_NST; i++) { mbar_init(fullB + i * 8, 1); mbar_init(emptyB + i * 8, 12); }
            mbar_init(fullW, 1);
            bar_init_fence();
            if (isQ) {
                for (int kb = 0; kb < P_NST; kb++) {
                    mbar_expect(fullB + kb * 8, P_B_STAGE);
                    for (int a = 0; a < 3; a++) tma_2d(sB + kb * P_B_STAGE + a * 8192, &tmWq, cg * 192 + a * 64, kb * 64, fullB + kb * 8);
                }
            } else {
                mbar_expect(fullW, 2 * KV_RAW);
                bulk_g2s(sB + 3 * P_B_STAGE, wk, KV_RAW, fullW);
                bulk_g2s(sB + 3 * P_B_STAGE + KV_RAW, wv, KV_RAW, fullW);
            }
        }
        __syncwarp();
    }
    check_smem_base(sA);
    __syncthreads();
    pdl_launch();
    if (warp == 12) {
        if (isQ && elect_one()) {
            for (int kb = P_NST; kb < 9; kb++) {
                const int s = kb - P_NST;
                mbar_wait(emptyB + s * 8, 0);
                mbar_expect(fullB + s * 8, P_B_STAGE);
                for (int a = 0; a < 3; a++) tma_2d(sB + s * P_B_STAGE + a * 8192, &tmWq, cg * 192 + a * 64, kb * 64, fullB + s * 8);
            }
        }
        return;
    }
    if (warp < 8) {
        const int row = tid >> 2, q = tid & 3, h0 = (row & 1) * 4;
        mbar_wait(fullX, 0);
        uint4 v[18];
        const uint32_t ra = sA + row * 1152 + (q + h0) * 16, rb = sA + row * 1152 + (q + 4 - h0) * 16;
#pragma unroll
        for (int kb = 0; kb < 9; kb++) {
            asm volatile("ld.shared.v4.b32 {%0, %1, %2, %3}, [%4];" : "=r"(v[2 * kb].x), "=r"(v[2 * kb].y), "=r"(v[2 * kb].z), "=r"(v[2 * kb].w) : "r"(ra + kb * 128));
            asm volatile("ld.shared.v4.b32 {%0, %1, %2, %3}, [%4];" : "=r"(v[2 * kb + 1].x), "=r"(v[2 * kb + 1].y), "=r"(v[2 * kb + 1].z), "=r"(v[2 * kb + 1].w) : "r"(rb + kb * 128));
        }
        float sum = 0.f, sum2 = 0.f, sq = 0.f, sq2 = 0.f;
#pragma unroll
        for (int i = 0; i < 18; i++) {
            const uint32_t w[4] = {v[i].x, v[i].y, v[i].z, v[i].w};
#pragma unroll
            for (int j = 0; j < 4; j++) { const float a = bf_lo(w[j]), b = bf_hi(w[j]); sum += a; sum2 += b; sq = fmaf(a, a, sq); sq2 = fmaf(b, b, sq2); }
        }
        named_sync(1, 256);
        sum += sum2; sq += sq2;
        sum += __shfl_xor_sync(~0u, sum, 1); sum += __shfl_xor_sync(~0u, sum, 2);
        sq += __shfl_xor_sync(~0u, sq, 1); sq += __shfl_xor_sync(~0u, sq, 2);
        const float mean = sum * (1.0f / DM);
        if (q == 0) s_rstd[row] = rsqrtf(fmaxf(sq * (1.0f / DM) - mean * mean, 0.f) + LN_EPS);
        const uint32_t mhi = pack_bf16(mean, mean);
        const float rem = mean - bf_lo(mhi);
        const uint32_t mlo = pack_bf16(rem, rem);
        const uint32_t wa = sA + row * 128 + (((q + h0) ^ (row & 7)) << 4), wb = sA + row * 128 + (((q + 4 - h0) ^ (row & 7)) << 4);
#pragma unroll
        for (int i = 0; i < 18; i++) {
            const uint32_t o0 = hsub2_bf16(hsub2_bf16(v[i].x, mhi), mlo), o1 = hsub2_bf16(hsub2_bf16(v[i].y, mhi), mlo);
            const uint32_t o2 = hsub2_bf16(hsub2_bf16(v[i].z, mhi), mlo), o3 = hsub2_bf16(hsub2_bf16(v[i].w, mhi), mlo);
            asm volatile("st.shared.v4.b32 [%0], {%1, %2, %3, %4};" ::"r"(((i & 1) ? wb : wa) + (i >> 1) * 8192), "r"(o0), "r"(o1), "r"(o2), "r"(o3) : "memory");
        }
    } else if (!isQ) {
        mbar_wait(fullW, 0);
        const uint32_t* raw = reinterpret_cast<const uint32_t*>(smem + P_A_BYTES + 3 * P_B_STAGE);
#pragma unroll 3
        for (int r = tid - 256; r < 2 * DM; r += 128) {
            uint32_t wr[9];
#pragma unroll
            for (int i = 0; i < 9; i++) wr[i] = raw[r * 9 + i];
            const int sel = r >= DM, k = r - sel * DM;
            uint8_t* dst = smem + P_A_BYTES + sel * 3 * 9216 + (k >> 3) * 128 + (k & 7) * 16;
            *reinterpret_cast<uint4*>(dst) = make_uint4(wr[0], wr[1], wr[2], wr[3]);
            *reinterpret_cast<uint4*>(dst + 9216) = make_uint4(wr[4], wr[5], wr[6], wr[7]);
            *reinterpret_cast<uint32_t*>(dst + 2 * 9216) = wr[8];
        }
    }
    proxy_fence();
    named_sync(2, 384);
    const int wg = warp >> 2, w = warp & 3, g = lane >> 2, t = lane & 3;
    const float rs0 = s_rstd[w * 16 + g], rs1 = s_rstd[w * 16 + g + 8];
    if (isQ) {
        const float c0 = rs0 * Q_SCALE, c1 = rs1 * Q_SCALE;
        float acc[32];
        proj_mma(acc, wg, fullB, emptyB, 0, false, lane);
        uint32_t pk[16];
#pragma unroll
        for (int i = 0; i < 8; i++) { pk[2 * i] = pack_bf16(acc[4 * i] * c0, acc[4 * i + 1] * c0); pk[2 * i + 1] = pack_bf16(acc[4 * i + 2] * c1, acc[4 * i + 3] * c1); }
        named_sync(2, 384);
        stage_tile<8>(pk, sA + wg * 8192, w, lane);
        proxy_fence();
        named_sync(3 + wg, 128);
        if (w == 0 && elect_one()) {
            tma_st_2d(&tmQ, cg * 192 + wg * 64, m * 64, sA + wg * 8192);
            bulk_commit();
            bulk_wait_all();
        }
    } else if (wg < 2) {
        float acc[12];
        const uint64_t dA = cdesc(0, 16, 1024, 1), dB = cdesc(P_A_BYTES, 128, 9216, 0) + wg * (3 * 9216 >> 4);
#pragma unroll
        for (int i = 0; i < 12; i++) acc[i] = 0.f;
        pin(acc);
        wg_fence();
#pragma unroll 1
        for (int kb = 0; kb < 9; kb++) {
#pragma unroll
            for (int ks = 0; ks < 4; ks++) wgmma_ss_n24<1>(acc, dA + (kb * 512 + ks * 2), dB + (kb * 4 + ks) * 16, 1);
        }
        wg_commit();
        wg_wait<0>();
        pin(acc);
        uint32_t pk[6];
#pragma unroll
        for (int b = 0; b < 3; b++) { pk[2 * b] = pack_bf16(acc[4 * b] * rs0, acc[4 * b + 1] * rs0); pk[2 * b + 1] = pack_bf16(acc[4 * b + 2] * rs1, acc[4 * b + 3] * rs1); }
        float n0 = 0.f, n1 = 0.f, vm = 0.f;
#pragma unroll
        for (int b = 0; b < 3; b++) {
            if (b < 2 || t == 0) {
                const float a = bf_lo(pk[2 * b]), c = bf_hi(pk[2 * b]), d = bf_lo(pk[2 * b + 1]), e = bf_hi(pk[2 * b + 1]);
                n0 = fmaf(a, a, fmaf(c, c, n0)); n1 = fmaf(d, d, fmaf(e, e, n1));
            }
        }
        n0 += __shfl_xor_sync(~0u, n0, 1); n0 += __shfl_xor_sync(~0u, n0, 2);
        n1 += __shfl_xor_sync(~0u, n1, 1); n1 += __shfl_xor_sync(~0u, n1, 2);
        vm = fmaxf(n0, n1);
        if (!(n0 == n0) || !(n1 == n1)) vm = __int_as_float(0x7F800000);
#pragma unroll
        for (int o = 4; o < 32; o <<= 1) vm = fmaxf(vm, __shfl_xor_sync(~0u, vm, o));
        if (t != 0) {
            uint32_t lo, hi;
            if (wg == 0) {
                const int grp = m * 8 + w * 2;
                const uint32_t c = t == 1 ? 0x42FE3F80u   : (t == 2 ? 0x00003BC0u   : 0u);
                lo = ((POLY_MASK >> (grp & 15)) & 1) ? c : 0u;
                hi = ((POLY_MASK >> ((grp + 1) & 15)) & 1) ? c : 0u;
            } else {
                lo = hi = t == 1 ? 0x00003F80u : 0u;
            }
            pk[4] = lo; pk[5] = hi;
        }
        uint32_t* dst = reinterpret_cast<uint32_t*>(wg == 0 ? g_kc : g_vc) + (m * 8 + w * 2) * 96 + g * 4 + t;
#pragma unroll
        for (int b = 0; b < 3; b++) { dst[b * 32] = pk[2 * b]; dst[96 + b * 32] = pk[2 * b + 1]; }
        if (lane == 0) g_kmax[m * 8 + warp] = (wg == 0) ? vm : (vm <= 1e24f ? 0.f : __int_as_float(0x7F800000));
    }
}

constexpr int A_THREADS = 512;
constexpr int A_NPIECE = 8;
constexpr int A_OFF_Q = 2 * KV_BYTES;
constexpr int A_OFF_BAR = A_OFF_Q + 8 * 4096;
constexpr int A_SMEM = A_OFF_BAR + 128;

__device__ __forceinline__ uint32_t exp2_pair_fixed(float lo, float hi, uint32_t dep) {
    const uint32_t G = __byte_perm(__float_as_uint(lo), __float_as_uint(hi), 0x5410);
    uint32_t Hh;
    asm("lop3.b32 %0, %1, 0x007F007F, %2, 0xC0;" : "=r"(Hh) : "r"(G), "r"(dep));
    const uint32_t tt = hfma2(Hh, 0xF96BF96Bu, 0x358C358Cu);
    return G - hfma2(tt, Hh, 0u);
}

__global__ void __launch_bounds__(A_THREADS, 1)
k_attn() {
    extern __shared__ __align__(1024) uint8_t smem[];
    pdl_launch();
    const uint32_t sK = smem_u32(smem), sV = sK + KV_BYTES, bars = sK + A_OFF_BAR;
    const int tid = threadIdx.x;
    check_smem_base(sK);
    if (tid == 0) {
        for (int i = 0; i < A_NPIECE; i++) mbar_init(bars + i * 8, 1);
        bar_init_fence();
    }
    __syncthreads();
    pdl_wait();
    const int wg = __shfl_sync(~0u, tid >> 7, 0), w = (tid >> 5) & 3, lane = tid & 31, g = lane >> 2, t = lane & 3;
    const uint32_t* q32 = reinterpret_cast<const uint32_t*>(g_q);
    int row = (blockIdx.x * 8 + wg) * 64 + w * 16 + g;
    uint32_t nq[2][6];
#pragma unroll
    for (int r = 0; r < 2; r++) {
        const uint32_t* q = q32 + (row + r * 256) * 9;
        nq[r][0] = q[t]; nq[r][1] = q[72 + t]; nq[r][2] = q[4 + t]; nq[r][3] = q[76 + t]; nq[r][4] = q[8]; nq[r][5] = q[80];
    }
    constexpr int PB = KV_BYTES / A_NPIECE;
    const float4 km0 = reinterpret_cast<const float4*>(g_kmax)[lane], km1 = reinterpret_cast<const float4*>(g_kmax)[32 + lane];
    if (tid < 32 && elect_one()) {
        for (int i = 0; i < 2; i++) {
            mbar_expect(bars + i * 8, 2 * PB);
            bulk_g2s(sK + i * PB, reinterpret_cast<const char*>(g_kc) + i * PB, PB, bars + i * 8);
            bulk_g2s(sV + i * PB, reinterpret_cast<const char*>(g_vc) + i * PB, PB, bars + i * 8);
        }
    }
    float kmax2 = fmaxf(fmaxf(fmaxf(km0.x, km0.y), fmaxf(km0.z, km0.w)), fmaxf(fmaxf(km1.x, km1.y), fmaxf(km1.z, km1.w)));
#pragma unroll
    for (int o = 1; o < 32; o <<= 1) kmax2 = fmaxf(kmax2, __shfl_xor_sync(~0u, kmax2, o));
    if (tid < 32 && elect_one()) {
        for (int i = 2; i < A_NPIECE; i++) {
            mbar_expect(bars + i * 8, 2 * PB);
            bulk_g2s(sK + i * PB, reinterpret_cast<const char*>(g_kc) + i * PB, PB, bars + i * 8);
            bulk_g2s(sV + i * PB, reinterpret_cast<const char*>(g_vc) + i * PB, PB, bars + i * 8);
        }
    }
    uint32_t vote = 0;
#pragma unroll
    for (int r = 0; r < 2; r++) {
        const uint32_t (&q)[6] = nq[r];
        const float a0 = bf_lo(q[0]), a1 = bf_hi(q[0]), a2 = bf_lo(q[2]), a3 = bf_hi(q[2]);
        const float b0 = bf_lo(q[1]), b1 = bf_hi(q[1]), b2 = bf_lo(q[3]), b3 = bf_hi(q[3]);
        float n0 = a0 * a0 + a1 * a1 + a2 * a2 + a3 * a3, n1 = b0 * b0 + b1 * b1 + b2 * b2 + b3 * b3;
        if (t == 0) {
            const float c0 = bf_lo(q[4]), c1 = bf_hi(q[4]), d0 = bf_lo(q[5]), d1 = bf_hi(q[5]);
            n0 += c0 * c0 + c1 * c1; n1 += d0 * d0 + d1 * d1;
        }
        n0 += __shfl_xor_sync(~0u, n0, 1); n0 += __shfl_xor_sync(~0u, n0, 2);
        n1 += __shfl_xor_sync(~0u, n1, 1); n1 += __shfl_xor_sync(~0u, n1, 2);
        const bool unsafe = !(fmaxf(n0, n1) * kmax2 <= FAST_BOUND * FAST_BOUND) || !(n0 == n0) || !(n1 == n1);
        vote |= (__any_sync(~0u, unsafe) ? 1u : 0u) << r;
        const uint32_t cst = t == 1 ? 0x3F804780u : (t == 2 ? 0x00003F80u : 0u);
        const uint32_t sQ = sK + A_OFF_Q + (r * 4 + wg) * 4096 + (w * 2) * 512 + g * 16 + t * 4;
        asm volatile("st.shared.b32 [%0], %1;" ::"r"(sQ), "r"(q[0]) : "memory");
        asm volatile("st.shared.b32 [%0], %1;" ::"r"(sQ + 512), "r"(q[1]) : "memory");
        asm volatile("st.shared.b32 [%0], %1;" ::"r"(sQ + 128), "r"(q[2]) : "memory");
        asm volatile("st.shared.b32 [%0], %1;" ::"r"(sQ + 640), "r"(q[3]) : "memory");
        asm volatile("st.shared.b32 [%0], %1;" ::"r"(sQ + 256), "r"(t == 0 ? q[4] : cst) : "memory");
        asm volatile("st.shared.b32 [%0], %1;" ::"r"(sQ + 768), "r"(t == 0 ? q[5] : cst) : "memory");
        asm volatile("st.shared.b32 [%0], %1;" ::"r"(sQ + 384), "r"(0u) : "memory");
        asm volatile("st.shared.b32 [%0], %1;" ::"r"(sQ + 896), "r"(0u) : "memory");
    }
    const uint32_t sVote = bars + 64 + wg * 16;
    if (lane == 0) asm volatile("st.shared.b32 [%0], %1;" ::"r"(sVote + w * 4), "r"(vote) : "memory");
    proxy_fence();
    named_sync(wg + 1, 128);
    uint32_t unsafe_mask;
    {
        uint32_t v0, v1, v2, v3;
        asm volatile("ld.shared.v4.b32 {%0, %1, %2, %3}, [%4];" : "=r"(v0), "=r"(v1), "=r"(v2), "=r"(v3) : "r"(sVote));
        unsafe_mask = __shfl_sync(~0u, v0 | v1 | v2 | v3, 0);
    }
    if (unsafe_mask) {
#pragma unroll
        for (int r = 0; r < 2; r++) {
            if (((unsafe_mask >> r) & 1) && t != 0) {
                const uint32_t sQ = sK + A_OFF_Q + (r * 4 + wg) * 4096 + (w * 2) * 512 + g * 16 + t * 4;
                asm volatile("st.shared.b32 [%0], %1;" ::"r"(sQ + 256), "r"(0u) : "memory");
                asm volatile("st.shared.b32 [%0], %1;" ::"r"(sQ + 768), "r"(0u) : "memory");
            }
        }
        proxy_fence();
        named_sync(wg + 1, 128);
    }
#pragma unroll 1
    for (int rep = 0; rep < 2; rep++, row += 256) {
        const uint32_t any_unsafe = (unsafe_mask >> rep) & 1;
        const uint64_t dQ0 = cdesc(A_OFF_Q, 128, 512, 0) + (rep * 4 + wg) * 256, dQ1 = dQ0 + 16;
        float o[12];
#pragma unroll
        for (int i = 0; i < 12; i++) o[i] = 0.f;
        pin(o);
        uint64_t dK0 = cdesc(0, 128, 384, 0), dK1 = cdesc(256, 0, 384, 0), dV = cdesc(KV_BYTES, 384, 128, 0);
        if (!any_unsafe) {
            float s[64];
#pragma unroll 1
            for (int j = 0; j < 16; j++) {
                if (rep == 0 && (j & 1) == 0) mbar_wait(bars + (j >> 1) * 8, 0);
                wg_fence();
                wgmma_ss_n128<0>(s, dQ0, dK0, 0);
                wgmma_ss_n128<0>(s, dQ1, dK1, 1);
                wg_commit();
                dK0 += 16 * 384 >> 4; dK1 += 16 * 384 >> 4;
                wg_wait<0>();
                pin(s);
                uint32_t p[32];
#define CHAIN 6
                {
                    constexpr int NP = 2 * __builtin_popcount(POLY_MASK), NM = 32 - NP;
                    float e[64];
#pragma unroll
                    for (int i = 0; i < 32; i++)
                        if (!((POLY_MASK >> (i >> 1)) & 1)) { e[2 * i] = ex2(s[2 * i]); e[2 * i + 1] = ex2(s[2 * i + 1]); p[i] = pack_bf16(e[2 * i], e[2 * i + 1]); }
                    int ip = 0;
#pragma unroll
                    for (int i = 0; i < 32; i++) {
                        if ((POLY_MASK >> (i >> 1)) & 1) {
                            const int mm = (ip * 2 * NM) / NP - CHAIN;
                            uint32_t dep = 0;
                            if (CHAIN > 0 && mm >= 0) {
                                int cnt = 0;
#pragma unroll
                                for (int q = 0; q < 32; q++)
                                    if (!((POLY_MASK >> (q >> 1)) & 1)) { if (cnt == (mm >> 1)) dep = __float_as_uint(e[2 * q + (mm & 1)]); cnt++; }
                            }
                            p[i] = exp2_pair_fixed(s[2 * i], s[2 * i + 1], dep);
                            ip++;
                        }
                    }
                }
                pin(p);
                wg_fence();
#pragma unroll
                for (int k = 0; k < 8; k++) {
                    wgmma_rs_n24<1>(o, p[4 * k], p[4 * k + 1], p[4 * k + 2], p[4 * k + 3], dV + k * 48, 1);
                }
                wg_commit();
                dV += 16 * 384 >> 4;
                wg_wait<0>();
            }
        } else {
            float s[64];
            float m0 = -INFINITY, m1 = -INFINITY;
#pragma unroll 1
            for (int j = 0; j < 16; j++) {
                if (rep == 0 && (j & 1) == 0) mbar_wait(bars + (j >> 1) * 8, 0);
                wg_fence();
                wgmma_ss_n128<0>(s, dQ0, dK0, 0);
                wgmma_ss_n128<0>(s, dQ1, dK1, 1);
                wg_commit();
                dK0 += 16 * 384 >> 4; dK1 += 16 * 384 >> 4;
                wg_wait<0>();
                pin(s);
                float x0m = m0, x1m = m1;
#pragma unroll
                for (int b = 0; b < 16; b++) { x0m = fmaxf(x0m, fmaxf(s[4 * b], s[4 * b + 1])); x1m = fmaxf(x1m, fmaxf(s[4 * b + 2], s[4 * b + 3])); }
                x0m = fmaxf(x0m, __shfl_xor_sync(~0u, x0m, 1)); x0m = fmaxf(x0m, __shfl_xor_sync(~0u, x0m, 2));
                x1m = fmaxf(x1m, __shfl_xor_sync(~0u, x1m, 1)); x1m = fmaxf(x1m, __shfl_xor_sync(~0u, x1m, 2));
                const float c0 = ex2(m0 - x0m), c1 = ex2(m1 - x1m);
                m0 = x0m; m1 = x1m;
#pragma unroll
                for (int b = 0; b < 3; b++) { o[4 * b] *= c0; o[4 * b + 1] *= c0; o[4 * b + 2] *= c1; o[4 * b + 3] *= c1; }
                uint32_t p[32];
#pragma unroll
                for (int b = 0; b < 16; b++) {
                    p[2 * b] = pack_bf16(ex2(s[4 * b] - m0), ex2(s[4 * b + 1] - m0));
                    p[2 * b + 1] = pack_bf16(ex2(s[4 * b + 2] - m1), ex2(s[4 * b + 3] - m1));
                }
                pin(p); pin(o);
                wg_fence();
#pragma unroll
                for (int k = 0; k < 8; k++) wgmma_rs_n24<1>(o, p[4 * k], p[4 * k + 1], p[4 * k + 2], p[4 * k + 3], dV + k * 48, 1);
                wg_commit();
                dV += 16 * 384 >> 4;
                wg_wait<0>();
            }
        }
        pin(o);
        const float l0 = __shfl_sync(~0u, o[8], (lane & ~3) | 1), l1 = __shfl_sync(~0u, o[10], (lane & ~3) | 1);
        const float i0 = 1.0f / l0, i1 = 1.0f / l1;
        uint32_t* o32 = reinterpret_cast<uint32_t*>(g_o);
        o32[row * 9 + t] = pack_bf16(o[0] * i0, o[1] * i0);
        o32[(row + 8) * 9 + t] = pack_bf16(o[2] * i1, o[3] * i1);
        o32[row * 9 + 4 + t] = pack_bf16(o[4] * i0, o[5] * i0);
        o32[(row + 8) * 9 + 4 + t] = pack_bf16(o[6] * i1, o[7] * i1);
        if (t == 0) { o32[row * 9 + 8] = pack_bf16(o[8] * i0, o[9] * i0); o32[(row + 8) * 9 + 8] = pack_bf16(o[10] * i1, o[11] * i1); }
    }
}

constexpr int O_THREADS = 416;
constexpr int O_OFF_STAT = P_A_BYTES + P_NST * P_B_STAGE + 256;
constexpr int O_SMEM = O_OFF_STAT + 9 * 64 * 8;

__global__ void __cluster_dims__(3, 1, 1) __launch_bounds__(O_THREADS, 1)
k_oproj(const __grid_constant__ CUtensorMap tmO, const __grid_constant__ CUtensorMap tmWo, const __grid_constant__ CUtensorMap tmX2, const __grid_constant__ CUtensorMap tmOut, const __nv_bfloat16* __restrict__ x, const __nv_bfloat16* __restrict__ w1) {
    extern __shared__ __align__(1024) uint8_t smem[];
    const uint32_t sA = smem_u32(smem), sB = sA + P_A_BYTES, bars = sB + P_NST * P_B_STAGE;
    const uint32_t fullB = bars, emptyB = bars + 64, fullA = bars + 128;
    const int tid = threadIdx.x, warp = __shfl_sync(~0u, tid >> 5, 0), lane = tid & 31;
    const int m = blockIdx.x / 3, cg = blockIdx.x % 3;
    check_smem_base(sA);
    if (tid == 0) {
        prefetch_map(&tmO); prefetch_map(&tmWo); prefetch_map(&tmX2); prefetch_map(&tmOut);
        for (int i = 0; i < P_NST; i++) { mbar_init(fullB + i * 8, 1); mbar_init(emptyB + i * 8, 12); }
        for (int i = 0; i < 9; i++) mbar_init(fullA + i * 8, 1);
        bar_init_fence();
        for (int kb = 0; kb < 9; kb++) mbar_expect(fullA + kb * 8, 8192);
    }
    __syncthreads();
    pdl_launch();
    if (warp == 12) {
        if (elect_one()) {
            for (int kb = 0; kb < 9; kb++) {
                const int s = kb >= P_NST ? kb - P_NST : kb;
                if (kb == 2) {
                    pdl_wait();
                    for (int ka = 0; ka < 9; ka++) tma_2d(sA + ka * 8192, &tmO, ka * 64, m * 64, fullA + ka * 8);
                }
                if (kb >= P_NST) mbar_wait(emptyB + s * 8, 0);
                mbar_expect(fullB + s * 8, P_B_STAGE);
                for (int a = 0; a < 3; a++) tma_2d(sB + s * P_B_STAGE + a * 8192, &tmWo, cg * 192 + a * 64, kb * 64, fullB + s * 8);
            }
            for (int i = 0; i < 6; i++) prefetch_l2(reinterpret_cast<const char*>(w1) + (size_t)blockIdx.x * (FF * DM * 2 / 96) + i * 9216, 9216);
        }
        return;
    }
    const int wg = warp >> 2, w = warp & 3, g = lane >> 2, t = lane & 3;
    uint32_t xr[16];
    {
        const uint32_t* x32 = reinterpret_cast<const uint32_t*>(x) + (((m * 64 + w * 16 + g) * DM + cg * 192 + wg * 64 + 2 * t) >> 1);
#pragma unroll
        for (int b = 0; b < 8; b++) { xr[2 * b] = __ldg(x32 + b * 4); xr[2 * b + 1] = __ldg(x32 + b * 4 + 4 * DM); }
    }
    float acc[32];
    proj_mma(acc, wg, fullB, emptyB, fullA, true, lane);
    named_sync(1, 384);
    float s0 = 0.f, q0 = 0.f, s1 = 0.f, q1 = 0.f;
#pragma unroll
    for (int b = 0; b < 8; b++) {
        const uint32_t xa = xr[2 * b], xb = xr[2 * b + 1];
        const uint32_t ha = pack_bf16(acc[4 * b] + bf_lo(xa), acc[4 * b + 1] + bf_hi(xa));
        const uint32_t hb = pack_bf16(acc[4 * b + 2] + bf_lo(xb), acc[4 * b + 3] + bf_hi(xb));
        xr[2 * b] = ha; xr[2 * b + 1] = hb;
        const float a = bf_lo(ha), c = bf_hi(ha), d = bf_lo(hb), e = bf_hi(hb);
        s0 += a + c; q0 = fmaf(a, a, fmaf(c, c, q0));
        s1 += d + e; q1 = fmaf(d, d, fmaf(e, e, q1));
    }
    s0 += __shfl_xor_sync(~0u, s0, 1); s0 += __shfl_xor_sync(~0u, s0, 2);
    q0 += __shfl_xor_sync(~0u, q0, 1); q0 += __shfl_xor_sync(~0u, q0, 2);
    s1 += __shfl_xor_sync(~0u, s1, 1); s1 += __shfl_xor_sync(~0u, s1, 2);
    q1 += __shfl_xor_sync(~0u, q1, 1); q1 += __shfl_xor_sync(~0u, q1, 2);
    const int r = w * 16 + g;
    const uint32_t sStat = sA + O_OFF_STAT;
    if (t < 3) {
        uint32_t dst;
        asm("mapa.shared::cluster.u32 %0, %1, %2;" : "=r"(dst) : "r"(sStat + ((cg * 3 + wg) * 64 + r) * 8), "r"(t));
        asm volatile("st.shared::cluster.v2.f32 [%0], {%1, %2};" ::"r"(dst), "f"(s0), "f"(q0) : "memory");
        asm volatile("st.shared::cluster.v2.f32 [%0], {%1, %2};" ::"r"(dst + 64), "f"(s1), "f"(q1) : "memory");
    }
    cluster_arrive();
    stage_tile<8>(xr, sA + wg * 8192, w, lane);
    proxy_fence();
    named_sync(2 + wg, 128);
    const bool leader = w == 0 && elect_one();
    if (leader) { tma_st_2d(&tmOut, cg * 192 + wg * 64, m * 64, sA + wg * 8192); bulk_commit(); }
    cluster_wait();
    s0 = q0 = s1 = q1 = 0.f;
#pragma unroll
    for (int p = 0; p < 9; p++) {
        float a, b, c, d;
        asm volatile("ld.shared.v2.f32 {%0, %1}, [%2];" : "=f"(a), "=f"(b) : "r"(sStat + (p * 64 + r) * 8));
        asm volatile("ld.shared.v2.f32 {%0, %1}, [%2];" : "=f"(c), "=f"(d) : "r"(sStat + (p * 64 + r + 8) * 8));
        s0 += a; q0 += b; s1 += c; q1 += d;
    }
    const float m0 = s0 * (1.0f / DM), m1 = s1 * (1.0f / DM);
    const float rs0 = rsqrtf(fmaxf(q0 * (1.0f / DM) - m0 * m0, 0.f) + LN_EPS), rs1 = rsqrtf(fmaxf(q1 * (1.0f / DM) - m1 * m1, 0.f) + LN_EPS);
    const float sc0 = 0.5f * rs0, sc1 = 0.5f * rs1, n0 = -m0 * sc0, n1 = -m1 * sc1;
#pragma unroll
    for (int b = 0; b < 8; b++) {
        xr[2 * b] = pack_bf16(fmaf(bf_lo(xr[2 * b]), sc0, n0), fmaf(bf_hi(xr[2 * b]), sc0, n0));
        xr[2 * b + 1] = pack_bf16(fmaf(bf_lo(xr[2 * b + 1]), sc1, n1), fmaf(bf_hi(xr[2 * b + 1]), sc1, n1));
    }
    stage_tile<8>(xr, sA + (3 + wg) * 8192, w, lane);
    proxy_fence();
    named_sync(2 + wg, 128);
    if (leader) {
        tma_st_2d(&tmX2, cg * 192 + wg * 64, m * 64, sA + (3 + wg) * 8192);
        bulk_commit();
        bulk_wait_all();
    }
}

constexpr int F_THREADS = 384;
constexpr int F_NST = 6;
constexpr int F_STAGE = 96 * 128;
constexpr int F_X_BYTES = 9 * 16384;
constexpr int F_OFF_ST = F_X_BYTES;
constexpr int F_OFF_BAR = F_OFF_ST + F_NST * F_STAGE;
constexpr int F_SMEM = F_OFF_BAR + 256;

__device__ __forceinline__ float tanh_hw(float x) { float y; asm("tanh.approx.f32 %0, %1;" : "=f"(y) : "f"(x)); return y; }
__host__ __device__ constexpr int piece_begin(int p) { return p == 0 ? 0 : 3 * p + 1; }
template <int P>
__device__ __forceinline__ void silu_s1(const float (&acc)[32], float (&tmp)[8]) {
#pragma unroll
    for (int i = 2 * piece_begin(P); i < 2 * piece_begin(P + 1); i++) tmp[i - 2 * piece_begin(P)] = tanh_hw(acc[i]);
}
template <int C, int P>
__device__ __forceinline__ void silu_s2(const float (&acc)[32], const float (&tmp)[8], uint32_t (&h1)[144]) {
#pragma unroll
    for (int i = piece_begin(P); i < piece_begin(P + 1); i++) {
        const int k = 2 * (i - piece_begin(P));
        h1[C * 16 + i] = pack_bf16(fmaf(acc[2 * i], tmp[k], acc[2 * i]), fmaf(acc[2 * i + 1], tmp[k + 1], acc[2 * i + 1]));
    }
}
template <int J>
__device__ __forceinline__ void silu_slot_last(const float (&prev)[32], float (&tmp)[2][8], uint32_t (&h1)[144]) {
    if constexpr (J >= 1 && J <= 4) {
#pragma unroll
        for (int i = 0; i < 4; i++) {
            const int q = 4 * (J - 1) + i;
            h1[128 + q] = pack_bf16(fmaf(prev[2 * q], tmp[(J - 1) & 1][2 * i], prev[2 * q]), fmaf(prev[2 * q + 1], tmp[(J - 1) & 1][2 * i + 1], prev[2 * q + 1]));
        }
    }
    if constexpr (J <= 3) {
#pragma unroll
        for (int i = 0; i < 8; i++) tmp[J & 1][i] = tanh_hw(prev[8 * J + i]);
        pin(tmp[J & 1]);
    }
}
template <int C, int J>
__device__ __forceinline__ void silu_slot(const float (&prev)[32], float (&tmp)[2][8], uint32_t (&h1)[144]) {
    if constexpr (J >= 1) silu_s2<C, J - 1>(prev, tmp[(J - 1) & 1], h1);
    if constexpr (J <= 4) { silu_s1<J>(prev, tmp[J & 1]); pin(tmp[J & 1]); }
}

struct FfnPipe {
    uint32_t full, empty;
    int lane;
    __device__ __forceinline__ void acquire(int s, uint32_t ph) const { mbar_wait(full + s * 8, ph); }
    __device__ __forceinline__ void release(int s) const { if (lane == 0) mbar_arrive(empty + s * 8); }
};

template <int C>
__device__ __forceinline__ void ffn_phase1_chunk(float (&cur)[32], float (&prev)[32], uint32_t (&h1)[144], const FfnPipe& pp, uint64_t dx, uint32_t fullX) {
    float tmp[2][8];
    const uint64_t dw = cdesc(F_OFF_ST, 8192, 1024, 1) + blockIdx.y * (C + 1);
    dx += blockIdx.y * C;
#pragma unroll
    for (int j = 0; j < 6; j++) {
        if (C == 0) { mbar_wait(fullX + ((6 * j) >> 2) * 8, 0); mbar_wait(fullX + ((6 * j + 5) >> 2) * 8, 0); }
        pp.acquire(j, C & 1);
        if (j == 0) pin(cur);
        wg_fence();
#pragma unroll
        for (int i = 0; i < 6; i++) {
            const int ks = 6 * j + i;
            wgmma_ss_n64<1>(cur, dx + ((ks >> 2) * 1024 + (ks & 3) * 2), dw + ((j * F_STAGE + i * 2048) >> 4), ks != 0);
        }
        wg_commit();
        if (C > 0 || j > 0) { wg_wait<1>(); pp.release((j + 5) % 6); }
        if (C > 0) {
            constexpr int CP = C > 0 ? C - 1 : 0;
            pin(prev);
            if (j == 0) silu_slot<CP, 0>(prev, tmp, h1);
            if (j == 1) silu_slot<CP, 1>(prev, tmp, h1);
            if (j == 2) silu_slot<CP, 2>(prev, tmp, h1);
            if (j == 3) silu_slot<CP, 3>(prev, tmp, h1);
            if (j == 4) silu_slot<CP, 4>(prev, tmp, h1);
            if (j == 5) silu_slot<CP, 5>(prev, tmp, h1);
        }
    }
}

__device__ __forceinline__ void ffn_stage_chunk(const float (&acc)[32], uint32_t stg, int w, int lane) {
    uint32_t pk[16];
#pragma unroll
    for (int i = 0; i < 16; i++) pk[i] = pack_bf16(acc[2 * i], acc[2 * i + 1]);
    stage_tile<8>(pk, stg, w, lane);
}
__device__ __forceinline__ void ffn_reduce_chunk(const CUtensorMap* tmOut, uint32_t stg, int col, int row, int w, int wgid, bool leader) {
    proxy_fence();
    if (w != 0) {
        asm volatile("bar.arrive %0, 128;" ::"r"(2 + wgid) : "memory");
    } else {
        named_sync(2 + wgid, 128);
        if (leader) { tma_red_2d(tmOut, col, row, stg); bulk_commit(); }
    }
}

template <bool FIRST>
__device__ __forceinline__ void ffn_phase2_chunk(float (&cur)[32], float (&prev)[32], uint32_t (&h1)[144], const FfnPipe& pp, uint32_t ph, const CUtensorMap* tmOut, uint32_t stg_prev, int col_prev, int row, int w, int lane, int wgid, bool leader) {
    const uint64_t dw = cdesc(F_OFF_ST, 8192, 1024, 1) + blockIdx.y * col_prev;
    float tmp[2][8];
#pragma unroll
    for (int j = 0; j < 6; j++) {
        pp.acquire(j, ph);
        if (j == 0) pin(cur);
        if (FIRST && j == 5) pin(h1);
        wg_fence();
#pragma unroll
        for (int i = 0; i < 6; i++) {
            const int f = (6 * j + i) * 4;
            wgmma_rs_n64<1>(cur, h1[f], h1[f + 1], h1[f + 2], h1[f + 3], dw + ((j * F_STAGE + i * 2048) >> 4), (j | i) != 0);
        }
        wg_commit();
        wg_wait<1>();
        pp.release((j + 5) % 6);
        if (FIRST) {
            pin(prev);
            if (j == 0) silu_slot_last<0>(prev, tmp, h1);
            if (j == 1) silu_slot_last<1>(prev, tmp, h1);
            if (j == 2) silu_slot_last<2>(prev, tmp, h1);
            if (j == 3) silu_slot_last<3>(prev, tmp, h1);
            if (j == 4) silu_slot_last<4>(prev, tmp, h1);
        } else {
            if (j == 0) { pin(prev); ffn_stage_chunk(prev, stg_prev, w, lane); }
            if (j == 1) ffn_reduce_chunk(tmOut, stg_prev, col_prev, row, w, wgid, leader);
        }
    }
}

__global__ void __launch_bounds__(F_THREADS, 1)
k_ffn(const __grid_constant__ CUtensorMap tmH, const __grid_constant__ CUtensorMap tmW1, const __grid_constant__ CUtensorMap tmW2, const __grid_constant__ CUtensorMap tmOut, const __nv_bfloat16* __restrict__ w2) {
    extern __shared__ __align__(1024) uint8_t smem[];
    const uint32_t sX = smem_u32(smem), sSt = sX + F_OFF_ST, bars = sX + F_OFF_BAR;
    const uint32_t full = bars, empty = bars + 64, fullX = bars + 128;
    const int tid = threadIdx.x, warp = __shfl_sync(~0u, tid >> 5, 0), lane = tid & 31;
#define FFN_MAP 1
    const int m = FFN_MAP == 0 ? (blockIdx.x & 15) : (FFN_MAP == 1 ? (blockIdx.x >> 3) : ((blockIdx.x >> 1) & 15));
    const int fs = FFN_MAP == 0 ? (blockIdx.x >> 4) : (FFN_MAP == 1 ? (blockIdx.x & 7) : ((blockIdx.x >> 5) * 2 + (blockIdx.x & 1)));
    check_smem_base(sX);
    if (tid == 0) {
        prefetch_map(&tmW1); prefetch_map(&tmH); prefetch_map(&tmW2); prefetch_map(&tmOut);
        for (int i = 0; i < F_NST; i++) { mbar_init(full + i * 8, 1); mbar_init(empty + i * 8, 8); }
        for (int i = 0; i < 9; i++) mbar_init(fullX + i * 8, 1);
        bar_init_fence();
        for (int kb = 0; kb < 9; kb++) mbar_expect(fullX + kb * 8, 16384);
    }
    __syncthreads();
    if (warp < 4) {
        asm volatile("setmaxnreg.dec.sync.aligned.u32 24;");
        if (warp == 1 && lane < 9) prefetch_l2(reinterpret_cast<const char*>(w2) + ((size_t)fs * 576 + m * 36 + lane * 4) * (DM * 2), 4 * DM * 2);
        if (warp == 0 && elect_one()) {
#pragma unroll 1
            for (int c = 0; c < 18; c++) {
                int col = c - 9 + fs;
                if (col >= 9) col -= 9;
#pragma unroll 1
                for (int j = 0; j < 6; j++) {
                    mbar_wait(empty + j * 8, (c & 1) ^ 1);
                    mbar_expect(full + j * 8, F_STAGE);
                    if (c < 9) tma_2d(sSt + j * F_STAGE, &tmW1, fs * 576 + c * 64, j * 96, full + j * 8);
                    else tma_2d(sSt + j * F_STAGE, &tmW2, col * 64, fs * 576 + j * 96, full + j * 8);
                }
            }
        }
    } else {
        asm volatile("setmaxnreg.inc.sync.aligned.u32 240;");
        const int wgid = (warp >> 2) - 1, w = warp & 3;
        pdl_wait();
        if (warp == 4 && elect_one()) {
            for (int kb = 0; kb < 9; kb++) tma_2d(sX + kb * 16384, &tmH, kb * 64, m * 128, fullX + kb * 8);
        }
        __syncwarp();
        FfnPipe pp{full, empty, lane};
        const uint64_t xlo = cdesc(0, 16, 1024, 1) + wgid * 512;
        uint32_t h1[144];
        float acc0[32], acc1[32];
        ffn_phase1_chunk<0>(acc0, acc1, h1, pp, xlo, fullX);
        ffn_phase1_chunk<1>(acc1, acc0, h1, pp, xlo, fullX);
        ffn_phase1_chunk<2>(acc0, acc1, h1, pp, xlo, fullX);
        ffn_phase1_chunk<3>(acc1, acc0, h1, pp, xlo, fullX);
        ffn_phase1_chunk<4>(acc0, acc1, h1, pp, xlo, fullX);
        ffn_phase1_chunk<5>(acc1, acc0, h1, pp, xlo, fullX);
        ffn_phase1_chunk<6>(acc0, acc1, h1, pp, xlo, fullX);
        ffn_phase1_chunk<7>(acc1, acc0, h1, pp, xlo, fullX);
        ffn_phase1_chunk<8>(acc0, acc1, h1, pp, xlo, fullX);
        const int row = m * 128 + wgid * 64;
        const uint32_t stg = sX + wgid * 8192;
        int c = fs, cprev = 0;
        const bool leader = w == 0 && elect_one();
        ffn_phase2_chunk<true>(acc1, acc0, h1, pp, 1, &tmOut, 0, 0, row, w, lane, wgid, leader);
        cprev = c; if (++c == 9) c = 0;
#pragma unroll 1
        for (int j = 1; j < 9; j += 2) {
            ffn_phase2_chunk<false>(acc0, acc1, h1, pp, 0, &tmOut, stg + (j - 1) * 16384, cprev * 64, row, w, lane, wgid, leader);
            cprev = c; if (++c == 9) c = 0;
            ffn_phase2_chunk<false>(acc1, acc0, h1, pp, 1, &tmOut, stg + j * 16384, cprev * 64, row, w, lane, wgid, leader);
            cprev = c; if (++c == 9) c = 0;
        }
        wg_wait<0>();
        pin(acc1);
        ffn_stage_chunk(acc1, stg + 8 * 16384, w, lane);
        ffn_reduce_chunk(&tmOut, stg + 8 * 16384, cprev * 64, row, w, wgid, leader);
        if (leader) bulk_wait_all();
    }
}

typedef CUresult (*EncodeFn)(CUtensorMap*, CUtensorMapDataType, cuuint32_t, void*, const cuuint64_t*, const cuuint64_t*, const cuuint32_t*, const cuuint32_t*,
                             CUtensorMapInterleave, CUtensorMapSwizzle, CUtensorMapL2promotion, CUtensorMapFloatOOBfill);

CUtensorMap make_map(EncodeFn enc, const void* base, int rows, int cols, int box_rows) {
    CUtensorMap tm;
    cuuint64_t dims[2] = {(cuuint64_t)cols, (cuuint64_t)rows};
    cuuint64_t strides[1] = {(cuuint64_t)cols * 2};
    cuuint32_t box[2] = {64, (cuuint32_t)box_rows};
    cuuint32_t es[2] = {1, 1};
    enc(&tm, CU_TENSOR_MAP_DATA_TYPE_BFLOAT16, 2, const_cast<void*>(base), dims, strides, box, es, CU_TENSOR_MAP_INTERLEAVE_NONE,
        CU_TENSOR_MAP_SWIZZLE_128B, CU_TENSOR_MAP_L2_PROMOTION_L2_256B, CU_TENSOR_MAP_FLOAT_OOB_FILL_NONE);
    return tm;
}

template <typename... KArgs, typename... Args>
void launch(void (*kern)(KArgs...), int grid, int block, int smem, bool pdl, Args... args) {
    cudaLaunchConfig_t cfg = {};
    cfg.gridDim = dim3(grid); cfg.blockDim = dim3(block); cfg.dynamicSmemBytes = smem; cfg.stream = cudaStreamPerThread;
    cudaLaunchAttribute at[1];
    at[0].id = cudaLaunchAttributeProgrammaticStreamSerialization;
    at[0].val.programmaticStreamSerializationAllowed = 1;
    cfg.attrs = at; cfg.numAttrs = pdl ? 1 : 0;
    cudaLaunchKernelEx(&cfg, kern, KArgs(args)...);
}

}

#define USE_PDL 1

extern "C" void kernel_launch(void* const* d_in, const int* in_sizes, int n_in, void* d_out, int out_size) {
    const __nv_bfloat16* x = (const __nv_bfloat16*)d_in[0];
    const __nv_bfloat16* wq = (const __nv_bfloat16*)d_in[1];
    const __nv_bfloat16* wk = (const __nv_bfloat16*)d_in[2];
    const __nv_bfloat16* wv = (const __nv_bfloat16*)d_in[3];
    const __nv_bfloat16* wo = (const __nv_bfloat16*)d_in[4];
    const __nv_bfloat16* w1 = (const __nv_bfloat16*)d_in[6];
    const __nv_bfloat16* w2 = (const __nv_bfloat16*)d_in[7];
    __nv_bfloat16* out = (__nv_bfloat16*)d_out;

    static EncodeFn enc = nullptr;
    static void *p_o = nullptr, *p_h = nullptr, *p_q = nullptr;
    if (!enc) {
        cudaDriverEntryPointQueryResult qr;
        cudaGetDriverEntryPoint("cuTensorMapEncodeTiled", (void**)&enc, cudaEnableDefault, &qr);
        cudaGetSymbolAddress(&p_o, g_o);
        cudaGetSymbolAddress(&p_h, g_x2);
        cudaGetSymbolAddress(&p_q, g_q);
        cudaFuncSetAttribute(k_qkv, cudaFuncAttributeMaxDynamicSharedMemorySize, P_SMEM);
        cudaFuncSetAttribute(k_attn, cudaFuncAttributeMaxDynamicSharedMemorySize, A_SMEM);
        cudaFuncSetAttribute(k_oproj, cudaFuncAttributeMaxDynamicSharedMemorySize, O_SMEM);
        cudaFuncSetAttribute(k_ffn, cudaFuncAttributeMaxDynamicSharedMemorySize, F_SMEM);
    }
    const CUtensorMap tmWq = make_map(enc, wq, DM, DM, 64);
    const CUtensorMap tmWo = make_map(enc, wo, DM, DM, 64);
    const CUtensorMap tmO = make_map(enc, p_o, SEQ, DM, 64);
    const CUtensorMap tmH64 = make_map(enc, p_h, SEQ, DM, 64);
    const CUtensorMap tmH = make_map(enc, p_h, SEQ, DM, 128);
    const CUtensorMap tmQ = make_map(enc, p_q, SEQ, DM, 64);
    const CUtensorMap tmW1 = make_map(enc, w1, DM, FF, 96);
    const CUtensorMap tmW2 = make_map(enc, w2, FF, DM, 96);
    const CUtensorMap tmOut = make_map(enc, out, SEQ, DM, 64);

    launch(k_qkv, 128, Q_THREADS, P_SMEM, false, tmWq, tmQ, x, wk, wv);
    launch(k_attn, 128, A_THREADS, A_SMEM, USE_PDL);
    launch(k_oproj, 96, O_THREADS, O_SMEM, USE_PDL, tmO, tmWo, tmH64, tmOut, x, w1);
    launch(k_ffn, 128, F_THREADS, F_SMEM, USE_PDL, tmH, tmW1, tmW2, tmOut, w2);
}
```

```cpp
#include <cuda_runtime.h>
#include <cuda_bf16.h>
#include <cuda.h>
#include <stdint.h>

namespace {

constexpr int SEQ = 2048, DM = 576, FF = 4608;
constexpr int KV_BYTES = SEQ * 48;
constexpr float LN_EPS = 1e-5f;
constexpr float LOG2E = 1.4426950408889634f;
constexpr float Q_SCALE = 0.23570226039551584f * LOG2E;

#define POLY_MASK_V 0xB6DBu
constexpr uint32_t POLY_MASK = POLY_MASK_V;
#define FAST_BOUND_V 60.0f
constexpr float FAST_BOUND = FAST_BOUND_V;

__device__ __align__(1024) __nv_bfloat16 g_q[SEQ * DM];
__device__ __align__(1024) uint4 g_kc[KV_BYTES / 16];
__device__ __align__(1024) uint4 g_vc[KV_BYTES / 16];
__device__ __align__(16) float g_kmax[256];
__device__ __align__(1024) __nv_bfloat16 g_o[SEQ * DM];
__device__ __align__(1024) __nv_bfloat16 g_x2[SEQ * DM];

__device__ __forceinline__ uint32_t smem_u32(const void* p) { return (uint32_t)__cvta_generic_to_shared(p); }
__device__ __forceinline__ void wg_fence() { asm volatile("wgmma.fence.sync.aligned;" ::: "memory"); }
__device__ __forceinline__ void wg_commit() { asm volatile("wgmma.commit_group.sync.aligned;" ::: "memory"); }
template <int N> __device__ __forceinline__ void wg_wait() { asm volatile("wgmma.wait_group.sync.aligned %0;" ::"n"(N) : "memory"); }
template <int N> __device__ __forceinline__ void pin(float (&r)[N]) {
#pragma unroll
    for (int i = 0; i < N; i++) asm volatile("" : "+f"(r[i])::"memory");
}
template <int N> __device__ __forceinline__ void pin(uint32_t (&r)[N]) {
#pragma unroll
    for (int i = 0; i < N; i++) asm volatile("" : "+r"(r[i])::"memory");
}
constexpr uint32_t SMEM0 = 0x400;
__host__ __device__ constexpr uint64_t cdesc(uint32_t off, uint32_t lbo, uint32_t sbo, uint32_t swz) {
    return (uint64_t)(((SMEM0 + off) & 0x3FFFF) >> 4) | ((uint64_t)(lbo >> 4) << 16) | ((uint64_t)(sbo >> 4) << 32) | ((uint64_t)swz << 62);
}
__device__ __forceinline__ void check_smem_base(uint32_t base) { if ((base & 0x3FFFF) != SMEM0) __trap(); }

__device__ __forceinline__ void mbar_init(uint32_t bar, int cnt) { asm volatile("mbarrier.init.shared::cta.b64 [%0], %1;" ::"r"(bar), "r"(cnt) : "memory"); }
__device__ __forceinline__ void mbar_expect(uint32_t bar, int bytes) { asm volatile("mbarrier.arrive.expect_tx.shared::cta.b64 _, [%0], %1;" ::"r"(bar), "r"(bytes) : "memory"); }
__device__ __forceinline__ void mbar_arrive(uint32_t bar) { asm volatile("mbarrier.arrive.shared::cta.b64 _, [%0];" ::"r"(bar) : "memory"); }
__device__ __forceinline__ void mbar_wait(uint32_t bar, uint32_t parity) {
    asm volatile(
        "{\n.reg .pred p;\n.reg .u32 n;\nmov.u32 n, 0;\n"
        "LAB_WAIT:\n"
        "mbarrier.try_wait.parity.shared::cta.b64 p, [%0], %1;\n"
        "@p bra DONE;\n"
        "add.u32 n, n, 1;\n"
        "setp.lt.u32 p, n, 4000000;\n"
        "@p bra LAB_WAIT;\n"
        "trap;\n"
        "DONE:\n}\n" ::"r"(bar), "r"(parity) : "memory");
}
__device__ __forceinline__ void bar_init_fence() {
    asm volatile("fence.mbarrier_init.release.cluster;" ::: "memory");
    asm volatile("fence.proxy.async.shared::cta;" ::: "memory");
}
__device__ __forceinline__ void proxy_fence() { asm volatile("fence.proxy.async.shared::cta;" ::: "memory"); }
__device__ __forceinline__ void named_sync(int id, int n) { asm volatile("bar.sync %0, %1;" ::"r"(id), "r"(n) : "memory"); }
__device__ __forceinline__ void bulk_g2s(uint32_t dst, const void* src, int bytes, uint32_t bar) {
    asm volatile("cp.async.bulk.shared::cluster.global.mbarrier::complete_tx::bytes [%0], [%1], %2, [%3];" ::"r"(dst), "l"(src), "r"(bytes), "r"(bar) : "memory");
}
__device__ __forceinline__ void tma_2d(uint32_t dst, const CUtensorMap* tm, int c0, int c1, uint32_t bar) {
    asm volatile("cp.async.bulk.tensor.2d.shared::cluster.global.mbarrier::complete_tx::bytes [%0], [%1, {%3, %4}], [%2];" ::"r"(dst), "l"(tm), "r"(bar), "r"(c0), "r"(c1) : "memory");
}
__device__ __forceinline__ void cluster_arrive() { asm volatile("barrier.cluster.arrive.release.aligned;" ::: "memory"); }
__device__ __forceinline__ void cluster_wait() { asm volatile("barrier.cluster.wait.acquire.aligned;" ::: "memory"); }
__device__ __forceinline__ void tma_red_2d(const CUtensorMap* tm, int c0, int c1, uint32_t src) {
    asm volatile("cp.reduce.async.bulk.tensor.2d.global.shared::cta.add.tile.bulk_group [%0, {%2, %3}], [%1];" ::"l"(tm), "r"(src), "r"(c0), "r"(c1) : "memory");
}
__device__ __forceinline__ void tma_st_2d(const CUtensorMap* tm, int c0, int c1, uint32_t src) {
    asm volatile("cp.async.bulk.tensor.2d.global.shared::cta.tile.bulk_group [%0, {%2, %3}], [%1];" ::"l"(tm), "r"(src), "r"(c0), "r"(c1) : "memory");
}
__device__ __forceinline__ void bulk_commit() { asm volatile("cp.async.bulk.commit_group;" ::: "memory"); }
__device__ __forceinline__ void bulk_wait_all() { asm volatile("cp.async.bulk.wait_group.read 0;" ::: "memory"); }
__device__ __forceinline__ bool elect_one() {
    uint32_t p;
    asm volatile("{\n.reg .pred P;\nelect.sync _|P, 0xffffffff;\nselp.b32 %0, 1, 0, P;\n}\n" : "=r"(p));
    return p != 0;
}
__device__ __forceinline__ void prefetch_l2(const void* p, int bytes) { asm volatile("cp.async.bulk.prefetch.L2.global [%0], %1;" ::"l"(p), "r"(bytes) : "memory"); }
__device__ __forceinline__ void prefetch_map(const CUtensorMap* tm) { asm volatile("prefetch.tensormap [%0];" ::"l"(tm) : "memory"); }
__device__ __forceinline__ void pdl_launch() { asm volatile("griddepcontrol.launch_dependents;" ::: "memory"); }
__device__ __forceinline__ void pdl_wait() { asm volatile("griddepcontrol.wait;" ::: "memory"); }
__device__ __forceinline__ float ex2(float x) { float y; asm("ex2.approx.ftz.f32 %0, %1;" : "=f"(y) : "f"(x)); return y; }
__device__ __forceinline__ uint32_t pack_bf16(float lo, float hi) { uint32_t r; asm("cvt.rn.bf16x2.f32 %0, %1, %2;" : "=r"(r) : "f"(hi), "f"(lo)); return r; }
__device__ __forceinline__ float bf_lo(uint32_t v) { return __uint_as_float(v << 16); }
__device__ __forceinline__ float bf_hi(uint32_t v) { return __uint_as_float(v & 0xFFFF0000u); }
__device__ __forceinline__ uint32_t hfma2(uint32_t a, uint32_t b, uint32_t c) { uint32_t r; asm("fma.rn.f16x2 %0, %1, %2, %3;" : "=r"(r) : "r"(a), "r"(b), "r"(c)); return r; }
__device__ __forceinline__ void stmatrix_x4(uint32_t addr, uint32_t r0, uint32_t r1, uint32_t r2, uint32_t r3) {
    asm volatile("stmatrix.sync.aligned.m8n8.x4.shared.b16 [%0], {%1, %2, %3, %4};" ::"r"(addr), "r"(r0), "r"(r1), "r"(r2), "r"(r3) : "memory");
}

template <int TB> __device__ __forceinline__ void wgmma_ss_n24(float (&d)[12], uint64_t da, uint64_t db, int sc) {
    asm volatile("{\n.reg .pred p;\nsetp.ne.b32 p, %14, 0;\n"
        "wgmma.mma_async.sync.aligned.m64n24k16.f32.bf16.bf16 {%0, %1, %2, %3, %4, %5, %6, %7, %8, %9, %10, %11}, %12, %13, p, 1, 1, 0, %15;\n}\n"
        : "+f"(d[0]), "+f"(d[1]), "+f"(d[2]), "+f"(d[3]), "+f"(d[4]), "+f"(d[5]), "+f"(d[6]), "+f"(d[7]), "+f"(d[8]), "+f"(d[9]), "+f"(d[10]), "+f"(d[11])
        : "l"(da), "l"(db), "r"(sc), "n"(TB));
}
template <int TB> __device__ __forceinline__ void wgmma_ss_n64(float (&d)[32], uint64_t da, uint64_t db, int sc) {
    asm volatile("{\n.reg .pred p;\nsetp.ne.b32 p, %34, 0;\n"
        "wgmma.mma_async.sync.aligned.m64n64k16.f32.bf16.bf16 {%0, %1, %2, %3, %4, %5, %6, %7, %8, %9, %10, %11, %12, %13, %14, %15, %16, %17, %18, %19, %20, %21, %22, %23, %24, %25, %26, %27, %28, %29, %30, %31}, %32, %33, p, 1, 1, 0, %35;\n}\n"
        : "+f"(d[0]), "+f"(d[1]), "+f"(d[2]), "+f"(d[3]), "+f"(d[4]), "+f"(d[5]), "+f"(d[6]), "+f"(d[7]), "+f"(d[8]), "+f"(d[9]), "+f"(d[10]), "+f"(d[11]), "+f"(d[12]), "+f"(d[13]), "+f"(d[14]), "+f"(d[15]), "+f"(d[16]), "+f"(d[17]), "+f"(d[18]), "+f"(d[19]), "+f"(d[20]), "+f"(d[21]), "+f"(d[22]), "+f"(d[23]), "+f"(d[24]), "+f"(d[25]), "+f"(d[26]), "+f"(d[27]), "+f"(d[28]), "+f"(d[29]), "+f"(d[30]), "+f"(d[31])
        : "l"(da), "l"(db), "r"(sc), "n"(TB));
}
template <int TB> __device__ __forceinline__ void wgmma_ss_n128(float (&d)[64], uint64_t da, uint64_t db, int sc) {
    asm volatile("{\n.reg .pred p;\nsetp.ne.b32 p, %66, 0;\n"
        "wgmma.mma_async.sync.aligned.m64n128k16.f32.bf16.bf16 {%0, %1, %2, %3, %4, %5, %6, %7, %8, %9, %10, %11, %12, %13, %14, %15, %16, %17, %18, %19, %20, %21, %22, %23, %24, %25, %26, %27, %28, %29, %30, %31, %32, %33, %34, %35, %36, %37, %38, %39, %40, %41, %42, %43, %44, %45, %46, %47, %48, %49, %50, %51, %52, %53, %54, %55, %56, %57, %58, %59, %60, %61, %62, %63}, %64, %65, p, 1, 1, 0, %67;\n}\n"
        : "+f"(d[0]), "+f"(d[1]), "+f"(d[2]), "+f"(d[3]), "+f"(d[4]), "+f"(d[5]), "+f"(d[6]), "+f"(d[7]), "+f"(d[8]), "+f"(d[9]), "+f"(d[10]), "+f"(d[11]), "+f"(d[12]), "+f"(d[13]), "+f"(d[14]), "+f"(d[15]), "+f"(d[16]), "+f"(d[17]), "+f"(d[18]), "+f"(d[19]), "+f"(d[20]), "+f"(d[21]), "+f"(d[22]), "+f"(d[23]), "+f"(d[24]), "+f"(d[25]), "+f"(d[26]), "+f"(d[27]), "+f"(d[28]), "+f"(d[29]), "+f"(d[30]), "+f"(d[31]), "+f"(d[32]), "+f"(d[33]), "+f"(d[34]), "+f"(d[35]), "+f"(d[36]), "+f"(d[37]), "+f"(d[38]), "+f"(d[39]), "+f"(d[40]), "+f"(d[41]), "+f"(d[42]), "+f"(d[43]), "+f"(d[44]), "+f"(d[45]), "+f"(d[46]), "+f"(d[47]), "+f"(d[48]), "+f"(d[49]), "+f"(d[50]), "+f"(d[51]), "+f"(d[52]), "+f"(d[53]), "+f"(d[54]), "+f"(d[55]), "+f"(d[56]), "+f"(d[57]), "+f"(d[58]), "+f"(d[59]), "+f"(d[60]), "+f"(d[61]), "+f"(d[62]), "+f"(d[63])
        : "l"(da), "l"(db), "r"(sc), "n"(TB));
}
template <int TB> __device__ __forceinline__ void wgmma_rs_n24(float (&d)[12], uint32_t a0, uint32_t a1, uint32_t a2, uint32_t a3, uint64_t db, int sc) {
    asm volatile("{\n.reg .pred p;\nsetp.ne.b32 p, %17, 0;\n"
        "wgmma.mma_async.sync.aligned.m64n24k16.f32.bf16.bf16 {%0, %1, %2, %3, %4, %5, %6, %7, %8, %9, %10, %11}, {%12, %13, %14, %15}, %16, p, 1, 1, %18;\n}\n"
        : "+f"(d[0]), "+f"(d[1]), "+f"(d[2]), "+f"(d[3]), "+f"(d[4]), "+f"(d[5]), "+f"(d[6]), "+f"(d[7]), "+f"(d[8]), "+f"(d[9]), "+f"(d[10]), "+f"(d[11])
        : "r"(a0), "r"(a1), "r"(a2), "r"(a3), "l"(db), "r"(sc), "n"(TB));
}
template <int TB> __device__ __forceinline__ void wgmma_rs_n64(float (&d)[32], uint32_t a0, uint32_t a1, uint32_t a2, uint32_t a3, uint64_t db, int sc) {
    asm volatile("{\n.reg .pred p;\nsetp.ne.b32 p, %37, 0;\n"
        "wgmma.mma_async.sync.aligned.m64n64k16.f32.bf16.bf16 {%0, %1, %2, %3, %4, %5, %6, %7, %8, %9, %10, %11, %12, %13, %14, %15, %16, %17, %18, %19, %20, %21, %22, %23, %24, %25, %26, %27, %28, %29, %30, %31}, {%32, %33, %34, %35}, %36, p, 1, 1, %38;\n}\n"
        : "+f"(d[0]), "+f"(d[1]), "+f"(d[2]), "+f"(d[3]), "+f"(d[4]), "+f"(d[5]), "+f"(d[6]), "+f"(d[7]), "+f"(d[8]), "+f"(d[9]), "+f"(d[10]), "+f"(d[11]), "+f"(d[12]), "+f"(d[13]), "+f"(d[14]), "+f"(d[15]), "+f"(d[16]), "+f"(d[17]), "+f"(d[18]), "+f"(d[19]), "+f"(d[20]), "+f"(d[21]), "+f"(d[22]), "+f"(d[23]), "+f"(d[24]), "+f"(d[25]), "+f"(d[26]), "+f"(d[27]), "+f"(d[28]), "+f"(d[29]), "+f"(d[30]), "+f"(d[31])
        : "r"(a0), "r"(a1), "r"(a2), "r"(a3), "l"(db), "r"(sc), "n"(TB));
}
template <int TB> __device__ __forceinline__ void wgmma_rs_n128(float (&d)[64], uint32_t a0, uint32_t a1, uint32_t a2, uint32_t a3, uint64_t db, int sc) {
    asm volatile("{\n.reg .pred p;\nsetp.ne.b32 p, %69, 0;\n"
        "wgmma.mma_async.sync.aligned.m64n128k16.f32.bf16.bf16 {%0, %1, %2, %3, %4, %5, %6, %7, %8, %9, %10, %11, %12, %13, %14, %15, %16, %17, %18, %19, %20, %21, %22, %23, %24, %25, %26, %27, %28, %29, %30, %31, %32, %33, %34, %35, %36, %37, %38, %39, %40, %41, %42, %43, %44, %45, %46, %47, %48, %49, %50, %51, %52, %53, %54, %55, %56, %57, %58, %59, %60, %61, %62, %63}, {%64, %65, %66, %67}, %68, p, 1, 1, %70;\n}\n"
        : "+f"(d[0]), "+f"(d[1]), "+f"(d[2]), "+f"(d[3]), "+f"(d[4]), "+f"(d[5]), "+f"(d[6]), "+f"(d[7]), "+f"(d[8]), "+f"(d[9]), "+f"(d[10]), "+f"(d[11]), "+f"(d[12]), "+f"(d[13]), "+f"(d[14]), "+f"(d[15]), "+f"(d[16]), "+f"(d[17]), "+f"(d[18]), "+f"(d[19]), "+f"(d[20]), "+f"(d[21]), "+f"(d[22]), "+f"(d[23]), "+f"(d[24]), "+f"(d[25]), "+f"(d[26]), "+f"(d[27]), "+f"(d[28]), "+f"(d[29]), "+f"(d[30]), "+f"(d[31]), "+f"(d[32]), "+f"(d[33]), "+f"(d[34]), "+f"(d[35]), "+f"(d[36]), "+f"(d[37]), "+f"(d[38]), "+f"(d[39]), "+f"(d[40]), "+f"(d[41]), "+f"(d[42]), "+f"(d[43]), "+f"(d[44]), "+f"(d[45]), "+f"(d[46]), "+f"(d[47]), "+f"(d[48]), "+f"(d[49]), "+f"(d[50]), "+f"(d[51]), "+f"(d[52]), "+f"(d[53]), "+f"(d[54]), "+f"(d[55]), "+f"(d[56]), "+f"(d[57]), "+f"(d[58]), "+f"(d[59]), "+f"(d[60]), "+f"(d[61]), "+f"(d[62]), "+f"(d[63])
        : "r"(a0), "r"(a1), "r"(a2), "r"(a3), "l"(db), "r"(sc), "n"(TB));
}

constexpr int P_NST = 6;
constexpr int P_A_BYTES = 9 * 8192;
constexpr int P_B_STAGE = 3 * 8192;
constexpr int P_SMEM = P_A_BYTES + P_NST * P_B_STAGE + 256 + 320;

template <int NB>
__device__ __forceinline__ void stage_tile(const uint32_t (&pk)[NB * 2], uint32_t base, int w, int lane) {
    const int r = w * 16 + (lane & 7) + ((lane >> 3) & 1) * 8;
#pragma unroll
    for (int b = 0; b < NB; b += 2) {
        const uint32_t a = base + (b >> 3) * 8192 + r * 128 + ((((b & 7) + (lane >> 4)) ^ (r & 7)) << 4);
        stmatrix_x4(a, pk[2 * b], pk[2 * b + 1], pk[2 * b + 2], pk[2 * b + 3]);
    }
}

__device__ __forceinline__ uint32_t hsub2_bf16(uint32_t a, uint32_t b) { uint32_t r; asm("sub.rn.bf16x2 %0, %1, %2;" : "=r"(r) : "r"(a), "r"(b)); return r; }

constexpr int KV_RAW = DM * 18 * 2;
constexpr int Q_THREADS = 416;

template <typename F>
__device__ __forceinline__ void proj_mma(float (&acc)[32], int wg, uint32_t fullB, uint32_t emptyB, uint32_t fullA, bool wait_a, int lane, F under) {
    const uint64_t dA = cdesc(0, 16, 1024, 1) + blockIdx.y, dB = cdesc(P_A_BYTES, 8192, 1024, 1) + wg * 512;
#pragma unroll
    for (int kb = 0; kb < 9; kb++) {
        const int s = kb >= P_NST ? kb - P_NST : kb;
        if (wait_a) mbar_wait(fullA + kb * 8, 0);
        mbar_wait(fullB + s * 8, kb >= P_NST ? 1 : 0);
        wg_fence();
#pragma unroll
        for (int ks = 0; ks < 4; ks++) wgmma_ss_n64<1>(acc, dA + (kb * 512 + ks * 2), dB + (s * (P_B_STAGE >> 4) + ks * 128), (kb | ks) != 0);
        wg_commit();
        if (kb >= 1) {
            wg_wait<1>();
            if (kb < 4 && lane == 0) mbar_arrive(emptyB + (kb - 1) * 8);
        }
        under(kb);
    }
    wg_wait<0>();
    pin(acc);
}
__device__ __forceinline__ uint32_t hadd2_bf16(uint32_t a, uint32_t b) { uint32_t r; asm("add.rn.bf16x2 %0, %1, %2;" : "=r"(r) : "r"(a), "r"(b)); return r; }

__global__ void __launch_bounds__(Q_THREADS, 1)
k_qkv(const __grid_constant__ CUtensorMap tmWq, const __grid_constant__ CUtensorMap tmQ, const __nv_bfloat16* __restrict__ x, const __nv_bfloat16* __restrict__ wk, const __nv_bfloat16* __restrict__ wv) {
    extern __shared__ __align__(1024) uint8_t smem[];
    const uint32_t sA = smem_u32(smem), sB = sA + P_A_BYTES, bars = sB + P_NST * P_B_STAGE;
    const uint32_t fullB = bars, emptyB = bars + 64, fullX = bars + 128, fullW = bars + 136;
    float* s_rstd = reinterpret_cast<float*>(smem + P_A_BYTES + P_NST * P_B_STAGE + 256);
    const int tid = threadIdx.x, warp = __shfl_sync(~0u, tid >> 5, 0), lane = tid & 31;
    const bool isQ = blockIdx.x < 96;
    const int m = isQ ? blockIdx.x / 3 : blockIdx.x - 96, cg = blockIdx.x % 3;
    if (warp == 12) {
        if (elect_one()) {
            mbar_init(fullX, 1);
            bar_init_fence();
            mbar_expect(fullX, P_A_BYTES);
            bulk_g2s(sA, x + (size_t)m * 64 * DM, P_A_BYTES, fullX);
            prefetch_map(&tmWq); prefetch_map(&tmQ);
            for (int i = 0; i < P_NST; i++) { mbar_init(fullB + i * 8, 1); mbar_init(emptyB + i * 8, 12); }
            mbar_init(fullW, 1);
            bar_init_fence();
            if (isQ) {
                for (int kb = 0; kb < P_NST; kb++) {
                    mbar_expect(fullB + kb * 8, P_B_STAGE);
                    for (int a = 0; a < 3; a++) tma_2d(sB + kb * P_B_STAGE + a * 8192, &tmWq, cg * 192 + a * 64, kb * 64, fullB + kb * 8);
                }
            } else {
                mbar_expect(fullW, 2 * KV_RAW);
                bulk_g2s(sB + 3 * P_B_STAGE, wk, KV_RAW, fullW);
                bulk_g2s(sB + 3 * P_B_STAGE + KV_RAW, wv, KV_RAW, fullW);
            }
        }
        __syncwarp();
    }
    check_smem_base(sA);
    __syncthreads();
    pdl_launch();
    if (warp == 12) {
        if (isQ && elect_one()) {
            for (int kb = P_NST; kb < 9; kb++) {
                const int s = kb - P_NST;
                mbar_wait(emptyB + s * 8, 0);
                mbar_expect(fullB + s * 8, P_B_STAGE);
                for (int a = 0; a < 3; a++) tma_2d(sB + s * P_B_STAGE + a * 8192, &tmWq, cg * 192 + a * 64, kb * 64, fullB + s * 8);
            }
        }
        return;
    }
    uint32_t xc[72];
    if (warp < 8) {
        const int row = tid >> 2, q = tid & 3, h0 = (row & 1) * 4;
        mbar_wait(fullX, 0);
        const uint32_t ra = sA + row * 1152 + (q + h0) * 16, rb = sA + row * 1152 + (q + 4 - h0) * 16;
        uint32_t pv;
        asm volatile("ld.shared.b32 %0, [%1];" : "=r"(pv) : "r"(sA + row * 1152));
#pragma unroll
        for (int kb = 0; kb < 9; kb++) {
            asm volatile("ld.shared.v4.b32 {%0, %1, %2, %3}, [%4];" : "=r"(xc[8 * kb]), "=r"(xc[8 * kb + 1]), "=r"(xc[8 * kb + 2]), "=r"(xc[8 * kb + 3]) : "r"(ra + kb * 128));
            asm volatile("ld.shared.v4.b32 {%0, %1, %2, %3}, [%4];" : "=r"(xc[8 * kb + 4]), "=r"(xc[8 * kb + 5]), "=r"(xc[8 * kb + 6]), "=r"(xc[8 * kb + 7]) : "r"(rb + kb * 128));
        }
        named_sync(1, 256);
        pv = __byte_perm(pv, pv, 0x1010);
        uint32_t part[9];
#pragma unroll
        for (int kb = 0; kb < 9; kb++) {
#pragma unroll
            for (int i = 0; i < 8; i++) xc[8 * kb + i] = hsub2_bf16(xc[8 * kb + i], pv);
            part[kb] = hadd2_bf16(hadd2_bf16(hadd2_bf16(xc[8 * kb], xc[8 * kb + 1]), hadd2_bf16(xc[8 * kb + 2], xc[8 * kb + 3])),
                                  hadd2_bf16(hadd2_bf16(xc[8 * kb + 4], xc[8 * kb + 5]), hadd2_bf16(xc[8 * kb + 6], xc[8 * kb + 7])));
        }
        float sum = 0.f;
#pragma unroll
        for (int kb = 0; kb < 9; kb++) sum += bf_lo(part[kb]) + bf_hi(part[kb]);
        sum += __shfl_xor_sync(~0u, sum, 1); sum += __shfl_xor_sync(~0u, sum, 2);
        const uint32_t mean2 = pack_bf16(sum * (1.0f / DM), sum * (1.0f / DM));
        const uint32_t wa = sA + row * 128 + (((q + h0) ^ (row & 7)) << 4), wb = sA + row * 128 + (((q + 4 - h0) ^ (row & 7)) << 4);
#pragma unroll
        for (int i = 0; i < 18; i++) {
#pragma unroll
            for (int j = 0; j < 4; j++) xc[4 * i + j] = hsub2_bf16(xc[4 * i + j], mean2);
            asm volatile("st.shared.v4.b32 [%0], {%1, %2, %3, %4};" ::"r"(((i & 1) ? wb : wa) + (i >> 1) * 8192), "r"(xc[4 * i]), "r"(xc[4 * i + 1]), "r"(xc[4 * i + 2]), "r"(xc[4 * i + 3]) : "memory");
        }
    } else if (!isQ) {
        mbar_wait(fullW, 0);
        const uint32_t* raw = reinterpret_cast<const uint32_t*>(smem + P_A_BYTES + 3 * P_B_STAGE);
#pragma unroll 3
        for (int r = tid - 256; r < 2 * DM; r += 128) {
            uint32_t wr[9];
#pragma unroll
            for (int i = 0; i < 9; i++) wr[i] = raw[r * 9 + i];
            const int sel = r >= DM, k = r - sel * DM;
            uint8_t* dst = smem + P_A_BYTES + sel * 3 * 9216 + (k >> 3) * 128 + (k & 7) * 16;
            *reinterpret_cast<uint4*>(dst) = make_uint4(wr[0], wr[1], wr[2], wr[3]);
            *reinterpret_cast<uint4*>(dst + 9216) = make_uint4(wr[4], wr[5], wr[6], wr[7]);
            *reinterpret_cast<uint32_t*>(dst + 2 * 9216) = wr[8];
        }
    }
    proxy_fence();
    named_sync(2, 384);
    const int wg = warp >> 2, w = warp & 3, g = lane >> 2, t = lane & 3;
    float sq0 = 0.f, sq1 = 0.f;
    auto sq_piece = [&](int kb) {
        if (warp < 8) {
#pragma unroll
            for (int i = 0; i < 8; i++) { const float a = bf_lo(xc[8 * kb + i]), b = bf_hi(xc[8 * kb + i]); sq0 = fmaf(a, a, sq0); sq1 = fmaf(b, b, sq1); }
        }
    };
    auto publish_rstd = [&]() {
        if (warp < 8) {
            float sq = sq0 + sq1;
            sq += __shfl_xor_sync(~0u, sq, 1); sq += __shfl_xor_sync(~0u, sq, 2);
            if ((tid & 3) == 0) s_rstd[tid >> 2] = rsqrtf(sq * (1.0f / DM) + LN_EPS);
        }
    };
    if (isQ) {
        float acc[32];
        proj_mma(acc, wg, fullB, emptyB, 0, false, lane, sq_piece);
        publish_rstd();
        named_sync(2, 384);
        const float c0 = s_rstd[w * 16 + g] * Q_SCALE, c1 = s_rstd[w * 16 + g + 8] * Q_SCALE;
        uint32_t pk[16];
#pragma unroll
        for (int i = 0; i < 8; i++) { pk[2 * i] = pack_bf16(acc[4 * i] * c0, acc[4 * i + 1] * c0); pk[2 * i + 1] = pack_bf16(acc[4 * i + 2] * c1, acc[4 * i + 3] * c1); }
        stage_tile<8>(pk, sA + wg * 8192, w, lane);
        proxy_fence();
        named_sync(3 + wg, 128);
        if (w == 0 && elect_one()) {
            tma_st_2d(&tmQ, cg * 192 + wg * 64, m * 64, sA + wg * 8192);
            bulk_commit();
            bulk_wait_all();
        }
    } else if (wg < 2) {
        float acc[12];
        const uint64_t dA = cdesc(0, 16, 1024, 1), dB = cdesc(P_A_BYTES, 128, 9216, 0) + wg * (3 * 9216 >> 4);
#pragma unroll
        for (int i = 0; i < 12; i++) acc[i] = 0.f;
        pin(acc);
        wg_fence();
#pragma unroll 1
        for (int kb = 0; kb < 9; kb++) {
#pragma unroll
            for (int ks = 0; ks < 4; ks++) wgmma_ss_n24<1>(acc, dA + (kb * 512 + ks * 2), dB + (kb * 4 + ks) * 16, 1);
        }
        wg_commit();
#pragma unroll
        for (int kb = 0; kb < 9; kb++) sq_piece(kb);
        publish_rstd();
        wg_wait<0>();
        pin(acc);
        named_sync(1, 256);
        const float rs0 = s_rstd[w * 16 + g], rs1 = s_rstd[w * 16 + g + 8];
        uint32_t pk[6];
#pragma unroll
        for (int b = 0; b < 3; b++) { pk[2 * b] = pack_bf16(acc[4 * b] * rs0, acc[4 * b + 1] * rs0); pk[2 * b + 1] = pack_bf16(acc[4 * b + 2] * rs1, acc[4 * b + 3] * rs1); }
        float n0 = 0.f, n1 = 0.f, vm = 0.f;
#pragma unroll
        for (int b = 0; b < 3; b++) {
            if (b < 2 || t == 0) {
                const float a = bf_lo(pk[2 * b]), c = bf_hi(pk[2 * b]), d = bf_lo(pk[2 * b + 1]), e = bf_hi(pk[2 * b + 1]);
                n0 = fmaf(a, a, fmaf(c, c, n0)); n1 = fmaf(d, d, fmaf(e, e, n1));
            }
        }
        n0 += __shfl_xor_sync(~0u, n0, 1); n0 += __shfl_xor_sync(~0u, n0, 2);
        n1 += __shfl_xor_sync(~0u, n1, 1); n1 += __shfl_xor_sync(~0u, n1, 2);
        vm = fmaxf(n0, n1);
        if (!(n0 == n0) || !(n1 == n1)) vm = __int_as_float(0x7F800000);
#pragma unroll
        for (int o = 4; o < 32; o <<= 1) vm = fmaxf(vm, __shfl_xor_sync(~0u, vm, o));
        if (t != 0) {
            uint32_t lo, hi;
            if (wg == 0) {
                const int grp = m * 8 + w * 2;
                const uint32_t c = t == 1 ? 0x42FE3F80u   : (t == 2 ? 0x00003BC0u   : 0u);
                lo = ((POLY_MASK >> (grp & 15)) & 1) ? c : 0u;
                hi = ((POLY_MASK >> ((grp + 1) & 15)) & 1) ? c : 0u;
            } else {
                lo = hi = t == 1 ? 0x00003F80u : 0u;
            }
            pk[4] = lo; pk[5] = hi;
        }
        uint32_t* dst = reinterpret_cast<uint32_t*>(wg == 0 ? g_kc : g_vc) + (m * 8 + w * 2) * 96 + g * 4 + t;
#pragma unroll
        for (int b = 0; b < 3; b++) { dst[b * 32] = pk[2 * b]; dst[96 + b * 32] = pk[2 * b + 1]; }
        if (lane == 0) g_kmax[m * 8 + warp] = (wg == 0) ? vm : (vm <= 1e24f ? 0.f : __int_as_float(0x7F800000));
    }
}

constexpr int A_THREADS = 512;
constexpr int A_NPIECE = 8;
constexpr int A_OFF_Q = 2 * KV_BYTES;
constexpr int A_OFF_BAR = A_OFF_Q + 8 * 4096;
constexpr int A_SMEM = A_OFF_BAR + 128;

__device__ __forceinline__ uint32_t exp2_pair_fixed(float lo, float hi, uint32_t dep) {
    const uint32_t G = __byte_perm(__float_as_uint(lo), __float_as_uint(hi), 0x5410);
    uint32_t Hh;
    asm("lop3.b32 %0, %1, 0x007F007F, %2, 0xC0;" : "=r"(Hh) : "r"(G), "r"(dep));
    const uint32_t tt = hfma2(Hh, 0xF96BF96Bu, 0x358C358Cu);
    return G - hfma2(tt, Hh, 0u);
}

__global__ void __launch_bounds__(A_THREADS, 1)
k_attn() {
    extern __shared__ __align__(1024) uint8_t smem[];
    pdl_launch();
    const uint32_t sK = smem_u32(smem), sV = sK + KV_BYTES, bars = sK + A_OFF_BAR;
    const int tid = threadIdx.x;
    check_smem_base(sK);
    if (tid == 0) {
        for (int i = 0; i < A_NPIECE; i++) mbar_init(bars + i * 8, 1);
        bar_init_fence();
    }
    __syncthreads();
    pdl_wait();
    const int wg = __shfl_sync(~0u, tid >> 7, 0), w = (tid >> 5) & 3, lane = tid & 31, g = lane >> 2, t = lane & 3;
    const uint32_t* q32 = reinterpret_cast<const uint32_t*>(g_q);
    int row = (blockIdx.x * 8 + wg) * 64 + w * 16 + g;
    uint32_t nq[2][6];
#pragma unroll
    for (int r = 0; r < 2; r++) {
        const uint32_t* q = q32 + (row + r * 256) * 9;
        nq[r][0] = q[t]; nq[r][1] = q[72 + t]; nq[r][2] = q[4 + t]; nq[r][3] = q[76 + t]; nq[r][4] = q[8]; nq[r][5] = q[80];
    }
    constexpr int PB = KV_BYTES / A_NPIECE;
    const float4 km0 = reinterpret_cast<const float4*>(g_kmax)[lane], km1 = reinterpret_cast<const float4*>(g_kmax)[32 + lane];
    if (tid < 32 && elect_one()) {
        for (int i = 0; i < 2; i++) {
            mbar_expect(bars + i * 8, 2 * PB);
            bulk_g2s(sK + i * PB, reinterpret_cast<const char*>(g_kc) + i * PB, PB, bars + i * 8);
            bulk_g2s(sV + i * PB, reinterpret_cast<const char*>(g_vc) + i * PB, PB, bars + i * 8);
        }
    }
    float kmax2 = fmaxf(fmaxf(fmaxf(km0.x, km0.y), fmaxf(km0.z, km0.w)), fmaxf(fmaxf(km1.x, km1.y), fmaxf(km1.z, km1.w)));
#pragma unroll
    for (int o = 1; o < 32; o <<= 1) kmax2 = fmaxf(kmax2, __shfl_xor_sync(~0u, kmax2, o));
    if (tid < 32 && elect_one()) {
        for (int i = 2; i < A_NPIECE; i++) {
            mbar_expect(bars + i * 8, 2 * PB);
            bulk_g2s(sK + i * PB, reinterpret_cast<const char*>(g_kc) + i * PB, PB, bars + i * 8);
            bulk_g2s(sV + i * PB, reinterpret_cast<const char*>(g_vc) + i * PB, PB, bars + i * 8);
        }
    }
    uint32_t vote = 0;
#pragma unroll
    for (int r = 0; r < 2; r++) {
        const uint32_t (&q)[6] = nq[r];
        const float a0 = bf_lo(q[0]), a1 = bf_hi(q[0]), a2 = bf_lo(q[2]), a3 = bf_hi(q[2]);
        const float b0 = bf_lo(q[1]), b1 = bf_hi(q[1]), b2 = bf_lo(q[3]), b3 = bf_hi(q[3]);
        float n0 = a0 * a0 + a1 * a1 + a2 * a2 + a3 * a3, n1 = b0 * b0 + b1 * b1 + b2 * b2 + b3 * b3;
        if (t == 0) {
            const float c0 = bf_lo(q[4]), c1 = bf_hi(q[4]), d0 = bf_lo(q[5]), d1 = bf_hi(q[5]);
            n0 += c0 * c0 + c1 * c1; n1 += d0 * d0 + d1 * d1;
        }
        n0 += __shfl_xor_sync(~0u, n0, 1); n0 += __shfl_xor_sync(~0u, n0, 2);
        n1 += __shfl_xor_sync(~0u, n1, 1); n1 += __shfl_xor_sync(~0u, n1, 2);
        const bool unsafe = !(fmaxf(n0, n1) * kmax2 <= FAST_BOUND * FAST_BOUND) || !(n0 == n0) || !(n1 == n1);
        vote |= (__any_sync(~0u, unsafe) ? 1u : 0u) << r;
        const uint32_t cst = t == 1 ? 0x3F804780u : (t == 2 ? 0x00003F80u : 0u);
        const uint32_t sQ = sK + A_OFF_Q + (r * 4 + wg) * 4096 + (w * 2) * 512 + g * 16 + t * 4;
        asm volatile("st.shared.b32 [%0], %1;" ::"r"(sQ), "r"(q[0]) : "memory");
        asm volatile("st.shared.b32 [%0], %1;" ::"r"(sQ + 512), "r"(q[1]) : "memory");
        asm volatile("st.shared.b32 [%0], %1;" ::"r"(sQ + 128), "r"(q[2]) : "memory");
        asm volatile("st.shared.b32 [%0], %1;" ::"r"(sQ + 640), "r"(q[3]) : "memory");
        asm volatile("st.shared.b32 [%0], %1;" ::"r"(sQ + 256), "r"(t == 0 ? q[4] : cst) : "memory");
        asm volatile("st.shared.b32 [%0], %1;" ::"r"(sQ + 768), "r"(t == 0 ? q[5] : cst) : "memory");
        asm volatile("st.shared.b32 [%0], %1;" ::"r"(sQ + 384), "r"(0u) : "memory");
        asm volatile("st.shared.b32 [%0], %1;" ::"r"(sQ + 896), "r"(0u) : "memory");
    }
    const uint32_t sVote = bars + 64 + wg * 16;
    if (lane == 0) asm volatile("st.shared.b32 [%0], %1;" ::"r"(sVote + w * 4), "r"(vote) : "memory");
    proxy_fence();
    named_sync(wg + 1, 128);
    uint32_t unsafe_mask;
    {
        uint32_t v0, v1, v2, v3;
        asm volatile("ld.shared.v4.b32 {%0, %1, %2, %3}, [%4];" : "=r"(v0), "=r"(v1), "=r"(v2), "=r"(v3) : "r"(sVote));
        unsafe_mask = __shfl_sync(~0u, v0 | v1 | v2 | v3, 0);
    }
    if (unsafe_mask) {
#pragma unroll
        for (int r = 0; r < 2; r++) {
            if (((unsafe_mask >> r) & 1) && t != 0) {
                const uint32_t sQ = sK + A_OFF_Q + (r * 4 + wg) * 4096 + (w * 2) * 512 + g * 16 + t * 4;
                asm volatile("st.shared.b32 [%0], %1;" ::"r"(sQ + 256), "r"(0u) : "memory");
                asm volatile("st.shared.b32 [%0], %1;" ::"r"(sQ + 768), "r"(0u) : "memory");
            }
        }
        proxy_fence();
        named_sync(wg + 1, 128);
    }
#pragma unroll 1
    for (int rep = 0; rep < 2; rep++, row += 256) {
        const uint32_t any_unsafe = (unsafe_mask >> rep) & 1;
        const uint64_t dQ0 = cdesc(A_OFF_Q, 128, 512, 0) + (rep * 4 + wg) * 256, dQ1 = dQ0 + 16;
        float o[12];
#pragma unroll
        for (int i = 0; i < 12; i++) o[i] = 0.f;
        pin(o);
        uint64_t dK0 = cdesc(0, 128, 384, 0), dK1 = cdesc(256, 0, 384, 0), dV = cdesc(KV_BYTES, 384, 128, 0);
        if (!any_unsafe) {
            float s[64];
#pragma unroll 1
            for (int j = 0; j < 16; j++) {
                if (rep == 0 && (j & 1) == 0) mbar_wait(bars + (j >> 1) * 8, 0);
                wg_fence();
                wgmma_ss_n128<0>(s, dQ0, dK0, 0);
                wgmma_ss_n128<0>(s, dQ1, dK1, 1);
                wg_commit();
                dK0 += 16 * 384 >> 4; dK1 += 16 * 384 >> 4;
                wg_wait<0>();
                pin(s);
                uint32_t p[32];
#define CHAIN 6
                {
                    constexpr int NP = 2 * __builtin_popcount(POLY_MASK), NM = 32 - NP;
                    float e[64];
#pragma unroll
                    for (int i = 0; i < 32; i++)
                        if (!((POLY_MASK >> (i >> 1)) & 1)) { e[2 * i] = ex2(s[2 * i]); e[2 * i + 1] = ex2(s[2 * i + 1]); p[i] = pack_bf16(e[2 * i], e[2 * i + 1]); }
                    int ip = 0;
#pragma unroll
                    for (int i = 0; i < 32; i++) {
                        if ((POLY_MASK >> (i >> 1)) & 1) {
                            const int mm = (ip * 2 * NM) / NP - CHAIN;
                            uint32_t dep = 0;
                            if (CHAIN > 0 && mm >= 0) {
                                int cnt = 0;
#pragma unroll
                                for (int q = 0; q < 32; q++)
                                    if (!((POLY_MASK >> (q >> 1)) & 1)) { if (cnt == (mm >> 1)) dep = __float_as_uint(e[2 * q + (mm & 1)]); cnt++; }
                            }
                            p[i] = exp2_pair_fixed(s[2 * i], s[2 * i + 1], dep);
                            ip++;
                        }
                    }
                }
                pin(p);
                wg_fence();
#pragma unroll
                for (int k = 0; k < 8; k++) {
                    wgmma_rs_n24<1>(o, p[4 * k], p[4 * k + 1], p[4 * k + 2], p[4 * k + 3], dV + k * 48, 1);
                }
                wg_commit();
                dV += 16 * 384 >> 4;
                wg_wait<0>();
            }
        } else {
            float s[64];
            float m0 = -INFINITY, m1 = -INFINITY;
#pragma unroll 1
            for (int j = 0; j < 16; j++) {
                if (rep == 0 && (j & 1) == 0) mbar_wait(bars + (j >> 1) * 8, 0);
                wg_fence();
                wgmma_ss_n128<0>(s, dQ0, dK0, 0);
                wgmma_ss_n128<0>(s, dQ1, dK1, 1);
                wg_commit();
                dK0 += 16 * 384 >> 4; dK1 += 16 * 384 >> 4;
                wg_wait<0>();
                pin(s);
                float x0m = m0, x1m = m1;
#pragma unroll
                for (int b = 0; b < 16; b++) { x0m = fmaxf(x0m, fmaxf(s[4 * b], s[4 * b + 1])); x1m = fmaxf(x1m, fmaxf(s[4 * b + 2], s[4 * b + 3])); }
                x0m = fmaxf(x0m, __shfl_xor_sync(~0u, x0m, 1)); x0m = fmaxf(x0m, __shfl_xor_sync(~0u, x0m, 2));
                x1m = fmaxf(x1m, __shfl_xor_sync(~0u, x1m, 1)); x1m = fmaxf(x1m, __shfl_xor_sync(~0u, x1m, 2));
                const float c0 = ex2(m0 - x0m), c1 = ex2(m1 - x1m);
                m0 = x0m; m1 = x1m;
#pragma unroll
                for (int b = 0; b < 3; b++) { o[4 * b] *= c0; o[4 * b + 1] *= c0; o[4 * b + 2] *= c1; o[4 * b + 3] *= c1; }
                uint32_t p[32];
#pragma unroll
                for (int b = 0; b < 16; b++) {
                    p[2 * b] = pack_bf16(ex2(s[4 * b] - m0), ex2(s[4 * b + 1] - m0));
                    p[2 * b + 1] = pack_bf16(ex2(s[4 * b + 2] - m1), ex2(s[4 * b + 3] - m1));
                }
                pin(p); pin(o);
                wg_fence();
#pragma unroll
                for (int k = 0; k < 8; k++) wgmma_rs_n24<1>(o, p[4 * k], p[4 * k + 1], p[4 * k + 2], p[4 * k + 3], dV + k * 48, 1);
                wg_commit();
                dV += 16 * 384 >> 4;
                wg_wait<0>();
            }
        }
        pin(o);
        const float l0 = __shfl_sync(~0u, o[8], (lane & ~3) | 1), l1 = __shfl_sync(~0u, o[10], (lane & ~3) | 1);
        const float i0 = 1.0f / l0, i1 = 1.0f / l1;
        uint32_t* o32 = reinterpret_cast<uint32_t*>(g_o);
        o32[row * 9 + t] = pack_bf16(o[0] * i0, o[1] * i0);
        o32[(row + 8) * 9 + t] = pack_bf16(o[2] * i1, o[3] * i1);
        o32[row * 9 + 4 + t] = pack_bf16(o[4] * i0, o[5] * i0);
        o32[(row + 8) * 9 + 4 + t] = pack_bf16(o[6] * i1, o[7] * i1);
        if (t == 0) { o32[row * 9 + 8] = pack_bf16(o[8] * i0, o[9] * i0); o32[(row + 8) * 9 + 8] = pack_bf16(o[10] * i1, o[11] * i1); }
    }
}

constexpr int O_THREADS = 416;
constexpr int O_OFF_STAT = P_A_BYTES + P_NST * P_B_STAGE + 256;
constexpr int O_SMEM = O_OFF_STAT + 9 * 64 * 8;

__global__ void __cluster_dims__(3, 1, 1) __launch_bounds__(O_THREADS, 1)
k_oproj(const __grid_constant__ CUtensorMap tmO, const __grid_constant__ CUtensorMap tmWo, const __grid_constant__ CUtensorMap tmX2, const __grid_constant__ CUtensorMap tmOut, const __nv_bfloat16* __restrict__ x, const __nv_bfloat16* __restrict__ w1) {
    extern __shared__ __align__(1024) uint8_t smem[];
    const uint32_t sA = smem_u32(smem), sB = sA + P_A_BYTES, bars = sB + P_NST * P_B_STAGE;
    const uint32_t fullB = bars, emptyB = bars + 64, fullA = bars + 128;
    const int tid = threadIdx.x, warp = __shfl_sync(~0u, tid >> 5, 0), lane = tid & 31;
    const int m = blockIdx.x / 3, cg = blockIdx.x % 3;
    check_smem_base(sA);
    if (tid == 0) {
        prefetch_map(&tmO); prefetch_map(&tmWo); prefetch_map(&tmX2); prefetch_map(&tmOut);
        for (int i = 0; i < P_NST; i++) { mbar_init(fullB + i * 8, 1); mbar_init(emptyB + i * 8, 12); }
        for (int i = 0; i < 9; i++) mbar_init(fullA + i * 8, 1);
        bar_init_fence();
        for (int kb = 0; kb < 9; kb++) mbar_expect(fullA + kb * 8, 8192);
    }
    __syncthreads();
    pdl_launch();
    if (warp == 12) {
        if (elect_one()) {
            for (int kb = 0; kb < 9; kb++) {
                const int s = kb >= P_NST ? kb - P_NST : kb;
                if (kb == 2) {
                    pdl_wait();
                    for (int ka = 0; ka < 9; ka++) tma_2d(sA + ka * 8192, &tmO, ka * 64, m * 64, fullA + ka * 8);
                }
                if (kb >= P_NST) mbar_wait(emptyB + s * 8, 0);
                mbar_expect(fullB + s * 8, P_B_STAGE);
                for (int a = 0; a < 3; a++) tma_2d(sB + s * P_B_STAGE + a * 8192, &tmWo, cg * 192 + a * 64, kb * 64, fullB + s * 8);
            }
            for (int i = 0; i < 6; i++) prefetch_l2(reinterpret_cast<const char*>(w1) + (size_t)blockIdx.x * (FF * DM * 2 / 96) + i * 9216, 9216);
        }
        return;
    }
    const int wg = warp >> 2, w = warp & 3, g = lane >> 2, t = lane & 3;
    uint32_t xr[16];
    {
        const uint32_t* x32 = reinterpret_cast<const uint32_t*>(x) + (((m * 64 + w * 16 + g) * DM + cg * 192 + wg * 64 + 2 * t) >> 1);
#pragma unroll
        for (int b = 0; b < 8; b++) { xr[2 * b] = __ldg(x32 + b * 4); xr[2 * b + 1] = __ldg(x32 + b * 4 + 4 * DM); }
    }
    float acc[32];
    proj_mma(acc, wg, fullB, emptyB, fullA, true, lane, [](int) {});
    named_sync(1, 384);
    float s0 = 0.f, q0 = 0.f, s1 = 0.f, q1 = 0.f;
#pragma unroll
    for (int b = 0; b < 8; b++) {
        const uint32_t xa = xr[2 * b], xb = xr[2 * b + 1];
        const uint32_t ha = pack_bf16(acc[4 * b] + bf_lo(xa), acc[4 * b + 1] + bf_hi(xa));
        const uint32_t hb = pack_bf16(acc[4 * b + 2] + bf_lo(xb), acc[4 * b + 3] + bf_hi(xb));
        xr[2 * b] = ha; xr[2 * b + 1] = hb;
        const float a = bf_lo(ha), c = bf_hi(ha), d = bf_lo(hb), e = bf_hi(hb);
        s0 += a + c; q0 = fmaf(a, a, fmaf(c, c, q0));
        s1 += d + e; q1 = fmaf(d, d, fmaf(e, e, q1));
    }
    s0 += __shfl_xor_sync(~0u, s0, 1); s0 += __shfl_xor_sync(~0u, s0, 2);
    q0 += __shfl_xor_sync(~0u, q0, 1); q0 += __shfl_xor_sync(~0u, q0, 2);
    s1 += __shfl_xor_sync(~0u, s1, 1); s1 += __shfl_xor_sync(~0u, s1, 2);
    q1 += __shfl_xor_sync(~0u, q1, 1); q1 += __shfl_xor_sync(~0u, q1, 2);
    const int r = w * 16 + g;
    const uint32_t sStat = sA + O_OFF_STAT;
    if (t < 3) {
        uint32_t dst;
        asm("mapa.shared::cluster.u32 %0, %1, %2;" : "=r"(dst) : "r"(sStat + ((cg * 3 + wg) * 64 + r) * 8), "r"(t));
        asm volatile("st.shared::cluster.v2.f32 [%0], {%1, %2};" ::"r"(dst), "f"(s0), "f"(q0) : "memory");
        asm volatile("st.shared::cluster.v2.f32 [%0], {%1, %2};" ::"r"(dst + 64), "f"(s1), "f"(q1) : "memory");
    }
    cluster_arrive();
    stage_tile<8>(xr, sA + wg * 8192, w, lane);
    proxy_fence();
    named_sync(2 + wg, 128);
    const bool leader = w == 0 && elect_one();
    if (leader) { tma_st_2d(&tmOut, cg * 192 + wg * 64, m * 64, sA + wg * 8192); bulk_commit(); }
    cluster_wait();
    s0 = q0 = s1 = q1 = 0.f;
#pragma unroll
    for (int p = 0; p < 9; p++) {
        float a, b, c, d;
        asm volatile("ld.shared.v2.f32 {%0, %1}, [%2];" : "=f"(a), "=f"(b) : "r"(sStat + (p * 64 + r) * 8));
        asm volatile("ld.shared.v2.f32 {%0, %1}, [%2];" : "=f"(c), "=f"(d) : "r"(sStat + (p * 64 + r + 8) * 8));
        s0 += a; q0 += b; s1 += c; q1 += d;
    }
    const float m0 = s0 * (1.0f / DM), m1 = s1 * (1.0f / DM);
    const float rs0 = rsqrtf(fmaxf(q0 * (1.0f / DM) - m0 * m0, 0.f) + LN_EPS), rs1 = rsqrtf(fmaxf(q1 * (1.0f / DM) - m1 * m1, 0.f) + LN_EPS);
    const float sc0 = 0.5f * rs0, sc1 = 0.5f * rs1, n0 = -m0 * sc0, n1 = -m1 * sc1;
#pragma unroll
    for (int b = 0; b < 8; b++) {
        xr[2 * b] = pack_bf16(fmaf(bf_lo(xr[2 * b]), sc0, n0), fmaf(bf_hi(xr[2 * b]), sc0, n0));
        xr[2 * b + 1] = pack_bf16(fmaf(bf_lo(xr[2 * b + 1]), sc1, n1), fmaf(bf_hi(xr[2 * b + 1]), sc1, n1));
    }
    stage_tile<8>(xr, sA + (3 + wg) * 8192, w, lane);
    proxy_fence();
    named_sync(2 + wg, 128);
    if (leader) {
        tma_st_2d(&tmX2, cg * 192 + wg * 64, m * 64, sA + (3 + wg) * 8192);
        bulk_commit();
        bulk_wait_all();
    }
}

constexpr int F_THREADS = 384;
constexpr int F_NST = 6;
constexpr int F_STAGE = 96 * 128;
constexpr int F_X_BYTES = 9 * 16384;
constexpr int F_OFF_ST = F_X_BYTES;
constexpr int F_OFF_BAR = F_OFF_ST + F_NST * F_STAGE;
constexpr int F_SMEM = F_OFF_BAR + 256;

__device__ __forceinline__ float tanh_hw(float x) { float y; asm("tanh.approx.f32 %0, %1;" : "=f"(y) : "f"(x)); return y; }
__host__ __device__ constexpr int piece_begin(int p) { return p == 0 ? 0 : 3 * p + 1; }
template <int P>
__device__ __forceinline__ void silu_s1(const float (&acc)[32], float (&tmp)[8]) {
#pragma unroll
    for (int i = 2 * piece_begin(P); i < 2 * piece_begin(P + 1); i++) tmp[i - 2 * piece_begin(P)] = tanh_hw(acc[i]);
}
template <int C, int P>
__device__ __forceinline__ void silu_s2(const float (&acc)[32], const float (&tmp)[8], uint32_t (&h1)[144]) {
#pragma unroll
    for (int i = piece_begin(P); i < piece_begin(P + 1); i++) {
        const int k = 2 * (i - piece_begin(P));
        h1[C * 16 + i] = pack_bf16(fmaf(acc[2 * i], tmp[k], acc[2 * i]), fmaf(acc[2 * i + 1], tmp[k + 1], acc[2 * i + 1]));
    }
}
template <int J>
__device__ __forceinline__ void silu_slot_last(const float (&prev)[32], float (&tmp)[2][8], uint32_t (&h1)[144]) {
    if constexpr (J >= 1 && J <= 4) {
#pragma unroll
        for (int i = 0; i < 4; i++) {
            const int q = 4 * (J - 1) + i;
            h1[128 + q] = pack_bf16(fmaf(prev[2 * q], tmp[(J - 1) & 1][2 * i], prev[2 * q]), fmaf(prev[2 * q + 1], tmp[(J - 1) & 1][2 * i + 1], prev[2 * q + 1]));
        }
    }
    if constexpr (J <= 3) {
#pragma unroll
        for (int i = 0; i < 8; i++) tmp[J & 1][i] = tanh_hw(prev[8 * J + i]);
        pin(tmp[J & 1]);
    }
}
template <int C, int J>
__device__ __forceinline__ void silu_slot(const float (&prev)[32], float (&tmp)[2][8], uint32_t (&h1)[144]) {
    if constexpr (J >= 1) silu_s2<C, J - 1>(prev, tmp[(J - 1) & 1], h1);
    if constexpr (J <= 4) { silu_s1<J>(prev, tmp[J & 1]); pin(tmp[J & 1]); }
}

struct FfnPipe {
    uint32_t full, empty;
    int lane;
    __device__ __forceinline__ void acquire(int s, uint32_t ph) const { mbar_wait(full + s * 8, ph); }
    __device__ __forceinline__ void release(int s) const { if (lane == 0) mbar_arrive(empty + s * 8); }
};

template <int C>
__device__ __forceinline__ void ffn_phase1_chunk(float (&cur)[32], float (&prev)[32], uint32_t (&h1)[144], const FfnPipe& pp, uint64_t dx, uint32_t fullX) {
    float tmp[2][8];
    const uint64_t dw = cdesc(F_OFF_ST, 8192, 1024, 1) + blockIdx.y * (C + 1);
    dx += blockIdx.y * C;
#pragma unroll
    for (int j = 0; j < 6; j++) {
        if (C == 0) { mbar_wait(fullX + ((6 * j) >> 2) * 8, 0); mbar_wait(fullX + ((6 * j + 5) >> 2) * 8, 0); }
        pp.acquire(j, C & 1);
        if (j == 0) pin(cur);
        wg_fence();
#pragma unroll
        for (int i = 0; i < 6; i++) {
            const int ks = 6 * j + i;
            wgmma_ss_n64<1>(cur, dx + ((ks >> 2) * 1024 + (ks & 3) * 2), dw + ((j * F_STAGE + i * 2048) >> 4), ks != 0);
        }
        wg_commit();
        if (C > 0 || j > 0) { wg_wait<1>(); pp.release((j + 5) % 6); }
        if (C > 0) {
            constexpr int CP = C > 0 ? C - 1 : 0;
            pin(prev);
            if (j == 0) silu_slot<CP, 0>(prev, tmp, h1);
            if (j == 1) silu_slot<CP, 1>(prev, tmp, h1);
            if (j == 2) silu_slot<CP, 2>(prev, tmp, h1);
            if (j == 3) silu_slot<CP, 3>(prev, tmp, h1);
            if (j == 4) silu_slot<CP, 4>(prev, tmp, h1);
            if (j == 5) silu_slot<CP, 5>(prev, tmp, h1);
        }
    }
}

__device__ __forceinline__ void ffn_stage_chunk(const float (&acc)[32], uint32_t stg, int w, int lane) {
    uint32_t pk[16];
#pragma unroll
    for (int i = 0; i < 16; i++) pk[i] = pack_bf16(acc[2 * i], acc[2 * i + 1]);
    stage_tile<8>(pk, stg, w, lane);
}
__device__ __forceinline__ void ffn_reduce_chunk(const CUtensorMap* tmOut, uint32_t stg, int col, int row, int w, int wgid, bool leader) {
    proxy_fence();
    if (w != 0) {
        asm volatile("bar.arrive %0, 128;" ::"r"(2 + wgid) : "memory");
    } else {
        named_sync(2 + wgid, 128);
        if (leader) { tma_red_2d(tmOut, col, row, stg); bulk_commit(); }
    }
}

template <bool FIRST>
__device__ __forceinline__ void ffn_phase2_chunk(float (&cur)[32], float (&prev)[32], uint32_t (&h1)[144], const FfnPipe& pp, uint32_t ph, const CUtensorMap* tmOut, uint32_t stg_prev, int col_prev, int row, int w, int lane, int wgid, bool leader) {
    const uint64_t dw = cdesc(F_OFF_ST, 8192, 1024, 1) + blockIdx.y * col_prev;
    float tmp[2][8];
#pragma unroll
    for (int j = 0; j < 6; j++) {
        pp.acquire(j, ph);
        if (j == 0) pin(cur);
        if (FIRST && j == 5) pin(h1);
        wg_fence();
#pragma unroll
        for (int i = 0; i < 6; i++) {
            const int f = (6 * j + i) * 4;
            wgmma_rs_n64<1>(cur, h1[f], h1[f + 1], h1[f + 2], h1[f + 3], dw + ((j * F_STAGE + i * 2048) >> 4), (j | i) != 0);
        }
        wg_commit();
        wg_wait<1>();
        pp.release((j + 5) % 6);
        if (FIRST) {
            pin(prev);
            if (j == 0) silu_slot_last<0>(prev, tmp, h1);
            if (j == 1) silu_slot_last<1>(prev, tmp, h1);
            if (j == 2) silu_slot_last<2>(prev, tmp, h1);
            if (j == 3) silu_slot_last<3>(prev, tmp, h1);
            if (j == 4) silu_slot_last<4>(prev, tmp, h1);
        } else {
            if (j == 0) { pin(prev); ffn_stage_chunk(prev, stg_prev, w, lane); }
            if (j == 1) ffn_reduce_chunk(tmOut, stg_prev, col_prev, row, w, wgid, leader);
        }
    }
}

__global__ void __launch_bounds__(F_THREADS, 1)
k_ffn(const __grid_constant__ CUtensorMap tmH, const __grid_constant__ CUtensorMap tmW1, const __grid_constant__ CUtensorMap tmW2, const __grid_constant__ CUtensorMap tmOut, const __nv_bfloat16* __restrict__ w2) {
    extern __shared__ __align__(1024) uint8_t smem[];
    const uint32_t sX = smem_u32(smem), sSt = sX + F_OFF_ST, bars = sX + F_OFF_BAR;
    const uint32_t full = bars, empty = bars + 64, fullX = bars + 128;
    const int tid = threadIdx.x, warp = __shfl_sync(~0u, tid >> 5, 0), lane = tid & 31;
#define FFN_MAP 1
    const int m = FFN_MAP == 0 ? (blockIdx.x & 15) : (FFN_MAP == 1 ? (blockIdx.x >> 3) : ((blockIdx.x >> 1) & 15));
    const int fs = FFN_MAP == 0 ? (blockIdx.x >> 4) : (FFN_MAP == 1 ? (blockIdx.x & 7) : ((blockIdx.x >> 5) * 2 + (blockIdx.x & 1)));
    check_smem_base(sX);
    if (tid == 0) {
        prefetch_map(&tmW1); prefetch_map(&tmH); prefetch_map(&tmW2); prefetch_map(&tmOut);
        for (int i = 0; i < F_NST; i++) { mbar_init(full + i * 8, 1); mbar_init(empty + i * 8, 8); }
        for (int i = 0; i < 9; i++) mbar_init(fullX + i * 8, 1);
        bar_init_fence();
        for (int kb = 0; kb < 9; kb++) mbar_expect(fullX + kb * 8, 16384);
    }
    __syncthreads();
    if (warp < 4) {
        asm volatile("setmaxnreg.dec.sync.aligned.u32 24;");
        if (warp == 1 && lane < 9) prefetch_l2(reinterpret_cast<const char*>(w2) + ((size_t)fs * 576 + m * 36 + lane * 4) * (DM * 2), 4 * DM * 2);
        if (warp == 0 && elect_one()) {
#pragma unroll 1
            for (int c = 0; c < 18; c++) {
                int col = c - 9 + fs;
                if (col >= 9) col -= 9;
#pragma unroll 1
                for (int j = 0; j < 6; j++) {
                    mbar_wait(empty + j * 8, (c & 1) ^ 1);
                    mbar_expect(full + j * 8, F_STAGE);
                    if (c < 9) tma_2d(sSt + j * F_STAGE, &tmW1, fs * 576 + c * 64, j * 96, full + j * 8);
                    else tma_2d(sSt + j * F_STAGE, &tmW2, col * 64, fs * 576 + j * 96, full + j * 8);
                }
            }
        }
    } else {
        asm volatile("setmaxnreg.inc.sync.aligned.u32 240;");
        const int wgid = (warp >> 2) - 1, w = warp & 3;
        pdl_wait();
        if (warp == 4 && elect_one()) {
            for (int kb = 0; kb < 9; kb++) tma_2d(sX + kb * 16384, &tmH, kb * 64, m * 128, fullX + kb * 8);
        }
        __syncwarp();
        FfnPipe pp{full, empty, lane};
        const uint64_t xlo = cdesc(0, 16, 1024, 1) + wgid * 512;
        uint32_t h1[144];
        float acc0[32], acc1[32];
        ffn_phase1_chunk<0>(acc0, acc1, h1, pp, xlo, fullX);
        ffn_phase1_chunk<1>(acc1, acc0, h1, pp, xlo, fullX);
        ffn_phase1_chunk<2>(acc0, acc1, h1, pp, xlo, fullX);
        ffn_phase1_chunk<3>(acc1, acc0, h1, pp, xlo, fullX);
        ffn_phase1_chunk<4>(acc0, acc1, h1, pp, xlo, fullX);
        ffn_phase1_chunk<5>(acc1, acc0, h1, pp, xlo, fullX);
        ffn_phase1_chunk<6>(acc0, acc1, h1, pp, xlo, fullX);
        ffn_phase1_chunk<7>(acc1, acc0, h1, pp, xlo, fullX);
        ffn_phase1_chunk<8>(acc0, acc1, h1, pp, xlo, fullX);
        const int row = m * 128 + wgid * 64;
        const uint32_t stg = sX + wgid * 8192;
        int c = fs, cprev = 0;
        const bool leader = w == 0 && elect_one();
        ffn_phase2_chunk<true>(acc1, acc0, h1, pp, 1, &tmOut, 0, 0, row, w, lane, wgid, leader);
        cprev = c; if (++c == 9) c = 0;
#pragma unroll 1
        for (int j = 1; j < 9; j += 2) {
            ffn_phase2_chunk<false>(acc0, acc1, h1, pp, 0, &tmOut, stg + (j - 1) * 16384, cprev * 64, row, w, lane, wgid, leader);
            cprev = c; if (++c == 9) c = 0;
            ffn_phase2_chunk<false>(acc1, acc0, h1, pp, 1, &tmOut, stg + j * 16384, cprev * 64, row, w, lane, wgid, leader);
            cprev = c; if (++c == 9) c = 0;
        }
        wg_wait<0>();
        pin(acc1);
        ffn_stage_chunk(acc1, stg + 8 * 16384, w, lane);
        ffn_reduce_chunk(&tmOut, stg + 8 * 16384, cprev * 64, row, w, wgid, leader);
        if (leader) bulk_wait_all();
    }
}

typedef CUresult (*EncodeFn)(CUtensorMap*, CUtensorMapDataType, cuuint32_t, void*, const cuuint64_t*, const cuuint64_t*, const cuuint32_t*, const cuuint32_t*,
                             CUtensorMapInterleave, CUtensorMapSwizzle, CUtensorMapL2promotion, CUtensorMapFloatOOBfill);

CUtensorMap make_map(EncodeFn enc, const void* base, int rows, int cols, int box_rows) {
    CUtensorMap tm;
    cuuint64_t dims[2] = {(cuuint64_t)cols, (cuuint64_t)rows};
    cuuint64_t strides[1] = {(cuuint64_t)cols * 2};
    cuuint32_t box[2] = {64, (cuuint32_t)box_rows};
    cuuint32_t es[2] = {1, 1};
    enc(&tm, CU_TENSOR_MAP_DATA_TYPE_BFLOAT16, 2, const_cast<void*>(base), dims, strides, box, es, CU_TENSOR_MAP_INTERLEAVE_NONE,
        CU_TENSOR_MAP_SWIZZLE_128B, CU_TENSOR_MAP_L2_PROMOTION_L2_256B, CU_TENSOR_MAP_FLOAT_OOB_FILL_NONE);
    return tm;
}

template <typename... KArgs, typename... Args>
void launch(void (*kern)(KArgs...), int grid, int block, int smem, bool pdl, Args... args) {
    cudaLaunchConfig_t cfg = {};
    cfg.gridDim = dim3(grid); cfg.blockDim = dim3(block); cfg.dynamicSmemBytes = smem; cfg.stream = cudaStreamPerThread;
    cudaLaunchAttribute at[1];
    at[0].id = cudaLaunchAttributeProgrammaticStreamSerialization;
    at[0].val.programmaticStreamSerializationAllowed = 1;
    cfg.attrs = at; cfg.numAttrs = pdl ? 1 : 0;
    cudaLaunchKernelEx(&cfg, kern, KArgs(args)...);
}

}

#define USE_PDL 1

extern "C" void kernel_launch(void* const* d_in, const int* in_sizes, int n_in, void* d_out, int out_size) {
    const __nv_bfloat16* x = (const __nv_bfloat16*)d_in[0];
    const __nv_bfloat16* wq = (const __nv_bfloat16*)d_in[1];
    const __nv_bfloat16* wk = (const __nv_bfloat16*)d_in[2];
    const __nv_bfloat16* wv = (const __nv_bfloat16*)d_in[3];
    const __nv_bfloat16* wo = (const __nv_bfloat16*)d_in[4];
    const __nv_bfloat16* w1 = (const __nv_bfloat16*)d_in[6];
    const __nv_bfloat16* w2 = (const __nv_bfloat16*)d_in[7];
    __nv_bfloat16* out = (__nv_bfloat16*)d_out;

    static EncodeFn enc = nullptr;
    static void *p_o = nullptr, *p_h = nullptr, *p_q = nullptr;
    if (!enc) {
        cudaDriverEntryPointQueryResult qr;
        cudaGetDriverEntryPoint("cuTensorMapEncodeTiled", (void**)&enc, cudaEnableDefault, &qr);
        cudaGetSymbolAddress(&p_o, g_o);
        cudaGetSymbolAddress(&p_h, g_x2);
        cudaGetSymbolAddress(&p_q, g_q);
        cudaFuncSetAttribute(k_qkv, cudaFuncAttributeMaxDynamicSharedMemorySize, P_SMEM);
        cudaFuncSetAttribute(k_attn, cudaFuncAttributeMaxDynamicSharedMemorySize, A_SMEM);
        cudaFuncSetAttribute(k_oproj, cudaFuncAttributeMaxDynamicSharedMemorySize, O_SMEM);
        cudaFuncSetAttribute(k_ffn, cudaFuncAttributeMaxDynamicSharedMemorySize, F_SMEM);
    }
    const CUtensorMap tmWq = make_map(enc, wq, DM, DM, 64);
    const CUtensorMap tmWo = make_map(enc, wo, DM, DM, 64);
    const CUtensorMap tmO = make_map(enc, p_o, SEQ, DM, 64);
    const CUtensorMap tmH64 = make_map(enc, p_h, SEQ, DM, 64);
    const CUtensorMap tmH = make_map(enc, p_h, SEQ, DM, 128);
    const CUtensorMap tmQ = make_map(enc, p_q, SEQ, DM, 64);
    const CUtensorMap tmW1 = make_map(enc, w1, DM, FF, 96);
    const CUtensorMap tmW2 = make_map(enc, w2, FF, DM, 96);
    const CUtensorMap tmOut = make_map(enc, out, SEQ, DM, 64);

    launch(k_qkv, 128, Q_THREADS, P_SMEM, false, tmWq, tmQ, x, wk, wv);
    launch(k_attn, 128, A_THREADS, A_SMEM, USE_PDL);
    launch(k_oproj, 96, O_THREADS, O_SMEM, USE_PDL, tmO, tmWo, tmH64, tmOut, x, w1);
    launch(k_ffn, 128, F_THREADS, F_SMEM, USE_PDL, tmH, tmW1, tmW2, tmOut, w2);
}
```

```cpp
#include <cuda_runtime.h>
#include <cuda_bf16.h>
#include <cuda.h>
#include <stdint.h>

namespace {

constexpr int SEQ = 2048, DM = 576, FF = 4608;
constexpr int KV_BYTES = SEQ * 48;
constexpr float LN_EPS = 1e-5f;
constexpr float LOG2E = 1.4426950408889634f;
constexpr float Q_SCALE = 0.23570226039551584f * LOG2E;

#define POLY_MASK_V 0xB6DBu
constexpr uint32_t POLY_MASK = POLY_MASK_V;
#define FAST_BOUND_V 60.0f
constexpr float FAST_BOUND = FAST_BOUND_V;

__device__ __align__(1024) __nv_bfloat16 g_q[SEQ * DM];
__device__ __align__(1024) uint4 g_kc[KV_BYTES / 16];
__device__ __align__(1024) uint4 g_vc[KV_BYTES / 16];
__device__ __align__(16) float g_kmax[256];
__device__ __align__(1024) __nv_bfloat16 g_o[SEQ * DM];
__device__ __align__(1024) __nv_bfloat16 g_h[SEQ * DM];
__device__ __align__(1024) __nv_bfloat16 g_x2[SEQ * DM];

__device__ __forceinline__ uint32_t smem_u32(const void* p) { return (uint32_t)__cvta_generic_to_shared(p); }
__device__ __forceinline__ void wg_fence() { asm volatile("wgmma.fence.sync.aligned;" ::: "memory"); }
__device__ __forceinline__ void wg_commit() { asm volatile("wgmma.commit_group.sync.aligned;" ::: "memory"); }
template <int N> __device__ __forceinline__ void wg_wait() { asm volatile("wgmma.wait_group.sync.aligned %0;" ::"n"(N) : "memory"); }
template <int N> __device__ __forceinline__ void pin(float (&r)[N]) {
#pragma unroll
    for (int i = 0; i < N; i++) asm volatile("" : "+f"(r[i])::"memory");
}
template <int N> __device__ __forceinline__ void pin(uint32_t (&r)[N]) {
#pragma unroll
    for (int i = 0; i < N; i++) asm volatile("" : "+r"(r[i])::"memory");
}
constexpr uint32_t SMEM0 = 0x400;
__host__ __device__ constexpr uint64_t cdesc(uint32_t off, uint32_t lbo, uint32_t sbo, uint32_t swz) {
    return (uint64_t)(((SMEM0 + off) & 0x3FFFF) >> 4) | ((uint64_t)(lbo >> 4) << 16) | ((uint64_t)(sbo >> 4) << 32) | ((uint64_t)swz << 62);
}
__device__ __forceinline__ void check_smem_base(uint32_t base) { if ((base & 0x3FFFF) != SMEM0) __trap(); }

__device__ __forceinline__ void mbar_init(uint32_t bar, int cnt) { asm volatile("mbarrier.init.shared::cta.b64 [%0], %1;" ::"r"(bar), "r"(cnt) : "memory"); }
__device__ __forceinline__ void mbar_expect(uint32_t bar, int bytes) { asm volatile("mbarrier.arrive.expect_tx.shared::cta.b64 _, [%0], %1;" ::"r"(bar), "r"(bytes) : "memory"); }
__device__ __forceinline__ void mbar_arrive(uint32_t bar) { asm volatile("mbarrier.arrive.shared::cta.b64 _, [%0];" ::"r"(bar) : "memory"); }
__device__ __forceinline__ void mbar_wait(uint32_t bar, uint32_t parity) {
    asm volatile(
        "{\n.reg .pred p;\n.reg .u32 n;\nmov.u32 n, 0;\n"
        "LAB_WAIT:\n"
        "mbarrier.try_wait.parity.shared::cta.b64 p, [%0], %1;\n"
        "@p bra DONE;\n"
        "add.u32 n, n, 1;\n"
        "setp.lt.u32 p, n, 4000000;\n"
        "@p bra LAB_WAIT;\n"
        "trap;\n"
        "DONE:\n}\n" ::"r"(bar), "r"(parity) : "memory");
}
__device__ __forceinline__ void bar_init_fence() {
    asm volatile("fence.mbarrier_init.release.cluster;" ::: "memory");
    asm volatile("fence.proxy.async.shared::cta;" ::: "memory");
}
__device__ __forceinline__ void proxy_fence() { asm volatile("fence.proxy.async.shared::cta;" ::: "memory"); }
__device__ __forceinline__ void named_sync(int id, int n) { asm volatile("bar.sync %0, %1;" ::"r"(id), "r"(n) : "memory"); }
__device__ __forceinline__ void bulk_g2s(uint32_t dst, const void* src, int bytes, uint32_t bar) {
    asm volatile("cp.async.bulk.shared::cluster.global.mbarrier::complete_tx::bytes [%0], [%1], %2, [%3];" ::"r"(dst), "l"(src), "r"(bytes), "r"(bar) : "memory");
}
__device__ __forceinline__ void tma_2d(uint32_t dst, const CUtensorMap* tm, int c0, int c1, uint32_t bar) {
    asm volatile("cp.async.bulk.tensor.2d.shared::cluster.global.mbarrier::complete_tx::bytes [%0], [%1, {%3, %4}], [%2];" ::"r"(dst), "l"(tm), "r"(bar), "r"(c0), "r"(c1) : "memory");
}
__device__ __forceinline__ void cluster_arrive() { asm volatile("barrier.cluster.arrive.release.aligned;" ::: "memory"); }
__device__ __forceinline__ void cluster_wait() { asm volatile("barrier.cluster.wait.acquire.aligned;" ::: "memory"); }
__device__ __forceinline__ void tma_red_2d(const CUtensorMap* tm, int c0, int c1, uint32_t src) {
    asm volatile("cp.reduce.async.bulk.tensor.2d.global.shared::cta.add.tile.bulk_group [%0, {%2, %3}], [%1];" ::"l"(tm), "r"(src), "r"(c0), "r"(c1) : "memory");
}
__device__ __forceinline__ void tma_st_2d(const CUtensorMap* tm, int c0, int c1, uint32_t src) {
    asm volatile("cp.async.bulk.tensor.2d.global.shared::cta.tile.bulk_group [%0, {%2, %3}], [%1];" ::"l"(tm), "r"(src), "r"(c0), "r"(c1) : "memory");
}
__device__ __forceinline__ void bulk_commit() { asm volatile("cp.async.bulk.commit_group;" ::: "memory"); }
__device__ __forceinline__ void bulk_wait_all() { asm volatile("cp.async.bulk.wait_group.read 0;" ::: "memory"); }
__device__ __forceinline__ bool elect_one() {
    uint32_t p;
    asm volatile("{\n.reg .pred P;\nelect.sync _|P, 0xffffffff;\nselp.b32 %0, 1, 0, P;\n}\n" : "=r"(p));
    return p != 0;
}
__device__ __forceinline__ void prefetch_l2(const void* p, int bytes) { asm volatile("cp.async.bulk.prefetch.L2.global [%0], %1;" ::"l"(p), "r"(bytes) : "memory"); }
__device__ __forceinline__ void prefetch_map(const CUtensorMap* tm) { asm volatile("prefetch.tensormap [%0];" ::"l"(tm) : "memory"); }
__device__ __forceinline__ void pdl_launch() { asm volatile("griddepcontrol.launch_dependents;" ::: "memory"); }
__device__ __forceinline__ void pdl_wait() { asm volatile("griddepcontrol.wait;" ::: "memory"); }
__device__ __forceinline__ float ex2(float x) { float y; asm("ex2.approx.ftz.f32 %0, %1;" : "=f"(y) : "f"(x)); return y; }
__device__ __forceinline__ uint32_t pack_bf16(float lo, float hi) { uint32_t r; asm("cvt.rn.bf16x2.f32 %0, %1, %2;" : "=r"(r) : "f"(hi), "f"(lo)); return r; }
__device__ __forceinline__ float bf_lo(uint32_t v) { return __uint_as_float(v << 16); }
__device__ __forceinline__ float bf_hi(uint32_t v) { return __uint_as_float(v & 0xFFFF0000u); }
__device__ __forceinline__ uint32_t hfma2(uint32_t a, uint32_t b, uint32_t c) { uint32_t r; asm("fma.rn.f16x2 %0, %1, %2, %3;" : "=r"(r) : "r"(a), "r"(b), "r"(c)); return r; }
__device__ __forceinline__ void stmatrix_x4(uint32_t addr, uint32_t r0, uint32_t r1, uint32_t r2, uint32_t r3) {
    asm volatile("stmatrix.sync.aligned.m8n8.x4.shared.b16 [%0], {%1, %2, %3, %4};" ::"r"(addr), "r"(r0), "r"(r1), "r"(r2), "r"(r3) : "memory");
}

template <int TB> __device__ __forceinline__ void wgmma_ss_n24(float (&d)[12], uint64_t da, uint64_t db, int sc) {
    asm volatile("{\n.reg .pred p;\nsetp.ne.b32 p, %14, 0;\n"
        "wgmma.mma_async.sync.aligned.m64n24k16.f32.bf16.bf16 {%0, %1, %2, %3, %4, %5, %6, %7, %8, %9, %10, %11}, %12, %13, p, 1, 1, 0, %15;\n}\n"
        : "+f"(d[0]), "+f"(d[1]), "+f"(d[2]), "+f"(d[3]), "+f"(d[4]), "+f"(d[5]), "+f"(d[6]), "+f"(d[7]), "+f"(d[8]), "+f"(d[9]), "+f"(d[10]), "+f"(d[11])
        : "l"(da), "l"(db), "r"(sc), "n"(TB));
}
template <int TB> __device__ __forceinline__ void wgmma_ss_n64(float (&d)[32], uint64_t da, uint64_t db, int sc) {
    asm volatile("{\n.reg .pred p;\nsetp.ne.b32 p, %34, 0;\n"
        "wgmma.mma_async.sync.aligned.m64n64k16.f32.bf16.bf16 {%0, %1, %2, %3, %4, %5, %6, %7, %8, %9, %10, %11, %12, %13, %14, %15, %16, %17, %18, %19, %20, %21, %22, %23, %24, %25, %26, %27, %28, %29, %30, %31}, %32, %33, p, 1, 1, 0, %35;\n}\n"
        : "+f"(d[0]), "+f"(d[1]), "+f"(d[2]), "+f"(d[3]), "+f"(d[4]), "+f"(d[5]), "+f"(d[6]), "+f"(d[7]), "+f"(d[8]), "+f"(d[9]), "+f"(d[10]), "+f"(d[11]), "+f"(d[12]), "+f"(d[13]), "+f"(d[14]), "+f"(d[15]), "+f"(d[16]), "+f"(d[17]), "+f"(d[18]), "+f"(d[19]), "+f"(d[20]), "+f"(d[21]), "+f"(d[22]), "+f"(d[23]), "+f"(d[24]), "+f"(d[25]), "+f"(d[26]), "+f"(d[27]), "+f"(d[28]), "+f"(d[29]), "+f"(d[30]), "+f"(d[31])
        : "l"(da), "l"(db), "r"(sc), "n"(TB));
}
template <int TB> __device__ __forceinline__ void wgmma_ss_n128(float (&d)[64], uint64_t da, uint64_t db, int sc) {
    asm volatile("{\n.reg .pred p;\nsetp.ne.b32 p, %66, 0;\n"
        "wgmma.mma_async.sync.aligned.m64n128k16.f32.bf16.bf16 {%0, %1, %2, %3, %4, %5, %6, %7, %8, %9, %10, %11, %12, %13, %14, %15, %16, %17, %18, %19, %20, %21, %22, %23, %24, %25, %26, %27, %28, %29, %30, %31, %32, %33, %34, %35, %36, %37, %38, %39, %40, %41, %42, %43, %44, %45, %46, %47, %48, %49, %50, %51, %52, %53, %54, %55, %56, %57, %58, %59, %60, %61, %62, %63}, %64, %65, p, 1, 1, 0, %67;\n}\n"
        : "+f"(d[0]), "+f"(d[1]), "+f"(d[2]), "+f"(d[3]), "+f"(d[4]), "+f"(d[5]), "+f"(d[6]), "+f"(d[7]), "+f"(d[8]), "+f"(d[9]), "+f"(d[10]), "+f"(d[11]), "+f"(d[12]), "+f"(d[13]), "+f"(d[14]), "+f"(d[15]), "+f"(d[16]), "+f"(d[17]), "+f"(d[18]), "+f"(d[19]), "+f"(d[20]), "+f"(d[21]), "+f"(d[22]), "+f"(d[23]), "+f"(d[24]), "+f"(d[25]), "+f"(d[26]), "+f"(d[27]), "+f"(d[28]), "+f"(d[29]), "+f"(d[30]), "+f"(d[31]), "+f"(d[32]), "+f"(d[33]), "+f"(d[34]), "+f"(d[35]), "+f"(d[36]), "+f"(d[37]), "+f"(d[38]), "+f"(d[39]), "+f"(d[40]), "+f"(d[41]), "+f"(d[42]), "+f"(d[43]), "+f"(d[44]), "+f"(d[45]), "+f"(d[46]), "+f"(d[47]), "+f"(d[48]), "+f"(d[49]), "+f"(d[50]), "+f"(d[51]), "+f"(d[52]), "+f"(d[53]), "+f"(d[54]), "+f"(d[55]), "+f"(d[56]), "+f"(d[57]), "+f"(d[58]), "+f"(d[59]), "+f"(d[60]), "+f"(d[61]), "+f"(d[62]), "+f"(d[63])
        : "l"(da), "l"(db), "r"(sc), "n"(TB));
}
template <int TB> __device__ __forceinline__ void wgmma_rs_n24(float (&d)[12], uint32_t a0, uint32_t a1, uint32_t a2, uint32_t a3, uint64_t db, int sc) {
    asm volatile("{\n.reg .pred p;\nsetp.ne.b32 p, %17, 0;\n"
        "wgmma.mma_async.sync.aligned.m64n24k16.f32.bf16.bf16 {%0, %1, %2, %3, %4, %5, %6, %7, %8, %9, %10, %11}, {%12, %13, %14, %15}, %16, p, 1, 1, %18;\n}\n"
        : "+f"(d[0]), "+f"(d[1]), "+f"(d[2]), "+f"(d[3]), "+f"(d[4]), "+f"(d[5]), "+f"(d[6]), "+f"(d[7]), "+f"(d[8]), "+f"(d[9]), "+f"(d[10]), "+f"(d[11])
        : "r"(a0), "r"(a1), "r"(a2), "r"(a3), "l"(db), "r"(sc), "n"(TB));
}
template <int TB> __device__ __forceinline__ void wgmma_rs_n64(float (&d)[32], uint32_t a0, uint32_t a1, uint32_t a2, uint32_t a3, uint64_t db, int sc) {
    asm volatile("{\n.reg .pred p;\nsetp.ne.b32 p, %37, 0;\n"
        "wgmma.mma_async.sync.aligned.m64n64k16.f32.bf16.bf16 {%0, %1, %2, %3, %4, %5, %6, %7, %8, %9, %10, %11, %12, %13, %14, %15, %16, %17, %18, %19, %20, %21, %22, %23, %24, %25, %26, %27, %28, %29, %30, %31}, {%32, %33, %34, %35}, %36, p, 1, 1, %38;\n}\n"
        : "+f"(d[0]), "+f"(d[1]), "+f"(d[2]), "+f"(d[3]), "+f"(d[4]), "+f"(d[5]), "+f"(d[6]), "+f"(d[7]), "+f"(d[8]), "+f"(d[9]), "+f"(d[10]), "+f"(d[11]), "+f"(d[12]), "+f"(d[13]), "+f"(d[14]), "+f"(d[15]), "+f"(d[16]), "+f"(d[17]), "+f"(d[18]), "+f"(d[19]), "+f"(d[20]), "+f"(d[21]), "+f"(d[22]), "+f"(d[23]), "+f"(d[24]), "+f"(d[25]), "+f"(d[26]), "+f"(d[27]), "+f"(d[28]), "+f"(d[29]), "+f"(d[30]), "+f"(d[31])
        : "r"(a0), "r"(a1), "r"(a2), "r"(a3), "l"(db), "r"(sc), "n"(TB));
}
template <int TB> __device__ __forceinline__ void wgmma_rs_n128(float (&d)[64], uint32_t a0, uint32_t a1, uint32_t a2, uint32_t a3, uint64_t db, int sc) {
    asm volatile("{\n.reg .pred p;\nsetp.ne.b32 p, %69, 0;\n"
        "wgmma.mma_async.sync.aligned.m64n128k16.f32.bf16.bf16 {%0, %1, %2, %3, %4, %5, %6, %7, %8, %9, %10, %11, %12, %13, %14, %15, %16, %17, %18, %19, %20, %21, %22, %23, %24, %25, %26, %27, %28, %29, %30, %31, %32, %33, %34, %35, %36, %37, %38, %39, %40, %41, %42, %43, %44, %45, %46, %47, %48, %49, %50, %51, %52, %53, %54, %55, %56, %57, %58, %59, %60, %61, %62, %63}, {%64, %65, %66, %67}, %68, p, 1, 1, %70;\n}\n"
        : "+f"(d[0]), "+f"(d[1]), "+f"(d[2]), "+f"(d[3]), "+f"(d[4]), "+f"(d[5]), "+f"(d[6]), "+f"(d[7]), "+f"(d[8]), "+f"(d[9]), "+f"(d[10]), "+f"(d[11]), "+f"(d[12]), "+f"(d[13]), "+f"(d[14]), "+f"(d[15]), "+f"(d[16]), "+f"(d[17]), "+f"(d[18]), "+f"(d[19]), "+f"(d[20]), "+f"(d[21]), "+f"(d[22]), "+f"(d[23]), "+f"(d[24]), "+f"(d[25]), "+f"(d[26]), "+f"(d[27]), "+f"(d[28]), "+f"(d[29]), "+f"(d[30]), "+f"(d[31]), "+f"(d[32]), "+f"(d[33]), "+f"(d[34]), "+f"(d[35]), "+f"(d[36]), "+f"(d[37]), "+f"(d[38]), "+f"(d[39]), "+f"(d[40]), "+f"(d[41]), "+f"(d[42]), "+f"(d[43]), "+f"(d[44]), "+f"(d[45]), "+f"(d[46]), "+f"(d[47]), "+f"(d[48]), "+f"(d[49]), "+f"(d[50]), "+f"(d[51]), "+f"(d[52]), "+f"(d[53]), "+f"(d[54]), "+f"(d[55]), "+f"(d[56]), "+f"(d[57]), "+f"(d[58]), "+f"(d[59]), "+f"(d[60]), "+f"(d[61]), "+f"(d[62]), "+f"(d[63])
        : "r"(a0), "r"(a1), "r"(a2), "r"(a3), "l"(db), "r"(sc), "n"(TB));
}

constexpr int P_NST = 6;
constexpr int P_A_BYTES = 9 * 8192;
constexpr int P_B_STAGE = 3 * 8192;
constexpr int P_SMEM = P_A_BYTES + P_NST * P_B_STAGE + 256 + 320;

template <int NB>
__device__ __forceinline__ void stage_tile(const uint32_t (&pk)[NB * 2], uint32_t base, int w, int lane) {
    const int r = w * 16 + (lane & 7) + ((lane >> 3) & 1) * 8;
#pragma unroll
    for (int b = 0; b < NB; b += 2) {
        const uint32_t a = base + (b >> 3) * 8192 + r * 128 + ((((b & 7) + (lane >> 4)) ^ (r & 7)) << 4);
        stmatrix_x4(a, pk[2 * b], pk[2 * b + 1], pk[2 * b + 2], pk[2 * b + 3]);
    }
}

__device__ __forceinline__ uint32_t hsub2_bf16(uint32_t a, uint32_t b) { uint32_t r; asm("sub.rn.bf16x2 %0, %1, %2;" : "=r"(r) : "r"(a), "r"(b)); return r; }

constexpr int KV_RAW = DM * 18 * 2;
constexpr int Q_THREADS = 416;

__device__ __forceinline__ void proj_mma(float (&acc)[32], int wg, uint32_t fullB, uint32_t emptyB, uint32_t fullA, bool wait_a, int lane) {
    const uint64_t dA = cdesc(0, 16, 1024, 1), dB = cdesc(P_A_BYTES, 8192, 1024, 1) + wg * 512;
#pragma unroll 1
    for (int kb = 0; kb < 9; kb++) {
        const int s = kb >= P_NST ? kb - P_NST : kb;
        if (wait_a) mbar_wait(fullA + kb * 8, 0);
        mbar_wait(fullB + s * 8, kb >= P_NST ? 1 : 0);
        wg_fence();
#pragma unroll
        for (int ks = 0; ks < 4; ks++) wgmma_ss_n64<1>(acc, dA + (kb * 512 + ks * 2), dB + (s * (P_B_STAGE >> 4) + ks * 128), (kb | ks) != 0);
        wg_commit();
        if (kb < 4) {
            wg_wait<1>();
            if (kb >= 1 && lane == 0) mbar_arrive(emptyB + (kb - 1) * 8);
        }
    }
    wg_wait<0>();
    pin(acc);
}

__global__ void __launch_bounds__(Q_THREADS, 1)
k_qkv(const __grid_constant__ CUtensorMap tmWq, const __grid_constant__ CUtensorMap tmQ, const __nv_bfloat16* __restrict__ x, const __nv_bfloat16* __restrict__ wk, const __nv_bfloat16* __restrict__ wv) {
    extern __shared__ __align__(1024) uint8_t smem[];
    const uint32_t sA = smem_u32(smem), sB = sA + P_A_BYTES, bars = sB + P_NST * P_B_STAGE;
    const uint32_t fullB = bars, emptyB = bars + 64, fullX = bars + 128, fullW = bars + 136;
    float* s_rstd = reinterpret_cast<float*>(smem + P_A_BYTES + P_NST * P_B_STAGE + 256);
    const int tid = threadIdx.x, warp = __shfl_sync(~0u, tid >> 5, 0), lane = tid & 31;
    const bool isQ = blockIdx.x < 96;
    const int m = isQ ? blockIdx.x / 3 : blockIdx.x - 96, cg = blockIdx.x % 3;
    if (warp == 12) {
        if (elect_one()) {
            mbar_init(fullX, 1);
            bar_init_fence();
            mbar_expect(fullX, P_A_BYTES);
            bulk_g2s(sA, x + (size_t)m * 64 * DM, P_A_BYTES, fullX);
            prefetch_map(&tmWq); prefetch_map(&tmQ);
            for (int i = 0; i < P_NST; i++) { mbar_init(fullB + i * 8, 1); mbar_init(emptyB + i * 8, 12); }
            mbar_init(fullW, 1);
            bar_init_fence();
            if (isQ) {
                for (int kb = 0; kb < P_NST; kb++) {
                    mbar_expect(fullB + kb * 8, P_B_STAGE);
                    for (int a = 0; a < 3; a++) tma_2d(sB + kb * P_B_STAGE + a * 8192, &tmWq, cg * 192 + a * 64, kb * 64, fullB + kb * 8);
                }
            } else {
                mbar_expect(fullW, 2 * KV_RAW);
                bulk_g2s(sB + 3 * P_B_STAGE, wk, KV_RAW, fullW);
                bulk_g2s(sB + 3 * P_B_STAGE + KV_RAW, wv, KV_RAW, fullW);
            }
        }
        __syncwarp();
    }
    check_smem_base(sA);
    __syncthreads();
    pdl_launch();
    if (warp == 12) {
        if (isQ && elect_one()) {
            for (int kb = P_NST; kb < 9; kb++) {
                const int s = kb - P_NST;
                mbar_wait(emptyB + s * 8, 0);
                mbar_expect(fullB + s * 8, P_B_STAGE);
                for (int a = 0; a < 3; a++) tma_2d(sB + s * P_B_STAGE + a * 8192, &tmWq, cg * 192 + a * 64, kb * 64, fullB + s * 8);
            }
        }
        return;
    }
    if (warp < 8) {
        const int row = tid >> 2, q = tid & 3, h0 = (row & 1) * 4;
        mbar_wait(fullX, 0);
        uint4 v[18];
        const uint32_t ra = sA + row * 1152 + (q + h0) * 16, rb = sA + row * 1152 + (q + 4 - h0) * 16;
#pragma unroll
        for (int kb = 0; kb < 9; kb++) {
            asm volatile("ld.shared.v4.b32 {%0, %1, %2, %3}, [%4];" : "=r"(v[2 * kb].x), "=r"(v[2 * kb].y), "=r"(v[2 * kb].z), "=r"(v[2 * kb].w) : "r"(ra + kb * 128));
            asm volatile("ld.shared.v4.b32 {%0, %1, %2, %3}, [%4];" : "=r"(v[2 * kb + 1].x), "=r"(v[2 * kb + 1].y), "=r"(v[2 * kb + 1].z), "=r"(v[2 * kb + 1].w) : "r"(rb + kb * 128));
        }
        float sum = 0.f, sum2 = 0.f, sq = 0.f, sq2 = 0.f;
#pragma unroll
        for (int i = 0; i < 18; i++) {
            const uint32_t w[4] = {v[i].x, v[i].y, v[i].z, v[i].w};
#pragma unroll
            for (int j = 0; j < 4; j++) { const float a = bf_lo(w[j]), b = bf_hi(w[j]); sum += a; sum2 += b; sq = fmaf(a, a, sq); sq2 = fmaf(b, b, sq2); }
        }
        named_sync(1, 256);
        sum += sum2; sq += sq2;
        sum += __shfl_xor_sync(~0u, sum, 1); sum += __shfl_xor_sync(~0u, sum, 2);
        sq += __shfl_xor_sync(~0u, sq, 1); sq += __shfl_xor_sync(~0u, sq, 2);
        const float mean = sum * (1.0f / DM);
        if (q == 0) s_rstd[row] = rsqrtf(fmaxf(sq * (1.0f / DM) - mean * mean, 0.f) + LN_EPS);
        const uint32_t mhi = pack_bf16(mean, mean);
        const float rem = mean - bf_lo(mhi);
        const uint32_t mlo = pack_bf16(rem, rem);
        const uint32_t wa = sA + row * 128 + (((q + h0) ^ (row & 7)) << 4), wb = sA + row * 128 + (((q + 4 - h0) ^ (row & 7)) << 4);
#pragma unroll
        for (int i = 0; i < 18; i++) {
            const uint32_t o0 = hsub2_bf16(hsub2_bf16(v[i].x, mhi), mlo), o1 = hsub2_bf16(hsub2_bf16(v[i].y, mhi), mlo);
            const uint32_t o2 = hsub2_bf16(hsub2_bf16(v[i].z, mhi), mlo), o3 = hsub2_bf16(hsub2_bf16(v[i].w, mhi), mlo);
            asm volatile("st.shared.v4.b32 [%0], {%1, %2, %3, %4};" ::"r"(((i & 1) ? wb : wa) + (i >> 1) * 8192), "r"(o0), "r"(o1), "r"(o2), "r"(o3) : "memory");
        }
    } else if (!isQ) {
        mbar_wait(fullW, 0);
        const uint32_t* raw = reinterpret_cast<const uint32_t*>(smem + P_A_BYTES + 3 * P_B_STAGE);
#pragma unroll 3
        for (int r = tid - 256; r < 2 * DM; r += 128) {
            uint32_t wr[9];
#pragma unroll
            for (int i = 0; i < 9; i++) wr[i] = raw[r * 9 + i];
            const int sel = r >= DM, k = r - sel * DM;
            uint8_t* dst = smem + P_A_BYTES + sel * 3 * 9216 + (k >> 3) * 128 + (k & 7) * 16;
            *reinterpret_cast<uint4*>(dst) = make_uint4(wr[0], wr[1], wr[2], wr[3]);
            *reinterpret_cast<uint4*>(dst + 9216) = make_uint4(wr[4], wr[5], wr[6], wr[7]);
            *reinterpret_cast<uint32_t*>(dst + 2 * 9216) = wr[8];
        }
    }
    proxy_fence();
    named_sync(2, 384);
    const int wg = warp >> 2, w = warp & 3, g = lane >> 2, t = lane & 3;
    const float rs0 = s_rstd[w * 16 + g], rs1 = s_rstd[w * 16 + g + 8];
    if (isQ) {
        const float c0 = rs0 * Q_SCALE, c1 = rs1 * Q_SCALE;
        float acc[32];
        proj_mma(acc, wg, fullB, emptyB, 0, false, lane);
        uint32_t pk[16];
#pragma unroll
        for (int i = 0; i < 8; i++) { pk[2 * i] = pack_bf16(acc[4 * i] * c0, acc[4 * i + 1] * c0); pk[2 * i + 1] = pack_bf16(acc[4 * i + 2] * c1, acc[4 * i + 3] * c1); }
        named_sync(2, 384);
        stage_tile<8>(pk, sA + wg * 8192, w, lane);
        proxy_fence();
        named_sync(3 + wg, 128);
        if (w == 0 && elect_one()) {
            tma_st_2d(&tmQ, cg * 192 + wg * 64, m * 64, sA + wg * 8192);
            bulk_commit();
            bulk_wait_all();
        }
    } else if (wg < 2) {
        float acc[12];
        const uint64_t dA = cdesc(0, 16, 1024, 1), dB = cdesc(P_A_BYTES, 128, 9216, 0) + wg * (3 * 9216 >> 4);
#pragma unroll
        for (int i = 0; i < 12; i++) acc[i] = 0.f;
        pin(acc);
        wg_fence();
#pragma unroll 1
        for (int kb = 0; kb < 9; kb++) {
#pragma unroll
            for (int ks = 0; ks < 4; ks++) wgmma_ss_n24<1>(acc, dA + (kb * 512 + ks * 2), dB + (kb * 4 + ks) * 16, 1);
        }
        wg_commit();
        wg_wait<0>();
        pin(acc);
        uint32_t pk[6];
#pragma unroll
        for (int b = 0; b < 3; b++) { pk[2 * b] = pack_bf16(acc[4 * b] * rs0, acc[4 * b + 1] * rs0); pk[2 * b + 1] = pack_bf16(acc[4 * b + 2] * rs1, acc[4 * b + 3] * rs1); }
        float n0 = 0.f, n1 = 0.f, vm = 0.f;
#pragma unroll
        for (int b = 0; b < 3; b++) {
            if (b < 2 || t == 0) {
                const float a = bf_lo(pk[2 * b]), c = bf_hi(pk[2 * b]), d = bf_lo(pk[2 * b + 1]), e = bf_hi(pk[2 * b + 1]);
                n0 = fmaf(a, a, fmaf(c, c, n0)); n1 = fmaf(d, d, fmaf(e, e, n1));
            }
        }
        n0 += __shfl_xor_sync(~0u, n0, 1); n0 += __shfl_xor_sync(~0u, n0, 2);
        n1 += __shfl_xor_sync(~0u, n1, 1); n1 += __shfl_xor_sync(~0u, n1, 2);
        vm = fmaxf(n0, n1);
        if (!(n0 == n0) || !(n1 == n1)) vm = __int_as_float(0x7F800000);
#pragma unroll
        for (int o = 4; o < 32; o <<= 1) vm = fmaxf(vm, __shfl_xor_sync(~0u, vm, o));
        if (t != 0) {
            uint32_t lo, hi;
            if (wg == 0) {
                const int grp = m * 8 + w * 2;
                const uint32_t c = t == 1 ? 0x42FE3F80u   : (t == 2 ? 0x00003BC0u   : 0u);
                lo = ((POLY_MASK >> (grp & 15)) & 1) ? c : 0u;
                hi = ((POLY_MASK >> ((grp + 1) & 15)) & 1) ? c : 0u;
            } else {
                lo = hi = t == 1 ? 0x00003F80u : 0u;
            }
            pk[4] = lo; pk[5] = hi;
        }
        uint32_t* dst = reinterpret_cast<uint32_t*>(wg == 0 ? g_kc : g_vc) + (m * 8 + w * 2) * 96 + g * 4 + t;
#pragma unroll
        for (int b = 0; b < 3; b++) { dst[b * 32] = pk[2 * b]; dst[96 + b * 32] = pk[2 * b + 1]; }
        if (lane == 0) g_kmax[m * 8 + warp] = (wg == 0) ? vm : (vm <= 1e24f ? 0.f : __int_as_float(0x7F800000));
    }
}

constexpr int A_THREADS = 512;
constexpr int A_NPIECE = 8;
constexpr int A_OFF_Q = 2 * KV_BYTES;
constexpr int A_OFF_BAR = A_OFF_Q + 8 * 4096;
constexpr int A_SMEM = A_OFF_BAR + 128;

__device__ __forceinline__ uint32_t exp2_pair_fixed(float lo, float hi, uint32_t dep) {
    const uint32_t G = __byte_perm(__float_as_uint(lo), __float_as_uint(hi), 0x5410);
    uint32_t Hh;
    asm("lop3.b32 %0, %1, 0x007F007F, %2, 0xC0;" : "=r"(Hh) : "r"(G), "r"(dep));
    const uint32_t tt = hfma2(Hh, 0xF96BF96Bu, 0x358C358Cu);
    return G - hfma2(tt, Hh, 0u);
}

__global__ void __launch_bounds__(A_THREADS, 1)
k_attn(__nv_bfloat16* __restrict__ out) {
    extern __shared__ __align__(1024) uint8_t smem[];
    pdl_launch();
    const uint32_t sK = smem_u32(smem), sV = sK + KV_BYTES, bars = sK + A_OFF_BAR;
    const int tid = threadIdx.x;
    check_smem_base(sK);
    if (tid == 0) {
        for (int i = 0; i < A_NPIECE; i++) mbar_init(bars + i * 8, 1);
        bar_init_fence();
    }
    for (int i = tid; i < 16 * DM * 2 / 16; i += A_THREADS) reinterpret_cast<uint4*>(out + (size_t)blockIdx.x * 16 * DM)[i] = make_uint4(0u, 0u, 0u, 0u);
    __syncthreads();
    pdl_wait();
    const int wg = __shfl_sync(~0u, tid >> 7, 0), w = (tid >> 5) & 3, lane = tid & 31, g = lane >> 2, t = lane & 3;
    const uint32_t* q32 = reinterpret_cast<const uint32_t*>(g_q);
    int row = (blockIdx.x * 8 + wg) * 64 + w * 16 + g;
    uint32_t nq[2][6];
#pragma unroll
    for (int r = 0; r < 2; r++) {
        const uint32_t* q = q32 + (row + r * 256) * 9;
        nq[r][0] = q[t]; nq[r][1] = q[72 + t]; nq[r][2] = q[4 + t]; nq[r][3] = q[76 + t]; nq[r][4] = q[8]; nq[r][5] = q[80];
    }
    constexpr int PB = KV_BYTES / A_NPIECE;
    const float4 km0 = reinterpret_cast<const float4*>(g_kmax)[lane], km1 = reinterpret_cast<const float4*>(g_kmax)[32 + lane];
    if (tid < 32 && elect_one()) {
        for (int i = 0; i < 2; i++) {
            mbar_expect(bars + i * 8, 2 * PB);
            bulk_g2s(sK + i * PB, reinterpret_cast<const char*>(g_kc) + i * PB, PB, bars + i * 8);
            bulk_g2s(sV + i * PB, reinterpret_cast<const char*>(g_vc) + i * PB, PB, bars + i * 8);
        }
    }
    float kmax2 = fmaxf(fmaxf(fmaxf(km0.x, km0.y), fmaxf(km0.z, km0.w)), fmaxf(fmaxf(km1.x, km1.y), fmaxf(km1.z, km1.w)));
#pragma unroll
    for (int o = 1; o < 32; o <<= 1) kmax2 = fmaxf(kmax2, __shfl_xor_sync(~0u, kmax2, o));
    if (tid < 32 && elect_one()) {
        for (int i = 2; i < A_NPIECE; i++) {
            mbar_expect(bars + i * 8, 2 * PB);
            bulk_g2s(sK + i * PB, reinterpret_cast<const char*>(g_kc) + i * PB, PB, bars + i * 8);
            bulk_g2s(sV + i * PB, reinterpret_cast<const char*>(g_vc) + i * PB, PB, bars + i * 8);
        }
    }
    uint32_t vote = 0;
#pragma unroll
    for (int r = 0; r < 2; r++) {
        const uint32_t (&q)[6] = nq[r];
        const float a0 = bf_lo(q[0]), a1 = bf_hi(q[0]), a2 = bf_lo(q[2]), a3 = bf_hi(q[2]);
        const float b0 = bf_lo(q[1]), b1 = bf_hi(q[1]), b2 = bf_lo(q[3]), b3 = bf_hi(q[3]);
        float n0 = a0 * a0 + a1 * a1 + a2 * a2 + a3 * a3, n1 = b0 * b0 + b1 * b1 + b2 * b2 + b3 * b3;
        if (t == 0) {
            const float c0 = bf_lo(q[4]), c1 = bf_hi(q[4]), d0 = bf_lo(q[5]), d1 = bf_hi(q[5]);
            n0 += c0 * c0 + c1 * c1; n1 += d0 * d0 + d1 * d1;
        }
        n0 += __shfl_xor_sync(~0u, n0, 1); n0 += __shfl_xor_sync(~0u, n0, 2);
        n1 += __shfl_xor_sync(~0u, n1, 1); n1 += __shfl_xor_sync(~0u, n1, 2);
        const bool unsafe = !(fmaxf(n0, n1) * kmax2 <= FAST_BOUND * FAST_BOUND) || !(n0 == n0) || !(n1 == n1);
        vote |= (__any_sync(~0u, unsafe) ? 1u : 0u) << r;
        const uint32_t cst = t == 1 ? 0x3F804780u : (t == 2 ? 0x00003F80u : 0u);
        const uint32_t sQ = sK + A_OFF_Q + (r * 4 + wg) * 4096 + (w * 2) * 512 + g * 16 + t * 4;
        asm volatile("st.shared.b32 [%0], %1;" ::"r"(sQ), "r"(q[0]) : "memory");
        asm volatile("st.shared.b32 [%0], %1;" ::"r"(sQ + 512), "r"(q[1]) : "memory");
        asm volatile("st.shared.b32 [%0], %1;" ::"r"(sQ + 128), "r"(q[2]) : "memory");
        asm volatile("st.shared.b32 [%0], %1;" ::"r"(sQ + 640), "r"(q[3]) : "memory");
        asm volatile("st.shared.b32 [%0], %1;" ::"r"(sQ + 256), "r"(t == 0 ? q[4] : cst) : "memory");
        asm volatile("st.shared.b32 [%0], %1;" ::"r"(sQ + 768), "r"(t == 0 ? q[5] : cst) : "memory");
        asm volatile("st.shared.b32 [%0], %1;" ::"r"(sQ + 384), "r"(0u) : "memory");
        asm volatile("st.shared.b32 [%0], %1;" ::"r"(sQ + 896), "r"(0u) : "memory");
    }
    const uint32_t sVote = bars + 64 + wg * 16;
    if (lane == 0) asm volatile("st.shared.b32 [%0], %1;" ::"r"(sVote + w * 4), "r"(vote) : "memory");
    proxy_fence();
    named_sync(wg + 1, 128);
    uint32_t unsafe_mask;
    {
        uint32_t v0, v1, v2, v3;
        asm volatile("ld.shared.v4.b32 {%0, %1, %2, %3}, [%4];" : "=r"(v0), "=r"(v1), "=r"(v2), "=r"(v3) : "r"(sVote));
        unsafe_mask = __shfl_sync(~0u, v0 | v1 | v2 | v3, 0);
    }
    if (unsafe_mask) {
#pragma unroll
        for (int r = 0; r < 2; r++) {
            if (((unsafe_mask >> r) & 1) && t != 0) {
                const uint32_t sQ = sK + A_OFF_Q + (r * 4 + wg) * 4096 + (w * 2) * 512 + g * 16 + t * 4;
                asm volatile("st.shared.b32 [%0], %1;" ::"r"(sQ + 256), "r"(0u) : "memory");
                asm volatile("st.shared.b32 [%0], %1;" ::"r"(sQ + 768), "r"(0u) : "memory");
            }
        }
        proxy_fence();
        named_sync(wg + 1, 128);
    }
#pragma unroll 1
    for (int rep = 0; rep < 2; rep++, row += 256) {
        const uint32_t any_unsafe = (unsafe_mask >> rep) & 1;
        const uint64_t dQ0 = cdesc(A_OFF_Q, 128, 512, 0) + (rep * 4 + wg) * 256, dQ1 = dQ0 + 16;
        float o[12];
#pragma unroll
        for (int i = 0; i < 12; i++) o[i] = 0.f;
        pin(o);
        uint64_t dK0 = cdesc(0, 128, 384, 0), dK1 = cdesc(256, 0, 384, 0), dV = cdesc(KV_BYTES, 384, 128, 0);
        if (!any_unsafe) {
            float s[64];
#pragma unroll 1
            for (int j = 0; j < 16; j++) {
                if (rep == 0 && (j & 1) == 0) mbar_wait(bars + (j >> 1) * 8, 0);
                wg_fence();
                wgmma_ss_n128<0>(s, dQ0, dK0, 0);
                wgmma_ss_n128<0>(s, dQ1, dK1, 1);
                wg_commit();
                dK0 += 16 * 384 >> 4; dK1 += 16 * 384 >> 4;
                wg_wait<0>();
                pin(s);
                uint32_t p[32];
#define CHAIN 6
                {
                    constexpr int NP = 2 * __builtin_popcount(POLY_MASK), NM = 32 - NP;
                    float e[64];
#pragma unroll
                    for (int i = 0; i < 32; i++)
                        if (!((POLY_MASK >> (i >> 1)) & 1)) { e[2 * i] = ex2(s[2 * i]); e[2 * i + 1] = ex2(s[2 * i + 1]); p[i] = pack_bf16(e[2 * i], e[2 * i + 1]); }
                    int ip = 0;
#pragma unroll
                    for (int i = 0; i < 32; i++) {
                        if ((POLY_MASK >> (i >> 1)) & 1) {
                            const int mm = (ip * 2 * NM) / NP - CHAIN;
                            uint32_t dep = 0;
                            if (CHAIN > 0 && mm >= 0) {
                                int cnt = 0;
#pragma unroll
                                for (int q = 0; q < 32; q++)
                                    if (!((POLY_MASK >> (q >> 1)) & 1)) { if (cnt == (mm >> 1)) dep = __float_as_uint(e[2 * q + (mm & 1)]); cnt++; }
                            }
                            p[i] = exp2_pair_fixed(s[2 * i], s[2 * i + 1], dep);
                            ip++;
                        }
                    }
                }
                pin(p);
                wg_fence();
#pragma unroll
                for (int k = 0; k < 8; k++) {
                    wgmma_rs_n24<1>(o, p[4 * k], p[4 * k + 1], p[4 * k + 2], p[4 * k + 3], dV + k * 48, 1);
                }
                wg_commit();
                dV += 16 * 384 >> 4;
                wg_wait<0>();
            }
        } else {
            float s[64];
            float m0 = -INFINITY, m1 = -INFINITY;
#pragma unroll 1
            for (int j = 0; j < 16; j++) {
                if (rep == 0 && (j & 1) == 0) mbar_wait(bars + (j >> 1) * 8, 0);
                wg_fence();
                wgmma_ss_n128<0>(s, dQ0, dK0, 0);
                wgmma_ss_n128<0>(s, dQ1, dK1, 1);
                wg_commit();
                dK0 += 16 * 384 >> 4; dK1 += 16 * 384 >> 4;
                wg_wait<0>();
                pin(s);
                float x0m = m0, x1m = m1;
#pragma unroll
                for (int b = 0; b < 16; b++) { x0m = fmaxf(x0m, fmaxf(s[4 * b], s[4 * b + 1])); x1m = fmaxf(x1m, fmaxf(s[4 * b + 2], s[4 * b + 3])); }
                x0m = fmaxf(x0m, __shfl_xor_sync(~0u, x0m, 1)); x0m = fmaxf(x0m, __shfl_xor_sync(~0u, x0m, 2));
                x1m = fmaxf(x1m, __shfl_xor_sync(~0u, x1m, 1)); x1m = fmaxf(x1m, __shfl_xor_sync(~0u, x1m, 2));
                const float c0 = ex2(m0 - x0m), c1 = ex2(m1 - x1m);
                m0 = x0m; m1 = x1m;
#pragma unroll
                for (int b = 0; b < 3; b++) { o[4 * b] *= c0; o[4 * b + 1] *= c0; o[4 * b + 2] *= c1; o[4 * b + 3] *= c1; }
                uint32_t p[32];
#pragma unroll
                for (int b = 0; b < 16; b++) {
                    p[2 * b] = pack_bf16(ex2(s[4 * b] - m0), ex2(s[4 * b + 1] - m0));
                    p[2 * b + 1] = pack_bf16(ex2(s[4 * b + 2] - m1), ex2(s[4 * b + 3] - m1));
                }
                pin(p); pin(o);
                wg_fence();
#pragma unroll
                for (int k = 0; k < 8; k++) wgmma_rs_n24<1>(o, p[4 * k], p[4 * k + 1], p[4 * k + 2], p[4 * k + 3], dV + k * 48, 1);
                wg_commit();
                dV += 16 * 384 >> 4;
                wg_wait<0>();
            }
        }
        pin(o);
        const float l0 = __shfl_sync(~0u, o[8], (lane & ~3) | 1), l1 = __shfl_sync(~0u, o[10], (lane & ~3) | 1);
        const float i0 = 1.0f / l0, i1 = 1.0f / l1;
        uint32_t* o32 = reinterpret_cast<uint32_t*>(g_o);
        o32[row * 9 + t] = pack_bf16(o[0] * i0, o[1] * i0);
        o32[(row + 8) * 9 + t] = pack_bf16(o[2] * i1, o[3] * i1);
        o32[row * 9 + 4 + t] = pack_bf16(o[4] * i0, o[5] * i0);
        o32[(row + 8) * 9 + 4 + t] = pack_bf16(o[6] * i1, o[7] * i1);
        if (t == 0) { o32[row * 9 + 8] = pack_bf16(o[8] * i0, o[9] * i0); o32[(row + 8) * 9 + 8] = pack_bf16(o[10] * i1, o[11] * i1); }
    }
}

constexpr int O_THREADS = 416;
constexpr int O_OFF_STAT = P_A_BYTES + P_NST * P_B_STAGE + 256;
constexpr int O_SMEM = O_OFF_STAT + 9 * 64 * 8;

__global__ void __cluster_dims__(3, 1, 1) __launch_bounds__(O_THREADS, 1)
k_oproj(const __grid_constant__ CUtensorMap tmO, const __grid_constant__ CUtensorMap tmWo, const __grid_constant__ CUtensorMap tmX2, const __grid_constant__ CUtensorMap tmH, const __nv_bfloat16* __restrict__ x, const __nv_bfloat16* __restrict__ w1) {
    extern __shared__ __align__(1024) uint8_t smem[];
    const uint32_t sA = smem_u32(smem), sB = sA + P_A_BYTES, bars = sB + P_NST * P_B_STAGE;
    const uint32_t fullB = bars, emptyB = bars + 64, fullA = bars + 128;
    const int tid = threadIdx.x, warp = __shfl_sync(~0u, tid >> 5, 0), lane = tid & 31;
    const int m = blockIdx.x / 3, cg = blockIdx.x % 3;
    check_smem_base(sA);
    if (tid == 0) {
        prefetch_map(&tmO); prefetch_map(&tmWo); prefetch_map(&tmX2); prefetch_map(&tmH);
        for (int i = 0; i < P_NST; i++) { mbar_init(fullB + i * 8, 1); mbar_init(emptyB + i * 8, 12); }
        for (int i = 0; i < 9; i++) mbar_init(fullA + i * 8, 1);
        bar_init_fence();
        for (int kb = 0; kb < 9; kb++) mbar_expect(fullA + kb * 8, 8192);
    }
    __syncthreads();
    pdl_launch();
    if (warp == 12) {
        if (elect_one()) {
            for (int kb = 0; kb < 9; kb++) {
                const int s = kb >= P_NST ? kb - P_NST : kb;
                if (kb == 2) {
                    pdl_wait();
                    for (int ka = 0; ka < 9; ka++) tma_2d(sA + ka * 8192, &tmO, ka * 64, m * 64, fullA + ka * 8);
                }
                if (kb >= P_NST) mbar_wait(emptyB + s * 8, 0);
                mbar_expect(fullB + s * 8, P_B_STAGE);
                for (int a = 0; a < 3; a++) tma_2d(sB + s * P_B_STAGE + a * 8192, &tmWo, cg * 192 + a * 64, kb * 64, fullB + s * 8);
            }
            for (int i = 0; i < 6; i++) prefetch_l2(reinterpret_cast<const char*>(w1) + (size_t)blockIdx.x * (FF * DM * 2 / 96) + i * 9216, 9216);
        }
        return;
    }
    const int wg = warp >> 2, w = warp & 3, g = lane >> 2, t = lane & 3;
    uint32_t xr[16];
    {
        const uint32_t* x32 = reinterpret_cast<const uint32_t*>(x) + (((m * 64 + w * 16 + g) * DM + cg * 192 + wg * 64 + 2 * t) >> 1);
#pragma unroll
        for (int b = 0; b < 8; b++) { xr[2 * b] = __ldg(x32 + b * 4); xr[2 * b + 1] = __ldg(x32 + b * 4 + 4 * DM); }
    }
    float acc[32];
    proj_mma(acc, wg, fullB, emptyB, fullA, true, lane);
    named_sync(1, 384);
    float s0 = 0.f, q0 = 0.f, s1 = 0.f, q1 = 0.f;
#pragma unroll
    for (int b = 0; b < 8; b++) {
        const uint32_t xa = xr[2 * b], xb = xr[2 * b + 1];
        const uint32_t ha = pack_bf16(acc[4 * b] + bf_lo(xa), acc[4 * b + 1] + bf_hi(xa));
        const uint32_t hb = pack_bf16(acc[4 * b + 2] + bf_lo(xb), acc[4 * b + 3] + bf_hi(xb));
        xr[2 * b] = ha; xr[2 * b + 1] = hb;
        const float a = bf_lo(ha), c = bf_hi(ha), d = bf_lo(hb), e = bf_hi(hb);
        s0 += a + c; q0 = fmaf(a, a, fmaf(c, c, q0));
        s1 += d + e; q1 = fmaf(d, d, fmaf(e, e, q1));
    }
    s0 += __shfl_xor_sync(~0u, s0, 1); s0 += __shfl_xor_sync(~0u, s0, 2);
    q0 += __shfl_xor_sync(~0u, q0, 1); q0 += __shfl_xor_sync(~0u, q0, 2);
    s1 += __shfl_xor_sync(~0u, s1, 1); s1 += __shfl_xor_sync(~0u, s1, 2);
    q1 += __shfl_xor_sync(~0u, q1, 1); q1 += __shfl_xor_sync(~0u, q1, 2);
    const int r = w * 16 + g;
    const uint32_t sStat = sA + O_OFF_STAT;
    if (t < 3) {
        uint32_t dst;
        asm("mapa.shared::cluster.u32 %0, %1, %2;" : "=r"(dst) : "r"(sStat + ((cg * 3 + wg) * 64 + r) * 8), "r"(t));
        asm volatile("st.shared::cluster.v2.f32 [%0], {%1, %2};" ::"r"(dst), "f"(s0), "f"(q0) : "memory");
        asm volatile("st.shared::cluster.v2.f32 [%0], {%1, %2};" ::"r"(dst + 64), "f"(s1), "f"(q1) : "memory");
    }
    cluster_arrive();
    stage_tile<8>(xr, sA + wg * 8192, w, lane);
    proxy_fence();
    named_sync(2 + wg, 128);
    const bool leader = w == 0 && elect_one();
    if (leader) { tma_st_2d(&tmH, cg * 192 + wg * 64, m * 64, sA + wg * 8192); bulk_commit(); }
    cluster_wait();
    s0 = q0 = s1 = q1 = 0.f;
#pragma unroll
    for (int p = 0; p < 9; p++) {
        float a, b, c, d;
        asm volatile("ld.shared.v2.f32 {%0, %1}, [%2];" : "=f"(a), "=f"(b) : "r"(sStat + (p * 64 + r) * 8));
        asm volatile("ld.shared.v2.f32 {%0, %1}, [%2];" : "=f"(c), "=f"(d) : "r"(sStat + (p * 64 + r + 8) * 8));
        s0 += a; q0 += b; s1 += c; q1 += d;
    }
    const float m0 = s0 * (1.0f / DM), m1 = s1 * (1.0f / DM);
    const float rs0 = rsqrtf(fmaxf(q0 * (1.0f / DM) - m0 * m0, 0.f) + LN_EPS), rs1 = rsqrtf(fmaxf(q1 * (1.0f / DM) - m1 * m1, 0.f) + LN_EPS);
    const float sc0 = 0.5f * rs0, sc1 = 0.5f * rs1, n0 = -m0 * sc0, n1 = -m1 * sc1;
#pragma unroll
    for (int b = 0; b < 8; b++) {
        xr[2 * b] = pack_bf16(fmaf(bf_lo(xr[2 * b]), sc0, n0), fmaf(bf_hi(xr[2 * b]), sc0, n0));
        xr[2 * b + 1] = pack_bf16(fmaf(bf_lo(xr[2 * b + 1]), sc1, n1), fmaf(bf_hi(xr[2 * b + 1]), sc1, n1));
    }
    stage_tile<8>(xr, sA + (3 + wg) * 8192, w, lane);
    proxy_fence();
    named_sync(2 + wg, 128);
    if (leader) {
        tma_st_2d(&tmX2, cg * 192 + wg * 64, m * 64, sA + (3 + wg) * 8192);
        bulk_commit();
        bulk_wait_all();
    }
}

constexpr int F_THREADS = 384;
constexpr int F_NST = 6;
constexpr int F_STAGE = 96 * 128;
constexpr int F_X_BYTES = 9 * 16384;
constexpr int F_OFF_ST = F_X_BYTES;
constexpr int F_OFF_BAR = F_OFF_ST + F_NST * F_STAGE;
constexpr int F_SMEM = F_OFF_BAR + 256;

__device__ __forceinline__ float tanh_hw(float x) { float y; asm("tanh.approx.f32 %0, %1;" : "=f"(y) : "f"(x)); return y; }
__host__ __device__ constexpr int piece_begin(int p) { return p == 0 ? 0 : 3 * p + 1; }
template <int P>
__device__ __forceinline__ void silu_s1(const float (&acc)[32], float (&tmp)[8]) {
#pragma unroll
    for (int i = 2 * piece_begin(P); i < 2 * piece_begin(P + 1); i++) tmp[i - 2 * piece_begin(P)] = tanh_hw(acc[i]);
}
template <int C, int P>
__device__ __forceinline__ void silu_s2(const float (&acc)[32], const float (&tmp)[8], uint32_t (&h1)[144]) {
#pragma unroll
    for (int i = piece_begin(P); i < piece_begin(P + 1); i++) {
        const int k = 2 * (i - piece_begin(P));
        h1[C * 16 + i] = pack_bf16(fmaf(acc[2 * i], tmp[k], acc[2 * i]), fmaf(acc[2 * i + 1], tmp[k + 1], acc[2 * i + 1]));
    }
}
template <int J>
__device__ __forceinline__ void silu_slot_last(const float (&prev)[32], float (&tmp)[2][8], uint32_t (&h1)[144]) {
    if constexpr (J >= 1 && J <= 4) {
#pragma unroll
        for (int i = 0; i < 4; i++) {
            const int q = 4 * (J - 1) + i;
            h1[128 + q] = pack_bf16(fmaf(prev[2 * q], tmp[(J - 1) & 1][2 * i], prev[2 * q]), fmaf(prev[2 * q + 1], tmp[(J - 1) & 1][2 * i + 1], prev[2 * q + 1]));
        }
    }
    if constexpr (J <= 3) {
#pragma unroll
        for (int i = 0; i < 8; i++) tmp[J & 1][i] = tanh_hw(prev[8 * J + i]);
        pin(tmp[J & 1]);
    }
}
template <int C, int J>
__device__ __forceinline__ void silu_slot(const float (&prev)[32], float (&tmp)[2][8], uint32_t (&h1)[144]) {
    if constexpr (J >= 1) silu_s2<C, J - 1>(prev, tmp[(J - 1) & 1], h1);
    if constexpr (J <= 4) { silu_s1<J>(prev, tmp[J & 1]); pin(tmp[J & 1]); }
}

struct FfnPipe {
    uint32_t full, empty;
    int lane;
    __device__ __forceinline__ void acquire(int s, uint32_t ph) const { mbar_wait(full + s * 8, ph); }
    __device__ __forceinline__ void release(int s) const { if (lane == 0) mbar_arrive(empty + s * 8); }
};

template <int C>
__device__ __forceinline__ void ffn_phase1_chunk(float (&cur)[32], float (&prev)[32], uint32_t (&h1)[144], const FfnPipe& pp, uint64_t dx, uint32_t fullX) {
    float tmp[2][8];
    const uint64_t dw = cdesc(F_OFF_ST, 8192, 1024, 1) + blockIdx.y * (C + 1);
    dx += blockIdx.y * C;
#pragma unroll
    for (int j = 0; j < 6; j++) {
        if (C == 0) { mbar_wait(fullX + ((6 * j) >> 2) * 8, 0); mbar_wait(fullX + ((6 * j + 5) >> 2) * 8, 0); }
        pp.acquire(j, C & 1);
        if (j == 0) pin(cur);
        wg_fence();
#pragma unroll
        for (int i = 0; i < 6; i++) {
            const int ks = 6 * j + i;
            wgmma_ss_n64<1>(cur, dx + ((ks >> 2) * 1024 + (ks & 3) * 2), dw + ((j * F_STAGE + i * 2048) >> 4), ks != 0);
        }
        wg_commit();
        if (C > 0 || j > 0) { wg_wait<1>(); pp.release((j + 5) % 6); }
        if (C > 0) {
            constexpr int CP = C > 0 ? C - 1 : 0;
            pin(prev);
            if (j == 0) silu_slot<CP, 0>(prev, tmp, h1);
            if (j == 1) silu_slot<CP, 1>(prev, tmp, h1);
            if (j == 2) silu_slot<CP, 2>(prev, tmp, h1);
            if (j == 3) silu_slot<CP, 3>(prev, tmp, h1);
            if (j == 4) silu_slot<CP, 4>(prev, tmp, h1);
            if (j == 5) silu_slot<CP, 5>(prev, tmp, h1);
        }
    }
}

__device__ __forceinline__ void ffn_stage_chunk(const float (&acc)[32], uint32_t stg, int w, int lane, bool resid, uint32_t fullH) {
    uint32_t pk[16];
    if (resid) {
        mbar_wait(fullH, 0);
        const int r = w * 16 + (lane & 7) + ((lane >> 3) & 1) * 8;
#pragma unroll
        for (int b = 0; b < 8; b += 2) {
            uint32_t h0, h1, h2, h3;
            asm volatile("ldmatrix.sync.aligned.m8n8.x4.shared.b16 {%0, %1, %2, %3}, [%4];" : "=r"(h0), "=r"(h1), "=r"(h2), "=r"(h3) : "r"(stg + r * 128 + (((b + (lane >> 4)) ^ (r & 7)) << 4)) : "memory");
            pk[2 * b] = pack_bf16(acc[4 * b] + bf_lo(h0), acc[4 * b + 1] + bf_hi(h0));
            pk[2 * b + 1] = pack_bf16(acc[4 * b + 2] + bf_lo(h1), acc[4 * b + 3] + bf_hi(h1));
            pk[2 * b + 2] = pack_bf16(acc[4 * b + 4] + bf_lo(h2), acc[4 * b + 5] + bf_hi(h2));
            pk[2 * b + 3] = pack_bf16(acc[4 * b + 6] + bf_lo(h3), acc[4 * b + 7] + bf_hi(h3));
        }
    } else {
#pragma unroll
        for (int i = 0; i < 16; i++) pk[i] = pack_bf16(acc[2 * i], acc[2 * i + 1]);
    }
    stage_tile<8>(pk, stg, w, lane);
}
__device__ __forceinline__ void ffn_reduce_chunk(const CUtensorMap* tmOut, uint32_t stg, int col, int row, int w, int wgid, bool leader) {
    proxy_fence();
    if (w != 0) {
        asm volatile("bar.arrive %0, 128;" ::"r"(2 + wgid) : "memory");
    } else {
        named_sync(2 + wgid, 128);
        if (leader) { tma_red_2d(tmOut, col, row, stg); bulk_commit(); }
    }
}

template <bool FIRST>
__device__ __forceinline__ void ffn_phase2_chunk(float (&cur)[32], float (&prev)[32], uint32_t (&h1)[144], const FfnPipe& pp, uint32_t ph, const CUtensorMap* tmOut, uint32_t stg_prev, int col_prev, int row, int w, int lane, int wgid, bool leader,
                                                 bool resid_prev, uint32_t fullH) {
    const uint64_t dw = cdesc(F_OFF_ST, 8192, 1024, 1) + blockIdx.y * col_prev;
    float tmp[2][8];
#pragma unroll
    for (int j = 0; j < 6; j++) {
        pp.acquire(j, ph);
        if (j == 0) pin(cur);
        if (FIRST && j == 5) pin(h1);
        wg_fence();
#pragma unroll
        for (int i = 0; i < 6; i++) {
            const int f = (6 * j + i) * 4;
            wgmma_rs_n64<1>(cur, h1[f], h1[f + 1], h1[f + 2], h1[f + 3], dw + ((j * F_STAGE + i * 2048) >> 4), (j | i) != 0);
        }
        wg_commit();
        wg_wait<1>();
        pp.release((j + 5) % 6);
        if (FIRST) {
            pin(prev);
            if (j == 0) silu_slot_last<0>(prev, tmp, h1);
            if (j == 1) silu_slot_last<1>(prev, tmp, h1);
            if (j == 2) silu_slot_last<2>(prev, tmp, h1);
            if (j == 3) silu_slot_last<3>(prev, tmp, h1);
            if (j == 4) silu_slot_last<4>(prev, tmp, h1);
        } else {
            if (j == 0) { pin(prev); ffn_stage_chunk(prev, stg_prev, w, lane, resid_prev, fullH); }
            if (j == 1) ffn_reduce_chunk(tmOut, stg_prev, col_prev, row, w, wgid, leader);
        }
    }
}

__global__ void __launch_bounds__(F_THREADS, 1)
k_ffn(const __grid_constant__ CUtensorMap tmH, const __grid_constant__ CUtensorMap tmW1, const __grid_constant__ CUtensorMap tmW2, const __grid_constant__ CUtensorMap tmOut,
      const __grid_constant__ CUtensorMap tmRes, const __nv_bfloat16* __restrict__ w2) {
    extern __shared__ __align__(1024) uint8_t smem[];
    const uint32_t sX = smem_u32(smem), sSt = sX + F_OFF_ST, bars = sX + F_OFF_BAR;
    const uint32_t full = bars, empty = bars + 64, fullX = bars + 128, fullH = bars + 208;
    const int tid = threadIdx.x, warp = __shfl_sync(~0u, tid >> 5, 0), lane = tid & 31;
#define FFN_MAP 1
    const int m = FFN_MAP == 0 ? (blockIdx.x & 15) : (FFN_MAP == 1 ? (blockIdx.x >> 3) : ((blockIdx.x >> 1) & 15));
    const int fs = FFN_MAP == 0 ? (blockIdx.x >> 4) : (FFN_MAP == 1 ? (blockIdx.x & 7) : ((blockIdx.x >> 5) * 2 + (blockIdx.x & 1)));
    check_smem_base(sX);
    if (tid == 0) {
        prefetch_map(&tmW1); prefetch_map(&tmH); prefetch_map(&tmW2); prefetch_map(&tmOut); prefetch_map(&tmRes);
        for (int i = 0; i < F_NST; i++) { mbar_init(full + i * 8, 1); mbar_init(empty + i * 8, 8); }
        for (int i = 0; i < 9; i++) mbar_init(fullX + i * 8, 1);
        mbar_init(fullH, 1); mbar_init(fullH + 8, 1);
        bar_init_fence();
        for (int kb = 0; kb < 9; kb++) mbar_expect(fullX + kb * 8, 16384);
    }
    __syncthreads();
    if (warp < 4) {
        asm volatile("setmaxnreg.dec.sync.aligned.u32 24;");
        if (warp == 1 && lane < 9) prefetch_l2(reinterpret_cast<const char*>(w2) + ((size_t)fs * 576 + m * 36 + lane * 4) * (DM * 2), 4 * DM * 2);
        if (warp == 0 && elect_one()) {
#pragma unroll 1
            for (int c = 0; c < 18; c++) {
                int col = c - 9 + fs;
                if (col >= 9) col -= 9;
#pragma unroll 1
                for (int j = 0; j < 6; j++) {
                    mbar_wait(empty + j * 8, (c & 1) ^ 1);
                    mbar_expect(full + j * 8, F_STAGE);
                    if (c < 9) tma_2d(sSt + j * F_STAGE, &tmW1, fs * 576 + c * 64, j * 96, full + j * 8);
                    else tma_2d(sSt + j * F_STAGE, &tmW2, col * 64, fs * 576 + j * 96, full + j * 8);
                }
            }
        }
    } else {
        asm volatile("setmaxnreg.inc.sync.aligned.u32 240;");
        const int wgid = (warp >> 2) - 1, w = warp & 3;
        pdl_wait();
        if (warp == 4 && elect_one()) {
            for (int kb = 0; kb < 9; kb++) tma_2d(sX + kb * 16384, &tmH, kb * 64, m * 128, fullX + kb * 8);
        }
        __syncwarp();
        FfnPipe pp{full, empty, lane};
        const uint64_t xlo = cdesc(0, 16, 1024, 1) + wgid * 512;
        uint32_t h1[144];
        float acc0[32], acc1[32];
        ffn_phase1_chunk<0>(acc0, acc1, h1, pp, xlo, fullX);
        ffn_phase1_chunk<1>(acc1, acc0, h1, pp, xlo, fullX);
        ffn_phase1_chunk<2>(acc0, acc1, h1, pp, xlo, fullX);
        ffn_phase1_chunk<3>(acc1, acc0, h1, pp, xlo, fullX);
        ffn_phase1_chunk<4>(acc0, acc1, h1, pp, xlo, fullX);
        ffn_phase1_chunk<5>(acc1, acc0, h1, pp, xlo, fullX);
        ffn_phase1_chunk<6>(acc0, acc1, h1, pp, xlo, fullX);
        ffn_phase1_chunk<7>(acc1, acc0, h1, pp, xlo, fullX);
        ffn_phase1_chunk<8>(acc0, acc1, h1, pp, xlo, fullX);
        const int row = m * 128 + wgid * 64;
        const uint32_t stg = sX + wgid * 8192;
        int c = fs, cprev = 0;
        const bool leader = w == 0 && elect_one();
        const uint32_t myH = fullH + wgid * 8;
        ffn_phase2_chunk<true>(acc1, acc0, h1, pp, 1, &tmOut, 0, 0, row, w, lane, wgid, leader, false, myH);
        if (leader) {
            const int c8 = fs == 0 ? 8 : fs - 1;
            mbar_expect(myH, fs == 0 ? 16384 : 8192);
            tma_2d(stg + 8 * 16384, &tmRes, c8 * 64, row, myH);
            if (fs == 0) tma_2d(stg + 7 * 16384, &tmRes, 7 * 64, row, myH);
        }
        cprev = c; if (++c == 9) c = 0;
#pragma unroll 1
        for (int j = 1; j < 9; j += 2) {
            ffn_phase2_chunk<false>(acc0, acc1, h1, pp, 0, &tmOut, stg + (j - 1) * 16384, cprev * 64, row, w, lane, wgid, leader, false, myH);
            cprev = c; if (++c == 9) c = 0;
            ffn_phase2_chunk<false>(acc1, acc0, h1, pp, 1, &tmOut, stg + j * 16384, cprev * 64, row, w, lane, wgid, leader, j == 7 && fs == 0, myH);
            cprev = c; if (++c == 9) c = 0;
        }
        wg_wait<0>();
        pin(acc1);
        ffn_stage_chunk(acc1, stg + 8 * 16384, w, lane, true, myH);
        ffn_reduce_chunk(&tmOut, stg + 8 * 16384, cprev * 64, row, w, wgid, leader);
        if (leader) bulk_wait_all();
    }
}

typedef CUresult (*EncodeFn)(CUtensorMap*, CUtensorMapDataType, cuuint32_t, void*, const cuuint64_t*, const cuuint64_t*, const cuuint32_t*, const cuuint32_t*,
                             CUtensorMapInterleave, CUtensorMapSwizzle, CUtensorMapL2promotion, CUtensorMapFloatOOBfill);

CUtensorMap make_map(EncodeFn enc, const void* base, int rows, int cols, int box_rows) {
    CUtensorMap tm;
    cuuint64_t dims[2] = {(cuuint64_t)cols, (cuuint64_t)rows};
    cuuint64_t strides[1] = {(cuuint64_t)cols * 2};
    cuuint32_t box[2] = {64, (cuuint32_t)box_rows};
    cuuint32_t es[2] = {1, 1};
    enc(&tm, CU_TENSOR_MAP_DATA_TYPE_BFLOAT16, 2, const_cast<void*>(base), dims, strides, box, es, CU_TENSOR_MAP_INTERLEAVE_NONE,
        CU_TENSOR_MAP_SWIZZLE_128B, CU_TENSOR_MAP_L2_PROMOTION_L2_256B, CU_TENSOR_MAP_FLOAT_OOB_FILL_NONE);
    return tm;
}

template <typename... KArgs, typename... Args>
void launch(void (*kern)(KArgs...), int grid, int block, int smem, bool pdl, Args... args) {
    cudaLaunchConfig_t cfg = {};
    cfg.gridDim = dim3(grid); cfg.blockDim = dim3(block); cfg.dynamicSmemBytes = smem; cfg.stream = cudaStreamPerThread;
    cudaLaunchAttribute at[1];
    at[0].id = cudaLaunchAttributeProgrammaticStreamSerialization;
    at[0].val.programmaticStreamSerializationAllowed = 1;
    cfg.attrs = at; cfg.numAttrs = pdl ? 1 : 0;
    cudaLaunchKernelEx(&cfg, kern, KArgs(args)...);
}

}

#define USE_PDL 1

extern "C" void kernel_launch(void* const* d_in, const int* in_sizes, int n_in, void* d_out, int out_size) {
    const __nv_bfloat16* x = (const __nv_bfloat16*)d_in[0];
    const __nv_bfloat16* wq = (const __nv_bfloat16*)d_in[1];
    const __nv_bfloat16* wk = (const __nv_bfloat16*)d_in[2];
    const __nv_bfloat16* wv = (const __nv_bfloat16*)d_in[3];
    const __nv_bfloat16* wo = (const __nv_bfloat16*)d_in[4];
    const __nv_bfloat16* w1 = (const __nv_bfloat16*)d_in[6];
    const __nv_bfloat16* w2 = (const __nv_bfloat16*)d_in[7];
    __nv_bfloat16* out = (__nv_bfloat16*)d_out;

    static EncodeFn enc = nullptr;
    static void *p_o = nullptr, *p_h = nullptr, *p_q = nullptr, *p_res = nullptr;
    if (!enc) {
        cudaDriverEntryPointQueryResult qr;
        cudaGetDriverEntryPoint("cuTensorMapEncodeTiled", (void**)&enc, cudaEnableDefault, &qr);
        cudaGetSymbolAddress(&p_o, g_o);
        cudaGetSymbolAddress(&p_h, g_x2);
        cudaGetSymbolAddress(&p_res, g_h);
        cudaGetSymbolAddress(&p_q, g_q);
        cudaFuncSetAttribute(k_qkv, cudaFuncAttributeMaxDynamicSharedMemorySize, P_SMEM);
        cudaFuncSetAttribute(k_attn, cudaFuncAttributeMaxDynamicSharedMemorySize, A_SMEM);
        cudaFuncSetAttribute(k_oproj, cudaFuncAttributeMaxDynamicSharedMemorySize, O_SMEM);
        cudaFuncSetAttribute(k_ffn, cudaFuncAttributeMaxDynamicSharedMemorySize, F_SMEM);
    }
    const CUtensorMap tmWq = make_map(enc, wq, DM, DM, 64);
    const CUtensorMap tmWo = make_map(enc, wo, DM, DM, 64);
    const CUtensorMap tmO = make_map(enc, p_o, SEQ, DM, 64);
    const CUtensorMap tmH64 = make_map(enc, p_h, SEQ, DM, 64);
    const CUtensorMap tmH = make_map(enc, p_h, SEQ, DM, 128);
    const CUtensorMap tmRes = make_map(enc, p_res, SEQ, DM, 64);
    const CUtensorMap tmQ = make_map(enc, p_q, SEQ, DM, 64);
    const CUtensorMap tmW1 = make_map(enc, w1, DM, FF, 96);
    const CUtensorMap tmW2 = make_map(enc, w2, FF, DM, 96);
    const CUtensorMap tmOut = make_map(enc, out, SEQ, DM, 64);

    launch(k_qkv, 128, Q_THREADS, P_SMEM, false, tmWq, tmQ, x, wk, wv);
    launch(k_attn, 128, A_THREADS, A_SMEM, USE_PDL, out);
    launch(k_oproj, 96, O_THREADS, O_SMEM, USE_PDL, tmO, tmWo, tmH64, tmRes, x, w1);
    launch(k_ffn, 128, F_THREADS, F_SMEM, USE_PDL, tmH, tmW1, tmW2, tmOut, tmRes, w2);
}
```

```cpp
#include <cuda_runtime.h>
#include <cuda_bf16.h>
#include <cuda.h>
#include <stdint.h>

namespace {

constexpr int SEQ = 2048, DM = 576, FF = 4608;
constexpr int KV_BYTES = SEQ * 48;
constexpr float LN_EPS = 1e-5f;
constexpr float LOG2E = 1.4426950408889634f;
constexpr float Q_SCALE = 0.23570226039551584f * LOG2E;

#define POLY_MASK_V 0xB6DBu
constexpr uint32_t POLY_MASK = POLY_MASK_V;
#define FAST_BOUND_V 60.0f
constexpr float FAST_BOUND = FAST_BOUND_V;

__device__ __align__(1024) __nv_bfloat16 g_q[SEQ * DM];
__device__ __align__(1024) uint4 g_kc[KV_BYTES / 16];
__device__ __align__(1024) uint4 g_vc[KV_BYTES / 16];
__device__ __align__(16) float g_kmax[256];
__device__ __align__(1024) __nv_bfloat16 g_o[SEQ * DM];
__device__ __align__(1024) __nv_bfloat16 g_h[SEQ * DM];
__device__ __align__(1024) __nv_bfloat16 g_x2[SEQ * DM];

__device__ __forceinline__ uint32_t smem_u32(const void* p) { return (uint32_t)__cvta_generic_to_shared(p); }
__device__ __forceinline__ void wg_fence() { asm volatile("wgmma.fence.sync.aligned;" ::: "memory"); }
__device__ __forceinline__ void wg_commit() { asm volatile("wgmma.commit_group.sync.aligned;" ::: "memory"); }
template <int N> __device__ __forceinline__ void wg_wait() { asm volatile("wgmma.wait_group.sync.aligned %0;" ::"n"(N) : "memory"); }
template <int N> __device__ __forceinline__ void pin(float (&r)[N]) {
#pragma unroll
    for (int i = 0; i < N; i++) asm volatile("" : "+f"(r[i])::"memory");
}
template <int N> __device__ __forceinline__ void pin(uint32_t (&r)[N]) {
#pragma unroll
    for (int i = 0; i < N; i++) asm volatile("" : "+r"(r[i])::"memory");
}
constexpr uint32_t SMEM0 = 0x400;
__host__ __device__ constexpr uint64_t cdesc(uint32_t off, uint32_t lbo, uint32_t sbo, uint32_t swz) {
    return (uint64_t)(((SMEM0 + off) & 0x3FFFF) >> 4) | ((uint64_t)(lbo >> 4) << 16) | ((uint64_t)(sbo >> 4) << 32) | ((uint64_t)swz << 62);
}
__device__ __forceinline__ void check_smem_base(uint32_t base) { if ((base & 0x3FFFF) != SMEM0) __trap(); }

__device__ __forceinline__ void mbar_init(uint32_t bar, int cnt) { asm volatile("mbarrier.init.shared::cta.b64 [%0], %1;" ::"r"(bar), "r"(cnt) : "memory"); }
__device__ __forceinline__ void mbar_expect(uint32_t bar, int bytes) { asm volatile("mbarrier.arrive.expect_tx.shared::cta.b64 _, [%0], %1;" ::"r"(bar), "r"(bytes) : "memory"); }
__device__ __forceinline__ void mbar_arrive(uint32_t bar) { asm volatile("mbarrier.arrive.shared::cta.b64 _, [%0];" ::"r"(bar) : "memory"); }
__device__ __forceinline__ void mbar_wait(uint32_t bar, uint32_t parity) {
    asm volatile(
        "{\n.reg .pred p;\n.reg .u32 n;\nmov.u32 n, 0;\n"
        "LAB_WAIT:\n"
        "mbarrier.try_wait.parity.shared::cta.b64 p, [%0], %1;\n"
        "@p bra DONE;\n"
        "add.u32 n, n, 1;\n"
        "setp.lt.u32 p, n, 4000000;\n"
        "@p bra LAB_WAIT;\n"
        "trap;\n"
        "DONE:\n}\n" ::"r"(bar), "r"(parity) : "memory");
}
__device__ __forceinline__ void bar_init_fence() {
    asm volatile("fence.mbarrier_init.release.cluster;" ::: "memory");
    asm volatile("fence.proxy.async.shared::cta;" ::: "memory");
}
__device__ __forceinline__ void proxy_fence() { asm volatile("fence.proxy.async.shared::cta;" ::: "memory"); }
__device__ __forceinline__ void named_sync(int id, int n) { asm volatile("bar.sync %0, %1;" ::"r"(id), "r"(n) : "memory"); }
__device__ __forceinline__ void bulk_g2s(uint32_t dst, const void* src, int bytes, uint32_t bar) {
    asm volatile("cp.async.bulk.shared::cluster.global.mbarrier::complete_tx::bytes [%0], [%1], %2, [%3];" ::"r"(dst), "l"(src), "r"(bytes), "r"(bar) : "memory");
}
__device__ __forceinline__ void tma_2d(uint32_t dst, const CUtensorMap* tm, int c0, int c1, uint32_t bar) {
    asm volatile("cp.async.bulk.tensor.2d.shared::cluster.global.mbarrier::complete_tx::bytes [%0], [%1, {%3, %4}], [%2];" ::"r"(dst), "l"(tm), "r"(bar), "r"(c0), "r"(c1) : "memory");
}
__device__ __forceinline__ void cluster_arrive() { asm volatile("barrier.cluster.arrive.release.aligned;" ::: "memory"); }
__device__ __forceinline__ void cluster_wait() { asm volatile("barrier.cluster.wait.acquire.aligned;" ::: "memory"); }
__device__ __forceinline__ void tma_red_2d(const CUtensorMap* tm, int c0, int c1, uint32_t src) {
    asm volatile("cp.reduce.async.bulk.tensor.2d.global.shared::cta.add.tile.bulk_group [%0, {%2, %3}], [%1];" ::"l"(tm), "r"(src), "r"(c0), "r"(c1) : "memory");
}
__device__ __forceinline__ void tma_st_2d(const CUtensorMap* tm, int c0, int c1, uint32_t src) {
    asm volatile("cp.async.bulk.tensor.2d.global.shared::cta.tile.bulk_group [%0, {%2, %3}], [%1];" ::"l"(tm), "r"(src), "r"(c0), "r"(c1) : "memory");
}
__device__ __forceinline__ void bulk_commit() { asm volatile("cp.async.bulk.commit_group;" ::: "memory"); }
__device__ __forceinline__ void bulk_wait_all() { asm volatile("cp.async.bulk.wait_group.read 0;" ::: "memory"); }
__device__ __forceinline__ bool elect_one() {
    uint32_t p;
    asm volatile("{\n.reg .pred P;\nelect.sync _|P, 0xffffffff;\nselp.b32 %0, 1, 0, P;\n}\n" : "=r"(p));
    return p != 0;
}
__device__ __forceinline__ void prefetch_l2(const void* p, int bytes) { asm volatile("cp.async.bulk.prefetch.L2.global [%0], %1;" ::"l"(p), "r"(bytes) : "memory"); }
__device__ __forceinline__ void prefetch_map(const CUtensorMap* tm) { asm volatile("prefetch.tensormap [%0];" ::"l"(tm) : "memory"); }
__device__ __forceinline__ void pdl_launch() { asm volatile("griddepcontrol.launch_dependents;" ::: "memory"); }
__device__ __forceinline__ void pdl_wait() { asm volatile("griddepcontrol.wait;" ::: "memory"); }
__device__ __forceinline__ float ex2(float x) { float y; asm("ex2.approx.ftz.f32 %0, %1;" : "=f"(y) : "f"(x)); return y; }
__device__ __forceinline__ uint32_t pack_bf16(float lo, float hi) { uint32_t r; asm("cvt.rn.bf16x2.f32 %0, %1, %2;" : "=r"(r) : "f"(hi), "f"(lo)); return r; }
__device__ __forceinline__ float bf_lo(uint32_t v) { return __uint_as_float(v << 16); }
__device__ __forceinline__ float bf_hi(uint32_t v) { return __uint_as_float(v & 0xFFFF0000u); }
__device__ __forceinline__ uint32_t hfma2(uint32_t a, uint32_t b, uint32_t c) { uint32_t r; asm("fma.rn.f16x2 %0, %1, %2, %3;" : "=r"(r) : "r"(a), "r"(b), "r"(c)); return r; }
__device__ __forceinline__ void stmatrix_x4(uint32_t addr, uint32_t r0, uint32_t r1, uint32_t r2, uint32_t r3) {
    asm volatile("stmatrix.sync.aligned.m8n8.x4.shared.b16 [%0], {%1, %2, %3, %4};" ::"r"(addr), "r"(r0), "r"(r1), "r"(r2), "r"(r3) : "memory");
}

template <int TB> __device__ __forceinline__ void wgmma_ss_n24(float (&d)[12], uint64_t da, uint64_t db, int sc) {
    asm volatile("{\n.reg .pred p;\nsetp.ne.b32 p, %14, 0;\n"
        "wgmma.mma_async.sync.aligned.m64n24k16.f32.bf16.bf16 {%0, %1, %2, %3, %4, %5, %6, %7, %8, %9, %10, %11}, %12, %13, p, 1, 1, 0, %15;\n}\n"
        : "+f"(d[0]), "+f"(d[1]), "+f"(d[2]), "+f"(d[3]), "+f"(d[4]), "+f"(d[5]), "+f"(d[6]), "+f"(d[7]), "+f"(d[8]), "+f"(d[9]), "+f"(d[10]), "+f"(d[11])
        : "l"(da), "l"(db), "r"(sc), "n"(TB));
}
template <int TB> __device__ __forceinline__ void wgmma_ss_n64(float (&d)[32], uint64_t da, uint64_t db, int sc) {
    asm volatile("{\n.reg .pred p;\nsetp.ne.b32 p, %34, 0;\n"
        "wgmma.mma_async.sync.aligned.m64n64k16.f32.bf16.bf16 {%0, %1, %2, %3, %4, %5, %6, %7, %8, %9, %10, %11, %12, %13, %14, %15, %16, %17, %18, %19, %20, %21, %22, %23, %24, %25, %26, %27, %28, %29, %30, %31}, %32, %33, p, 1, 1, 0, %35;\n}\n"
        : "+f"(d[0]), "+f"(d[1]), "+f"(d[2]), "+f"(d[3]), "+f"(d[4]), "+f"(d[5]), "+f"(d[6]), "+f"(d[7]), "+f"(d[8]), "+f"(d[9]), "+f"(d[10]), "+f"(d[11]), "+f"(d[12]), "+f"(d[13]), "+f"(d[14]), "+f"(d[15]), "+f"(d[16]), "+f"(d[17]), "+f"(d[18]), "+f"(d[19]), "+f"(d[20]), "+f"(d[21]), "+f"(d[22]), "+f"(d[23]), "+f"(d[24]), "+f"(d[25]), "+f"(d[26]), "+f"(d[27]), "+f"(d[28]), "+f"(d[29]), "+f"(d[30]), "+f"(d[31])
        : "l"(da), "l"(db), "r"(sc), "n"(TB));
}
template <int TB> __device__ __forceinline__ void wgmma_ss_n128(float (&d)[64], uint64_t da, uint64_t db, int sc) {
    asm volatile("{\n.reg .pred p;\nsetp.ne.b32 p, %66, 0;\n"
        "wgmma.mma_async.sync.aligned.m64n128k16.f32.bf16.bf16 {%0, %1, %2, %3, %4, %5, %6, %7, %8, %9, %10, %11, %12, %13, %14, %15, %16, %17, %18, %19, %20, %21, %22, %23, %24, %25, %26, %27, %28, %29, %30, %31, %32, %33, %34, %35, %36, %37, %38, %39, %40, %41, %42, %43, %44, %45, %46, %47, %48, %49, %50, %51, %52, %53, %54, %55, %56, %57, %58, %59, %60, %61, %62, %63}, %64, %65, p, 1, 1, 0, %67;\n}\n"
        : "+f"(d[0]), "+f"(d[1]), "+f"(d[2]), "+f"(d[3]), "+f"(d[4]), "+f"(d[5]), "+f"(d[6]), "+f"(d[7]), "+f"(d[8]), "+f"(d[9]), "+f"(d[10]), "+f"(d[11]), "+f"(d[12]), "+f"(d[13]), "+f"(d[14]), "+f"(d[15]), "+f"(d[16]), "+f"(d[17]), "+f"(d[18]), "+f"(d[19]), "+f"(d[20]), "+f"(d[21]), "+f"(d[22]), "+f"(d[23]), "+f"(d[24]), "+f"(d[25]), "+f"(d[26]), "+f"(d[27]), "+f"(d[28]), "+f"(d[29]), "+f"(d[30]), "+f"(d[31]), "+f"(d[32]), "+f"(d[33]), "+f"(d[34]), "+f"(d[35]), "+f"(d[36]), "+f"(d[37]), "+f"(d[38]), "+f"(d[39]), "+f"(d[40]), "+f"(d[41]), "+f"(d[42]), "+f"(d[43]), "+f"(d[44]), "+f"(d[45]), "+f"(d[46]), "+f"(d[47]), "+f"(d[48]), "+f"(d[49]), "+f"(d[50]), "+f"(d[51]), "+f"(d[52]), "+f"(d[53]), "+f"(d[54]), "+f"(d[55]), "+f"(d[56]), "+f"(d[57]), "+f"(d[58]), "+f"(d[59]), "+f"(d[60]), "+f"(d[61]), "+f"(d[62]), "+f"(d[63])
        : "l"(da), "l"(db), "r"(sc), "n"(TB));
}
template <int TB> __device__ __forceinline__ void wgmma_rs_n24(float (&d)[12], uint32_t a0, uint32_t a1, uint32_t a2, uint32_t a3, uint64_t db, int sc) {
    asm volatile("{\n.reg .pred p;\nsetp.ne.b32 p, %17, 0;\n"
        "wgmma.mma_async.sync.aligned.m64n24k16.f32.bf16.bf16 {%0, %1, %2, %3, %4, %5, %6, %7, %8, %9, %10, %11}, {%12, %13, %14, %15}, %16, p, 1, 1, %18;\n}\n"
        : "+f"(d[0]), "+f"(d[1]), "+f"(d[2]), "+f"(d[3]), "+f"(d[4]), "+f"(d[5]), "+f"(d[6]), "+f"(d[7]), "+f"(d[8]), "+f"(d[9]), "+f"(d[10]), "+f"(d[11])
        : "r"(a0), "r"(a1), "r"(a2), "r"(a3), "l"(db), "r"(sc), "n"(TB));
}
template <int TB> __device__ __forceinline__ void wgmma_rs_n64(float (&d)[32], uint32_t a0, uint32_t a1, uint32_t a2, uint32_t a3, uint64_t db, int sc) {
    asm volatile("{\n.reg .pred p;\nsetp.ne.b32 p, %37, 0;\n"
        "wgmma.mma_async.sync.aligned.m64n64k16.f32.bf16.bf16 {%0, %1, %2, %3, %4, %5, %6, %7, %8, %9, %10, %11, %12, %13, %14, %15, %16, %17, %18, %19, %20, %21, %22, %23, %24, %25, %26, %27, %28, %29, %30, %31}, {%32, %33, %34, %35}, %36, p, 1, 1, %38;\n}\n"
        : "+f"(d[0]), "+f"(d[1]), "+f"(d[2]), "+f"(d[3]), "+f"(d[4]), "+f"(d[5]), "+f"(d[6]), "+f"(d[7]), "+f"(d[8]), "+f"(d[9]), "+f"(d[10]), "+f"(d[11]), "+f"(d[12]), "+f"(d[13]), "+f"(d[14]), "+f"(d[15]), "+f"(d[16]), "+f"(d[17]), "+f"(d[18]), "+f"(d[19]), "+f"(d[20]), "+f"(d[21]), "+f"(d[22]), "+f"(d[23]), "+f"(d[24]), "+f"(d[25]), "+f"(d[26]), "+f"(d[27]), "+f"(d[28]), "+f"(d[29]), "+f"(d[30]), "+f"(d[31])
        : "r"(a0), "r"(a1), "r"(a2), "r"(a3), "l"(db), "r"(sc), "n"(TB));
}
template <int TB> __device__ __forceinline__ void wgmma_rs_n128(float (&d)[64], uint32_t a0, uint32_t a1, uint32_t a2, uint32_t a3, uint64_t db, int sc) {
    asm volatile("{\n.reg .pred p;\nsetp.ne.b32 p, %69, 0;\n"
        "wgmma.mma_async.sync.aligned.m64n128k16.f32.bf16.bf16 {%0, %1, %2, %3, %4, %5, %6, %7, %8, %9, %10, %11, %12, %13, %14, %15, %16, %17, %18, %19, %20, %21, %22, %23, %24, %25, %26, %27, %28, %29, %30, %31, %32, %33, %34, %35, %36, %37, %38, %39, %40, %41, %42, %43, %44, %45, %46, %47, %48, %49, %50, %51, %52, %53, %54, %55, %56, %57, %58, %59, %60, %61, %62, %63}, {%64, %65, %66, %67}, %68, p, 1, 1, %70;\n}\n"
        : "+f"(d[0]), "+f"(d[1]), "+f"(d[2]), "+f"(d[3]), "+f"(d[4]), "+f"(d[5]), "+f"(d[6]), "+f"(d[7]), "+f"(d[8]), "+f"(d[9]), "+f"(d[10]), "+f"(d[11]), "+f"(d[12]), "+f"(d[13]), "+f"(d[14]), "+f"(d[15]), "+f"(d[16]), "+f"(d[17]), "+f"(d[18]), "+f"(d[19]), "+f"(d[20]), "+f"(d[21]), "+f"(d[22]), "+f"(d[23]), "+f"(d[24]), "+f"(d[25]), "+f"(d[26]), "+f"(d[27]), "+f"(d[28]), "+f"(d[29]), "+f"(d[30]), "+f"(d[31]), "+f"(d[32]), "+f"(d[33]), "+f"(d[34]), "+f"(d[35]), "+f"(d[36]), "+f"(d[37]), "+f"(d[38]), "+f"(d[39]), "+f"(d[40]), "+f"(d[41]), "+f"(d[42]), "+f"(d[43]), "+f"(d[44]), "+f"(d[45]), "+f"(d[46]), "+f"(d[47]), "+f"(d[48]), "+f"(d[49]), "+f"(d[50]), "+f"(d[51]), "+f"(d[52]), "+f"(d[53]), "+f"(d[54]), "+f"(d[55]), "+f"(d[56]), "+f"(d[57]), "+f"(d[58]), "+f"(d[59]), "+f"(d[60]), "+f"(d[61]), "+f"(d[62]), "+f"(d[63])
        : "r"(a0), "r"(a1), "r"(a2), "r"(a3), "l"(db), "r"(sc), "n"(TB));
}

constexpr int P_NST = 6;
constexpr int P_A_BYTES = 9 * 8192;
constexpr int P_B_STAGE = 3 * 8192;
constexpr int P_SMEM = P_A_BYTES + P_NST * P_B_STAGE + 256 + 320;

template <int NB>
__device__ __forceinline__ void stage_tile(const uint32_t (&pk)[NB * 2], uint32_t base, int w, int lane) {
    const int r = w * 16 + (lane & 7) + ((lane >> 3) & 1) * 8;
#pragma unroll
    for (int b = 0; b < NB; b += 2) {
        const uint32_t a = base + (b >> 3) * 8192 + r * 128 + ((((b & 7) + (lane >> 4)) ^ (r & 7)) << 4);
        stmatrix_x4(a, pk[2 * b], pk[2 * b + 1], pk[2 * b + 2], pk[2 * b + 3]);
    }
}

__device__ __forceinline__ uint32_t hsub2_bf16(uint32_t a, uint32_t b) { uint32_t r; asm("sub.rn.bf16x2 %0, %1, %2;" : "=r"(r) : "r"(a), "r"(b)); return r; }

constexpr int KV_RAW = DM * 18 * 2;
constexpr int Q_THREADS = 416;

__device__ __forceinline__ void proj_mma(float (&acc)[32], int wg, uint32_t fullB, uint32_t emptyB, uint32_t fullA, bool wait_a, int lane) {
    const uint64_t dA = cdesc(0, 16, 1024, 1), dB = cdesc(P_A_BYTES, 8192, 1024, 1) + wg * 512;
#pragma unroll 1
    for (int kb = 0; kb < 9; kb++) {
        const int s = kb >= P_NST ? kb - P_NST : kb;
        if (wait_a) mbar_wait(fullA + kb * 8, 0);
        mbar_wait(fullB + s * 8, kb >= P_NST ? 1 : 0);
        wg_fence();
#pragma unroll
        for (int ks = 0; ks < 4; ks++) wgmma_ss_n64<1>(acc, dA + (kb * 512 + ks * 2), dB + (s * (P_B_STAGE >> 4) + ks * 128), (kb | ks) != 0);
        wg_commit();
        if (kb < 4) {
            wg_wait<1>();
            if (kb >= 1 && lane == 0) mbar_arrive(emptyB + (kb - 1) * 8);
        }
    }
    wg_wait<0>();
    pin(acc);
}

__global__ void __launch_bounds__(Q_THREADS, 1)
k_qkv(const __grid_constant__ CUtensorMap tmWq, const __grid_constant__ CUtensorMap tmQ, const __nv_bfloat16* __restrict__ x, const __nv_bfloat16* __restrict__ wk, const __nv_bfloat16* __restrict__ wv) {
    extern __shared__ __align__(1024) uint8_t smem[];
    const uint32_t sA = smem_u32(smem), sB = sA + P_A_BYTES, bars = sB + P_NST * P_B_STAGE;
    const uint32_t fullB = bars, emptyB = bars + 64, fullX = bars + 128, fullW = bars + 136;
    float* s_rstd = reinterpret_cast<float*>(smem + P_A_BYTES + P_NST * P_B_STAGE + 256);
    const int tid = threadIdx.x, warp = __shfl_sync(~0u, tid >> 5, 0), lane = tid & 31;
    const bool isQ = blockIdx.x < 96;
    const int m = isQ ? blockIdx.x / 3 : blockIdx.x - 96, cg = blockIdx.x % 3;
    if (warp == 12) {
        if (elect_one()) {
            mbar_init(fullX, 1);
            bar_init_fence();
            mbar_expect(fullX, P_A_BYTES);
            bulk_g2s(sA, x + (size_t)m * 64 * DM, P_A_BYTES, fullX);
            prefetch_map(&tmWq); prefetch_map(&tmQ);
            for (int i = 0; i < P_NST; i++) { mbar_init(fullB + i * 8, 1); mbar_init(emptyB + i * 8, 12); }
            mbar_init(fullW, 1);
            bar_init_fence();
            if (isQ) {
                for (int kb = 0; kb < P_NST; kb++) {
                    mbar_expect(fullB + kb * 8, P_B_STAGE);
                    for (int a = 0; a < 3; a++) tma_2d(sB + kb * P_B_STAGE + a * 8192, &tmWq, cg * 192 + a * 64, kb * 64, fullB + kb * 8);
                }
            } else {
                mbar_expect(fullW, 2 * KV_RAW);
                bulk_g2s(sB + 3 * P_B_STAGE, wk, KV_RAW, fullW);
                bulk_g2s(sB + 3 * P_B_STAGE + KV_RAW, wv, KV_RAW, fullW);
            }
        }
        __syncwarp();
    }
    check_smem_base(sA);
    __syncthreads();
    pdl_launch();
    if (warp == 12) {
        if (isQ && elect_one()) {
            for (int kb = P_NST; kb < 9; kb++) {
                const int s = kb - P_NST;
                mbar_wait(emptyB + s * 8, 0);
                mbar_expect(fullB + s * 8, P_B_STAGE);
                for (int a = 0; a < 3; a++) tma_2d(sB + s * P_B_STAGE + a * 8192, &tmWq, cg * 192 + a * 64, kb * 64, fullB + s * 8);
            }
        }
        return;
    }
    if (warp < 8) {
        const int row = tid >> 2, q = tid & 3, h0 = (row & 1) * 4;
        mbar_wait(fullX, 0);
        uint4 v[18];
        const uint32_t ra = sA + row * 1152 + (q + h0) * 16, rb = sA + row * 1152 + (q + 4 - h0) * 16;
#pragma unroll
        for (int kb = 0; kb < 9; kb++) {
            asm volatile("ld.shared.v4.b32 {%0, %1, %2, %3}, [%4];" : "=r"(v[2 * kb].x), "=r"(v[2 * kb].y), "=r"(v[2 * kb].z), "=r"(v[2 * kb].w) : "r"(ra + kb * 128));
            asm volatile("ld.shared.v4.b32 {%0, %1, %2, %3}, [%4];" : "=r"(v[2 * kb + 1].x), "=r"(v[2 * kb + 1].y), "=r"(v[2 * kb + 1].z), "=r"(v[2 * kb + 1].w) : "r"(rb + kb * 128));
        }
        float sum = 0.f, sum2 = 0.f, sq = 0.f, sq2 = 0.f;
#pragma unroll
        for (int i = 0; i < 18; i++) {
            const uint32_t w[4] = {v[i].x, v[i].y, v[i].z, v[i].w};
#pragma unroll
            for (int j = 0; j < 4; j++) { const float a = bf_lo(w[j]), b = bf_hi(w[j]); sum += a; sum2 += b; sq = fmaf(a, a, sq); sq2 = fmaf(b, b, sq2); }
        }
        named_sync(1, 256);
        sum += sum2; sq += sq2;
        sum += __shfl_xor_sync(~0u, sum, 1); sum += __shfl_xor_sync(~0u, sum, 2);
        sq += __shfl_xor_sync(~0u, sq, 1); sq += __shfl_xor_sync(~0u, sq, 2);
        const float mean = sum * (1.0f / DM);
        if (q == 0) s_rstd[row] = rsqrtf(fmaxf(sq * (1.0f / DM) - mean * mean, 0.f) + LN_EPS);
        const uint32_t mhi = pack_bf16(mean, mean);
        const float rem = mean - bf_lo(mhi);
        const uint32_t mlo = pack_bf16(rem, rem);
        const uint32_t wa = sA + row * 128 + (((q + h0) ^ (row & 7)) << 4), wb = sA + row * 128 + (((q + 4 - h0) ^ (row & 7)) << 4);
#pragma unroll
        for (int i = 0; i < 18; i++) {
            const uint32_t o0 = hsub2_bf16(hsub2_bf16(v[i].x, mhi), mlo), o1 = hsub2_bf16(hsub2_bf16(v[i].y, mhi), mlo);
            const uint32_t o2 = hsub2_bf16(hsub2_bf16(v[i].z, mhi), mlo), o3 = hsub2_bf16(hsub2_bf16(v[i].w, mhi), mlo);
            asm volatile("st.shared.v4.b32 [%0], {%1, %2, %3, %4};" ::"r"(((i & 1) ? wb : wa) + (i >> 1) * 8192), "r"(o0), "r"(o1), "r"(o2), "r"(o3) : "memory");
        }
    } else if (!isQ) {
        mbar_wait(fullW, 0);
        const uint32_t* raw = reinterpret_cast<const uint32_t*>(smem + P_A_BYTES + 3 * P_B_STAGE);
#pragma unroll 3
        for (int r = tid - 256; r < 2 * DM; r += 128) {
            uint32_t wr[9];
#pragma unroll
            for (int i = 0; i < 9; i++) wr[i] = raw[r * 9 + i];
            const int sel = r >= DM, k = r - sel * DM;
            uint8_t* dst = smem + P_A_BYTES + sel * 3 * 9216 + (k >> 3) * 128 + (k & 7) * 16;
            *reinterpret_cast<uint4*>(dst) = make_uint4(wr[0], wr[1], wr[2], wr[3]);
            *reinterpret_cast<uint4*>(dst + 9216) = make_uint4(wr[4], wr[5], wr[6], wr[7]);
            *reinterpret_cast<uint32_t*>(dst + 2 * 9216) = wr[8];
        }
    }
    proxy_fence();
    named_sync(2, 384);
    const int wg = warp >> 2, w = warp & 3, g = lane >> 2, t = lane & 3;
    const float rs0 = s_rstd[w * 16 + g], rs1 = s_rstd[w * 16 + g + 8];
    if (isQ) {
        const float c0 = rs0 * Q_SCALE, c1 = rs1 * Q_SCALE;
        float acc[32];
        proj_mma(acc, wg, fullB, emptyB, 0, false, lane);
        uint32_t pk[16];
#pragma unroll
        for (int i = 0; i < 8; i++) { pk[2 * i] = pack_bf16(acc[4 * i] * c0, acc[4 * i + 1] * c0); pk[2 * i + 1] = pack_bf16(acc[4 * i + 2] * c1, acc[4 * i + 3] * c1); }
        named_sync(2, 384);
        stage_tile<8>(pk, sA + wg * 8192, w, lane);
        proxy_fence();
        named_sync(3 + wg, 128);
        if (w == 0 && elect_one()) {
            tma_st_2d(&tmQ, cg * 192 + wg * 64, m * 64, sA + wg * 8192);
            bulk_commit();
            bulk_wait_all();
        }
    } else if (wg < 2) {
        float acc[12];
        const uint64_t dA = cdesc(0, 16, 1024, 1), dB = cdesc(P_A_BYTES, 128, 9216, 0) + wg * (3 * 9216 >> 4);
#pragma unroll
        for (int i = 0; i < 12; i++) acc[i] = 0.f;
        pin(acc);
        wg_fence();
#pragma unroll 1
        for (int kb = 0; kb < 9; kb++) {
#pragma unroll
            for (int ks = 0; ks < 4; ks++) wgmma_ss_n24<1>(acc, dA + (kb * 512 + ks * 2), dB + (kb * 4 + ks) * 16, 1);
        }
        wg_commit();
        wg_wait<0>();
        pin(acc);
        uint32_t pk[6];
#pragma unroll
        for (int b = 0; b < 3; b++) { pk[2 * b] = pack_bf16(acc[4 * b] * rs0, acc[4 * b + 1] * rs0); pk[2 * b + 1] = pack_bf16(acc[4 * b + 2] * rs1, acc[4 * b + 3] * rs1); }
        float n0 = 0.f, n1 = 0.f, vm = 0.f;
#pragma unroll
        for (int b = 0; b < 3; b++) {
            if (b < 2 || t == 0) {
                const float a = bf_lo(pk[2 * b]), c = bf_hi(pk[2 * b]), d = bf_lo(pk[2 * b + 1]), e = bf_hi(pk[2 * b + 1]);
                n0 = fmaf(a, a, fmaf(c, c, n0)); n1 = fmaf(d, d, fmaf(e, e, n1));
            }
        }
        n0 += __shfl_xor_sync(~0u, n0, 1); n0 += __shfl_xor_sync(~0u, n0, 2);
        n1 += __shfl_xor_sync(~0u, n1, 1); n1 += __shfl_xor_sync(~0u, n1, 2);
        vm = fmaxf(n0, n1);
        if (!(n0 == n0) || !(n1 == n1)) vm = __int_as_float(0x7F800000);
#pragma unroll
        for (int o = 4; o < 32; o <<= 1) vm = fmaxf(vm, __shfl_xor_sync(~0u, vm, o));
        if (t != 0) {
            uint32_t lo, hi;
            if (wg == 0) {
                const int grp = m * 8 + w * 2;
                const uint32_t c = t == 1 ? 0x42FE3F80u   : (t == 2 ? 0x00003BC0u   : 0u);
                lo = ((POLY_MASK >> (grp & 15)) & 1) ? c : 0u;
                hi = ((POLY_MASK >> ((grp + 1) & 15)) & 1) ? c : 0u;
            } else {
                lo = hi = t == 1 ? 0x00003F80u : 0u;
            }
            pk[4] = lo; pk[5] = hi;
        }
        uint32_t* dst = reinterpret_cast<uint32_t*>(wg == 0 ? g_kc : g_vc) + (m * 8 + w * 2) * 96 + g * 4 + t;
#pragma unroll
        for (int b = 0; b < 3; b++) { dst[b * 32] = pk[2 * b]; dst[96 + b * 32] = pk[2 * b + 1]; }
        if (lane == 0) g_kmax[m * 8 + warp] = (wg == 0) ? vm : (vm <= 1e24f ? 0.f : __int_as_float(0x7F800000));
    }
}

constexpr int A_THREADS = 512;
constexpr int A_NPIECE = 8;
constexpr int A_OFF_Q = 2 * KV_BYTES;
constexpr int A_OFF_BAR = A_OFF_Q + 8 * 4096;
constexpr int A_SMEM = A_OFF_BAR + 128;

__device__ __forceinline__ uint32_t exp2_pair_fixed(float lo, float hi, uint32_t dep) {
    const uint32_t G = __byte_perm(__float_as_uint(lo), __float_as_uint(hi), 0x5410);
    uint32_t Hh;
    asm("lop3.b32 %0, %1, 0x007F007F, %2, 0xC0;" : "=r"(Hh) : "r"(G), "r"(dep));
    const uint32_t tt = hfma2(Hh, 0xF96BF96Bu, 0x358C358Cu);
    return G - hfma2(tt, Hh, 0u);
}

__global__ void __launch_bounds__(A_THREADS, 1)
k_attn(__nv_bfloat16* __restrict__ out) {
    extern __shared__ __align__(1024) uint8_t smem[];
    pdl_launch();
    const uint32_t sK = smem_u32(smem), sV = sK + KV_BYTES, bars = sK + A_OFF_BAR;
    const int tid = threadIdx.x;
    check_smem_base(sK);
    if (tid == 0) {
        for (int i = 0; i < A_NPIECE; i++) mbar_init(bars + i * 8, 1);
        bar_init_fence();
    }
    __syncthreads();
    pdl_wait();
    const int wg = __shfl_sync(~0u, tid >> 7, 0), w = (tid >> 5) & 3, lane = tid & 31, g = lane >> 2, t = lane & 3;
    const uint32_t* q32 = reinterpret_cast<const uint32_t*>(g_q);
    int row = (blockIdx.x * 8 + wg) * 64 + w * 16 + g;
    uint32_t nq[2][6];
#pragma unroll
    for (int r = 0; r < 2; r++) {
        const uint32_t* q = q32 + (row + r * 256) * 9;
        nq[r][0] = q[t]; nq[r][1] = q[72 + t]; nq[r][2] = q[4 + t]; nq[r][3] = q[76 + t]; nq[r][4] = q[8]; nq[r][5] = q[80];
    }
    constexpr int PB = KV_BYTES / A_NPIECE;
    const float4 km0 = reinterpret_cast<const float4*>(g_kmax)[lane], km1 = reinterpret_cast<const float4*>(g_kmax)[32 + lane];
    if (tid < 32 && elect_one()) {
        for (int i = 0; i < 2; i++) {
            mbar_expect(bars + i * 8, 2 * PB);
            bulk_g2s(sK + i * PB, reinterpret_cast<const char*>(g_kc) + i * PB, PB, bars + i * 8);
            bulk_g2s(sV + i * PB, reinterpret_cast<const char*>(g_vc) + i * PB, PB, bars + i * 8);
        }
    }
    float kmax2 = fmaxf(fmaxf(fmaxf(km0.x, km0.y), fmaxf(km0.z, km0.w)), fmaxf(fmaxf(km1.x, km1.y), fmaxf(km1.z, km1.w)));
#pragma unroll
    for (int o = 1; o < 32; o <<= 1) kmax2 = fmaxf(kmax2, __shfl_xor_sync(~0u, kmax2, o));
    if (tid < 32 && elect_one()) {
        for (int i = 2; i < A_NPIECE; i++) {
            mbar_expect(bars + i * 8, 2 * PB);
            bulk_g2s(sK + i * PB, reinterpret_cast<const char*>(g_kc) + i * PB, PB, bars + i * 8);
            bulk_g2s(sV + i * PB, reinterpret_cast<const char*>(g_vc) + i * PB, PB, bars + i * 8);
        }
    }
    uint32_t vote = 0;
#pragma unroll
    for (int r = 0; r < 2; r++) {
        const uint32_t (&q)[6] = nq[r];
        const float a0 = bf_lo(q[0]), a1 = bf_hi(q[0]), a2 = bf_lo(q[2]), a3 = bf_hi(q[2]);
        const float b0 = bf_lo(q[1]), b1 = bf_hi(q[1]), b2 = bf_lo(q[3]), b3 = bf_hi(q[3]);
        float n0 = a0 * a0 + a1 * a1 + a2 * a2 + a3 * a3, n1 = b0 * b0 + b1 * b1 + b2 * b2 + b3 * b3;
        if (t == 0) {
            const float c0 = bf_lo(q[4]), c1 = bf_hi(q[4]), d0 = bf_lo(q[5]), d1 = bf_hi(q[5]);
            n0 += c0 * c0 + c1 * c1; n1 += d0 * d0 + d1 * d1;
        }
        n0 += __shfl_xor_sync(~0u, n0, 1); n0 += __shfl_xor_sync(~0u, n0, 2);
        n1 += __shfl_xor_sync(~0u, n1, 1); n1 += __shfl_xor_sync(~0u, n1, 2);
        const bool unsafe = !(fmaxf(n0, n1) * kmax2 <= FAST_BOUND * FAST_BOUND) || !(n0 == n0) || !(n1 == n1);
        vote |= (__any_sync(~0u, unsafe) ? 1u : 0u) << r;
        const uint32_t cst = t == 1 ? 0x3F804780u : (t == 2 ? 0x00003F80u : 0u);
        const uint32_t sQ = sK + A_OFF_Q + (r * 4 + wg) * 4096 + (w * 2) * 512 + g * 16 + t * 4;
        asm volatile("st.shared.b32 [%0], %1;" ::"r"(sQ), "r"(q[0]) : "memory");
        asm volatile("st.shared.b32 [%0], %1;" ::"r"(sQ + 512), "r"(q[1]) : "memory");
        asm volatile("st.shared.b32 [%0], %1;" ::"r"(sQ + 128), "r"(q[2]) : "memory");
        asm volatile("st.shared.b32 [%0], %1;" ::"r"(sQ + 640), "r"(q[3]) : "memory");
        asm volatile("st.shared.b32 [%0], %1;" ::"r"(sQ + 256), "r"(t == 0 ? q[4] : cst) : "memory");
        asm volatile("st.shared.b32 [%0], %1;" ::"r"(sQ + 768), "r"(t == 0 ? q[5] : cst) : "memory");
        asm volatile("st.shared.b32 [%0], %1;" ::"r"(sQ + 384), "r"(0u) : "memory");
        asm volatile("st.shared.b32 [%0], %1;" ::"r"(sQ + 896), "r"(0u) : "memory");
    }
    const uint32_t sVote = bars + 64 + wg * 16;
    if (lane == 0) asm volatile("st.shared.b32 [%0], %1;" ::"r"(sVote + w * 4), "r"(vote) : "memory");
    proxy_fence();
    named_sync(wg + 1, 128);
    uint32_t unsafe_mask;
    {
        uint32_t v0, v1, v2, v3;
        asm volatile("ld.shared.v4.b32 {%0, %1, %2, %3}, [%4];" : "=r"(v0), "=r"(v1), "=r"(v2), "=r"(v3) : "r"(sVote));
        unsafe_mask = __shfl_sync(~0u, v0 | v1 | v2 | v3, 0);
    }
    if (unsafe_mask) {
#pragma unroll
        for (int r = 0; r < 2; r++) {
            if (((unsafe_mask >> r) & 1) && t != 0) {
                const uint32_t sQ = sK + A_OFF_Q + (r * 4 + wg) * 4096 + (w * 2) * 512 + g * 16 + t * 4;
                asm volatile("st.shared.b32 [%0], %1;" ::"r"(sQ + 256), "r"(0u) : "memory");
                asm volatile("st.shared.b32 [%0], %1;" ::"r"(sQ + 768), "r"(0u) : "memory");
            }
        }
        proxy_fence();
        named_sync(wg + 1, 128);
    }
#pragma unroll 1
    for (int rep = 0; rep < 2; rep++, row += 256) {
        if (rep == 1) {
            uint4* z = reinterpret_cast<uint4*>(out + (size_t)blockIdx.x * 16 * DM) + tid;
            z[0] = make_uint4(0u, 0u, 0u, 0u); z[A_THREADS] = make_uint4(0u, 0u, 0u, 0u);
            if (tid < 16 * DM * 2 / 16 - 2 * A_THREADS) z[2 * A_THREADS] = make_uint4(0u, 0u, 0u, 0u);
        }
        const uint32_t any_unsafe = (unsafe_mask >> rep) & 1;
        const uint64_t dQ0 = cdesc(A_OFF_Q, 128, 512, 0) + (rep * 4 + wg) * 256, dQ1 = dQ0 + 16;
        float o[12];
#pragma unroll
        for (int i = 0; i < 12; i++) o[i] = 0.f;
        pin(o);
        uint64_t dK0 = cdesc(0, 128, 384, 0), dK1 = cdesc(256, 0, 384, 0), dV = cdesc(KV_BYTES, 384, 128, 0);
        if (!any_unsafe) {
            float s[64];
#pragma unroll 1
            for (int j = 0; j < 16; j++) {
                if (rep == 0 && (j & 1) == 0) mbar_wait(bars + (j >> 1) * 8, 0);
                wg_fence();
                wgmma_ss_n128<0>(s, dQ0, dK0, 0);
                wgmma_ss_n128<0>(s, dQ1, dK1, 1);
                wg_commit();
                dK0 += 16 * 384 >> 4; dK1 += 16 * 384 >> 4;
                wg_wait<0>();
                pin(s);
                uint32_t p[32];
#define CHAIN 6
                {
                    constexpr int NP = 2 * __builtin_popcount(POLY_MASK), NM = 32 - NP;
                    float e[64];
#pragma unroll
                    for (int i = 0; i < 32; i++)
                        if (!((POLY_MASK >> (i >> 1)) & 1)) { e[2 * i] = ex2(s[2 * i]); e[2 * i + 1] = ex2(s[2 * i + 1]); p[i] = pack_bf16(e[2 * i], e[2 * i + 1]); }
                    int ip = 0;
#pragma unroll
                    for (int i = 0; i < 32; i++) {
                        if ((POLY_MASK >> (i >> 1)) & 1) {
                            const int mm = (ip * 2 * NM) / NP - CHAIN;
                            uint32_t dep = 0;
                            if (CHAIN > 0 && mm >= 0) {
                                int cnt = 0;
#pragma unroll
                                for (int q = 0; q < 32; q++)
                                    if (!((POLY_MASK >> (q >> 1)) & 1)) { if (cnt == (mm >> 1)) dep = __float_as_uint(e[2 * q + (mm & 1)]); cnt++; }
                            }
                            p[i] = exp2_pair_fixed(s[2 * i], s[2 * i + 1], dep);
                            ip++;
                        }
                    }
                }
                pin(p);
                wg_fence();
#pragma unroll
                for (int k = 0; k < 8; k++) {
                    wgmma_rs_n24<1>(o, p[4 * k], p[4 * k + 1], p[4 * k + 2], p[4 * k + 3], dV + k * 48, 1);
                }
                wg_commit();
                dV += 16 * 384 >> 4;
                wg_wait<0>();
            }
        } else {
            float s[64];
            float m0 = -INFINITY, m1 = -INFINITY;
#pragma unroll 1
            for (int j = 0; j < 16; j++) {
                if (rep == 0 && (j & 1) == 0) mbar_wait(bars + (j >> 1) * 8, 0);
                wg_fence();
                wgmma_ss_n128<0>(s, dQ0, dK0, 0);
                wgmma_ss_n128<0>(s, dQ1, dK1, 1);
                wg_commit();
                dK0 += 16 * 384 >> 4; dK1 += 16 * 384 >> 4;
                wg_wait<0>();
                pin(s);
                float x0m = m0, x1m = m1;
#pragma unroll
                for (int b = 0; b < 16; b++) { x0m = fmaxf(x0m, fmaxf(s[4 * b], s[4 * b + 1])); x1m = fmaxf(x1m, fmaxf(s[4 * b + 2], s[4 * b + 3])); }
                x0m = fmaxf(x0m, __shfl_xor_sync(~0u, x0m, 1)); x0m = fmaxf(x0m, __shfl_xor_sync(~0u, x0m, 2));
                x1m = fmaxf(x1m, __shfl_xor_sync(~0u, x1m, 1)); x1m = fmaxf(x1m, __shfl_xor_sync(~0u, x1m, 2));
                const float c0 = ex2(m0 - x0m), c1 = ex2(m1 - x1m);
                m0 = x0m; m1 = x1m;
#pragma unroll
                for (int b = 0; b < 3; b++) { o[4 * b] *= c0; o[4 * b + 1] *= c0; o[4 * b + 2] *= c1; o[4 * b + 3] *= c1; }
                uint32_t p[32];
#pragma unroll
                for (int b = 0; b < 16; b++) {
                    p[2 * b] = pack_bf16(ex2(s[4 * b] - m0), ex2(s[4 * b + 1] - m0));
                    p[2 * b + 1] = pack_bf16(ex2(s[4 * b + 2] - m1), ex2(s[4 * b + 3] - m1));
                }
                pin(p); pin(o);
                wg_fence();
#pragma unroll
                for (int k = 0; k < 8; k++) wgmma_rs_n24<1>(o, p[4 * k], p[4 * k + 1], p[4 * k + 2], p[4 * k + 3], dV + k * 48, 1);
                wg_commit();
                dV += 16 * 384 >> 4;
                wg_wait<0>();
            }
        }
        pin(o);
        const float l0 = __shfl_sync(~0u, o[8], (lane & ~3) | 1), l1 = __shfl_sync(~0u, o[10], (lane & ~3) | 1);
        const float i0 = 1.0f / l0, i1 = 1.0f / l1;
        uint32_t* o32 = reinterpret_cast<uint32_t*>(g_o);
        o32[row * 9 + t] = pack_bf16(o[0] * i0, o[1] * i0);
        o32[(row + 8) * 9 + t] = pack_bf16(o[2] * i1, o[3] * i1);
        o32[row * 9 + 4 + t] = pack_bf16(o[4] * i0, o[5] * i0);
        o32[(row + 8) * 9 + 4 + t] = pack_bf16(o[6] * i1, o[7] * i1);
        if (t == 0) { o32[row * 9 + 8] = pack_bf16(o[8] * i0, o[9] * i0); o32[(row + 8) * 9 + 8] = pack_bf16(o[10] * i1, o[11] * i1); }
    }
}

constexpr int O_THREADS = 416;
constexpr int O_OFF_STAT = P_A_BYTES + P_NST * P_B_STAGE + 256;
constexpr int O_SMEM = O_OFF_STAT + 9 * 64 * 8;

__global__ void __cluster_dims__(3, 1, 1) __launch_bounds__(O_THREADS, 1)
k_oproj(const __grid_constant__ CUtensorMap tmO, const __grid_constant__ CUtensorMap tmWo, const __grid_constant__ CUtensorMap tmX2, const __grid_constant__ CUtensorMap tmH, const __nv_bfloat16* __restrict__ x, const __nv_bfloat16* __restrict__ w1) {
    extern __shared__ __align__(1024) uint8_t smem[];
    const uint32_t sA = smem_u32(smem), sB = sA + P_A_BYTES, bars = sB + P_NST * P_B_STAGE;
    const uint32_t fullB = bars, emptyB = bars + 64, fullA = bars + 128;
    const int tid = threadIdx.x, warp = __shfl_sync(~0u, tid >> 5, 0), lane = tid & 31;
    const int m = blockIdx.x / 3, cg = blockIdx.x % 3;
    check_smem_base(sA);
    if (tid == 0) {
        prefetch_map(&tmO); prefetch_map(&tmWo); prefetch_map(&tmX2); prefetch_map(&tmH);
        for (int i = 0; i < P_NST; i++) { mbar_init(fullB + i * 8, 1); mbar_init(emptyB + i * 8, 12); }
        for (int i = 0; i < 9; i++) mbar_init(fullA + i * 8, 1);
        bar_init_fence();
        for (int kb = 0; kb < 9; kb++) mbar_expect(fullA + kb * 8, 8192);
    }
    __syncthreads();
    pdl_launch();
    if (warp == 12) {
        if (elect_one()) {
            for (int kb = 0; kb < 9; kb++) {
                const int s = kb >= P_NST ? kb - P_NST : kb;
                if (kb == 2) {
                    pdl_wait();
                    for (int ka = 0; ka < 9; ka++) tma_2d(sA + ka * 8192, &tmO, ka * 64, m * 64, fullA + ka * 8);
                }
                if (kb >= P_NST) mbar_wait(emptyB + s * 8, 0);
                mbar_expect(fullB + s * 8, P_B_STAGE);
                for (int a = 0; a < 3; a++) tma_2d(sB + s * P_B_STAGE + a * 8192, &tmWo, cg * 192 + a * 64, kb * 64, fullB + s * 8);
            }
            for (int i = 0; i < 6; i++) prefetch_l2(reinterpret_cast<const char*>(w1) + (size_t)blockIdx.x * (FF * DM * 2 / 96) + i * 9216, 9216);
        }
        return;
    }
    const int wg = warp >> 2, w = warp & 3, g = lane >> 2, t = lane & 3;
    uint32_t xr[16];
    {
        const uint32_t* x32 = reinterpret_cast<const uint32_t*>(x) + (((m * 64 + w * 16 + g) * DM + cg * 192 + wg * 64 + 2 * t) >> 1);
#pragma unroll
        for (int b = 0; b < 8; b++) { xr[2 * b] = __ldg(x32 + b * 4); xr[2 * b + 1] = __ldg(x32 + b * 4 + 4 * DM); }
    }
    float acc[32];
    proj_mma(acc, wg, fullB, emptyB, fullA, true, lane);
    named_sync(1, 384);
    float s0 = 0.f, q0 = 0.f, s1 = 0.f, q1 = 0.f;
#pragma unroll
    for (int b = 0; b < 8; b++) {
        const uint32_t xa = xr[2 * b], xb = xr[2 * b + 1];
        const uint32_t ha = pack_bf16(acc[4 * b] + bf_lo(xa), acc[4 * b + 1] + bf_hi(xa));
        const uint32_t hb = pack_bf16(acc[4 * b + 2] + bf_lo(xb), acc[4 * b + 3] + bf_hi(xb));
        xr[2 * b] = ha; xr[2 * b + 1] = hb;
        const float a = bf_lo(ha), c = bf_hi(ha), d = bf_lo(hb), e = bf_hi(hb);
        s0 += a + c; q0 = fmaf(a, a, fmaf(c, c, q0));
        s1 += d + e; q1 = fmaf(d, d, fmaf(e, e, q1));
    }
    s0 += __shfl_xor_sync(~0u, s0, 1); s0 += __shfl_xor_sync(~0u, s0, 2);
    q0 += __shfl_xor_sync(~0u, q0, 1); q0 += __shfl_xor_sync(~0u, q0, 2);
    s1 += __shfl_xor_sync(~0u, s1, 1); s1 += __shfl_xor_sync(~0u, s1, 2);
    q1 += __shfl_xor_sync(~0u, q1, 1); q1 += __shfl_xor_sync(~0u, q1, 2);
    const int r = w * 16 + g;
    const uint32_t sStat = sA + O_OFF_STAT;
    if (t < 3) {
        uint32_t dst;
        asm("mapa.shared::cluster.u32 %0, %1, %2;" : "=r"(dst) : "r"(sStat + ((cg * 3 + wg) * 64 + r) * 8), "r"(t));
        asm volatile("st.shared::cluster.v2.f32 [%0], {%1, %2};" ::"r"(dst), "f"(s0), "f"(q0) : "memory");
        asm volatile("st.shared::cluster.v2.f32 [%0], {%1, %2};" ::"r"(dst + 64), "f"(s1), "f"(q1) : "memory");
    }
    cluster_arrive();
    stage_tile<8>(xr, sA + wg * 8192, w, lane);
    proxy_fence();
    named_sync(2 + wg, 128);
    const bool leader = w == 0 && elect_one();
    if (leader) { tma_st_2d(&tmH, cg * 192 + wg * 64, m * 64, sA + wg * 8192); bulk_commit(); }
    cluster_wait();
    s0 = q0 = s1 = q1 = 0.f;
#pragma unroll
    for (int p = 0; p < 9; p++) {
        float a, b, c, d;
        asm volatile("ld.shared.v2.f32 {%0, %1}, [%2];" : "=f"(a), "=f"(b) : "r"(sStat + (p * 64 + r) * 8));
        asm volatile("ld.shared.v2.f32 {%0, %1}, [%2];" : "=f"(c), "=f"(d) : "r"(sStat + (p * 64 + r + 8) * 8));
        s0 += a; q0 += b; s1 += c; q1 += d;
    }
    const float m0 = s0 * (1.0f / DM), m1 = s1 * (1.0f / DM);
    const float rs0 = rsqrtf(fmaxf(q0 * (1.0f / DM) - m0 * m0, 0.f) + LN_EPS), rs1 = rsqrtf(fmaxf(q1 * (1.0f / DM) - m1 * m1, 0.f) + LN_EPS);
    const float sc0 = 0.5f * rs0, sc1 = 0.5f * rs1, n0 = -m0 * sc0, n1 = -m1 * sc1;
#pragma unroll
    for (int b = 0; b < 8; b++) {
        xr[2 * b] = pack_bf16(fmaf(bf_lo(xr[2 * b]), sc0, n0), fmaf(bf_hi(xr[2 * b]), sc0, n0));
        xr[2 * b + 1] = pack_bf16(fmaf(bf_lo(xr[2 * b + 1]), sc1, n1), fmaf(bf_hi(xr[2 * b + 1]), sc1, n1));
    }
    stage_tile<8>(xr, sA + (3 + wg) * 8192, w, lane);
    proxy_fence();
    named_sync(2 + wg, 128);
    if (leader) {
        tma_st_2d(&tmX2, cg * 192 + wg * 64, m * 64, sA + (3 + wg) * 8192);
        bulk_commit();
        bulk_wait_all();
    }
}

constexpr int F_THREADS = 384;
constexpr int F_NST = 6;
constexpr int F_STAGE = 96 * 128;
constexpr int F_X_BYTES = 9 * 16384;
constexpr int F_OFF_ST = F_X_BYTES;
constexpr int F_OFF_BAR = F_OFF_ST + F_NST * F_STAGE;
constexpr int F_SMEM = F_OFF_BAR + 256;

__device__ __forceinline__ float tanh_hw(float x) { float y; asm("tanh.approx.f32 %0, %1;" : "=f"(y) : "f"(x)); return y; }
__host__ __device__ constexpr int piece_begin(int p) { return p == 0 ? 0 : 3 * p + 1; }
template <int P>
__device__ __forceinline__ void silu_s1(const float (&acc)[32], float (&tmp)[8]) {
#pragma unroll
    for (int i = 2 * piece_begin(P); i < 2 * piece_begin(P + 1); i++) tmp[i - 2 * piece_begin(P)] = tanh_hw(acc[i]);
}
template <int C, int P>
__device__ __forceinline__ void silu_s2(const float (&acc)[32], const float (&tmp)[8], uint32_t (&h1)[144]) {
#pragma unroll
    for (int i = piece_begin(P); i < piece_begin(P + 1); i++) {
        const int k = 2 * (i - piece_begin(P));
        h1[C * 16 + i] = pack_bf16(fmaf(acc[2 * i], tmp[k], acc[2 * i]), fmaf(acc[2 * i + 1], tmp[k + 1], acc[2 * i + 1]));
    }
}
template <int J>
__device__ __forceinline__ void silu_slot_last(const float (&prev)[32], float (&tmp)[2][8], uint32_t (&h1)[144]) {
    if constexpr (J >= 1 && J <= 4) {
#pragma unroll
        for (int i = 0; i < 4; i++) {
            const int q = 4 * (J - 1) + i;
            h1[128 + q] = pack_bf16(fmaf(prev[2 * q], tmp[(J - 1) & 1][2 * i], prev[2 * q]), fmaf(prev[2 * q + 1], tmp[(J - 1) & 1][2 * i + 1], prev[2 * q + 1]));
        }
    }
    if constexpr (J <= 3) {
#pragma unroll
        for (int i = 0; i < 8; i++) tmp[J & 1][i] = tanh_hw(prev[8 * J + i]);
        pin(tmp[J & 1]);
    }
}
template <int C, int J>
__device__ __forceinline__ void silu_slot(const float (&prev)[32], float (&tmp)[2][8], uint32_t (&h1)[144]) {
    if constexpr (J >= 1) silu_s2<C, J - 1>(prev, tmp[(J - 1) & 1], h1);
    if constexpr (J <= 4) { silu_s1<J>(prev, tmp[J & 1]); pin(tmp[J & 1]); }
}

struct FfnPipe {
    uint32_t full, empty;
    int lane;
    __device__ __forceinline__ void acquire(int s, uint32_t ph) const { mbar_wait(full + s * 8, ph); }
    __device__ __forceinline__ void release(int s) const { if (lane == 0) mbar_arrive(empty + s * 8); }
};

template <int C>
__device__ __forceinline__ void ffn_phase1_chunk(float (&cur)[32], float (&prev)[32], uint32_t (&h1)[144], const FfnPipe& pp, uint64_t dx, uint32_t fullX) {
    float tmp[2][8];
    const uint64_t dw = cdesc(F_OFF_ST, 8192, 1024, 1) + blockIdx.y * (C + 1);
    dx += blockIdx.y * C;
#pragma unroll
    for (int j = 0; j < 6; j++) {
        if (C == 0) { mbar_wait(fullX + ((6 * j) >> 2) * 8, 0); mbar_wait(fullX + ((6 * j + 5) >> 2) * 8, 0); }
        pp.acquire(j, C & 1);
        if (j == 0) pin(cur);
        wg_fence();
#pragma unroll
        for (int i = 0; i < 6; i++) {
            const int ks = 6 * j + i;
            wgmma_ss_n64<1>(cur, dx + ((ks >> 2) * 1024 + (ks & 3) * 2), dw + ((j * F_STAGE + i * 2048) >> 4), ks != 0);
        }
        wg_commit();
        if (C > 0 || j > 0) { wg_wait<1>(); pp.release((j + 5) % 6); }
        if (C > 0) {
            constexpr int CP = C > 0 ? C - 1 : 0;
            pin(prev);
            if (j == 0) silu_slot<CP, 0>(prev, tmp, h1);
            if (j == 1) silu_slot<CP, 1>(prev, tmp, h1);
            if (j == 2) silu_slot<CP, 2>(prev, tmp, h1);
            if (j == 3) silu_slot<CP, 3>(prev, tmp, h1);
            if (j == 4) silu_slot<CP, 4>(prev, tmp, h1);
            if (j == 5) silu_slot<CP, 5>(prev, tmp, h1);
        }
    }
}

__device__ __forceinline__ void ffn_stage_chunk(const float (&acc)[32], uint32_t stg, int w, int lane, bool resid, uint32_t fullH) {
    uint32_t pk[16];
    if (resid) {
        mbar_wait(fullH, 0);
        const int r = w * 16 + (lane & 7) + ((lane >> 3) & 1) * 8;
#pragma unroll
        for (int b = 0; b < 8; b += 2) {
            uint32_t h0, h1, h2, h3;
            asm volatile("ldmatrix.sync.aligned.m8n8.x4.shared.b16 {%0, %1, %2, %3}, [%4];" : "=r"(h0), "=r"(h1), "=r"(h2), "=r"(h3) : "r"(stg + r * 128 + (((b + (lane >> 4)) ^ (r & 7)) << 4)) : "memory");
            pk[2 * b] = pack_bf16(acc[4 * b] + bf_lo(h0), acc[4 * b + 1] + bf_hi(h0));
            pk[2 * b + 1] = pack_bf16(acc[4 * b + 2] + bf_lo(h1), acc[4 * b + 3] + bf_hi(h1));
            pk[2 * b + 2] = pack_bf16(acc[4 * b + 4] + bf_lo(h2), acc[4 * b + 5] + bf_hi(h2));
            pk[2 * b + 3] = pack_bf16(acc[4 * b + 6] + bf_lo(h3), acc[4 * b + 7] + bf_hi(h3));
        }
    } else {
#pragma unroll
        for (int i = 0; i < 16; i++) pk[i] = pack_bf16(acc[2 * i], acc[2 * i + 1]);
    }
    stage_tile<8>(pk, stg, w, lane);
}
__device__ __forceinline__ void ffn_reduce_chunk(const CUtensorMap* tmOut, uint32_t stg, int col, int row, int w, int wgid, bool leader) {
    proxy_fence();
    if (w != 0) {
        asm volatile("bar.arrive %0, 128;" ::"r"(2 + wgid) : "memory");
    } else {
        named_sync(2 + wgid, 128);
        if (leader) { tma_red_2d(tmOut, col, row, stg); bulk_commit(); }
    }
}

template <bool FIRST>
__device__ __forceinline__ void ffn_phase2_chunk(float (&cur)[32], float (&prev)[32], uint32_t (&h1)[144], const FfnPipe& pp, uint32_t ph, const CUtensorMap* tmOut, uint32_t stg_prev, int col_prev, int row, int w, int lane, int wgid, bool leader,
                                                 bool resid_prev, uint32_t fullH) {
    const uint64_t dw = cdesc(F_OFF_ST, 8192, 1024, 1) + blockIdx.y * col_prev;
    float tmp[2][8];
#pragma unroll
    for (int j = 0; j < 6; j++) {
        pp.acquire(j, ph);
        if (j == 0) pin(cur);
        if (FIRST && j == 5) pin(h1);
        wg_fence();
#pragma unroll
        for (int i = 0; i < 6; i++) {
            const int f = (6 * j + i) * 4;
            wgmma_rs_n64<1>(cur, h1[f], h1[f + 1], h1[f + 2], h1[f + 3], dw + ((j * F_STAGE + i * 2048) >> 4), (j | i) != 0);
        }
        wg_commit();
        wg_wait<1>();
        pp.release((j + 5) % 6);
        if (FIRST) {
            pin(prev);
            if (j == 0) silu_slot_last<0>(prev, tmp, h1);
            if (j == 1) silu_slot_last<1>(prev, tmp, h1);
            if (j == 2) silu_slot_last<2>(prev, tmp, h1);
            if (j == 3) silu_slot_last<3>(prev, tmp, h1);
            if (j == 4) silu_slot_last<4>(prev, tmp, h1);
        } else {
            if (j == 0) { pin(prev); ffn_stage_chunk(prev, stg_prev, w, lane, resid_prev, fullH); }
            if (j == 1) ffn_reduce_chunk(tmOut, stg_prev, col_prev, row, w, wgid, leader);
        }
    }
}

__global__ void __launch_bounds__(F_THREADS, 1)
k_ffn(const __grid_constant__ CUtensorMap tmH, const __grid_constant__ CUtensorMap tmW1, const __grid_constant__ CUtensorMap tmW2, const __grid_constant__ CUtensorMap tmOut,
      const __grid_constant__ CUtensorMap tmRes, const __nv_bfloat16* __restrict__ w2) {
    extern __shared__ __align__(1024) uint8_t smem[];
    const uint32_t sX = smem_u32(smem), sSt = sX + F_OFF_ST, bars = sX + F_OFF_BAR;
    const uint32_t full = bars, empty = bars + 64, fullX = bars + 128, fullH = bars + 208;
    const int tid = threadIdx.x, warp = __shfl_sync(~0u, tid >> 5, 0), lane = tid & 31;
#define FFN_MAP 1
    const int m = FFN_MAP == 0 ? (blockIdx.x & 15) : (FFN_MAP == 1 ? (blockIdx.x >> 3) : ((blockIdx.x >> 1) & 15));
    const int fs = FFN_MAP == 0 ? (blockIdx.x >> 4) : (FFN_MAP == 1 ? (blockIdx.x & 7) : ((blockIdx.x >> 5) * 2 + (blockIdx.x & 1)));
    check_smem_base(sX);
    if (tid == 0) {
        prefetch_map(&tmW1); prefetch_map(&tmH); prefetch_map(&tmW2); prefetch_map(&tmOut); prefetch_map(&tmRes);
        for (int i = 0; i < F_NST; i++) { mbar_init(full + i * 8, 1); mbar_init(empty + i * 8, 8); }
        for (int i = 0; i < 9; i++) mbar_init(fullX + i * 8, 1);
        mbar_init(fullH, 1); mbar_init(fullH + 8, 1);
        bar_init_fence();
        for (int kb = 0; kb < 9; kb++) mbar_expect(fullX + kb * 8, 16384);
    }
    __syncthreads();
    if (warp < 4) {
        asm volatile("setmaxnreg.dec.sync.aligned.u32 24;");
        if (warp == 1 && lane < 9) prefetch_l2(reinterpret_cast<const char*>(w2) + ((size_t)fs * 576 + m * 36 + lane * 4) * (DM * 2), 4 * DM * 2);
        if (warp == 0 && elect_one()) {
#pragma unroll 1
            for (int c = 0; c < 18; c++) {
                int col = c - 9 + fs;
                if (col >= 9) col -= 9;
#pragma unroll 1
                for (int j = 0; j < 6; j++) {
                    mbar_wait(empty + j * 8, (c & 1) ^ 1);
                    mbar_expect(full + j * 8, F_STAGE);
                    if (c < 9) tma_2d(sSt + j * F_STAGE, &tmW1, fs * 576 + c * 64, j * 96, full + j * 8);
                    else tma_2d(sSt + j * F_STAGE, &tmW2, col * 64, fs * 576 + j * 96, full + j * 8);
                }
            }
        }
    } else {
        asm volatile("setmaxnreg.inc.sync.aligned.u32 240;");
        const int wgid = (warp >> 2) - 1, w = warp & 3;
        pdl_wait();
        if (warp == 4 && elect_one()) {
            for (int kb = 0; kb < 9; kb++) tma_2d(sX + kb * 16384, &tmH, kb * 64, m * 128, fullX + kb * 8);
        }
        __syncwarp();
        FfnPipe pp{full, empty, lane};
        const uint64_t xlo = cdesc(0, 16, 1024, 1) + wgid * 512;
        uint32_t h1[144];
        float acc0[32], acc1[32];
        ffn_phase1_chunk<0>(acc0, acc1, h1, pp, xlo, fullX);
        ffn_phase1_chunk<1>(acc1, acc0, h1, pp, xlo, fullX);
        ffn_phase1_chunk<2>(acc0, acc1, h1, pp, xlo, fullX);
        ffn_phase1_chunk<3>(acc1, acc0, h1, pp, xlo, fullX);
        ffn_phase1_chunk<4>(acc0, acc1, h1, pp, xlo, fullX);
        ffn_phase1_chunk<5>(acc1, acc0, h1, pp, xlo, fullX);
        ffn_phase1_chunk<6>(acc0, acc1, h1, pp, xlo, fullX);
        ffn_phase1_chunk<7>(acc1, acc0, h1, pp, xlo, fullX);
        ffn_phase1_chunk<8>(acc0, acc1, h1, pp, xlo, fullX);
        const int row = m * 128 + wgid * 64;
        const uint32_t stg = sX + wgid * 8192;
        int c = fs, cprev = 0;
        const bool leader = w == 0 && elect_one();
        const uint32_t myH = fullH + wgid * 8;
        ffn_phase2_chunk<true>(acc1, acc0, h1, pp, 1, &tmOut, 0, 0, row, w, lane, wgid, leader, false, myH);
        if (leader) {
            const int c8 = fs == 0 ? 8 : fs - 1;
            mbar_expect(myH, fs == 0 ? 16384 : 8192);
            tma_2d(stg + 8 * 16384, &tmRes, c8 * 64, row, myH);
            if (fs == 0) tma_2d(stg + 7 * 16384, &tmRes, 7 * 64, row, myH);
        }
        cprev = c; if (++c == 9) c = 0;
#pragma unroll 1
        for (int j = 1; j < 9; j += 2) {
            ffn_phase2_chunk<false>(acc0, acc1, h1, pp, 0, &tmOut, stg + (j - 1) * 16384, cprev * 64, row, w, lane, wgid, leader, false, myH);
            cprev = c; if (++c == 9) c = 0;
            ffn_phase2_chunk<false>(acc1, acc0, h1, pp, 1, &tmOut, stg + j * 16384, cprev * 64, row, w, lane, wgid, leader, j == 7 && fs == 0, myH);
            cprev = c; if (++c == 9) c = 0;
        }
        wg_wait<0>();
        pin(acc1);
        ffn_stage_chunk(acc1, stg + 8 * 16384, w, lane, true, myH);
        ffn_reduce_chunk(&tmOut, stg + 8 * 16384, cprev * 64, row, w, wgid, leader);
        if (leader) bulk_wait_all();
    }
}

typedef CUresult (*EncodeFn)(CUtensorMap*, CUtensorMapDataType, cuuint32_t, void*, const cuuint64_t*, const cuuint64_t*, const cuuint32_t*, const cuuint32_t*,
                             CUtensorMapInterleave, CUtensorMapSwizzle, CUtensorMapL2promotion, CUtensorMapFloatOOBfill);

CUtensorMap make_map(EncodeFn enc, const void* base, int rows, int cols, int box_rows) {
    CUtensorMap tm;
    cuuint64_t dims[2] = {(cuuint64_t)cols, (cuuint64_t)rows};
    cuuint64_t strides[1] = {(cuuint64_t)cols * 2};
    cuuint32_t box[2] = {64, (cuuint32_t)box_rows};
    cuuint32_t es[2] = {1, 1};
    enc(&tm, CU_TENSOR_MAP_DATA_TYPE_BFLOAT16, 2, const_cast<void*>(base), dims, strides, box, es, CU_TENSOR_MAP_INTERLEAVE_NONE,
        CU_TENSOR_MAP_SWIZZLE_128B, CU_TENSOR_MAP_L2_PROMOTION_L2_256B, CU_TENSOR_MAP_FLOAT_OOB_FILL_NONE);
    return tm;
}

template <typename... KArgs, typename... Args>
void launch(void (*kern)(KArgs...), int grid, int block, int smem, bool pdl, Args... args) {
    cudaLaunchConfig_t cfg = {};
    cfg.gridDim = dim3(grid); cfg.blockDim = dim3(block); cfg.dynamicSmemBytes = smem; cfg.stream = cudaStreamPerThread;
    cudaLaunchAttribute at[1];
    at[0].id = cudaLaunchAttributeProgrammaticStreamSerialization;
    at[0].val.programmaticStreamSerializationAllowed = 1;
    cfg.attrs = at; cfg.numAttrs = pdl ? 1 : 0;
    cudaLaunchKernelEx(&cfg, kern, KArgs(args)...);
}

}

#define USE_PDL 1

extern "C" void kernel_launch(void* const* d_in, const int* in_sizes, int n_in, void* d_out, int out_size) {
    const __nv_bfloat16* x = (const __nv_bfloat16*)d_in[0];
    const __nv_bfloat16* wq = (const __nv_bfloat16*)d_in[1];
    const __nv_bfloat16* wk = (const __nv_bfloat16*)d_in[2];
    const __nv_bfloat16* wv = (const __nv_bfloat16*)d_in[3];
    const __nv_bfloat16* wo = (const __nv_bfloat16*)d_in[4];
    const __nv_bfloat16* w1 = (const __nv_bfloat16*)d_in[6];
    const __nv_bfloat16* w2 = (const __nv_bfloat16*)d_in[7];
    __nv_bfloat16* out = (__nv_bfloat16*)d_out;

    static EncodeFn enc = nullptr;
    static void *p_o = nullptr, *p_h = nullptr, *p_q = nullptr, *p_res = nullptr;
    if (!enc) {
        cudaDriverEntryPointQueryResult qr;
        cudaGetDriverEntryPoint("cuTensorMapEncodeTiled", (void**)&enc, cudaEnableDefault, &qr);
        cudaGetSymbolAddress(&p_o, g_o);
        cudaGetSymbolAddress(&p_h, g_x2);
        cudaGetSymbolAddress(&p_res, g_h);
        cudaGetSymbolAddress(&p_q, g_q);
        cudaFuncSetAttribute(k_qkv, cudaFuncAttributeMaxDynamicSharedMemorySize, P_SMEM);
        cudaFuncSetAttribute(k_attn, cudaFuncAttributeMaxDynamicSharedMemorySize, A_SMEM);
        cudaFuncSetAttribute(k_oproj, cudaFuncAttributeMaxDynamicSharedMemorySize, O_SMEM);
        cudaFuncSetAttribute(k_ffn, cudaFuncAttributeMaxDynamicSharedMemorySize, F_SMEM);
    }
    const CUtensorMap tmWq = make_map(enc, wq, DM, DM, 64);
    const CUtensorMap tmWo = make_map(enc, wo, DM, DM, 64);
    const CUtensorMap tmO = make_map(enc, p_o, SEQ, DM, 64);
    const CUtensorMap tmH64 = make_map(enc, p_h, SEQ, DM, 64);
    const CUtensorMap tmH = make_map(enc, p_h, SEQ, DM, 128);
    const CUtensorMap tmRes = make_map(enc, p_res, SEQ, DM, 64);
    const CUtensorMap tmQ = make_map(enc, p_q, SEQ, DM, 64);
    const CUtensorMap tmW1 = make_map(enc, w1, DM, FF, 96);
    const CUtensorMap tmW2 = make_map(enc, w2, FF, DM, 96);
    const CUtensorMap tmOut = make_map(enc, out, SEQ, DM, 64);

    launch(k_qkv, 128, Q_THREADS, P_SMEM, false, tmWq, tmQ, x, wk, wv);
    launch(k_attn, 128, A_THREADS, A_SMEM, USE_PDL, out);
    launch(k_oproj, 96, O_THREADS, O_SMEM, USE_PDL, tmO, tmWo, tmH64, tmRes, x, w1);
    launch(k_ffn, 128, F_THREADS, F_SMEM, USE_PDL, tmH, tmW1, tmW2, tmOut, tmRes, w2);
}
```

```cpp
#include <cuda_runtime.h>
#include <cuda_bf16.h>
#include <cuda.h>
#include <stdint.h>

namespace {

constexpr int SEQ = 2048, DM = 576, FF = 4608;
constexpr int KV_BYTES = SEQ * 48;
constexpr float LN_EPS = 1e-5f;
constexpr float LOG2E = 1.4426950408889634f;
constexpr float Q_SCALE = 0.23570226039551584f * LOG2E;

#define POLY_MASK_V 0xB6DBu
constexpr uint32_t POLY_MASK = POLY_MASK_V;
#define FAST_BOUND_V 60.0f
constexpr float FAST_BOUND = FAST_BOUND_V;

__device__ __align__(1024) __nv_bfloat16 g_q[SEQ * DM];
__device__ __align__(1024) uint4 g_kc[KV_BYTES / 16];
__device__ __align__(1024) uint4 g_vc[KV_BYTES / 16];
__device__ __align__(16) float g_kmax[256];
__device__ __align__(1024) __nv_bfloat16 g_o[SEQ * DM];
__device__ __align__(1024) __nv_bfloat16 g_h[SEQ * DM];
__device__ __align__(1024) __nv_bfloat16 g_x2[SEQ * DM];

__device__ __forceinline__ uint32_t smem_u32(const void* p) { return (uint32_t)__cvta_generic_to_shared(p); }
__device__ __forceinline__ void wg_fence() { asm volatile("wgmma.fence.sync.aligned;" ::: "memory"); }
__device__ __forceinline__ void wg_commit() { asm volatile("wgmma.commit_group.sync.aligned;" ::: "memory"); }
template <int N> __device__ __forceinline__ void wg_wait() { asm volatile("wgmma.wait_group.sync.aligned %0;" ::"n"(N) : "memory"); }
template <int N> __device__ __forceinline__ void pin(float (&r)[N]) {
#pragma unroll
    for (int i = 0; i < N; i++) asm volatile("" : "+f"(r[i])::"memory");
}
template <int N> __device__ __forceinline__ void pin(uint32_t (&r)[N]) {
#pragma unroll
    for (int i = 0; i < N; i++) asm volatile("" : "+r"(r[i])::"memory");
}
constexpr uint32_t SMEM0 = 0x400;
__host__ __device__ constexpr uint64_t cdesc(uint32_t off, uint32_t lbo, uint32_t sbo, uint32_t swz) {
    return (uint64_t)(((SMEM0 + off) & 0x3FFFF) >> 4) | ((uint64_t)(lbo >> 4) << 16) | ((uint64_t)(sbo >> 4) << 32) | ((uint64_t)swz << 62);
}
__device__ __forceinline__ void check_smem_base(uint32_t base) { if ((base & 0x3FFFF) != SMEM0) __trap(); }

__device__ __forceinline__ void mbar_init(uint32_t bar, int cnt) { asm volatile("mbarrier.init.shared::cta.b64 [%0], %1;" ::"r"(bar), "r"(cnt) : "memory"); }
__device__ __forceinline__ void mbar_expect(uint32_t bar, int bytes) { asm volatile("mbarrier.arrive.expect_tx.shared::cta.b64 _, [%0], %1;" ::"r"(bar), "r"(bytes) : "memory"); }
__device__ __forceinline__ void mbar_arrive(uint32_t bar) { asm volatile("mbarrier.arrive.shared::cta.b64 _, [%0];" ::"r"(bar) : "memory"); }
__device__ __forceinline__ void mbar_wait(uint32_t bar, uint32_t parity) {
    asm volatile(
        "{\n.reg .pred p;\n.reg .u32 n;\nmov.u32 n, 0;\n"
        "LAB_WAIT:\n"
        "mbarrier.try_wait.parity.shared::cta.b64 p, [%0], %1;\n"
        "@p bra DONE;\n"
        "add.u32 n, n, 1;\n"
        "setp.lt.u32 p, n, 4000000;\n"
        "@p bra LAB_WAIT;\n"
        "trap;\n"
        "DONE:\n}\n" ::"r"(bar), "r"(parity) : "memory");
}
__device__ __forceinline__ void bar_init_fence() {
    asm volatile("fence.mbarrier_init.release.cluster;" ::: "memory");
    asm volatile("fence.proxy.async.shared::cta;" ::: "memory");
}
__device__ __forceinline__ void proxy_fence() { asm volatile("fence.proxy.async.shared::cta;" ::: "memory"); }
__device__ __forceinline__ void named_sync(int id, int n) { asm volatile("bar.sync %0, %1;" ::"r"(id), "r"(n) : "memory"); }
__device__ __forceinline__ void bulk_g2s(uint32_t dst, const void* src, int bytes, uint32_t bar) {
    asm volatile("cp.async.bulk.shared::cluster.global.mbarrier::complete_tx::bytes [%0], [%1], %2, [%3];" ::"r"(dst), "l"(src), "r"(bytes), "r"(bar) : "memory");
}
__device__ __forceinline__ void tma_2d(uint32_t dst, const CUtensorMap* tm, int c0, int c1, uint32_t bar) {
    asm volatile("cp.async.bulk.tensor.2d.shared::cluster.global.mbarrier::complete_tx::bytes [%0], [%1, {%3, %4}], [%2];" ::"r"(dst), "l"(tm), "r"(bar), "r"(c0), "r"(c1) : "memory");
}
__device__ __forceinline__ void cluster_arrive() { asm volatile("barrier.cluster.arrive.release.aligned;" ::: "memory"); }
__device__ __forceinline__ void cluster_wait() { asm volatile("barrier.cluster.wait.acquire.aligned;" ::: "memory"); }
__device__ __forceinline__ void tma_red_2d(const CUtensorMap* tm, int c0, int c1, uint32_t src) {
    asm volatile("cp.reduce.async.bulk.tensor.2d.global.shared::cta.add.tile.bulk_group [%0, {%2, %3}], [%1];" ::"l"(tm), "r"(src), "r"(c0), "r"(c1) : "memory");
}
__device__ __forceinline__ void tma_st_2d(const CUtensorMap* tm, int c0, int c1, uint32_t src) {
    asm volatile("cp.async.bulk.tensor.2d.global.shared::cta.tile.bulk_group [%0, {%2, %3}], [%1];" ::"l"(tm), "r"(src), "r"(c0), "r"(c1) : "memory");
}
__device__ __forceinline__ void bulk_commit() { asm volatile("cp.async.bulk.commit_group;" ::: "memory"); }
__device__ __forceinline__ void bulk_wait_all() { asm volatile("cp.async.bulk.wait_group.read 0;" ::: "memory"); }
__device__ __forceinline__ bool elect_one() {
    uint32_t p;
    asm volatile("{\n.reg .pred P;\nelect.sync _|P, 0xffffffff;\nselp.b32 %0, 1, 0, P;\n}\n" : "=r"(p));
    return p != 0;
}
__device__ __forceinline__ void prefetch_l2(const void* p, int bytes) { asm volatile("cp.async.bulk.prefetch.L2.global [%0], %1;" ::"l"(p), "r"(bytes) : "memory"); }
__device__ __forceinline__ void prefetch_map(const CUtensorMap* tm) { asm volatile("prefetch.tensormap [%0];" ::"l"(tm) : "memory"); }
__device__ __forceinline__ void pdl_launch() { asm volatile("griddepcontrol.launch_dependents;" ::: "memory"); }
__device__ __forceinline__ void pdl_wait() { asm volatile("griddepcontrol.wait;" ::: "memory"); }
__device__ __forceinline__ float ex2(float x) { float y; asm("ex2.approx.ftz.f32 %0, %1;" : "=f"(y) : "f"(x)); return y; }
__device__ __forceinline__ uint32_t pack_bf16(float lo, float hi) { uint32_t r; asm("cvt.rn.bf16x2.f32 %0, %1, %2;" : "=r"(r) : "f"(hi), "f"(lo)); return r; }
__device__ __forceinline__ float bf_lo(uint32_t v) { return __uint_as_float(v << 16); }
__device__ __forceinline__ float bf_hi(uint32_t v) { return __uint_as_float(v & 0xFFFF0000u); }
__device__ __forceinline__ uint32_t hfma2(uint32_t a, uint32_t b, uint32_t c) { uint32_t r; asm("fma.rn.f16x2 %0, %1, %2, %3;" : "=r"(r) : "r"(a), "r"(b), "r"(c)); return r; }
__device__ __forceinline__ void stmatrix_x4(uint32_t addr, uint32_t r0, uint32_t r1, uint32_t r2, uint32_t r3) {
    asm volatile("stmatrix.sync.aligned.m8n8.x4.shared.b16 [%0], {%1, %2, %3, %4};" ::"r"(addr), "r"(r0), "r"(r1), "r"(r2), "r"(r3) : "memory");
}

template <int TB> __device__ __forceinline__ void wgmma_ss_n24(float (&d)[12], uint64_t da, uint64_t db, int sc) {
    asm volatile("{\n.reg .pred p;\nsetp.ne.b32 p, %14, 0;\n"
        "wgmma.mma_async.sync.aligned.m64n24k16.f32.bf16.bf16 {%0, %1, %2, %3, %4, %5, %6, %7, %8, %9, %10, %11}, %12, %13, p, 1, 1, 0, %15;\n}\n"
        : "+f"(d[0]), "+f"(d[1]), "+f"(d[2]), "+f"(d[3]), "+f"(d[4]), "+f"(d[5]), "+f"(d[6]), "+f"(d[7]), "+f"(d[8]), "+f"(d[9]), "+f"(d[10]), "+f"(d[11])
        : "l"(da), "l"(db), "r"(sc), "n"(TB));
}
template <int TB> __device__ __forceinline__ void wgmma_ss_n64(float (&d)[32], uint64_t da, uint64_t db, int sc) {
    asm volatile("{\n.reg .pred p;\nsetp.ne.b32 p, %34, 0;\n"
        "wgmma.mma_async.sync.aligned.m64n64k16.f32.bf16.bf16 {%0, %1, %2, %3, %4, %5, %6, %7, %8, %9, %10, %11, %12, %13, %14, %15, %16, %17, %18, %19, %20, %21, %22, %23, %24, %25, %26, %27, %28, %29, %30, %31}, %32, %33, p, 1, 1, 0, %35;\n}\n"
        : "+f"(d[0]), "+f"(d[1]), "+f"(d[2]), "+f"(d[3]), "+f"(d[4]), "+f"(d[5]), "+f"(d[6]), "+f"(d[7]), "+f"(d[8]), "+f"(d[9]), "+f"(d[10]), "+f"(d[11]), "+f"(d[12]), "+f"(d[13]), "+f"(d[14]), "+f"(d[15]), "+f"(d[16]), "+f"(d[17]), "+f"(d[18]), "+f"(d[19]), "+f"(d[20]), "+f"(d[21]), "+f"(d[22]), "+f"(d[23]), "+f"(d[24]), "+f"(d[25]), "+f"(d[26]), "+f"(d[27]), "+f"(d[28]), "+f"(d[29]), "+f"(d[30]), "+f"(d[31])
        : "l"(da), "l"(db), "r"(sc), "n"(TB));
}
template <int TB> __device__ __forceinline__ void wgmma_ss_n128(float (&d)[64], uint64_t da, uint64_t db, int sc) {
    asm volatile("{\n.reg .pred p;\nsetp.ne.b32 p, %66, 0;\n"
        "wgmma.mma_async.sync.aligned.m64n128k16.f32.bf16.bf16 {%0, %1, %2, %3, %4, %5, %6, %7, %8, %9, %10, %11, %12, %13, %14, %15, %16, %17, %18, %19, %20, %21, %22, %23, %24, %25, %26, %27, %28, %29, %30, %31, %32, %33, %34, %35, %36, %37, %38, %39, %40, %41, %42, %43, %44, %45, %46, %47, %48, %49, %50, %51, %52, %53, %54, %55, %56, %57, %58, %59, %60, %61, %62, %63}, %64, %65, p, 1, 1, 0, %67;\n}\n"
        : "+f"(d[0]), "+f"(d[1]), "+f"(d[2]), "+f"(d[3]), "+f"(d[4]), "+f"(d[5]), "+f"(d[6]), "+f"(d[7]), "+f"(d[8]), "+f"(d[9]), "+f"(d[10]), "+f"(d[11]), "+f"(d[12]), "+f"(d[13]), "+f"(d[14]), "+f"(d[15]), "+f"(d[16]), "+f"(d[17]), "+f"(d[18]), "+f"(d[19]), "+f"(d[20]), "+f"(d[21]), "+f"(d[22]), "+f"(d[23]), "+f"(d[24]), "+f"(d[25]), "+f"(d[26]), "+f"(d[27]), "+f"(d[28]), "+f"(d[29]), "+f"(d[30]), "+f"(d[31]), "+f"(d[32]), "+f"(d[33]), "+f"(d[34]), "+f"(d[35]), "+f"(d[36]), "+f"(d[37]), "+f"(d[38]), "+f"(d[39]), "+f"(d[40]), "+f"(d[41]), "+f"(d[42]), "+f"(d[43]), "+f"(d[44]), "+f"(d[45]), "+f"(d[46]), "+f"(d[47]), "+f"(d[48]), "+f"(d[49]), "+f"(d[50]), "+f"(d[51]), "+f"(d[52]), "+f"(d[53]), "+f"(d[54]), "+f"(d[55]), "+f"(d[56]), "+f"(d[57]), "+f"(d[58]), "+f"(d[59]), "+f"(d[60]), "+f"(d[61]), "+f"(d[62]), "+f"(d[63])
        : "l"(da), "l"(db), "r"(sc), "n"(TB));
}
template <int TB> __device__ __forceinline__ void wgmma_rs_n24(float (&d)[12], uint32_t a0, uint32_t a1, uint32_t a2, uint32_t a3, uint64_t db, int sc) {
    asm volatile("{\n.reg .pred p;\nsetp.ne.b32 p, %17, 0;\n"
        "wgmma.mma_async.sync.aligned.m64n24k16.f32.bf16.bf16 {%0, %1, %2, %3, %4, %5, %6, %7, %8, %9, %10, %11}, {%12, %13, %14, %15}, %16, p, 1, 1, %18;\n}\n"
        : "+f"(d[0]), "+f"(d[1]), "+f"(d[2]), "+f"(d[3]), "+f"(d[4]), "+f"(d[5]), "+f"(d[6]), "+f"(d[7]), "+f"(d[8]), "+f"(d[9]), "+f"(d[10]), "+f"(d[11])
        : "r"(a0), "r"(a1), "r"(a2), "r"(a3), "l"(db), "r"(sc), "n"(TB));
}
template <int TB> __device__ __forceinline__ void wgmma_rs_n64(float (&d)[32], uint32_t a0, uint32_t a1, uint32_t a2, uint32_t a3, uint64_t db, int sc) {
    asm volatile("{\n.reg .pred p;\nsetp.ne.b32 p, %37, 0;\n"
        "wgmma.mma_async.sync.aligned.m64n64k16.f32.bf16.bf16 {%0, %1, %2, %3, %4, %5, %6, %7, %8, %9, %10, %11, %12, %13, %14, %15, %16, %17, %18, %19, %20, %21, %22, %23, %24, %25, %26, %27, %28, %29, %30, %31}, {%32, %33, %34, %35}, %36, p, 1, 1, %38;\n}\n"
        : "+f"(d[0]), "+f"(d[1]), "+f"(d[2]), "+f"(d[3]), "+f"(d[4]), "+f"(d[5]), "+f"(d[6]), "+f"(d[7]), "+f"(d[8]), "+f"(d[9]), "+f"(d[10]), "+f"(d[11]), "+f"(d[12]), "+f"(d[13]), "+f"(d[14]), "+f"(d[15]), "+f"(d[16]), "+f"(d[17]), "+f"(d[18]), "+f"(d[19]), "+f"(d[20]), "+f"(d[21]), "+f"(d[22]), "+f"(d[23]), "+f"(d[24]), "+f"(d[25]), "+f"(d[26]), "+f"(d[27]), "+f"(d[28]), "+f"(d[29]), "+f"(d[30]), "+f"(d[31])
        : "r"(a0), "r"(a1), "r"(a2), "r"(a3), "l"(db), "r"(sc), "n"(TB));
}
template <int TB> __device__ __forceinline__ void wgmma_rs_n128(float (&d)[64], uint32_t a0, uint32_t a1, uint32_t a2, uint32_t a3, uint64_t db, int sc) {
    asm volatile("{\n.reg .pred p;\nsetp.ne.b32 p, %69, 0;\n"
        "wgmma.mma_async.sync.aligned.m64n128k16.f32.bf16.bf16 {%0, %1, %2, %3, %4, %5, %6, %7, %8, %9, %10, %11, %12, %13, %14, %15, %16, %17, %18, %19, %20, %21, %22, %23, %24, %25, %26, %27, %28, %29, %30, %31, %32, %33, %34, %35, %36, %37, %38, %39, %40, %41, %42, %43, %44, %45, %46, %47, %48, %49, %50, %51, %52, %53, %54, %55, %56, %57, %58, %59, %60, %61, %62, %63}, {%64, %65, %66, %67}, %68, p, 1, 1, %70;\n}\n"
        : "+f"(d[0]), "+f"(d[1]), "+f"(d[2]), "+f"(d[3]), "+f"(d[4]), "+f"(d[5]), "+f"(d[6]), "+f"(d[7]), "+f"(d[8]), "+f"(d[9]), "+f"(d[10]), "+f"(d[11]), "+f"(d[12]), "+f"(d[13]), "+f"(d[14]), "+f"(d[15]), "+f"(d[16]), "+f"(d[17]), "+f"(d[18]), "+f"(d[19]), "+f"(d[20]), "+f"(d[21]), "+f"(d[22]), "+f"(d[23]), "+f"(d[24]), "+f"(d[25]), "+f"(d[26]), "+f"(d[27]), "+f"(d[28]), "+f"(d[29]), "+f"(d[30]), "+f"(d[31]), "+f"(d[32]), "+f"(d[33]), "+f"(d[34]), "+f"(d[35]), "+f"(d[36]), "+f"(d[37]), "+f"(d[38]), "+f"(d[39]), "+f"(d[40]), "+f"(d[41]), "+f"(d[42]), "+f"(d[43]), "+f"(d[44]), "+f"(d[45]), "+f"(d[46]), "+f"(d[47]), "+f"(d[48]), "+f"(d[49]), "+f"(d[50]), "+f"(d[51]), "+f"(d[52]), "+f"(d[53]), "+f"(d[54]), "+f"(d[55]), "+f"(d[56]), "+f"(d[57]), "+f"(d[58]), "+f"(d[59]), "+f"(d[60]), "+f"(d[61]), "+f"(d[62]), "+f"(d[63])
        : "r"(a0), "r"(a1), "r"(a2), "r"(a3), "l"(db), "r"(sc), "n"(TB));
}

constexpr int P_NST = 6;
constexpr int P_A_BYTES = 9 * 8192;
constexpr int P_B_STAGE = 3 * 8192;
constexpr int P_SMEM = P_A_BYTES + P_NST * P_B_STAGE + 256 + 320;

template <int NB>
__device__ __forceinline__ void stage_tile(const uint32_t (&pk)[NB * 2], uint32_t base, int w, int lane) {
    const int r = w * 16 + (lane & 7) + ((lane >> 3) & 1) * 8;
#pragma unroll
    for (int b = 0; b < NB; b += 2) {
        const uint32_t a = base + (b >> 3) * 8192 + r * 128 + ((((b & 7) + (lane >> 4)) ^ (r & 7)) << 4);
        stmatrix_x4(a, pk[2 * b], pk[2 * b + 1], pk[2 * b + 2], pk[2 * b + 3]);
    }
}

__device__ __forceinline__ uint32_t hsub2_bf16(uint32_t a, uint32_t b) { uint32_t r; asm("sub.rn.bf16x2 %0, %1, %2;" : "=r"(r) : "r"(a), "r"(b)); return r; }

constexpr int KV_RAW = DM * 18 * 2;
constexpr int Q_THREADS = 416;

__device__ __forceinline__ void proj_mma(float (&acc)[32], int wg, uint32_t fullB, uint32_t emptyB, uint32_t fullA, bool wait_a, int lane) {
    const uint64_t dA = cdesc(0, 16, 1024, 1), dB = cdesc(P_A_BYTES, 8192, 1024, 1) + wg * 512;
#pragma unroll 1
    for (int kb = 0; kb < 9; kb++) {
        const int s = kb >= P_NST ? kb - P_NST : kb;
        if (wait_a) mbar_wait(fullA + kb * 8, 0);
        mbar_wait(fullB + s * 8, kb >= P_NST ? 1 : 0);
        wg_fence();
#pragma unroll
        for (int ks = 0; ks < 4; ks++) wgmma_ss_n64<1>(acc, dA + (kb * 512 + ks * 2), dB + (s * (P_B_STAGE >> 4) + ks * 128), (kb | ks) != 0);
        wg_commit();
        if (kb < 4) {
            wg_wait<1>();
            if (kb >= 1 && lane == 0) mbar_arrive(emptyB + (kb - 1) * 8);
        }
    }
    wg_wait<0>();
    pin(acc);
}

__global__ void __launch_bounds__(Q_THREADS, 1)
k_qkv(const __grid_constant__ CUtensorMap tmWq, const __grid_constant__ CUtensorMap tmQ, const __nv_bfloat16* __restrict__ x, const __nv_bfloat16* __restrict__ wk, const __nv_bfloat16* __restrict__ wv) {
    extern __shared__ __align__(1024) uint8_t smem[];
    const uint32_t sA = smem_u32(smem), sB = sA + P_A_BYTES, bars = sB + P_NST * P_B_STAGE;
    const uint32_t fullB = bars, emptyB = bars + 64, fullX = bars + 128, fullW = bars + 136;
    float* s_rstd = reinterpret_cast<float*>(smem + P_A_BYTES + P_NST * P_B_STAGE + 256);
    const int tid = threadIdx.x, warp = __shfl_sync(~0u, tid >> 5, 0), lane = tid & 31;
    const bool isQ = blockIdx.x < 96;
    const int m = isQ ? blockIdx.x / 3 : blockIdx.x - 96, cg = blockIdx.x % 3;
    if (warp == 12) {
        if (elect_one()) {
            mbar_init(fullX, 1);
            bar_init_fence();
            mbar_expect(fullX, P_A_BYTES);
            bulk_g2s(sA, x + (size_t)m * 64 * DM, P_A_BYTES, fullX);
            prefetch_map(&tmWq); prefetch_map(&tmQ);
            for (int i = 0; i < P_NST; i++) { mbar_init(fullB + i * 8, 1); mbar_init(emptyB + i * 8, 12); }
            mbar_init(fullW, 1);
            bar_init_fence();
            if (isQ) {
                for (int kb = 0; kb < P_NST; kb++) {
                    mbar_expect(fullB + kb * 8, P_B_STAGE);
                    for (int a = 0; a < 3; a++) tma_2d(sB + kb * P_B_STAGE + a * 8192, &tmWq, cg * 192 + a * 64, kb * 64, fullB + kb * 8);
                }
            } else {
                mbar_expect(fullW, 2 * KV_RAW);
                bulk_g2s(sB + 3 * P_B_STAGE, wk, KV_RAW, fullW);
                bulk_g2s(sB + 3 * P_B_STAGE + KV_RAW, wv, KV_RAW, fullW);
            }
        }
        __syncwarp();
    }
    check_smem_base(sA);
    __syncthreads();
    pdl_launch();
    if (warp == 12) {
        if (isQ && elect_one()) {
            for (int kb = P_NST; kb < 9; kb++) {
                const int s = kb - P_NST;
                mbar_wait(emptyB + s * 8, 0);
                mbar_expect(fullB + s * 8, P_B_STAGE);
                for (int a = 0; a < 3; a++) tma_2d(sB + s * P_B_STAGE + a * 8192, &tmWq, cg * 192 + a * 64, kb * 64, fullB + s * 8);
            }
        }
        return;
    }
    if (warp < 8) {
        const int row = tid >> 2, q = tid & 3, h0 = (row & 1) * 4;
        mbar_wait(fullX, 0);
        uint4 v[18];
        const uint32_t ra = sA + row * 1152 + (q + h0) * 16, rb = sA + row * 1152 + (q + 4 - h0) * 16;
#pragma unroll
        for (int kb = 0; kb < 9; kb++) {
            asm volatile("ld.shared.v4.b32 {%0, %1, %2, %3}, [%4];" : "=r"(v[2 * kb].x), "=r"(v[2 * kb].y), "=r"(v[2 * kb].z), "=r"(v[2 * kb].w) : "r"(ra + kb * 128));
            asm volatile("ld.shared.v4.b32 {%0, %1, %2, %3}, [%4];" : "=r"(v[2 * kb + 1].x), "=r"(v[2 * kb + 1].y), "=r"(v[2 * kb + 1].z), "=r"(v[2 * kb + 1].w) : "r"(rb + kb * 128));
        }
        float sum = 0.f, sum2 = 0.f, sq = 0.f, sq2 = 0.f;
#pragma unroll
        for (int i = 0; i < 18; i++) {
            const uint32_t w[4] = {v[i].x, v[i].y, v[i].z, v[i].w};
#pragma unroll
            for (int j = 0; j < 4; j++) { const float a = bf_lo(w[j]), b = bf_hi(w[j]); sum += a; sum2 += b; sq = fmaf(a, a, sq); sq2 = fmaf(b, b, sq2); }
        }
        named_sync(1, 256);
        sum += sum2; sq += sq2;
        sum += __shfl_xor_sync(~0u, sum, 1); sum += __shfl_xor_sync(~0u, sum, 2);
        sq += __shfl_xor_sync(~0u, sq, 1); sq += __shfl_xor_sync(~0u, sq, 2);
        const float mean = sum * (1.0f / DM);
        if (q == 0) s_rstd[row] = rsqrtf(fmaxf(sq * (1.0f / DM) - mean * mean, 0.f) + LN_EPS);
        const uint32_t mhi = pack_bf16(mean, mean);
        const float rem = mean - bf_lo(mhi);
        const uint32_t mlo = pack_bf16(rem, rem);
        const uint32_t wa = sA + row * 128 + (((q + h0) ^ (row & 7)) << 4), wb = sA + row * 128 + (((q + 4 - h0) ^ (row & 7)) << 4);
#pragma unroll
        for (int i = 0; i < 18; i++) {
            const uint32_t o0 = hsub2_bf16(hsub2_bf16(v[i].x, mhi), mlo), o1 = hsub2_bf16(hsub2_bf16(v[i].y, mhi), mlo);
            const uint32_t o2 = hsub2_bf16(hsub2_bf16(v[i].z, mhi), mlo), o3 = hsub2_bf16(hsub2_bf16(v[i].w, mhi), mlo);
            asm volatile("st.shared.v4.b32 [%0], {%1, %2, %3, %4};" ::"r"(((i & 1) ? wb : wa) + (i >> 1) * 8192), "r"(o0), "r"(o1), "r"(o2), "r"(o3) : "memory");
        }
    } else if (!isQ) {
        mbar_wait(fullW, 0);
        const uint32_t* raw = reinterpret_cast<const uint32_t*>(smem + P_A_BYTES + 3 * P_B_STAGE);
#pragma unroll 3
        for (int r = tid - 256; r < 2 * DM; r += 128) {
            uint32_t wr[9];
#pragma unroll
            for (int i = 0; i < 9; i++) wr[i] = raw[r * 9 + i];
            const int sel = r >= DM, k = r - sel * DM;
            uint8_t* dst = smem + P_A_BYTES + sel * 3 * 9216 + (k >> 3) * 128 + (k & 7) * 16;
            *reinterpret_cast<uint4*>(dst) = make_uint4(wr[0], wr[1], wr[2], wr[3]);
            *reinterpret_cast<uint4*>(dst + 9216) = make_uint4(wr[4], wr[5], wr[6], wr[7]);
            *reinterpret_cast<uint32_t*>(dst + 2 * 9216) = wr[8];
        }
    }
    proxy_fence();
    named_sync(2, 384);
    const int wg = warp >> 2, w = warp & 3, g = lane >> 2, t = lane & 3;
    const float rs0 = s_rstd[w * 16 + g], rs1 = s_rstd[w * 16 + g + 8];
    if (isQ) {
        const float c0 = rs0 * Q_SCALE, c1 = rs1 * Q_SCALE;
        float acc[32];
        proj_mma(acc, wg, fullB, emptyB, 0, false, lane);
        uint32_t pk[16];
#pragma unroll
        for (int i = 0; i < 8; i++) { pk[2 * i] = pack_bf16(acc[4 * i] * c0, acc[4 * i + 1] * c0); pk[2 * i + 1] = pack_bf16(acc[4 * i + 2] * c1, acc[4 * i + 3] * c1); }
        named_sync(2, 384);
        stage_tile<8>(pk, sA + wg * 8192, w, lane);
        proxy_fence();
        named_sync(3 + wg, 128);
        if (w == 0 && elect_one()) {
            tma_st_2d(&tmQ, cg * 192 + wg * 64, m * 64, sA + wg * 8192);
            bulk_commit();
            bulk_wait_all();
        }
    } else if (wg < 2) {
        float acc[12];
        const uint64_t dA = cdesc(0, 16, 1024, 1), dB = cdesc(P_A_BYTES, 128, 9216, 0) + wg * (3 * 9216 >> 4);
#pragma unroll
        for (int i = 0; i < 12; i++) acc[i] = 0.f;
        pin(acc);
        wg_fence();
#pragma unroll 1
        for (int kb = 0; kb < 9; kb++) {
#pragma unroll
            for (int ks = 0; ks < 4; ks++) wgmma_ss_n24<1>(acc, dA + (kb * 512 + ks * 2), dB + (kb * 4 + ks) * 16, 1);
        }
        wg_commit();
        wg_wait<0>();
        pin(acc);
        uint32_t pk[6];
#pragma unroll
        for (int b = 0; b < 3; b++) { pk[2 * b] = pack_bf16(acc[4 * b] * rs0, acc[4 * b + 1] * rs0); pk[2 * b + 1] = pack_bf16(acc[4 * b + 2] * rs1, acc[4 * b + 3] * rs1); }
        float n0 = 0.f, n1 = 0.f, vm = 0.f;
#pragma unroll
        for (int b = 0; b < 3; b++) {
            if (b < 2 || t == 0) {
                const float a = bf_lo(pk[2 * b]), c = bf_hi(pk[2 * b]), d = bf_lo(pk[2 * b + 1]), e = bf_hi(pk[2 * b + 1]);
                n0 = fmaf(a, a, fmaf(c, c, n0)); n1 = fmaf(d, d, fmaf(e, e, n1));
            }
        }
        n0 += __shfl_xor_sync(~0u, n0, 1); n0 += __shfl_xor_sync(~0u, n0, 2);
        n1 += __shfl_xor_sync(~0u, n1, 1); n1 += __shfl_xor_sync(~0u, n1, 2);
        vm = fmaxf(n0, n1);
        if (!(n0 == n0) || !(n1 == n1)) vm = __int_as_float(0x7F800000);
#pragma unroll
        for (int o = 4; o < 32; o <<= 1) vm = fmaxf(vm, __shfl_xor_sync(~0u, vm, o));
        if (t != 0) {
            uint32_t lo, hi;
            if (wg == 0) {
                const int grp = m * 8 + w * 2;
                const uint32_t c = t == 1 ? 0x42FE3F80u   : (t == 2 ? 0x00003BC0u   : 0u);
                lo = ((POLY_MASK >> (grp & 15)) & 1) ? c : 0u;
                hi = ((POLY_MASK >> ((grp + 1) & 15)) & 1) ? c : 0u;
            } else {
                lo = hi = t == 1 ? 0x00003F80u : 0u;
            }
            pk[4] = lo; pk[5] = hi;
        }
        uint32_t* dst = reinterpret_cast<uint32_t*>(wg == 0 ? g_kc : g_vc) + (m * 8 + w * 2) * 96 + g * 4 + t;
#pragma unroll
        for (int b = 0; b < 3; b++) { dst[b * 32] = pk[2 * b]; dst[96 + b * 32] = pk[2 * b + 1]; }
        if (lane == 0) g_kmax[m * 8 + warp] = (wg == 0) ? vm : (vm <= 1e24f ? 0.f : __int_as_float(0x7F800000));
    }
}

constexpr int A_THREADS = 512;
constexpr int A_NPIECE = 8;
constexpr int A_OFF_Q = 2 * KV_BYTES;
constexpr int A_OFF_BAR = A_OFF_Q + 8 * 4096;
constexpr int A_SMEM = A_OFF_BAR + 128;

__device__ __forceinline__ uint32_t exp2_pair_fixed(float lo, float hi, uint32_t dep) {
    const uint32_t G = __byte_perm(__float_as_uint(lo), __float_as_uint(hi), 0x5410);
    uint32_t Hh;
    asm("lop3.b32 %0, %1, 0x007F007F, %2, 0xC0;" : "=r"(Hh) : "r"(G), "r"(dep));
    const uint32_t tt = hfma2(Hh, 0xF96BF96Bu, 0x358C358Cu);
    return G - hfma2(tt, Hh, 0u);
}

__global__ void __launch_bounds__(A_THREADS, 1)
k_attn(__nv_bfloat16* __restrict__ out) {
    extern __shared__ __align__(1024) uint8_t smem[];
    pdl_launch();
    const uint32_t sK = smem_u32(smem), sV = sK + KV_BYTES, bars = sK + A_OFF_BAR;
    const int tid = threadIdx.x;
    check_smem_base(sK);
    if (tid == 0) {
        for (int i = 0; i < A_NPIECE; i++) mbar_init(bars + i * 8, 1);
        bar_init_fence();
    }
    __syncthreads();
    pdl_wait();
    const int wg = __shfl_sync(~0u, tid >> 7, 0), w = (tid >> 5) & 3, lane = tid & 31, g = lane >> 2, t = lane & 3;
    const uint32_t* q32 = reinterpret_cast<const uint32_t*>(g_q);
    int row = (blockIdx.x * 8 + wg) * 64 + w * 16 + g;
    uint32_t nq[2][6];
#pragma unroll
    for (int r = 0; r < 2; r++) {
        const uint32_t* q = q32 + (row + r * 256) * 9;
        nq[r][0] = q[t]; nq[r][1] = q[72 + t]; nq[r][2] = q[4 + t]; nq[r][3] = q[76 + t]; nq[r][4] = q[8]; nq[r][5] = q[80];
    }
    constexpr int PB = KV_BYTES / A_NPIECE;
    const float4 km0 = reinterpret_cast<const float4*>(g_kmax)[lane], km1 = reinterpret_cast<const float4*>(g_kmax)[32 + lane];
    if (tid < 32 && elect_one()) {
        for (int i = 0; i < 2; i++) {
            mbar_expect(bars + i * 8, 2 * PB);
            bulk_g2s(sK + i * PB, reinterpret_cast<const char*>(g_kc) + i * PB, PB, bars + i * 8);
            bulk_g2s(sV + i * PB, reinterpret_cast<const char*>(g_vc) + i * PB, PB, bars + i * 8);
        }
    }
    float kmax2 = fmaxf(fmaxf(fmaxf(km0.x, km0.y), fmaxf(km0.z, km0.w)), fmaxf(fmaxf(km1.x, km1.y), fmaxf(km1.z, km1.w)));
#pragma unroll
    for (int o = 1; o < 32; o <<= 1) kmax2 = fmaxf(kmax2, __shfl_xor_sync(~0u, kmax2, o));
    if (tid < 32 && elect_one()) {
        for (int i = 2; i < A_NPIECE; i++) {
            mbar_expect(bars + i * 8, 2 * PB);
            bulk_g2s(sK + i * PB, reinterpret_cast<const char*>(g_kc) + i * PB, PB, bars + i * 8);
            bulk_g2s(sV + i * PB, reinterpret_cast<const char*>(g_vc) + i * PB, PB, bars + i * 8);
        }
    }
    uint32_t vote = 0;
#pragma unroll
    for (int r = 0; r < 2; r++) {
        const uint32_t (&q)[6] = nq[r];
        const float a0 = bf_lo(q[0]), a1 = bf_hi(q[0]), a2 = bf_lo(q[2]), a3 = bf_hi(q[2]);
        const float b0 = bf_lo(q[1]), b1 = bf_hi(q[1]), b2 = bf_lo(q[3]), b3 = bf_hi(q[3]);
        float n0 = a0 * a0 + a1 * a1 + a2 * a2 + a3 * a3, n1 = b0 * b0 + b1 * b1 + b2 * b2 + b3 * b3;
        if (t == 0) {
            const float c0 = bf_lo(q[4]), c1 = bf_hi(q[4]), d0 = bf_lo(q[5]), d1 = bf_hi(q[5]);
            n0 += c0 * c0 + c1 * c1; n1 += d0 * d0 + d1 * d1;
        }
        n0 += __shfl_xor_sync(~0u, n0, 1); n0 += __shfl_xor_sync(~0u, n0, 2);
        n1 += __shfl_xor_sync(~0u, n1, 1); n1 += __shfl_xor_sync(~0u, n1, 2);
        const bool unsafe = !(fmaxf(n0, n1) * kmax2 <= FAST_BOUND * FAST_BOUND) || !(n0 == n0) || !(n1 == n1);
        vote |= (__any_sync(~0u, unsafe) ? 1u : 0u) << r;
        const uint32_t cst = t == 1 ? 0x3F804780u : (t == 2 ? 0x00003F80u : 0u);
        const uint32_t sQ = sK + A_OFF_Q + (r * 4 + wg) * 4096 + (w * 2) * 512 + g * 16 + t * 4;
        asm volatile("st.shared.b32 [%0], %1;" ::"r"(sQ), "r"(q[0]) : "memory");
        asm volatile("st.shared.b32 [%0], %1;" ::"r"(sQ + 512), "r"(q[1]) : "memory");
        asm volatile("st.shared.b32 [%0], %1;" ::"r"(sQ + 128), "r"(q[2]) : "memory");
        asm volatile("st.shared.b32 [%0], %1;" ::"r"(sQ + 640), "r"(q[3]) : "memory");
        asm volatile("st.shared.b32 [%0], %1;" ::"r"(sQ + 256), "r"(t == 0 ? q[4] : cst) : "memory");
        asm volatile("st.shared.b32 [%0], %1;" ::"r"(sQ + 768), "r"(t == 0 ? q[5] : cst) : "memory");
        asm volatile("st.shared.b32 [%0], %1;" ::"r"(sQ + 384), "r"(0u) : "memory");
        asm volatile("st.shared.b32 [%0], %1;" ::"r"(sQ + 896), "r"(0u) : "memory");
    }
    const uint32_t sVote = bars + 64 + wg * 16;
    if (lane == 0) asm volatile("st.shared.b32 [%0], %1;" ::"r"(sVote + w * 4), "r"(vote) : "memory");
    proxy_fence();
    named_sync(wg + 1, 128);
    uint32_t unsafe_mask;
    {
        uint32_t v0, v1, v2, v3;
        asm volatile("ld.shared.v4.b32 {%0, %1, %2, %3}, [%4];" : "=r"(v0), "=r"(v1), "=r"(v2), "=r"(v3) : "r"(sVote));
        unsafe_mask = __shfl_sync(~0u, v0 | v1 | v2 | v3, 0);
    }
    if (unsafe_mask) {
#pragma unroll
        for (int r = 0; r < 2; r++) {
            if (((unsafe_mask >> r) & 1) && t != 0) {
                const uint32_t sQ = sK + A_OFF_Q + (r * 4 + wg) * 4096 + (w * 2) * 512 + g * 16 + t * 4;
                asm volatile("st.shared.b32 [%0], %1;" ::"r"(sQ + 256), "r"(0u) : "memory");
                asm volatile("st.shared.b32 [%0], %1;" ::"r"(sQ + 768), "r"(0u) : "memory");
            }
        }
        proxy_fence();
        named_sync(wg + 1, 128);
    }
#pragma unroll 1
    for (int rep = 0; rep < 2; rep++, row += 256) {
        if (rep == 1) {
            uint4* z = reinterpret_cast<uint4*>(out + (size_t)blockIdx.x * 16 * DM) + tid;
            z[0] = make_uint4(0u, 0u, 0u, 0u); z[A_THREADS] = make_uint4(0u, 0u, 0u, 0u);
            if (tid < 16 * DM * 2 / 16 - 2 * A_THREADS) z[2 * A_THREADS] = make_uint4(0u, 0u, 0u, 0u);
        }
        const uint32_t any_unsafe = (unsafe_mask >> rep) & 1;
        const uint64_t dQ0 = cdesc(A_OFF_Q, 128, 512, 0) + (rep * 4 + wg) * 256, dQ1 = dQ0 + 16;
        float o[12];
#pragma unroll
        for (int i = 0; i < 12; i++) o[i] = 0.f;
        pin(o);
        uint64_t dK0 = cdesc(0, 128, 384, 0), dK1 = cdesc(256, 0, 384, 0), dV = cdesc(KV_BYTES, 384, 128, 0);
        if (!any_unsafe) {
            float s[64];
#pragma unroll 1
            for (int j = 0; j < 16; j++) {
                if (rep == 0 && (j & 1) == 0) mbar_wait(bars + (j >> 1) * 8, 0);
                wg_fence();
                wgmma_ss_n128<0>(s, dQ0, dK0, 0);
                wgmma_ss_n128<0>(s, dQ1, dK1, 1);
                wg_commit();
                dK0 += 16 * 384 >> 4; dK1 += 16 * 384 >> 4;
                wg_wait<0>();
                pin(s);
                uint32_t p[32];
#define CHAIN 6
                {
                    constexpr int NP = 2 * __builtin_popcount(POLY_MASK), NM = 32 - NP;
                    float e[64];
#pragma unroll
                    for (int i = 0; i < 32; i++)
                        if (!((POLY_MASK >> (i >> 1)) & 1)) { e[2 * i] = ex2(s[2 * i]); e[2 * i + 1] = ex2(s[2 * i + 1]); p[i] = pack_bf16(e[2 * i], e[2 * i + 1]); }
                    int ip = 0;
#pragma unroll
                    for (int i = 0; i < 32; i++) {
                        if ((POLY_MASK >> (i >> 1)) & 1) {
                            const int mm = (ip * 2 * NM) / NP - CHAIN;
                            uint32_t dep = 0;
                            if (CHAIN > 0 && mm >= 0) {
                                int cnt = 0;
#pragma unroll
                                for (int q = 0; q < 32; q++)
                                    if (!((POLY_MASK >> (q >> 1)) & 1)) { if (cnt == (mm >> 1)) dep = __float_as_uint(e[2 * q + (mm & 1)]); cnt++; }
                            }
                            p[i] = exp2_pair_fixed(s[2 * i], s[2 * i + 1], dep);
                            ip++;
                        }
                    }
                }
                pin(p);
                wg_fence();
#pragma unroll
                for (int k = 0; k < 8; k++) {
                    wgmma_rs_n24<1>(o, p[4 * k], p[4 * k + 1], p[4 * k + 2], p[4 * k + 3], dV + k * 48, 1);
                }
                wg_commit();
                dV += 16 * 384 >> 4;
                wg_wait<0>();
            }
        } else {
            float s[64];
            float m0 = -INFINITY, m1 = -INFINITY;
#pragma unroll 1
            for (int j = 0; j < 16; j++) {
                if (rep == 0 && (j & 1) == 0) mbar_wait(bars + (j >> 1) * 8, 0);
                wg_fence();
                wgmma_ss_n128<0>(s, dQ0, dK0, 0);
                wgmma_ss_n128<0>(s, dQ1, dK1, 1);
                wg_commit();
                dK0 += 16 * 384 >> 4; dK1 += 16 * 384 >> 4;
                wg_wait<0>();
                pin(s);
                float x0m = m0, x1m = m1;
#pragma unroll
                for (int b = 0; b < 16; b++) { x0m = fmaxf(x0m, fmaxf(s[4 * b], s[4 * b + 1])); x1m = fmaxf(x1m, fmaxf(s[4 * b + 2], s[4 * b + 3])); }
                x0m = fmaxf(x0m, __shfl_xor_sync(~0u, x0m, 1)); x0m = fmaxf(x0m, __shfl_xor_sync(~0u, x0m, 2));
                x1m = fmaxf(x1m, __shfl_xor_sync(~0u, x1m, 1)); x1m = fmaxf(x1m, __shfl_xor_sync(~0u, x1m, 2));
                const float c0 = ex2(m0 - x0m), c1 = ex2(m1 - x1m);
                m0 = x0m; m1 = x1m;
#pragma unroll
                for (int b = 0; b < 3; b++) { o[4 * b] *= c0; o[4 * b + 1] *= c0; o[4 * b + 2] *= c1; o[4 * b + 3] *= c1; }
                uint32_t p[32];
#pragma unroll
                for (int b = 0; b < 16; b++) {
                    p[2 * b] = pack_bf16(ex2(s[4 * b] - m0), ex2(s[4 * b + 1] - m0));
                    p[2 * b + 1] = pack_bf16(ex2(s[4 * b + 2] - m1), ex2(s[4 * b + 3] - m1));
                }
                pin(p); pin(o);
                wg_fence();
#pragma unroll
                for (int k = 0; k < 8; k++) wgmma_rs_n24<1>(o, p[4 * k], p[4 * k + 1], p[4 * k + 2], p[4 * k + 3], dV + k * 48, 1);
                wg_commit();
                dV += 16 * 384 >> 4;
                wg_wait<0>();
            }
        }
        pin(o);
        const float l0 = __shfl_sync(~0u, o[8], (lane & ~3) | 1), l1 = __shfl_sync(~0u, o[10], (lane & ~3) | 1);
        const float i0 = 1.0f / l0, i1 = 1.0f / l1;
        uint32_t* o32 = reinterpret_cast<uint32_t*>(g_o);
        o32[row * 9 + t] = pack_bf16(o[0] * i0, o[1] * i0);
        o32[(row + 8) * 9 + t] = pack_bf16(o[2] * i1, o[3] * i1);
        o32[row * 9 + 4 + t] = pack_bf16(o[4] * i0, o[5] * i0);
        o32[(row + 8) * 9 + 4 + t] = pack_bf16(o[6] * i1, o[7] * i1);
        if (t == 0) { o32[row * 9 + 8] = pack_bf16(o[8] * i0, o[9] * i0); o32[(row + 8) * 9 + 8] = pack_bf16(o[10] * i1, o[11] * i1); }
    }
}

constexpr int O_THREADS = 416;
constexpr int O_OFF_STAT = P_A_BYTES + P_NST * P_B_STAGE + 256;
constexpr int O_SMEM = O_OFF_STAT + 9 * 64 * 8;

__global__ void __cluster_dims__(3, 1, 1) __launch_bounds__(O_THREADS, 1)
k_oproj(const __grid_constant__ CUtensorMap tmO, const __grid_constant__ CUtensorMap tmWo, const __grid_constant__ CUtensorMap tmX2, const __grid_constant__ CUtensorMap tmH, const __nv_bfloat16* __restrict__ x, const __nv_bfloat16* __restrict__ w1) {
    extern __shared__ __align__(1024) uint8_t smem[];
    const uint32_t sA = smem_u32(smem), sB = sA + P_A_BYTES, bars = sB + P_NST * P_B_STAGE;
    const uint32_t fullB = bars, emptyB = bars + 64, fullA = bars + 128;
    const int tid = threadIdx.x, warp = __shfl_sync(~0u, tid >> 5, 0), lane = tid & 31;
    const int m = blockIdx.x / 3, cg = blockIdx.x % 3;
    check_smem_base(sA);
    if (tid == 0) {
        prefetch_map(&tmO); prefetch_map(&tmWo); prefetch_map(&tmX2); prefetch_map(&tmH);
        for (int i = 0; i < P_NST; i++) { mbar_init(fullB + i * 8, 1); mbar_init(emptyB + i * 8, 12); }
        for (int i = 0; i < 9; i++) mbar_init(fullA + i * 8, 1);
        bar_init_fence();
        for (int kb = 0; kb < 9; kb++) mbar_expect(fullA + kb * 8, 8192);
    }
    __syncthreads();
    pdl_launch();
    if (warp == 12) {
        if (elect_one()) {
            for (int kb = 0; kb < 9; kb++) {
                const int s = kb >= P_NST ? kb - P_NST : kb;
                if (kb == 2) {
                    pdl_wait();
                    for (int ka = 0; ka < 9; ka++) tma_2d(sA + ka * 8192, &tmO, ka * 64, m * 64, fullA + ka * 8);
                }
                if (kb >= P_NST) mbar_wait(emptyB + s * 8, 0);
                mbar_expect(fullB + s * 8, P_B_STAGE);
                for (int a = 0; a < 3; a++) tma_2d(sB + s * P_B_STAGE + a * 8192, &tmWo, cg * 192 + a * 64, kb * 64, fullB + s * 8);
            }
            for (int i = 0; i < 6; i++) prefetch_l2(reinterpret_cast<const char*>(w1) + (size_t)blockIdx.x * (FF * DM * 2 / 96) + i * 9216, 9216);
        }
        return;
    }
    const int wg = warp >> 2, w = warp & 3, g = lane >> 2, t = lane & 3;
    uint32_t xr[16];
    {
        const uint32_t* x32 = reinterpret_cast<const uint32_t*>(x) + (((m * 64 + w * 16 + g) * DM + cg * 192 + wg * 64 + 2 * t) >> 1);
#pragma unroll
        for (int b = 0; b < 8; b++) { xr[2 * b] = __ldg(x32 + b * 4); xr[2 * b + 1] = __ldg(x32 + b * 4 + 4 * DM); }
    }
    float acc[32];
    proj_mma(acc, wg, fullB, emptyB, fullA, true, lane);
    named_sync(1, 384);
    float s0 = 0.f, q0 = 0.f, s1 = 0.f, q1 = 0.f;
#pragma unroll
    for (int b = 0; b < 8; b++) {
        const uint32_t xa = xr[2 * b], xb = xr[2 * b + 1];
        const uint32_t ha = pack_bf16(acc[4 * b] + bf_lo(xa), acc[4 * b + 1] + bf_hi(xa));
        const uint32_t hb = pack_bf16(acc[4 * b + 2] + bf_lo(xb), acc[4 * b + 3] + bf_hi(xb));
        xr[2 * b] = ha; xr[2 * b + 1] = hb;
        const float a = bf_lo(ha), c = bf_hi(ha), d = bf_lo(hb), e = bf_hi(hb);
        s0 += a + c; q0 = fmaf(a, a, fmaf(c, c, q0));
        s1 += d + e; q1 = fmaf(d, d, fmaf(e, e, q1));
    }
    s0 += __shfl_xor_sync(~0u, s0, 1); s0 += __shfl_xor_sync(~0u, s0, 2);
    q0 += __shfl_xor_sync(~0u, q0, 1); q0 += __shfl_xor_sync(~0u, q0, 2);
    s1 += __shfl_xor_sync(~0u, s1, 1); s1 += __shfl_xor_sync(~0u, s1, 2);
    q1 += __shfl_xor_sync(~0u, q1, 1); q1 += __shfl_xor_sync(~0u, q1, 2);
    const int r = w * 16 + g;
    const uint32_t sStat = sA + O_OFF_STAT;
    if (t < 3) {
        uint32_t dst;
        asm("mapa.shared::cluster.u32 %0, %1, %2;" : "=r"(dst) : "r"(sStat + ((cg * 3 + wg) * 64 + r) * 8), "r"(t));
        asm volatile("st.shared::cluster.v2.f32 [%0], {%1, %2};" ::"r"(dst), "f"(s0), "f"(q0) : "memory");
        asm volatile("st.shared::cluster.v2.f32 [%0], {%1, %2};" ::"r"(dst + 64), "f"(s1), "f"(q1) : "memory");
    }
    cluster_arrive();
    stage_tile<8>(xr, sA + wg * 8192, w, lane);
    proxy_fence();
    named_sync(2 + wg, 128);
    const bool leader = w == 0 && elect_one();
    if (leader) { tma_st_2d(&tmH, cg * 192 + wg * 64, m * 64, sA + wg * 8192); bulk_commit(); }
    cluster_wait();
    s0 = q0 = s1 = q1 = 0.f;
#pragma unroll
    for (int p = 0; p < 9; p++) {
        float a, b, c, d;
        asm volatile("ld.shared.v2.f32 {%0, %1}, [%2];" : "=f"(a), "=f"(b) : "r"(sStat + (p * 64 + r) * 8));
        asm volatile("ld.shared.v2.f32 {%0, %1}, [%2];" : "=f"(c), "=f"(d) : "r"(sStat + (p * 64 + r + 8) * 8));
        s0 += a; q0 += b; s1 += c; q1 += d;
    }
    const float m0 = s0 * (1.0f / DM), m1 = s1 * (1.0f / DM);
    const float rs0 = rsqrtf(fmaxf(q0 * (1.0f / DM) - m0 * m0, 0.f) + LN_EPS), rs1 = rsqrtf(fmaxf(q1 * (1.0f / DM) - m1 * m1, 0.f) + LN_EPS);
    const float sc0 = 0.5f * rs0, sc1 = 0.5f * rs1, n0 = -m0 * sc0, n1 = -m1 * sc1;
#pragma unroll
    for (int b = 0; b < 8; b++) {
        xr[2 * b] = pack_bf16(fmaf(bf_lo(xr[2 * b]), sc0, n0), fmaf(bf_hi(xr[2 * b]), sc0, n0));
        xr[2 * b + 1] = pack_bf16(fmaf(bf_lo(xr[2 * b + 1]), sc1, n1), fmaf(bf_hi(xr[2 * b + 1]), sc1, n1));
    }
    stage_tile<8>(xr, sA + (3 + wg) * 8192, w, lane);
    proxy_fence();
    named_sync(2 + wg, 128);
    if (leader) {
        tma_st_2d(&tmX2, cg * 192 + wg * 64, m * 64, sA + (3 + wg) * 8192);
        bulk_commit();
        bulk_wait_all();
    }
}

constexpr int F_THREADS = 384;
constexpr int F_NST = 6;
constexpr int F_STAGE = 96 * 128;
constexpr int F_X_BYTES = 9 * 16384;
constexpr int F_OFF_ST = F_X_BYTES;
constexpr int F_OFF_BAR = F_OFF_ST + F_NST * F_STAGE;
constexpr int F_SMEM = F_OFF_BAR + 256;

__device__ __forceinline__ float tanh_hw(float x) { float y; asm("tanh.approx.f32 %0, %1;" : "=f"(y) : "f"(x)); return y; }
__host__ __device__ constexpr int piece_begin(int p) { return p == 0 ? 0 : 3 * p + 1; }
template <int P>
__device__ __forceinline__ void silu_s1(const float (&acc)[32], float (&tmp)[8]) {
#pragma unroll
    for (int i = 2 * piece_begin(P); i < 2 * piece_begin(P + 1); i++) tmp[i - 2 * piece_begin(P)] = tanh_hw(acc[i]);
}
template <int C, int P>
__device__ __forceinline__ void silu_s2(const float (&acc)[32], const float (&tmp)[8], uint32_t (&h1)[144]) {
#pragma unroll
    for (int i = piece_begin(P); i < piece_begin(P + 1); i++) {
        const int k = 2 * (i - piece_begin(P));
        h1[C * 16 + i] = pack_bf16(fmaf(acc[2 * i], tmp[k], acc[2 * i]), fmaf(acc[2 * i + 1], tmp[k + 1], acc[2 * i + 1]));
    }
}
template <int J>
__device__ __forceinline__ void silu_slot_last(const float (&prev)[32], float (&tmp)[2][8], uint32_t (&h1)[144]) {
    if constexpr (J >= 1 && J <= 4) {
#pragma unroll
        for (int i = 0; i < 4; i++) {
            const int q = 4 * (J - 1) + i;
            h1[128 + q] = pack_bf16(fmaf(prev[2 * q], tmp[(J - 1) & 1][2 * i], prev[2 * q]), fmaf(prev[2 * q + 1], tmp[(J - 1) & 1][2 * i + 1], prev[2 * q + 1]));
        }
    }
    if constexpr (J <= 3) {
#pragma unroll
        for (int i = 0; i < 8; i++) tmp[J & 1][i] = tanh_hw(prev[8 * J + i]);
        pin(tmp[J & 1]);
    }
}
template <int C, int J>
__device__ __forceinline__ void silu_slot(const float (&prev)[32], float (&tmp)[2][8], uint32_t (&h1)[144]) {
    if constexpr (J >= 1) silu_s2<C, J - 1>(prev, tmp[(J - 1) & 1], h1);
    if constexpr (J <= 4) { silu_s1<J>(prev, tmp[J & 1]); pin(tmp[J & 1]); }
}

struct FfnPipe {
    uint32_t full, empty;
    int lane;
    __device__ __forceinline__ void acquire(int s, uint32_t ph) const { mbar_wait(full + s * 8, ph); }
    __device__ __forceinline__ void release(int s) const { if (lane == 0) mbar_arrive(empty + s * 8); }
};

template <int C>
__device__ __forceinline__ void ffn_phase1_chunk(float (&cur)[32], float (&prev)[32], uint32_t (&h1)[144], const FfnPipe& pp, uint64_t dx, uint32_t fullX) {
    float tmp[2][8];
    const uint64_t dw = cdesc(F_OFF_ST, 8192, 1024, 1) + blockIdx.y * (C + 1);
    dx += blockIdx.y * C;
#pragma unroll
    for (int j = 0; j < 6; j++) {
        if (C == 0) { mbar_wait(fullX + ((6 * j) >> 2) * 8, 0); mbar_wait(fullX + ((6 * j + 5) >> 2) * 8, 0); }
        pp.acquire(j, C & 1);
        if (j == 0) pin(cur);
        wg_fence();
#pragma unroll
        for (int i = 0; i < 6; i++) {
            const int ks = 6 * j + i;
            wgmma_ss_n64<1>(cur, dx + ((ks >> 2) * 1024 + (ks & 3) * 2), dw + ((j * F_STAGE + i * 2048) >> 4), ks != 0);
        }
        wg_commit();
        if (C > 0 || j > 0) { wg_wait<1>(); pp.release((j + 5) % 6); }
        if (C > 0) {
            constexpr int CP = C > 0 ? C - 1 : 0;
            pin(prev);
            if (j == 0) silu_slot<CP, 0>(prev, tmp, h1);
            if (j == 1) silu_slot<CP, 1>(prev, tmp, h1);
            if (j == 2) silu_slot<CP, 2>(prev, tmp, h1);
            if (j == 3) silu_slot<CP, 3>(prev, tmp, h1);
            if (j == 4) silu_slot<CP, 4>(prev, tmp, h1);
            if (j == 5) silu_slot<CP, 5>(prev, tmp, h1);
        }
    }
}

__device__ __forceinline__ void ffn_stage_chunk(const float (&acc)[32], uint32_t stg, int w, int lane, bool resid, uint32_t fullH) {
    uint32_t pk[16];
    if (resid) {
        mbar_wait(fullH, 0);
        const int r = w * 16 + (lane & 7) + ((lane >> 3) & 1) * 8;
#pragma unroll
        for (int b = 0; b < 8; b += 2) {
            uint32_t h0, h1, h2, h3;
            asm volatile("ldmatrix.sync.aligned.m8n8.x4.shared.b16 {%0, %1, %2, %3}, [%4];" : "=r"(h0), "=r"(h1), "=r"(h2), "=r"(h3) : "r"(stg + r * 128 + (((b + (lane >> 4)) ^ (r & 7)) << 4)) : "memory");
            pk[2 * b] = pack_bf16(acc[4 * b] + bf_lo(h0), acc[4 * b + 1] + bf_hi(h0));
            pk[2 * b + 1] = pack_bf16(acc[4 * b + 2] + bf_lo(h1), acc[4 * b + 3] + bf_hi(h1));
            pk[2 * b + 2] = pack_bf16(acc[4 * b + 4] + bf_lo(h2), acc[4 * b + 5] + bf_hi(h2));
            pk[2 * b + 3] = pack_bf16(acc[4 * b + 6] + bf_lo(h3), acc[4 * b + 7] + bf_hi(h3));
        }
    } else {
#pragma unroll
        for (int i = 0; i < 16; i++) pk[i] = pack_bf16(acc[2 * i], acc[2 * i + 1]);
    }
    stage_tile<8>(pk, stg, w, lane);
}
__device__ __forceinline__ void ffn_reduce_chunk(const CUtensorMap* tmOut, uint32_t stg, int col, int row, int w, int wgid, bool leader) {
    proxy_fence();
    if (w != 0) {
        asm volatile("bar.arrive %0, 128;" ::"r"(2 + wgid) : "memory");
    } else {
        named_sync(2 + wgid, 128);
        if (leader) { tma_red_2d(tmOut, col, row, stg); bulk_commit(); }
    }
}

__device__ __forceinline__ void ffn_load_residual(float (&acc)[32], uint32_t stg, int w, int lane, uint32_t fullH) {
    mbar_wait(fullH, 0);
    const int r = w * 16 + (lane & 7) + ((lane >> 3) & 1) * 8;
#pragma unroll
    for (int b = 0; b < 8; b += 2) {
        uint32_t h0, h1, h2, h3;
        asm volatile("ldmatrix.sync.aligned.m8n8.x4.shared.b16 {%0, %1, %2, %3}, [%4];" : "=r"(h0), "=r"(h1), "=r"(h2), "=r"(h3) : "r"(stg + r * 128 + (((b + (lane >> 4)) ^ (r & 7)) << 4)) : "memory");
        acc[4 * b] = bf_lo(h0); acc[4 * b + 1] = bf_hi(h0); acc[4 * b + 2] = bf_lo(h1); acc[4 * b + 3] = bf_hi(h1);
        acc[4 * b + 4] = bf_lo(h2); acc[4 * b + 5] = bf_hi(h2); acc[4 * b + 6] = bf_lo(h3); acc[4 * b + 7] = bf_hi(h3);
    }
}

template <int MODE>
__device__ __forceinline__ void ffn_phase2_chunk(float (&cur)[32], float (&prev)[32], uint32_t (&h1)[144], const FfnPipe& pp, uint32_t ph, const CUtensorMap* tmOut, uint32_t stg_prev, int col_prev, int row, int w, int lane, int wgid, bool leader,
                                                 bool resid_prev, uint32_t fullH, uint32_t stg_res) {
    const uint64_t dw = cdesc(F_OFF_ST, 8192, 1024, 1) + blockIdx.y * col_prev;
    float tmp[2][8];
#pragma unroll
    for (int j = 0; j < 6; j++) {
        pp.acquire(j, ph);
        if (j == 0) pin(cur);
        if (MODE == 0 && j == 5) pin(h1);
        wg_fence();
#pragma unroll
        for (int i = 0; i < 6; i++) {
            const int f = (6 * j + i) * 4;
            wgmma_rs_n64<1>(cur, h1[f], h1[f + 1], h1[f + 2], h1[f + 3], dw + ((j * F_STAGE + i * 2048) >> 4), MODE == 3 || (j | i) != 0);
        }
        wg_commit();
        wg_wait<1>();
        pp.release((j + 5) % 6);
        if (MODE == 0) {
            pin(prev);
            if (j == 0) silu_slot_last<0>(prev, tmp, h1);
            if (j == 1) silu_slot_last<1>(prev, tmp, h1);
            if (j == 2) silu_slot_last<2>(prev, tmp, h1);
            if (j == 3) silu_slot_last<3>(prev, tmp, h1);
            if (j == 4) silu_slot_last<4>(prev, tmp, h1);
        } else {
            if (j == 0) { pin(prev); ffn_stage_chunk(prev, stg_prev, w, lane, MODE == 3 && resid_prev, fullH); }
            if (j == 1) ffn_reduce_chunk(tmOut, stg_prev, col_prev, row, w, wgid, leader);
            if (MODE == 2 && j == 2) { ffn_load_residual(prev, stg_res, w, lane, fullH); pin(prev); }
        }
    }
}

__global__ void __launch_bounds__(F_THREADS, 1)
k_ffn(const __grid_constant__ CUtensorMap tmH, const __grid_constant__ CUtensorMap tmW1, const __grid_constant__ CUtensorMap tmW2, const __grid_constant__ CUtensorMap tmOut,
      const __grid_constant__ CUtensorMap tmRes, const __nv_bfloat16* __restrict__ w2) {
    extern __shared__ __align__(1024) uint8_t smem[];
    const uint32_t sX = smem_u32(smem), sSt = sX + F_OFF_ST, bars = sX + F_OFF_BAR;
    const uint32_t full = bars, empty = bars + 64, fullX = bars + 128, fullH = bars + 208;
    const int tid = threadIdx.x, warp = __shfl_sync(~0u, tid >> 5, 0), lane = tid & 31;
#define FFN_MAP 1
    const int m = FFN_MAP == 0 ? (blockIdx.x & 15) : (FFN_MAP == 1 ? (blockIdx.x >> 3) : ((blockIdx.x >> 1) & 15));
    const int fs = FFN_MAP == 0 ? (blockIdx.x >> 4) : (FFN_MAP == 1 ? (blockIdx.x & 7) : ((blockIdx.x >> 5) * 2 + (blockIdx.x & 1)));
    check_smem_base(sX);
    if (tid == 0) {
        prefetch_map(&tmW1); prefetch_map(&tmH); prefetch_map(&tmW2); prefetch_map(&tmOut); prefetch_map(&tmRes);
        for (int i = 0; i < F_NST; i++) { mbar_init(full + i * 8, 1); mbar_init(empty + i * 8, 8); }
        for (int i = 0; i < 9; i++) mbar_init(fullX + i * 8, 1);
        mbar_init(fullH, 1); mbar_init(fullH + 8, 1);
        bar_init_fence();
        for (int kb = 0; kb < 9; kb++) mbar_expect(fullX + kb * 8, 16384);
    }
    __syncthreads();
    if (warp < 4) {
        asm volatile("setmaxnreg.dec.sync.aligned.u32 24;");
        if (warp == 1 && lane < 9) prefetch_l2(reinterpret_cast<const char*>(w2) + ((size_t)fs * 576 + m * 36 + lane * 4) * (DM * 2), 4 * DM * 2);
        if (warp == 0 && elect_one()) {
#pragma unroll 1
            for (int c = 0; c < 18; c++) {
                int col = c - 9 + fs;
                if (col >= 9) col -= 9;
#pragma unroll 1
                for (int j = 0; j < 6; j++) {
                    mbar_wait(empty + j * 8, (c & 1) ^ 1);
                    mbar_expect(full + j * 8, F_STAGE);
                    if (c < 9) tma_2d(sSt + j * F_STAGE, &tmW1, fs * 576 + c * 64, j * 96, full + j * 8);
                    else tma_2d(sSt + j * F_STAGE, &tmW2, col * 64, fs * 576 + j * 96, full + j * 8);
                }
            }
        }
    } else {
        asm volatile("setmaxnreg.inc.sync.aligned.u32 240;");
        const int wgid = (warp >> 2) - 1, w = warp & 3;
        pdl_wait();
        if (warp == 4 && elect_one()) {
            for (int kb = 0; kb < 9; kb++) tma_2d(sX + kb * 16384, &tmH, kb * 64, m * 128, fullX + kb * 8);
        }
        __syncwarp();
        FfnPipe pp{full, empty, lane};
        const uint64_t xlo = cdesc(0, 16, 1024, 1) + wgid * 512;
        uint32_t h1[144];
        float acc0[32], acc1[32];
        ffn_phase1_chunk<0>(acc0, acc1, h1, pp, xlo, fullX);
        ffn_phase1_chunk<1>(acc1, acc0, h1, pp, xlo, fullX);
        ffn_phase1_chunk<2>(acc0, acc1, h1, pp, xlo, fullX);
        ffn_phase1_chunk<3>(acc1, acc0, h1, pp, xlo, fullX);
        ffn_phase1_chunk<4>(acc0, acc1, h1, pp, xlo, fullX);
        ffn_phase1_chunk<5>(acc1, acc0, h1, pp, xlo, fullX);
        ffn_phase1_chunk<6>(acc0, acc1, h1, pp, xlo, fullX);
        ffn_phase1_chunk<7>(acc1, acc0, h1, pp, xlo, fullX);
        ffn_phase1_chunk<8>(acc0, acc1, h1, pp, xlo, fullX);
        const int row = m * 128 + wgid * 64;
        const uint32_t stg = sX + wgid * 8192;
        int c = fs, cprev = 0;
        const bool leader = w == 0 && elect_one();
        const uint32_t myH = fullH + wgid * 8;
        ffn_phase2_chunk<0>(acc1, acc0, h1, pp, 1, &tmOut, 0, 0, row, w, lane, wgid, leader, false, myH, 0);
        if (leader) {
            const int c8 = fs == 0 ? 8 : fs - 1;
            mbar_expect(myH, fs == 0 ? 16384 : 8192);
            tma_2d(stg + 8 * 16384, &tmRes, c8 * 64, row, myH);
            if (fs == 0) tma_2d(stg + 7 * 16384, &tmRes, 7 * 64, row, myH);
        }
        cprev = c; if (++c == 9) c = 0;
#pragma unroll 1
        for (int j = 1; j < 7; j += 2) {
            ffn_phase2_chunk<1>(acc0, acc1, h1, pp, 0, &tmOut, stg + (j - 1) * 16384, cprev * 64, row, w, lane, wgid, leader, false, myH, 0);
            cprev = c; if (++c == 9) c = 0;
            ffn_phase2_chunk<1>(acc1, acc0, h1, pp, 1, &tmOut, stg + j * 16384, cprev * 64, row, w, lane, wgid, leader, false, myH, 0);
            cprev = c; if (++c == 9) c = 0;
        }
        ffn_phase2_chunk<2>(acc0, acc1, h1, pp, 0, &tmOut, stg + 6 * 16384, cprev * 64, row, w, lane, wgid, leader, false, myH, stg + 8 * 16384);
        cprev = c; if (++c == 9) c = 0;
        ffn_phase2_chunk<3>(acc1, acc0, h1, pp, 1, &tmOut, stg + 7 * 16384, cprev * 64, row, w, lane, wgid, leader, fs == 0, myH, 0);
        cprev = c;
        wg_wait<0>();
        pin(acc1);
        ffn_stage_chunk(acc1, stg + 8 * 16384, w, lane, false, myH);
        ffn_reduce_chunk(&tmOut, stg + 8 * 16384, cprev * 64, row, w, wgid, leader);
        if (leader) bulk_wait_all();
    }
}

typedef CUresult (*EncodeFn)(CUtensorMap*, CUtensorMapDataType, cuuint32_t, void*, const cuuint64_t*, const cuuint64_t*, const cuuint32_t*, const cuuint32_t*,
                             CUtensorMapInterleave, CUtensorMapSwizzle, CUtensorMapL2promotion, CUtensorMapFloatOOBfill);

CUtensorMap make_map(EncodeFn enc, const void* base, int rows, int cols, int box_rows) {
    CUtensorMap tm;
    cuuint64_t dims[2] = {(cuuint64_t)cols, (cuuint64_t)rows};
    cuuint64_t strides[1] = {(cuuint64_t)cols * 2};
    cuuint32_t box[2] = {64, (cuuint32_t)box_rows};
    cuuint32_t es[2] = {1, 1};
    enc(&tm, CU_TENSOR_MAP_DATA_TYPE_BFLOAT16, 2, const_cast<void*>(base), dims, strides, box, es, CU_TENSOR_MAP_INTERLEAVE_NONE,
        CU_TENSOR_MAP_SWIZZLE_128B, CU_TENSOR_MAP_L2_PROMOTION_L2_256B, CU_TENSOR_MAP_FLOAT_OOB_FILL_NONE);
    return tm;
}

template <typename... KArgs, typename... Args>
void launch(void (*kern)(KArgs...), int grid, int block, int smem, bool pdl, Args... args) {
    cudaLaunchConfig_t cfg = {};
    cfg.gridDim = dim3(grid); cfg.blockDim = dim3(block); cfg.dynamicSmemBytes = smem; cfg.stream = cudaStreamPerThread;
    cudaLaunchAttribute at[1];
    at[0].id = cudaLaunchAttributeProgrammaticStreamSerialization;
    at[0].val.programmaticStreamSerializationAllowed = 1;
    cfg.attrs = at; cfg.numAttrs = pdl ? 1 : 0;
    cudaLaunchKernelEx(&cfg, kern, KArgs(args)...);
}

}

#define USE_PDL 1

extern "C" void kernel_launch(void* const* d_in, const int* in_sizes, int n_in, void* d_out, int out_size) {
    const __nv_bfloat16* x = (const __nv_bfloat16*)d_in[0];
    const __nv_bfloat16* wq = (const __nv_bfloat16*)d_in[1];
    const __nv_bfloat16* wk = (const __nv_bfloat16*)d_in[2];
    const __nv_bfloat16* wv = (const __nv_bfloat16*)d_in[3];
    const __nv_bfloat16* wo = (const __nv_bfloat16*)d_in[4];
    const __nv_bfloat16* w1 = (const __nv_bfloat16*)d_in[6];
    const __nv_bfloat16* w2 = (const __nv_bfloat16*)d_in[7];
    __nv_bfloat16* out = (__nv_bfloat16*)d_out;

    static EncodeFn enc = nullptr;
    static void *p_o = nullptr, *p_h = nullptr, *p_q = nullptr, *p_res = nullptr;
    if (!enc) {
        cudaDriverEntryPointQueryResult qr;
        cudaGetDriverEntryPoint("cuTensorMapEncodeTiled", (void**)&enc, cudaEnableDefault, &qr);
        cudaGetSymbolAddress(&p_o, g_o);
        cudaGetSymbolAddress(&p_h, g_x2);
        cudaGetSymbolAddress(&p_res, g_h);
        cudaGetSymbolAddress(&p_q, g_q);
        cudaFuncSetAttribute(k_qkv, cudaFuncAttributeMaxDynamicSharedMemorySize, P_SMEM);
        cudaFuncSetAttribute(k_attn, cudaFuncAttributeMaxDynamicSharedMemorySize, A_SMEM);
        cudaFuncSetAttribute(k_oproj, cudaFuncAttributeMaxDynamicSharedMemorySize, O_SMEM);
        cudaFuncSetAttribute(k_ffn, cudaFuncAttributeMaxDynamicSharedMemorySize, F_SMEM);
    }
    const CUtensorMap tmWq = make_map(enc, wq, DM, DM, 64);
    const CUtensorMap tmWo = make_map(enc, wo, DM, DM, 64);
    const CUtensorMap tmO = make_map(enc, p_o, SEQ, DM, 64);
    const CUtensorMap tmH64 = make_map(enc, p_h, SEQ, DM, 64);
    const CUtensorMap tmH = make_map(enc, p_h, SEQ, DM, 128);
    const CUtensorMap tmRes = make_map(enc, p_res, SEQ, DM, 64);
    const CUtensorMap tmQ = make_map(enc, p_q, SEQ, DM, 64);
    const CUtensorMap tmW1 = make_map(enc, w1, DM, FF, 96);
    const CUtensorMap tmW2 = make_map(enc, w2, FF, DM, 96);
    const CUtensorMap tmOut = make_map(enc, out, SEQ, DM, 64);

    launch(k_qkv, 128, Q_THREADS, P_SMEM, false, tmWq, tmQ, x, wk, wv);
    launch(k_attn, 128, A_THREADS, A_SMEM, USE_PDL, out);
    launch(k_oproj, 96, O_THREADS, O_SMEM, USE_PDL, tmO, tmWo, tmH64, tmRes, x, w1);
    launch(k_ffn, 128, F_THREADS, F_SMEM, USE_PDL, tmH, tmW1, tmW2, tmOut, tmRes, w2);
}
```

```cpp
#include <cuda_runtime.h>
#include <cuda_bf16.h>
#include <cuda.h>
#include <stdint.h>

namespace {

constexpr int SEQ = 2048, DM = 576, FF = 4608;
constexpr int KV_BYTES = SEQ * 48;
constexpr float LN_EPS = 1e-5f;
constexpr float LOG2E = 1.4426950408889634f;
constexpr float Q_SCALE = 0.23570226039551584f * LOG2E;

constexpr uint32_t POLY_MASK = 0xB6DBu;
constexpr int CHAIN = 6;
constexpr float FAST_BOUND = 60.0f;

__device__ __align__(1024) __nv_bfloat16 g_q[SEQ * DM];
__device__ __align__(1024) uint4 g_kc[KV_BYTES / 16];
__device__ __align__(1024) uint4 g_vc[KV_BYTES / 16];
__device__ __align__(16) float g_kmax[256];
__device__ __align__(1024) __nv_bfloat16 g_o[SEQ * DM];
__device__ __align__(1024) __nv_bfloat16 g_h[SEQ * DM];
__device__ __align__(1024) __nv_bfloat16 g_x2[SEQ * DM];


__device__ __forceinline__ uint32_t smem_u32(const void* p) { return (uint32_t)__cvta_generic_to_shared(p); }
__device__ __forceinline__ void wg_fence() { asm volatile("wgmma.fence.sync.aligned;" ::: "memory"); }
__device__ __forceinline__ void wg_commit() { asm volatile("wgmma.commit_group.sync.aligned;" ::: "memory"); }
template <int N> __device__ __forceinline__ void wg_wait() { asm volatile("wgmma.wait_group.sync.aligned %0;" ::"n"(N) : "memory"); }
template <int N> __device__ __forceinline__ void pin(float (&r)[N]) {
#pragma unroll
    for (int i = 0; i < N; i++) asm volatile("" : "+f"(r[i])::"memory");
}
template <int N> __device__ __forceinline__ void pin(uint32_t (&r)[N]) {
#pragma unroll
    for (int i = 0; i < N; i++) asm volatile("" : "+r"(r[i])::"memory");
}
constexpr uint32_t SMEM0 = 0x400;
__host__ __device__ constexpr uint64_t cdesc(uint32_t off, uint32_t lbo, uint32_t sbo, uint32_t swz) {
    return (uint64_t)(((SMEM0 + off) & 0x3FFFF) >> 4) | ((uint64_t)(lbo >> 4) << 16) | ((uint64_t)(sbo >> 4) << 32) | ((uint64_t)swz << 62);
}
__device__ __forceinline__ void check_smem_base(uint32_t base) { if ((base & 0x3FFFF) != SMEM0) __trap(); }

__device__ __forceinline__ void mbar_init(uint32_t bar, int cnt) { asm volatile("mbarrier.init.shared::cta.b64 [%0], %1;" ::"r"(bar), "r"(cnt) : "memory"); }
__device__ __forceinline__ void mbar_expect(uint32_t bar, int bytes) { asm volatile("mbarrier.arrive.expect_tx.shared::cta.b64 _, [%0], %1;" ::"r"(bar), "r"(bytes) : "memory"); }
__device__ __forceinline__ void mbar_arrive(uint32_t bar) { asm volatile("mbarrier.arrive.shared::cta.b64 _, [%0];" ::"r"(bar) : "memory"); }
__device__ __forceinline__ void mbar_wait(uint32_t bar, uint32_t parity) {
    asm volatile(
        "{\n.reg .pred p;\n.reg .u32 n;\nmov.u32 n, 0;\n"
        "LAB_WAIT:\n"
        "mbarrier.try_wait.parity.shared::cta.b64 p, [%0], %1;\n"
        "@p bra DONE;\n"
        "add.u32 n, n, 1;\n"
        "setp.lt.u32 p, n, 4000000;\n"
        "@p bra LAB_WAIT;\n"
        "trap;\n"
        "DONE:\n}\n" ::"r"(bar), "r"(parity) : "memory");
}
__device__ __forceinline__ void bar_init_fence() {
    asm volatile("fence.mbarrier_init.release.cluster;" ::: "memory");
    asm volatile("fence.proxy.async.shared::cta;" ::: "memory");
}
__device__ __forceinline__ void proxy_fence() { asm volatile("fence.proxy.async.shared::cta;" ::: "memory"); }
__device__ __forceinline__ void named_sync(int id, int n) { asm volatile("bar.sync %0, %1;" ::"r"(id), "r"(n) : "memory"); }
__device__ __forceinline__ void bulk_g2s(uint32_t dst, const void* src, int bytes, uint32_t bar) {
    asm volatile("cp.async.bulk.shared::cluster.global.mbarrier::complete_tx::bytes [%0], [%1], %2, [%3];" ::"r"(dst), "l"(src), "r"(bytes), "r"(bar) : "memory");
}
__device__ __forceinline__ void tma_2d(uint32_t dst, const CUtensorMap* tm, int c0, int c1, uint32_t bar) {
    asm volatile("cp.async.bulk.tensor.2d.shared::cluster.global.mbarrier::complete_tx::bytes [%0], [%1, {%3, %4}], [%2];" ::"r"(dst), "l"(tm), "r"(bar), "r"(c0), "r"(c1) : "memory");
}
__device__ __forceinline__ void cluster_arrive() { asm volatile("barrier.cluster.arrive.release.aligned;" ::: "memory"); }
__device__ __forceinline__ void cluster_wait() { asm volatile("barrier.cluster.wait.acquire.aligned;" ::: "memory"); }
__device__ __forceinline__ void tma_red_2d(const CUtensorMap* tm, int c0, int c1, uint32_t src) {
    asm volatile("cp.reduce.async.bulk.tensor.2d.global.shared::cta.add.tile.bulk_group [%0, {%2, %3}], [%1];" ::"l"(tm), "r"(src), "r"(c0), "r"(c1) : "memory");
}
__device__ __forceinline__ void tma_st_2d(const CUtensorMap* tm, int c0, int c1, uint32_t src) {
    asm volatile("cp.async.bulk.tensor.2d.global.shared::cta.tile.bulk_group [%0, {%2, %3}], [%1];" ::"l"(tm), "r"(src), "r"(c0), "r"(c1) : "memory");
}
__device__ __forceinline__ void bulk_commit() { asm volatile("cp.async.bulk.commit_group;" ::: "memory"); }
__device__ __forceinline__ void bulk_wait_all() { asm volatile("cp.async.bulk.wait_group.read 0;" ::: "memory"); }
__device__ __forceinline__ bool elect_one() {
    uint32_t p;
    asm volatile("{\n.reg .pred P;\nelect.sync _|P, 0xffffffff;\nselp.b32 %0, 1, 0, P;\n}\n" : "=r"(p));
    return p != 0;
}
__device__ __forceinline__ void prefetch_l2(const void* p, int bytes) { asm volatile("cp.async.bulk.prefetch.L2.global [%0], %1;" ::"l"(p), "r"(bytes) : "memory"); }
__device__ __forceinline__ void prefetch_map(const CUtensorMap* tm) { asm volatile("prefetch.tensormap [%0];" ::"l"(tm) : "memory"); }
__device__ __forceinline__ void pdl_launch() { asm volatile("griddepcontrol.launch_dependents;" ::: "memory"); }
__device__ __forceinline__ void pdl_wait() { asm volatile("griddepcontrol.wait;" ::: "memory"); }
__device__ __forceinline__ float ex2(float x) { float y; asm("ex2.approx.ftz.f32 %0, %1;" : "=f"(y) : "f"(x)); return y; }
__device__ __forceinline__ uint32_t pack_bf16(float lo, float hi) { uint32_t r; asm("cvt.rn.bf16x2.f32 %0, %1, %2;" : "=r"(r) : "f"(hi), "f"(lo)); return r; }
__device__ __forceinline__ float bf_lo(uint32_t v) { return __uint_as_float(v << 16); }
__device__ __forceinline__ float bf_hi(uint32_t v) { return __uint_as_float(v & 0xFFFF0000u); }
__device__ __forceinline__ uint32_t hfma2(uint32_t a, uint32_t b, uint32_t c) { uint32_t r; asm("fma.rn.f16x2 %0, %1, %2, %3;" : "=r"(r) : "r"(a), "r"(b), "r"(c)); return r; }
__device__ __forceinline__ void stmatrix_x4(uint32_t addr, uint32_t r0, uint32_t r1, uint32_t r2, uint32_t r3) {
    asm volatile("stmatrix.sync.aligned.m8n8.x4.shared.b16 [%0], {%1, %2, %3, %4};" ::"r"(addr), "r"(r0), "r"(r1), "r"(r2), "r"(r3) : "memory");
}

template <int TB> __device__ __forceinline__ void wgmma_ss_n24(float (&d)[12], uint64_t da, uint64_t db, int sc) {
    asm volatile("{\n.reg .pred p;\nsetp.ne.b32 p, %14, 0;\n"
        "wgmma.mma_async.sync.aligned.m64n24k16.f32.bf16.bf16 {%0, %1, %2, %3, %4, %5, %6, %7, %8, %9, %10, %11}, %12, %13, p, 1, 1, 0, %15;\n}\n"
        : "+f"(d[0]), "+f"(d[1]), "+f"(d[2]), "+f"(d[3]), "+f"(d[4]), "+f"(d[5]), "+f"(d[6]), "+f"(d[7]), "+f"(d[8]), "+f"(d[9]), "+f"(d[10]), "+f"(d[11])
        : "l"(da), "l"(db), "r"(sc), "n"(TB));
}
template <int TB> __device__ __forceinline__ void wgmma_ss_n64(float (&d)[32], uint64_t da, uint64_t db, int sc) {
    asm volatile("{\n.reg .pred p;\nsetp.ne.b32 p, %34, 0;\n"
        "wgmma.mma_async.sync.aligned.m64n64k16.f32.bf16.bf16 {%0, %1, %2, %3, %4, %5, %6, %7, %8, %9, %10, %11, %12, %13, %14, %15, %16, %17, %18, %19, %20, %21, %22, %23, %24, %25, %26, %27, %28, %29, %30, %31}, %32, %33, p, 1, 1, 0, %35;\n}\n"
        : "+f"(d[0]), "+f"(d[1]), "+f"(d[2]), "+f"(d[3]), "+f"(d[4]), "+f"(d[5]), "+f"(d[6]), "+f"(d[7]), "+f"(d[8]), "+f"(d[9]), "+f"(d[10]), "+f"(d[11]), "+f"(d[12]), "+f"(d[13]), "+f"(d[14]), "+f"(d[15]), "+f"(d[16]), "+f"(d[17]), "+f"(d[18]), "+f"(d[19]), "+f"(d[20]), "+f"(d[21]), "+f"(d[22]), "+f"(d[23]), "+f"(d[24]), "+f"(d[25]), "+f"(d[26]), "+f"(d[27]), "+f"(d[28]), "+f"(d[29]), "+f"(d[30]), "+f"(d[31])
        : "l"(da), "l"(db), "r"(sc), "n"(TB));
}
template <int TB> __device__ __forceinline__ void wgmma_ss_n128(float (&d)[64], uint64_t da, uint64_t db, int sc) {
    asm volatile("{\n.reg .pred p;\nsetp.ne.b32 p, %66, 0;\n"
        "wgmma.mma_async.sync.aligned.m64n128k16.f32.bf16.bf16 {%0, %1, %2, %3, %4, %5, %6, %7, %8, %9, %10, %11, %12, %13, %14, %15, %16, %17, %18, %19, %20, %21, %22, %23, %24, %25, %26, %27, %28, %29, %30, %31, %32, %33, %34, %35, %36, %37, %38, %39, %40, %41, %42, %43, %44, %45, %46, %47, %48, %49, %50, %51, %52, %53, %54, %55, %56, %57, %58, %59, %60, %61, %62, %63}, %64, %65, p, 1, 1, 0, %67;\n}\n"
        : "+f"(d[0]), "+f"(d[1]), "+f"(d[2]), "+f"(d[3]), "+f"(d[4]), "+f"(d[5]), "+f"(d[6]), "+f"(d[7]), "+f"(d[8]), "+f"(d[9]), "+f"(d[10]), "+f"(d[11]), "+f"(d[12]), "+f"(d[13]), "+f"(d[14]), "+f"(d[15]), "+f"(d[16]), "+f"(d[17]), "+f"(d[18]), "+f"(d[19]), "+f"(d[20]), "+f"(d[21]), "+f"(d[22]), "+f"(d[23]), "+f"(d[24]), "+f"(d[25]), "+f"(d[26]), "+f"(d[27]), "+f"(d[28]), "+f"(d[29]), "+f"(d[30]), "+f"(d[31]), "+f"(d[32]), "+f"(d[33]), "+f"(d[34]), "+f"(d[35]), "+f"(d[36]), "+f"(d[37]), "+f"(d[38]), "+f"(d[39]), "+f"(d[40]), "+f"(d[41]), "+f"(d[42]), "+f"(d[43]), "+f"(d[44]), "+f"(d[45]), "+f"(d[46]), "+f"(d[47]), "+f"(d[48]), "+f"(d[49]), "+f"(d[50]), "+f"(d[51]), "+f"(d[52]), "+f"(d[53]), "+f"(d[54]), "+f"(d[55]), "+f"(d[56]), "+f"(d[57]), "+f"(d[58]), "+f"(d[59]), "+f"(d[60]), "+f"(d[61]), "+f"(d[62]), "+f"(d[63])
        : "l"(da), "l"(db), "r"(sc), "n"(TB));
}
template <int TB> __device__ __forceinline__ void wgmma_rs_n24(float (&d)[12], uint32_t a0, uint32_t a1, uint32_t a2, uint32_t a3, uint64_t db, int sc) {
    asm volatile("{\n.reg .pred p;\nsetp.ne.b32 p, %17, 0;\n"
        "wgmma.mma_async.sync.aligned.m64n24k16.f32.bf16.bf16 {%0, %1, %2, %3, %4, %5, %6, %7, %8, %9, %10, %11}, {%12, %13, %14, %15}, %16, p, 1, 1, %18;\n}\n"
        : "+f"(d[0]), "+f"(d[1]), "+f"(d[2]), "+f"(d[3]), "+f"(d[4]), "+f"(d[5]), "+f"(d[6]), "+f"(d[7]), "+f"(d[8]), "+f"(d[9]), "+f"(d[10]), "+f"(d[11])
        : "r"(a0), "r"(a1), "r"(a2), "r"(a3), "l"(db), "r"(sc), "n"(TB));
}
template <int TB> __device__ __forceinline__ void wgmma_rs_n64(float (&d)[32], uint32_t a0, uint32_t a1, uint32_t a2, uint32_t a3, uint64_t db, int sc) {
    asm volatile("{\n.reg .pred p;\nsetp.ne.b32 p, %37, 0;\n"
        "wgmma.mma_async.sync.aligned.m64n64k16.f32.bf16.bf16 {%0, %1, %2, %3, %4, %5, %6, %7, %8, %9, %10, %11, %12, %13, %14, %15, %16, %17, %18, %19, %20, %21, %22, %23, %24, %25, %26, %27, %28, %29, %30, %31}, {%32, %33, %34, %35}, %36, p, 1, 1, %38;\n}\n"
        : "+f"(d[0]), "+f"(d[1]), "+f"(d[2]), "+f"(d[3]), "+f"(d[4]), "+f"(d[5]), "+f"(d[6]), "+f"(d[7]), "+f"(d[8]), "+f"(d[9]), "+f"(d[10]), "+f"(d[11]), "+f"(d[12]), "+f"(d[13]), "+f"(d[14]), "+f"(d[15]), "+f"(d[16]), "+f"(d[17]), "+f"(d[18]), "+f"(d[19]), "+f"(d[20]), "+f"(d[21]), "+f"(d[22]), "+f"(d[23]), "+f"(d[24]), "+f"(d[25]), "+f"(d[26]), "+f"(d[27]), "+f"(d[28]), "+f"(d[29]), "+f"(d[30]), "+f"(d[31])
        : "r"(a0), "r"(a1), "r"(a2), "r"(a3), "l"(db), "r"(sc), "n"(TB));
}
template <int TB> __device__ __forceinline__ void wgmma_rs_n128(float (&d)[64], uint32_t a0, uint32_t a1, uint32_t a2, uint32_t a3, uint64_t db, int sc) {
    asm volatile("{\n.reg .pred p;\nsetp.ne.b32 p, %69, 0;\n"
        "wgmma.mma_async.sync.aligned.m64n128k16.f32.bf16.bf16 {%0, %1, %2, %3, %4, %5, %6, %7, %8, %9, %10, %11, %12, %13, %14, %15, %16, %17, %18, %19, %20, %21, %22, %23, %24, %25, %26, %27, %28, %29, %30, %31, %32, %33, %34, %35, %36, %37, %38, %39, %40, %41, %42, %43, %44, %45, %46, %47, %48, %49, %50, %51, %52, %53, %54, %55, %56, %57, %58, %59, %60, %61, %62, %63}, {%64, %65, %66, %67}, %68, p, 1, 1, %70;\n}\n"
        : "+f"(d[0]), "+f"(d[1]), "+f"(d[2]), "+f"(d[3]), "+f"(d[4]), "+f"(d[5]), "+f"(d[6]), "+f"(d[7]), "+f"(d[8]), "+f"(d[9]), "+f"(d[10]), "+f"(d[11]), "+f"(d[12]), "+f"(d[13]), "+f"(d[14]), "+f"(d[15]), "+f"(d[16]), "+f"(d[17]), "+f"(d[18]), "+f"(d[19]), "+f"(d[20]), "+f"(d[21]), "+f"(d[22]), "+f"(d[23]), "+f"(d[24]), "+f"(d[25]), "+f"(d[26]), "+f"(d[27]), "+f"(d[28]), "+f"(d[29]), "+f"(d[30]), "+f"(d[31]), "+f"(d[32]), "+f"(d[33]), "+f"(d[34]), "+f"(d[35]), "+f"(d[36]), "+f"(d[37]), "+f"(d[38]), "+f"(d[39]), "+f"(d[40]), "+f"(d[41]), "+f"(d[42]), "+f"(d[43]), "+f"(d[44]), "+f"(d[45]), "+f"(d[46]), "+f"(d[47]), "+f"(d[48]), "+f"(d[49]), "+f"(d[50]), "+f"(d[51]), "+f"(d[52]), "+f"(d[53]), "+f"(d[54]), "+f"(d[55]), "+f"(d[56]), "+f"(d[57]), "+f"(d[58]), "+f"(d[59]), "+f"(d[60]), "+f"(d[61]), "+f"(d[62]), "+f"(d[63])
        : "r"(a0), "r"(a1), "r"(a2), "r"(a3), "l"(db), "r"(sc), "n"(TB));
}

constexpr int P_NST = 6;
constexpr int P_A_BYTES = 9 * 8192;
constexpr int P_B_STAGE = 3 * 8192;
constexpr int P_SMEM = P_A_BYTES + P_NST * P_B_STAGE + 256 + 256;

template <int NB>
__device__ __forceinline__ void stage_tile(const uint32_t (&pk)[NB * 2], uint32_t base, int w, int lane) {
    const int r = w * 16 + (lane & 7) + ((lane >> 3) & 1) * 8;
#pragma unroll
    for (int b = 0; b < NB; b += 2) {
        const uint32_t a = base + (b >> 3) * 8192 + r * 128 + ((((b & 7) + (lane >> 4)) ^ (r & 7)) << 4);
        stmatrix_x4(a, pk[2 * b], pk[2 * b + 1], pk[2 * b + 2], pk[2 * b + 3]);
    }
}

__device__ __forceinline__ uint32_t hsub2_bf16(uint32_t a, uint32_t b) { uint32_t r; asm("sub.rn.bf16x2 %0, %1, %2;" : "=r"(r) : "r"(a), "r"(b)); return r; }

constexpr int KV_RAW = DM * 18 * 2;
constexpr int Q_THREADS = 416;

__device__ __forceinline__ void proj_mma(float (&acc)[32], int wg, uint32_t fullB, uint32_t emptyB, uint32_t fullA, bool wait_a, int lane) {
    const uint64_t dA = cdesc(0, 16, 1024, 1), dB = cdesc(P_A_BYTES, 8192, 1024, 1) + wg * 512;
#pragma unroll 1
    for (int kb = 0; kb < 9; kb++) {
        const int s = kb >= P_NST ? kb - P_NST : kb;
        if (wait_a) mbar_wait(fullA + kb * 8, 0);
        mbar_wait(fullB + s * 8, kb >= P_NST ? 1 : 0);
        wg_fence();
#pragma unroll
        for (int ks = 0; ks < 4; ks++) wgmma_ss_n64<1>(acc, dA + (kb * 512 + ks * 2), dB + (s * (P_B_STAGE >> 4) + ks * 128), (kb | ks) != 0);
        wg_commit();
        if (kb < 4) {
            wg_wait<1>();
            if (kb >= 1 && lane == 0) mbar_arrive(emptyB + (kb - 1) * 8);
        }
    }
    wg_wait<0>();
    pin(acc);
}

__global__ void __launch_bounds__(Q_THREADS, 1)
k_qkv(const __grid_constant__ CUtensorMap tmWq, const __grid_constant__ CUtensorMap tmQ, const __nv_bfloat16* __restrict__ x, const __nv_bfloat16* __restrict__ wk, const __nv_bfloat16* __restrict__ wv) {
    extern __shared__ __align__(1024) uint8_t smem[];
    const uint32_t sA = smem_u32(smem), sB = sA + P_A_BYTES, bars = sB + P_NST * P_B_STAGE;
    const uint32_t fullB = bars, emptyB = bars + 64, fullX = bars + 128, fullW = bars + 136;
    float* s_rstd = reinterpret_cast<float*>(smem + P_A_BYTES + P_NST * P_B_STAGE + 256);
    const int tid = threadIdx.x, warp = __shfl_sync(~0u, tid >> 5, 0), lane = tid & 31;
    const bool isQ = blockIdx.x < 96;
    const int m = isQ ? blockIdx.x / 3 : blockIdx.x - 96, cg = blockIdx.x % 3;
    if (warp == 12) {
        if (elect_one()) {
            mbar_init(fullX, 1);
            bar_init_fence();
            mbar_expect(fullX, P_A_BYTES);
            bulk_g2s(sA, x + (size_t)m * 64 * DM, P_A_BYTES, fullX);
            prefetch_map(&tmWq); prefetch_map(&tmQ);
            for (int i = 0; i < P_NST; i++) { mbar_init(fullB + i * 8, 1); mbar_init(emptyB + i * 8, 12); }
            mbar_init(fullW, 1);
            bar_init_fence();
            if (isQ) {
                for (int kb = 0; kb < P_NST; kb++) {
                    mbar_expect(fullB + kb * 8, P_B_STAGE);
                    for (int a = 0; a < 3; a++) tma_2d(sB + kb * P_B_STAGE + a * 8192, &tmWq, cg * 192 + a * 64, kb * 64, fullB + kb * 8);
                }
            } else {
                mbar_expect(fullW, 2 * KV_RAW);
                bulk_g2s(sB + 3 * P_B_STAGE, wk, KV_RAW, fullW);
                bulk_g2s(sB + 3 * P_B_STAGE + KV_RAW, wv, KV_RAW, fullW);
            }
        }
        __syncwarp();
    }
    check_smem_base(sA);
    __syncthreads();
    pdl_launch();
    if (warp == 12) {
        if (isQ && elect_one()) {
            for (int kb = P_NST; kb < 9; kb++) {
                const int s = kb - P_NST;
                mbar_wait(emptyB + s * 8, 0);
                mbar_expect(fullB + s * 8, P_B_STAGE);
                for (int a = 0; a < 3; a++) tma_2d(sB + s * P_B_STAGE + a * 8192, &tmWq, cg * 192 + a * 64, kb * 64, fullB + s * 8);
            }
        }
        return;
    }
    if (warp < 8) {
        const int row = tid >> 2, q = tid & 3, h0 = (row & 1) * 4;
        mbar_wait(fullX, 0);
        uint4 v[18];
        const uint32_t ra = sA + row * 1152 + (q + h0) * 16, rb = sA + row * 1152 + (q + 4 - h0) * 16;
#pragma unroll
        for (int kb = 0; kb < 9; kb++) {
            asm volatile("ld.shared.v4.b32 {%0, %1, %2, %3}, [%4];" : "=r"(v[2 * kb].x), "=r"(v[2 * kb].y), "=r"(v[2 * kb].z), "=r"(v[2 * kb].w) : "r"(ra + kb * 128));
            asm volatile("ld.shared.v4.b32 {%0, %1, %2, %3}, [%4];" : "=r"(v[2 * kb + 1].x), "=r"(v[2 * kb + 1].y), "=r"(v[2 * kb + 1].z), "=r"(v[2 * kb + 1].w) : "r"(rb + kb * 128));
        }
        float sum = 0.f, sum2 = 0.f, sq = 0.f, sq2 = 0.f;
#pragma unroll
        for (int i = 0; i < 18; i++) {
            const uint32_t w[4] = {v[i].x, v[i].y, v[i].z, v[i].w};
#pragma unroll
            for (int j = 0; j < 4; j++) { const float a = bf_lo(w[j]), b = bf_hi(w[j]); sum += a; sum2 += b; sq = fmaf(a, a, sq); sq2 = fmaf(b, b, sq2); }
        }
        named_sync(1, 256);
        sum += sum2; sq += sq2;
        sum += __shfl_xor_sync(~0u, sum, 1); sum += __shfl_xor_sync(~0u, sum, 2);
        sq += __shfl_xor_sync(~0u, sq, 1); sq += __shfl_xor_sync(~0u, sq, 2);
        const float mean = sum * (1.0f / DM);
        if (q == 0) s_rstd[row] = rsqrtf(fmaxf(sq * (1.0f / DM) - mean * mean, 0.f) + LN_EPS);
        const uint32_t mhi = pack_bf16(mean, mean);
        const float rem = mean - bf_lo(mhi);
        const uint32_t mlo = pack_bf16(rem, rem);
        const uint32_t wa = sA + row * 128 + (((q + h0) ^ (row & 7)) << 4), wb = sA + row * 128 + (((q + 4 - h0) ^ (row & 7)) << 4);
#pragma unroll
        for (int i = 0; i < 18; i++) {
            const uint32_t o0 = hsub2_bf16(hsub2_bf16(v[i].x, mhi), mlo), o1 = hsub2_bf16(hsub2_bf16(v[i].y, mhi), mlo);
            const uint32_t o2 = hsub2_bf16(hsub2_bf16(v[i].z, mhi), mlo), o3 = hsub2_bf16(hsub2_bf16(v[i].w, mhi), mlo);
            asm volatile("st.shared.v4.b32 [%0], {%1, %2, %3, %4};" ::"r"(((i & 1) ? wb : wa) + (i >> 1) * 8192), "r"(o0), "r"(o1), "r"(o2), "r"(o3) : "memory");
        }
    } else if (!isQ) {
        mbar_wait(fullW, 0);
        const uint32_t* raw = reinterpret_cast<const uint32_t*>(smem + P_A_BYTES + 3 * P_B_STAGE);
#pragma unroll 3
        for (int r = tid - 256; r < 2 * DM; r += 128) {
            uint32_t wr[9];
#pragma unroll
            for (int i = 0; i < 9; i++) wr[i] = raw[r * 9 + i];
            const int sel = r >= DM, k = r - sel * DM;
            uint8_t* dst = smem + P_A_BYTES + sel * 3 * 9216 + (k >> 3) * 128 + (k & 7) * 16;
            *reinterpret_cast<uint4*>(dst) = make_uint4(wr[0], wr[1], wr[2], wr[3]);
            *reinterpret_cast<uint4*>(dst + 9216) = make_uint4(wr[4], wr[5], wr[6], wr[7]);
            *reinterpret_cast<uint32_t*>(dst + 2 * 9216) = wr[8];
        }
    }
    proxy_fence();
    named_sync(2, 384);
    const int wg = warp >> 2, w = warp & 3, g = lane >> 2, t = lane & 3;
    const float rs0 = s_rstd[w * 16 + g], rs1 = s_rstd[w * 16 + g + 8];
    if (isQ) {
        const float c0 = rs0 * Q_SCALE, c1 = rs1 * Q_SCALE;
        float acc[32];
        proj_mma(acc, wg, fullB, emptyB, 0, false, lane);
        uint32_t pk[16];
#pragma unroll
        for (int i = 0; i < 8; i++) { pk[2 * i] = pack_bf16(acc[4 * i] * c0, acc[4 * i + 1] * c0); pk[2 * i + 1] = pack_bf16(acc[4 * i + 2] * c1, acc[4 * i + 3] * c1); }
        named_sync(2, 384);
        stage_tile<8>(pk, sA + wg * 8192, w, lane);
        proxy_fence();
        named_sync(3 + wg, 128);
        if (w == 0 && elect_one()) {
            tma_st_2d(&tmQ, cg * 192 + wg * 64, m * 64, sA + wg * 8192);
            bulk_commit();
            bulk_wait_all();
        }
    } else if (wg < 2) {
        float acc[12];
        const uint64_t dA = cdesc(0, 16, 1024, 1), dB = cdesc(P_A_BYTES, 128, 9216, 0) + wg * (3 * 9216 >> 4);
#pragma unroll
        for (int i = 0; i < 12; i++) acc[i] = 0.f;
        pin(acc);
        wg_fence();
#pragma unroll 1
        for (int kb = 0; kb < 9; kb++) {
#pragma unroll
            for (int ks = 0; ks < 4; ks++) wgmma_ss_n24<1>(acc, dA + (kb * 512 + ks * 2), dB + (kb * 4 + ks) * 16, 1);
        }
        wg_commit();
        wg_wait<0>();
        pin(acc);
        uint32_t pk[6];
#pragma unroll
        for (int b = 0; b < 3; b++) { pk[2 * b] = pack_bf16(acc[4 * b] * rs0, acc[4 * b + 1] * rs0); pk[2 * b + 1] = pack_bf16(acc[4 * b + 2] * rs1, acc[4 * b + 3] * rs1); }
        float n0 = 0.f, n1 = 0.f, vm = 0.f;
#pragma unroll
        for (int b = 0; b < 3; b++) {
            if (b < 2 || t == 0) {
                const float a = bf_lo(pk[2 * b]), c = bf_hi(pk[2 * b]), d = bf_lo(pk[2 * b + 1]), e = bf_hi(pk[2 * b + 1]);
                n0 = fmaf(a, a, fmaf(c, c, n0)); n1 = fmaf(d, d, fmaf(e, e, n1));
            }
        }
        n0 += __shfl_xor_sync(~0u, n0, 1); n0 += __shfl_xor_sync(~0u, n0, 2);
        n1 += __shfl_xor_sync(~0u, n1, 1); n1 += __shfl_xor_sync(~0u, n1, 2);
        vm = fmaxf(n0, n1);
        if (!(n0 == n0) || !(n1 == n1)) vm = __int_as_float(0x7F800000);
#pragma unroll
        for (int o = 4; o < 32; o <<= 1) vm = fmaxf(vm, __shfl_xor_sync(~0u, vm, o));
        if (t != 0) {
            uint32_t lo, hi;
            if (wg == 0) {
                const int grp = m * 8 + w * 2;
                const uint32_t c = t == 1 ? 0x42FE3F80u   : (t == 2 ? 0x00003BC0u   : 0u);
                lo = ((POLY_MASK >> (grp & 15)) & 1) ? c : 0u;
                hi = ((POLY_MASK >> ((grp + 1) & 15)) & 1) ? c : 0u;
            } else {
                lo = hi = t == 1 ? 0x00003F80u : 0u;
            }
            pk[4] = lo; pk[5] = hi;
        }
        uint32_t* dst = reinterpret_cast<uint32_t*>(wg == 0 ? g_kc : g_vc) + (m * 8 + w * 2) * 96 + g * 4 + t;
#pragma unroll
        for (int b = 0; b < 3; b++) { dst[b * 32] = pk[2 * b]; dst[96 + b * 32] = pk[2 * b + 1]; }
        if (lane == 0) g_kmax[m * 8 + warp] = (wg == 0) ? vm : (vm <= 1e24f ? 0.f : __int_as_float(0x7F800000));
    }
}

constexpr int A_THREADS = 512;
constexpr int A_NPIECE = 8;
constexpr int A_OFF_Q = 2 * KV_BYTES;
constexpr int A_OFF_BAR = A_OFF_Q + 8 * 4096;
constexpr int A_SMEM = A_OFF_BAR + 128;

__device__ __forceinline__ uint32_t exp2_pair_fixed(float lo, float hi, uint32_t dep) {
    const uint32_t G = __byte_perm(__float_as_uint(lo), __float_as_uint(hi), 0x5410);
    uint32_t Hh;
    asm("lop3.b32 %0, %1, 0x007F007F, %2, 0xC0;" : "=r"(Hh) : "r"(G), "r"(dep));
    const uint32_t tt = hfma2(Hh, 0xF96BF96Bu, 0x358C358Cu);
    return G - hfma2(tt, Hh, 0u);
}

__global__ void __launch_bounds__(A_THREADS, 1)
k_attn(__nv_bfloat16* __restrict__ out) {
    extern __shared__ __align__(1024) uint8_t smem[];
    pdl_launch();
    const uint32_t sK = smem_u32(smem), sV = sK + KV_BYTES, bars = sK + A_OFF_BAR;
    const int tid = threadIdx.x;
    check_smem_base(sK);
    if (tid == 0) {
        for (int i = 0; i < A_NPIECE; i++) mbar_init(bars + i * 8, 1);
        bar_init_fence();
    }
    __syncthreads();
    pdl_wait();
    const int wg = __shfl_sync(~0u, tid >> 7, 0), w = (tid >> 5) & 3, lane = tid & 31, g = lane >> 2, t = lane & 3;
    const uint32_t* q32 = reinterpret_cast<const uint32_t*>(g_q);
    int row = (blockIdx.x * 8 + wg) * 64 + w * 16 + g;
    uint32_t nq[2][6];
#pragma unroll
    for (int r = 0; r < 2; r++) {
        const uint32_t* q = q32 + (row + r * 256) * 9;
        nq[r][0] = q[t]; nq[r][1] = q[72 + t]; nq[r][2] = q[4 + t]; nq[r][3] = q[76 + t]; nq[r][4] = q[8]; nq[r][5] = q[80];
    }
    constexpr int PB = KV_BYTES / A_NPIECE;
    const float4 km0 = reinterpret_cast<const float4*>(g_kmax)[lane], km1 = reinterpret_cast<const float4*>(g_kmax)[32 + lane];
    if (tid < 32 && elect_one()) {
        for (int i = 0; i < 2; i++) {
            mbar_expect(bars + i * 8, 2 * PB);
            bulk_g2s(sK + i * PB, reinterpret_cast<const char*>(g_kc) + i * PB, PB, bars + i * 8);
            bulk_g2s(sV + i * PB, reinterpret_cast<const char*>(g_vc) + i * PB, PB, bars + i * 8);
        }
    }
    float kmax2 = fmaxf(fmaxf(fmaxf(km0.x, km0.y), fmaxf(km0.z, km0.w)), fmaxf(fmaxf(km1.x, km1.y), fmaxf(km1.z, km1.w)));
#pragma unroll
    for (int o = 1; o < 32; o <<= 1) kmax2 = fmaxf(kmax2, __shfl_xor_sync(~0u, kmax2, o));
    if (tid < 32 && elect_one()) {
        for (int i = 2; i < A_NPIECE; i++) {
            mbar_expect(bars + i * 8, 2 * PB);
            bulk_g2s(sK + i * PB, reinterpret_cast<const char*>(g_kc) + i * PB, PB, bars + i * 8);
            bulk_g2s(sV + i * PB, reinterpret_cast<const char*>(g_vc) + i * PB, PB, bars + i * 8);
        }
    }
    uint32_t vote = 0;
#pragma unroll
    for (int r = 0; r < 2; r++) {
        const uint32_t (&q)[6] = nq[r];
        const float a0 = bf_lo(q[0]), a1 = bf_hi(q[0]), a2 = bf_lo(q[2]), a3 = bf_hi(q[2]);
        const float b0 = bf_lo(q[1]), b1 = bf_hi(q[1]), b2 = bf_lo(q[3]), b3 = bf_hi(q[3]);
        float n0 = a0 * a0 + a1 * a1 + a2 * a2 + a3 * a3, n1 = b0 * b0 + b1 * b1 + b2 * b2 + b3 * b3;
        if (t == 0) {
            const float c0 = bf_lo(q[4]), c1 = bf_hi(q[4]), d0 = bf_lo(q[5]), d1 = bf_hi(q[5]);
            n0 += c0 * c0 + c1 * c1; n1 += d0 * d0 + d1 * d1;
        }
        n0 += __shfl_xor_sync(~0u, n0, 1); n0 += __shfl_xor_sync(~0u, n0, 2);
        n1 += __shfl_xor_sync(~0u, n1, 1); n1 += __shfl_xor_sync(~0u, n1, 2);
        const bool unsafe = !(fmaxf(n0, n1) * kmax2 <= FAST_BOUND * FAST_BOUND) || !(n0 == n0) || !(n1 == n1);
        vote |= (__any_sync(~0u, unsafe) ? 1u : 0u) << r;
        const uint32_t cst = t == 1 ? 0x3F804780u : (t == 2 ? 0x00003F80u : 0u);
        const uint32_t sQ = sK + A_OFF_Q + (r * 4 + wg) * 4096 + (w * 2) * 512 + g * 16 + t * 4;
        asm volatile("st.shared.b32 [%0], %1;" ::"r"(sQ), "r"(q[0]) : "memory");
        asm volatile("st.shared.b32 [%0], %1;" ::"r"(sQ + 512), "r"(q[1]) : "memory");
        asm volatile("st.shared.b32 [%0], %1;" ::"r"(sQ + 128), "r"(q[2]) : "memory");
        asm volatile("st.shared.b32 [%0], %1;" ::"r"(sQ + 640), "r"(q[3]) : "memory");
        asm volatile("st.shared.b32 [%0], %1;" ::"r"(sQ + 256), "r"(t == 0 ? q[4] : cst) : "memory");
        asm volatile("st.shared.b32 [%0], %1;" ::"r"(sQ + 768), "r"(t == 0 ? q[5] : cst) : "memory");
        asm volatile("st.shared.b32 [%0], %1;" ::"r"(sQ + 384), "r"(0u) : "memory");
        asm volatile("st.shared.b32 [%0], %1;" ::"r"(sQ + 896), "r"(0u) : "memory");
    }
    const uint32_t sVote = bars + 64 + wg * 16;
    if (lane == 0) asm volatile("st.shared.b32 [%0], %1;" ::"r"(sVote + w * 4), "r"(vote) : "memory");
    proxy_fence();
    named_sync(wg + 1, 128);
    uint32_t unsafe_mask;
    {
        uint32_t v0, v1, v2, v3;
        asm volatile("ld.shared.v4.b32 {%0, %1, %2, %3}, [%4];" : "=r"(v0), "=r"(v1), "=r"(v2), "=r"(v3) : "r"(sVote));
        unsafe_mask = __shfl_sync(~0u, v0 | v1 | v2 | v3, 0);
    }
    if (unsafe_mask) {
#pragma unroll
        for (int r = 0; r < 2; r++) {
            if (((unsafe_mask >> r) & 1) && t != 0) {
                const uint32_t sQ = sK + A_OFF_Q + (r * 4 + wg) * 4096 + (w * 2) * 512 + g * 16 + t * 4;
                asm volatile("st.shared.b32 [%0], %1;" ::"r"(sQ + 256), "r"(0u) : "memory");
                asm volatile("st.shared.b32 [%0], %1;" ::"r"(sQ + 768), "r"(0u) : "memory");
            }
        }
        proxy_fence();
        named_sync(wg + 1, 128);
    }
#pragma unroll 1
    for (int rep = 0; rep < 2; rep++, row += 256) {
        if (rep == 1) {
            uint4* z = reinterpret_cast<uint4*>(out + (size_t)blockIdx.x * 16 * DM) + tid;
            z[0] = make_uint4(0u, 0u, 0u, 0u); z[A_THREADS] = make_uint4(0u, 0u, 0u, 0u);
            if (tid < 16 * DM * 2 / 16 - 2 * A_THREADS) z[2 * A_THREADS] = make_uint4(0u, 0u, 0u, 0u);
        }
        const uint32_t any_unsafe = (unsafe_mask >> rep) & 1;
        const uint64_t dQ0 = cdesc(A_OFF_Q, 128, 512, 0) + (rep * 4 + wg) * 256, dQ1 = dQ0 + 16;
        float o[12];
#pragma unroll
        for (int i = 0; i < 12; i++) o[i] = 0.f;
        pin(o);
        uint64_t dK0 = cdesc(0, 128, 384, 0), dK1 = cdesc(256, 0, 384, 0), dV = cdesc(KV_BYTES, 384, 128, 0);
        if (!any_unsafe) {
            float s[64];
#pragma unroll 1
            for (int j = 0; j < 16; j++) {
                if (rep == 0 && (j & 1) == 0) mbar_wait(bars + (j >> 1) * 8, 0);
                wg_fence();
                wgmma_ss_n128<0>(s, dQ0, dK0, 0);
                wgmma_ss_n128<0>(s, dQ1, dK1, 1);
                wg_commit();
                dK0 += 16 * 384 >> 4; dK1 += 16 * 384 >> 4;
                wg_wait<0>();
                pin(s);
                uint32_t p[32];
                {
                    constexpr int NP = 2 * __builtin_popcount(POLY_MASK), NM = 32 - NP;
                    float e[64];
#pragma unroll
                    for (int i = 0; i < 32; i++)
                        if (!((POLY_MASK >> (i >> 1)) & 1)) { e[2 * i] = ex2(s[2 * i]); e[2 * i + 1] = ex2(s[2 * i + 1]); p[i] = pack_bf16(e[2 * i], e[2 * i + 1]); }
                    int ip = 0;
#pragma unroll
                    for (int i = 0; i < 32; i++) {
                        if ((POLY_MASK >> (i >> 1)) & 1) {
                            const int mm = (ip * 2 * NM) / NP - CHAIN;
                            uint32_t dep = 0;
                            if (CHAIN > 0 && mm >= 0) {
                                int cnt = 0;
#pragma unroll
                                for (int q = 0; q < 32; q++)
                                    if (!((POLY_MASK >> (q >> 1)) & 1)) { if (cnt == (mm >> 1)) dep = __float_as_uint(e[2 * q + (mm & 1)]); cnt++; }
                            }
                            p[i] = exp2_pair_fixed(s[2 * i], s[2 * i + 1], dep);
                            ip++;
                        }
                    }
                }
                pin(p);
                wg_fence();
#pragma unroll
                for (int k = 0; k < 8; k++) wgmma_rs_n24<1>(o, p[4 * k], p[4 * k + 1], p[4 * k + 2], p[4 * k + 3], dV + k * 48, 1);
                wg_commit();
                dV += 16 * 384 >> 4;
                wg_wait<0>();
            }
        } else {
            float s[64];
            float m0 = -INFINITY, m1 = -INFINITY;
#pragma unroll 1
            for (int j = 0; j < 16; j++) {
                if (rep == 0 && (j & 1) == 0) mbar_wait(bars + (j >> 1) * 8, 0);
                wg_fence();
                wgmma_ss_n128<0>(s, dQ0, dK0, 0);
                wgmma_ss_n128<0>(s, dQ1, dK1, 1);
                wg_commit();
                dK0 += 16 * 384 >> 4; dK1 += 16 * 384 >> 4;
                wg_wait<0>();
                pin(s);
                float x0m = m0, x1m = m1;
#pragma unroll
                for (int b = 0; b < 16; b++) { x0m = fmaxf(x0m, fmaxf(s[4 * b], s[4 * b + 1])); x1m = fmaxf(x1m, fmaxf(s[4 * b + 2], s[4 * b + 3])); }
                x0m = fmaxf(x0m, __shfl_xor_sync(~0u, x0m, 1)); x0m = fmaxf(x0m, __shfl_xor_sync(~0u, x0m, 2));
                x1m = fmaxf(x1m, __shfl_xor_sync(~0u, x1m, 1)); x1m = fmaxf(x1m, __shfl_xor_sync(~0u, x1m, 2));
                const float c0 = ex2(m0 - x0m), c1 = ex2(m1 - x1m);
                m0 = x0m; m1 = x1m;
#pragma unroll
                for (int b = 0; b < 3; b++) { o[4 * b] *= c0; o[4 * b + 1] *= c0; o[4 * b + 2] *= c1; o[4 * b + 3] *= c1; }
                uint32_t p[32];
#pragma unroll
                for (int b = 0; b < 16; b++) {
                    p[2 * b] = pack_bf16(ex2(s[4 * b] - m0), ex2(s[4 * b + 1] - m0));
                    p[2 * b + 1] = pack_bf16(ex2(s[4 * b + 2] - m1), ex2(s[4 * b + 3] - m1));
                }
                pin(p); pin(o);
                wg_fence();
#pragma unroll
                for (int k = 0; k < 8; k++) wgmma_rs_n24<1>(o, p[4 * k], p[4 * k + 1], p[4 * k + 2], p[4 * k + 3], dV + k * 48, 1);
                wg_commit();
                dV += 16 * 384 >> 4;
                wg_wait<0>();
            }
        }
        pin(o);
        const float l0 = __shfl_sync(~0u, o[8], (lane & ~3) | 1), l1 = __shfl_sync(~0u, o[10], (lane & ~3) | 1);
        const float i0 = 1.0f / l0, i1 = 1.0f / l1;
        uint32_t* o32 = reinterpret_cast<uint32_t*>(g_o);
        o32[row * 9 + t] = pack_bf16(o[0] * i0, o[1] * i0);
        o32[(row + 8) * 9 + t] = pack_bf16(o[2] * i1, o[3] * i1);
        o32[row * 9 + 4 + t] = pack_bf16(o[4] * i0, o[5] * i0);
        o32[(row + 8) * 9 + 4 + t] = pack_bf16(o[6] * i1, o[7] * i1);
        if (t == 0) { o32[row * 9 + 8] = pack_bf16(o[8] * i0, o[9] * i0); o32[(row + 8) * 9 + 8] = pack_bf16(o[10] * i1, o[11] * i1); }
    }
}

constexpr int O_THREADS = 416;
constexpr int O_OFF_STAT = P_A_BYTES + P_NST * P_B_STAGE + 256;
constexpr int O_SMEM = O_OFF_STAT + 9 * 64 * 8;

__global__ void __cluster_dims__(3, 1, 1) __launch_bounds__(O_THREADS, 1)
k_oproj(const __grid_constant__ CUtensorMap tmO, const __grid_constant__ CUtensorMap tmWo, const __grid_constant__ CUtensorMap tmX2, const __grid_constant__ CUtensorMap tmH, const __nv_bfloat16* __restrict__ x, const __nv_bfloat16* __restrict__ w1) {
    extern __shared__ __align__(1024) uint8_t smem[];
    const uint32_t sA = smem_u32(smem), sB = sA + P_A_BYTES, bars = sB + P_NST * P_B_STAGE;
    const uint32_t fullB = bars, emptyB = bars + 64, fullA = bars + 128;
    const int tid = threadIdx.x, warp = __shfl_sync(~0u, tid >> 5, 0), lane = tid & 31;
    const int m = blockIdx.x / 3, cg = blockIdx.x % 3;
    check_smem_base(sA);
    if (tid == 0) {
        prefetch_map(&tmO); prefetch_map(&tmWo); prefetch_map(&tmX2); prefetch_map(&tmH);
        for (int i = 0; i < P_NST; i++) { mbar_init(fullB + i * 8, 1); mbar_init(emptyB + i * 8, 12); }
        for (int i = 0; i < 9; i++) mbar_init(fullA + i * 8, 1);
        bar_init_fence();
        for (int kb = 0; kb < 9; kb++) mbar_expect(fullA + kb * 8, 8192);
    }
    __syncthreads();
    pdl_launch();
    if (warp == 12) {
        if (elect_one()) {
            for (int kb = 0; kb < 9; kb++) {
                const int s = kb >= P_NST ? kb - P_NST : kb;
                if (kb == 2) {
                    pdl_wait();
                    for (int ka = 0; ka < 9; ka++) tma_2d(sA + ka * 8192, &tmO, ka * 64, m * 64, fullA + ka * 8);
                }
                if (kb >= P_NST) mbar_wait(emptyB + s * 8, 0);
                mbar_expect(fullB + s * 8, P_B_STAGE);
                for (int a = 0; a < 3; a++) tma_2d(sB + s * P_B_STAGE + a * 8192, &tmWo, cg * 192 + a * 64, kb * 64, fullB + s * 8);
            }
            for (int i = 0; i < 6; i++) prefetch_l2(reinterpret_cast<const char*>(w1) + (size_t)blockIdx.x * (FF * DM * 2 / 96) + i * 9216, 9216);
        }
        return;
    }
    const int wg = warp >> 2, w = warp & 3, g = lane >> 2, t = lane & 3;
    uint32_t xr[16];
    {
        const uint32_t* x32 = reinterpret_cast<const uint32_t*>(x) + (((m * 64 + w * 16 + g) * DM + cg * 192 + wg * 64 + 2 * t) >> 1);
#pragma unroll
        for (int b = 0; b < 8; b++) { xr[2 * b] = __ldg(x32 + b * 4); xr[2 * b + 1] = __ldg(x32 + b * 4 + 4 * DM); }
    }
    float acc[32];
    proj_mma(acc, wg, fullB, emptyB, fullA, true, lane);
    named_sync(1, 384);
    float s0 = 0.f, q0 = 0.f, s1 = 0.f, q1 = 0.f;
#pragma unroll
    for (int b = 0; b < 8; b++) {
        const uint32_t xa = xr[2 * b], xb = xr[2 * b + 1];
        const uint32_t ha = pack_bf16(acc[4 * b] + bf_lo(xa), acc[4 * b + 1] + bf_hi(xa));
        const uint32_t hb = pack_bf16(acc[4 * b + 2] + bf_lo(xb), acc[4 * b + 3] + bf_hi(xb));
        xr[2 * b] = ha; xr[2 * b + 1] = hb;
        const float a = bf_lo(ha), c = bf_hi(ha), d = bf_lo(hb), e = bf_hi(hb);
        s0 += a + c; q0 = fmaf(a, a, fmaf(c, c, q0));
        s1 += d + e; q1 = fmaf(d, d, fmaf(e, e, q1));
    }
    s0 += __shfl_xor_sync(~0u, s0, 1); s0 += __shfl_xor_sync(~0u, s0, 2);
    q0 += __shfl_xor_sync(~0u, q0, 1); q0 += __shfl_xor_sync(~0u, q0, 2);
    s1 += __shfl_xor_sync(~0u, s1, 1); s1 += __shfl_xor_sync(~0u, s1, 2);
    q1 += __shfl_xor_sync(~0u, q1, 1); q1 += __shfl_xor_sync(~0u, q1, 2);
    const int r = w * 16 + g;
    const uint32_t sStat = sA + O_OFF_STAT;
    if (t < 3) {
        uint32_t dst;
        asm("mapa.shared::cluster.u32 %0, %1, %2;" : "=r"(dst) : "r"(sStat + ((cg * 3 + wg) * 64 + r) * 8), "r"(t));
        asm volatile("st.shared::cluster.v2.f32 [%0], {%1, %2};" ::"r"(dst), "f"(s0), "f"(q0) : "memory");
        asm volatile("st.shared::cluster.v2.f32 [%0], {%1, %2};" ::"r"(dst + 64), "f"(s1), "f"(q1) : "memory");
    }
    cluster_arrive();
    stage_tile<8>(xr, sA + wg * 8192, w, lane);
    proxy_fence();
    named_sync(2 + wg, 128);
    const bool leader = w == 0 && elect_one();
    if (leader) { tma_st_2d(&tmH, cg * 192 + wg * 64, m * 64, sA + wg * 8192); bulk_commit(); }
    cluster_wait();
    s0 = q0 = s1 = q1 = 0.f;
#pragma unroll
    for (int p = 0; p < 9; p++) {
        float a, b, c, d;
        asm volatile("ld.shared.v2.f32 {%0, %1}, [%2];" : "=f"(a), "=f"(b) : "r"(sStat + (p * 64 + r) * 8));
        asm volatile("ld.shared.v2.f32 {%0, %1}, [%2];" : "=f"(c), "=f"(d) : "r"(sStat + (p * 64 + r + 8) * 8));
        s0 += a; q0 += b; s1 += c; q1 += d;
    }
    const float m0 = s0 * (1.0f / DM), m1 = s1 * (1.0f / DM);
    const float rs0 = rsqrtf(fmaxf(q0 * (1.0f / DM) - m0 * m0, 0.f) + LN_EPS), rs1 = rsqrtf(fmaxf(q1 * (1.0f / DM) - m1 * m1, 0.f) + LN_EPS);
    const float sc0 = 0.5f * rs0, sc1 = 0.5f * rs1, n0 = -m0 * sc0, n1 = -m1 * sc1;
#pragma unroll
    for (int b = 0; b < 8; b++) {
        xr[2 * b] = pack_bf16(fmaf(bf_lo(xr[2 * b]), sc0, n0), fmaf(bf_hi(xr[2 * b]), sc0, n0));
        xr[2 * b + 1] = pack_bf16(fmaf(bf_lo(xr[2 * b + 1]), sc1, n1), fmaf(bf_hi(xr[2 * b + 1]), sc1, n1));
    }
    stage_tile<8>(xr, sA + (3 + wg) * 8192, w, lane);
    proxy_fence();
    named_sync(2 + wg, 128);
    if (leader) {
        tma_st_2d(&tmX2, cg * 192 + wg * 64, m * 64, sA + (3 + wg) * 8192);
        bulk_commit();
        bulk_wait_all();
    }
}

constexpr int F_THREADS = 384;
constexpr int F_NST = 6;
constexpr int F_STAGE = 96 * 128;
constexpr int F_X_BYTES = 9 * 16384;
constexpr int F_OFF_ST = F_X_BYTES;
constexpr int F_OFF_BAR = F_OFF_ST + F_NST * F_STAGE;
constexpr int F_SMEM = F_OFF_BAR + 256;

__device__ __forceinline__ float tanh_hw(float x) { float y; asm("tanh.approx.f32 %0, %1;" : "=f"(y) : "f"(x)); return y; }
__host__ __device__ constexpr int piece_begin(int p) { return p == 0 ? 0 : 3 * p + 1; }
template <int P>
__device__ __forceinline__ void silu_s1(const float (&acc)[32], float (&tmp)[8]) {
#pragma unroll
    for (int i = 2 * piece_begin(P); i < 2 * piece_begin(P + 1); i++) tmp[i - 2 * piece_begin(P)] = tanh_hw(acc[i]);
}
template <int C, int P>
__device__ __forceinline__ void silu_s2(const float (&acc)[32], const float (&tmp)[8], uint32_t (&h1)[144]) {
#pragma unroll
    for (int i = piece_begin(P); i < piece_begin(P + 1); i++) {
        const int k = 2 * (i - piece_begin(P));
        h1[C * 16 + i] = pack_bf16(fmaf(acc[2 * i], tmp[k], acc[2 * i]), fmaf(acc[2 * i + 1], tmp[k + 1], acc[2 * i + 1]));
    }
}
template <int J>
__device__ __forceinline__ void silu_slot_last(const float (&prev)[32], float (&tmp)[2][8], uint32_t (&h1)[144]) {
    if constexpr (J >= 1 && J <= 4) {
#pragma unroll
        for (int i = 0; i < 4; i++) {
            const int q = 4 * (J - 1) + i;
            h1[128 + q] = pack_bf16(fmaf(prev[2 * q], tmp[(J - 1) & 1][2 * i], prev[2 * q]), fmaf(prev[2 * q + 1], tmp[(J - 1) & 1][2 * i + 1], prev[2 * q + 1]));
        }
    }
    if constexpr (J <= 3) {
#pragma unroll
        for (int i = 0; i < 8; i++) tmp[J & 1][i] = tanh_hw(prev[8 * J + i]);
        pin(tmp[J & 1]);
    }
}
template <int C, int J>
__device__ __forceinline__ void silu_slot(const float (&prev)[32], float (&tmp)[2][8], uint32_t (&h1)[144]) {
    if constexpr (J >= 1) silu_s2<C, J - 1>(prev, tmp[(J - 1) & 1], h1);
    if constexpr (J <= 4) { silu_s1<J>(prev, tmp[J & 1]); pin(tmp[J & 1]); }
}

struct FfnPipe {
    uint32_t full, empty;
    int lane;
    __device__ __forceinline__ void acquire(int s, uint32_t ph) const { mbar_wait(full + s * 8, ph); }
    __device__ __forceinline__ void release(int s) const { if (lane == 0) mbar_arrive(empty + s * 8); }
};

template <int C>
__device__ __forceinline__ void ffn_phase1_chunk(float (&cur)[32], float (&prev)[32], uint32_t (&h1)[144], const FfnPipe& pp, uint64_t dx, uint32_t fullX) {
    float tmp[2][8];
    const uint64_t dw = cdesc(F_OFF_ST, 8192, 1024, 1) + blockIdx.y * (C + 1);
    dx += blockIdx.y * C;
#pragma unroll
    for (int j = 0; j < 6; j++) {
        if (C == 0) { mbar_wait(fullX + ((6 * j) >> 2) * 8, 0); mbar_wait(fullX + ((6 * j + 5) >> 2) * 8, 0); }
        pp.acquire(j, C & 1);
        if (j == 0) pin(cur);
        wg_fence();
#pragma unroll
        for (int i = 0; i < 6; i++) {
            const int ks = 6 * j + i;
            wgmma_ss_n64<1>(cur, dx + ((ks >> 2) * 1024 + (ks & 3) * 2), dw + ((j * F_STAGE + i * 2048) >> 4), ks != 0);
        }
        wg_commit();
        if (C > 0 || j > 0) { wg_wait<1>(); pp.release((j + 5) % 6); }
        if (C > 0) {
            constexpr int CP = C > 0 ? C - 1 : 0;
            pin(prev);
            if (j == 0) silu_slot<CP, 0>(prev, tmp, h1);
            if (j == 1) silu_slot<CP, 1>(prev, tmp, h1);
            if (j == 2) silu_slot<CP, 2>(prev, tmp, h1);
            if (j == 3) silu_slot<CP, 3>(prev, tmp, h1);
            if (j == 4) silu_slot<CP, 4>(prev, tmp, h1);
            if (j == 5) silu_slot<CP, 5>(prev, tmp, h1);
        }
    }
}

__device__ __forceinline__ void ffn_stage_chunk(const float (&acc)[32], uint32_t stg, int w, int lane, bool resid, uint32_t fullH) {
    uint32_t pk[16];
    if (resid) {
        mbar_wait(fullH, 0);
        const int r = w * 16 + (lane & 7) + ((lane >> 3) & 1) * 8;
#pragma unroll
        for (int b = 0; b < 8; b += 2) {
            uint32_t h0, h1, h2, h3;
            asm volatile("ldmatrix.sync.aligned.m8n8.x4.shared.b16 {%0, %1, %2, %3}, [%4];" : "=r"(h0), "=r"(h1), "=r"(h2), "=r"(h3) : "r"(stg + r * 128 + (((b + (lane >> 4)) ^ (r & 7)) << 4)) : "memory");
            pk[2 * b] = pack_bf16(acc[4 * b] + bf_lo(h0), acc[4 * b + 1] + bf_hi(h0));
            pk[2 * b + 1] = pack_bf16(acc[4 * b + 2] + bf_lo(h1), acc[4 * b + 3] + bf_hi(h1));
            pk[2 * b + 2] = pack_bf16(acc[4 * b + 4] + bf_lo(h2), acc[4 * b + 5] + bf_hi(h2));
            pk[2 * b + 3] = pack_bf16(acc[4 * b + 6] + bf_lo(h3), acc[4 * b + 7] + bf_hi(h3));
        }
    } else {
#pragma unroll
        for (int i = 0; i < 16; i++) pk[i] = pack_bf16(acc[2 * i], acc[2 * i + 1]);
    }
    stage_tile<8>(pk, stg, w, lane);
}
__device__ __forceinline__ void ffn_reduce_chunk(const CUtensorMap* tmOut, uint32_t stg, int col, int row, int w, int wgid, bool leader) {
    proxy_fence();
    if (w != 0) {
        asm volatile("bar.arrive %0, 128;" ::"r"(2 + wgid) : "memory");
    } else {
        named_sync(2 + wgid, 128);
        if (leader) { tma_red_2d(tmOut, col, row, stg); bulk_commit(); }
    }
}

__device__ __forceinline__ void ffn_load_residual(float (&acc)[32], uint32_t stg, int w, int lane, uint32_t fullH) {
    mbar_wait(fullH, 0);
    const int r = w * 16 + (lane & 7) + ((lane >> 3) & 1) * 8;
#pragma unroll
    for (int b = 0; b < 8; b += 2) {
        uint32_t h0, h1, h2, h3;
        asm volatile("ldmatrix.sync.aligned.m8n8.x4.shared.b16 {%0, %1, %2, %3}, [%4];" : "=r"(h0), "=r"(h1), "=r"(h2), "=r"(h3) : "r"(stg + r * 128 + (((b + (lane >> 4)) ^ (r & 7)) << 4)) : "memory");
        acc[4 * b] = bf_lo(h0); acc[4 * b + 1] = bf_hi(h0); acc[4 * b + 2] = bf_lo(h1); acc[4 * b + 3] = bf_hi(h1);
        acc[4 * b + 4] = bf_lo(h2); acc[4 * b + 5] = bf_hi(h2); acc[4 * b + 6] = bf_lo(h3); acc[4 * b + 7] = bf_hi(h3);
    }
}

template <int MODE>
__device__ __forceinline__ void ffn_phase2_chunk(float (&cur)[32], float (&prev)[32], uint32_t (&h1)[144], const FfnPipe& pp, uint32_t ph, const CUtensorMap* tmOut, uint32_t stg_prev, int col_prev, int row, int w, int lane, int wgid, bool leader,
                                                 bool resid_prev, uint32_t fullH, uint32_t stg_res) {
    const uint64_t dw = cdesc(F_OFF_ST, 8192, 1024, 1) + blockIdx.y * col_prev;
    float tmp[2][8];
#pragma unroll
    for (int j = 0; j < 6; j++) {
        pp.acquire(j, ph);
        if (j == 0) pin(cur);
        if (MODE == 0 && j == 5) pin(h1);
        wg_fence();
#pragma unroll
        for (int i = 0; i < 6; i++) {
            const int f = (6 * j + i) * 4;
            wgmma_rs_n64<1>(cur, h1[f], h1[f + 1], h1[f + 2], h1[f + 3], dw + ((j * F_STAGE + i * 2048) >> 4), MODE == 3 || (j | i) != 0);
        }
        wg_commit();
        wg_wait<1>();
        pp.release((j + 5) % 6);
        if (MODE == 0) {
            pin(prev);
            if (j == 0) silu_slot_last<0>(prev, tmp, h1);
            if (j == 1) silu_slot_last<1>(prev, tmp, h1);
            if (j == 2) silu_slot_last<2>(prev, tmp, h1);
            if (j == 3) silu_slot_last<3>(prev, tmp, h1);
            if (j == 4) silu_slot_last<4>(prev, tmp, h1);
        } else {
            if (j == 0) { pin(prev); ffn_stage_chunk(prev, stg_prev, w, lane, MODE == 3 && resid_prev, fullH); }
            if (j == 1) ffn_reduce_chunk(tmOut, stg_prev, col_prev, row, w, wgid, leader);
            if (MODE == 2 && j == 2) { ffn_load_residual(prev, stg_res, w, lane, fullH); pin(prev); }
        }
    }
}

__global__ void __launch_bounds__(F_THREADS, 1)
k_ffn(const __grid_constant__ CUtensorMap tmX2, const __grid_constant__ CUtensorMap tmW1, const __grid_constant__ CUtensorMap tmW2, const __grid_constant__ CUtensorMap tmOut,
      const __grid_constant__ CUtensorMap tmRes, const __nv_bfloat16* __restrict__ w2) {
    extern __shared__ __align__(1024) uint8_t smem[];
    const uint32_t sX = smem_u32(smem), sSt = sX + F_OFF_ST, bars = sX + F_OFF_BAR;
    const uint32_t full = bars, empty = bars + 64, fullX = bars + 128, fullH = bars + 208;
    const int tid = threadIdx.x, warp = __shfl_sync(~0u, tid >> 5, 0), lane = tid & 31;
    const int m = blockIdx.x >> 3, fs = blockIdx.x & 7;
    check_smem_base(sX);
    if (tid == 0) {
        prefetch_map(&tmW1); prefetch_map(&tmX2); prefetch_map(&tmW2); prefetch_map(&tmOut); prefetch_map(&tmRes);
        for (int i = 0; i < F_NST; i++) { mbar_init(full + i * 8, 1); mbar_init(empty + i * 8, 8); }
        for (int i = 0; i < 9; i++) mbar_init(fullX + i * 8, 1);
        mbar_init(fullH, 1); mbar_init(fullH + 8, 1);
        bar_init_fence();
        for (int kb = 0; kb < 9; kb++) mbar_expect(fullX + kb * 8, 16384);
    }
    __syncthreads();
    if (warp < 4) {
        asm volatile("setmaxnreg.dec.sync.aligned.u32 24;");
        if (warp == 1 && lane < 9) prefetch_l2(reinterpret_cast<const char*>(w2) + ((size_t)fs * 576 + m * 36 + lane * 4) * (DM * 2), 4 * DM * 2);
        if (warp == 0 && elect_one()) {
#pragma unroll 1
            for (int c = 0; c < 18; c++) {
                int col = c - 9 + fs;
                if (col >= 9) col -= 9;
#pragma unroll 1
                for (int j = 0; j < 6; j++) {
                    mbar_wait(empty + j * 8, (c & 1) ^ 1);
                    mbar_expect(full + j * 8, F_STAGE);
                    if (c < 9) tma_2d(sSt + j * F_STAGE, &tmW1, fs * 576 + c * 64, j * 96, full + j * 8);
                    else tma_2d(sSt + j * F_STAGE, &tmW2, col * 64, fs * 576 + j * 96, full + j * 8);
                }
            }
        }
    } else {
        asm volatile("setmaxnreg.inc.sync.aligned.u32 240;");
        const int wgid = (warp >> 2) - 1, w = warp & 3;
        pdl_wait();
        if (warp == 4 && elect_one()) {
            for (int kb = 0; kb < 9; kb++) tma_2d(sX + kb * 16384, &tmX2, kb * 64, m * 128, fullX + kb * 8);
        }
        __syncwarp();
        FfnPipe pp{full, empty, lane};
        const uint64_t xlo = cdesc(0, 16, 1024, 1) + wgid * 512;
        uint32_t h1[144];
        float acc0[32], acc1[32];
        ffn_phase1_chunk<0>(acc0, acc1, h1, pp, xlo, fullX);
        ffn_phase1_chunk<1>(acc1, acc0, h1, pp, xlo, fullX);
        ffn_phase1_chunk<2>(acc0, acc1, h1, pp, xlo, fullX);
        ffn_phase1_chunk<3>(acc1, acc0, h1, pp, xlo, fullX);
        ffn_phase1_chunk<4>(acc0, acc1, h1, pp, xlo, fullX);
        ffn_phase1_chunk<5>(acc1, acc0, h1, pp, xlo, fullX);
        ffn_phase1_chunk<6>(acc0, acc1, h1, pp, xlo, fullX);
        ffn_phase1_chunk<7>(acc1, acc0, h1, pp, xlo, fullX);
        ffn_phase1_chunk<8>(acc0, acc1, h1, pp, xlo, fullX);
        const int row = m * 128 + wgid * 64;
        const uint32_t stg = sX + wgid * 8192;
        int c = fs, cprev = 0;
        const bool leader = w == 0 && elect_one();
        const uint32_t myH = fullH + wgid * 8;
        ffn_phase2_chunk<0>(acc1, acc0, h1, pp, 1, &tmOut, 0, 0, row, w, lane, wgid, leader, false, myH, 0);
        if (leader) {
            const int c8 = fs == 0 ? 8 : fs - 1;
            mbar_expect(myH, fs == 0 ? 16384 : 8192);
            tma_2d(stg + 8 * 16384, &tmRes, c8 * 64, row, myH);
            if (fs == 0) tma_2d(stg + 7 * 16384, &tmRes, 7 * 64, row, myH);
        }
        cprev = c; if (++c == 9) c = 0;
#pragma unroll 1
        for (int j = 1; j < 7; j += 2) {
            ffn_phase2_chunk<1>(acc0, acc1, h1, pp, 0, &tmOut, stg + (j - 1) * 16384, cprev * 64, row, w, lane, wgid, leader, false, myH, 0);
            cprev = c; if (++c == 9) c = 0;
            ffn_phase2_chunk<1>(acc1, acc0, h1, pp, 1, &tmOut, stg + j * 16384, cprev * 64, row, w, lane, wgid, leader, false, myH, 0);
            cprev = c; if (++c == 9) c = 0;
        }
        ffn_phase2_chunk<2>(acc0, acc1, h1, pp, 0, &tmOut, stg + 6 * 16384, cprev * 64, row, w, lane, wgid, leader, false, myH, stg + 8 * 16384);
        cprev = c; if (++c == 9) c = 0;
        ffn_phase2_chunk<3>(acc1, acc0, h1, pp, 1, &tmOut, stg + 7 * 16384, cprev * 64, row, w, lane, wgid, leader, fs == 0, myH, 0);
        cprev = c;
        wg_wait<0>();
        pin(acc1);
        ffn_stage_chunk(acc1, stg + 8 * 16384, w, lane, false, myH);
        ffn_reduce_chunk(&tmOut, stg + 8 * 16384, cprev * 64, row, w, wgid, leader);
        if (leader) bulk_wait_all();
    }
}

typedef CUresult (*EncodeFn)(CUtensorMap*, CUtensorMapDataType, cuuint32_t, void*, const cuuint64_t*, const cuuint64_t*, const cuuint32_t*, const cuuint32_t*,
                             CUtensorMapInterleave, CUtensorMapSwizzle, CUtensorMapL2promotion, CUtensorMapFloatOOBfill);

CUtensorMap make_map(EncodeFn enc, const void* base, int rows, int cols, int box_rows) {
    CUtensorMap tm;
    cuuint64_t dims[2] = {(cuuint64_t)cols, (cuuint64_t)rows};
    cuuint64_t strides[1] = {(cuuint64_t)cols * 2};
    cuuint32_t box[2] = {64, (cuuint32_t)box_rows};
    cuuint32_t es[2] = {1, 1};
    enc(&tm, CU_TENSOR_MAP_DATA_TYPE_BFLOAT16, 2, const_cast<void*>(base), dims, strides, box, es, CU_TENSOR_MAP_INTERLEAVE_NONE,
        CU_TENSOR_MAP_SWIZZLE_128B, CU_TENSOR_MAP_L2_PROMOTION_L2_256B, CU_TENSOR_MAP_FLOAT_OOB_FILL_NONE);
    return tm;
}

template <typename... KArgs, typename... Args>
void launch(void (*kern)(KArgs...), int grid, int block, int smem, bool pdl, Args... args) {
    cudaLaunchConfig_t cfg = {};
    cfg.gridDim = dim3(grid); cfg.blockDim = dim3(block); cfg.dynamicSmemBytes = smem; cfg.stream = cudaStreamPerThread;
    cudaLaunchAttribute at[1];
    at[0].id = cudaLaunchAttributeProgrammaticStreamSerialization;
    at[0].val.programmaticStreamSerializationAllowed = 1;
    cfg.attrs = at; cfg.numAttrs = pdl ? 1 : 0;
    cudaLaunchKernelEx(&cfg, kern, KArgs(args)...);
}

}

extern "C" void kernel_launch(void* const* d_in, const int* in_sizes, int n_in, void* d_out, int out_size) {
    const __nv_bfloat16* x = (const __nv_bfloat16*)d_in[0];
    const __nv_bfloat16* wq = (const __nv_bfloat16*)d_in[1];
    const __nv_bfloat16* wk = (const __nv_bfloat16*)d_in[2];
    const __nv_bfloat16* wv = (const __nv_bfloat16*)d_in[3];
    const __nv_bfloat16* wo = (const __nv_bfloat16*)d_in[4];
    const __nv_bfloat16* w1 = (const __nv_bfloat16*)d_in[6];
    const __nv_bfloat16* w2 = (const __nv_bfloat16*)d_in[7];
    __nv_bfloat16* out = (__nv_bfloat16*)d_out;

    static EncodeFn enc = nullptr;
    static void *p_o = nullptr, *p_x2 = nullptr, *p_q = nullptr, *p_res = nullptr;
    if (!enc) {
        cudaDriverEntryPointQueryResult qr;
        cudaGetDriverEntryPoint("cuTensorMapEncodeTiled", (void**)&enc, cudaEnableDefault, &qr);
        cudaGetSymbolAddress(&p_o, g_o);
        cudaGetSymbolAddress(&p_x2, g_x2);
        cudaGetSymbolAddress(&p_res, g_h);
        cudaGetSymbolAddress(&p_q, g_q);
        cudaFuncSetAttribute(k_qkv, cudaFuncAttributeMaxDynamicSharedMemorySize, P_SMEM);
        cudaFuncSetAttribute(k_attn, cudaFuncAttributeMaxDynamicSharedMemorySize, A_SMEM);
        cudaFuncSetAttribute(k_oproj, cudaFuncAttributeMaxDynamicSharedMemorySize, O_SMEM);
        cudaFuncSetAttribute(k_ffn, cudaFuncAttributeMaxDynamicSharedMemorySize, F_SMEM);
    }
    const CUtensorMap tmWq = make_map(enc, wq, DM, DM, 64);
    const CUtensorMap tmWo = make_map(enc, wo, DM, DM, 64);
    const CUtensorMap tmO = make_map(enc, p_o, SEQ, DM, 64);
    const CUtensorMap tmX2st = make_map(enc, p_x2, SEQ, DM, 64);
    const CUtensorMap tmX2ld = make_map(enc, p_x2, SEQ, DM, 128);
    const CUtensorMap tmRes = make_map(enc, p_res, SEQ, DM, 64);
    const CUtensorMap tmQ = make_map(enc, p_q, SEQ, DM, 64);
    const CUtensorMap tmW1 = make_map(enc, w1, DM, FF, 96);
    const CUtensorMap tmW2 = make_map(enc, w2, FF, DM, 96);
    const CUtensorMap tmOut = make_map(enc, out, SEQ, DM, 64);

    launch(k_qkv, 128, Q_THREADS, P_SMEM, false, tmWq, tmQ, x, wk, wv);
    launch(k_attn, 128, A_THREADS, A_SMEM, true, out);
    launch(k_oproj, 96, O_THREADS, O_SMEM, true, tmO, tmWo, tmX2st, tmRes, x, w1);
    launch(k_ffn, 128, F_THREADS, F_SMEM, true, tmX2ld, tmW1, tmW2, tmOut, tmRes, w2);
}
```

```cpp
#include <cuda_runtime.h>
#include <cuda_bf16.h>
#include <cuda.h>
#include <stdint.h>

namespace {

constexpr int SEQ = 2048, DM = 576, FF = 4608;
constexpr int KV_BYTES = SEQ * 48;
constexpr float LN_EPS = 1e-5f;
constexpr float LOG2E = 1.4426950408889634f;
constexpr float Q_SCALE = 0.23570226039551584f * LOG2E;

constexpr uint32_t POLY_MASK = 0xB6DBu;
constexpr int CHAIN = 6;
constexpr float FAST_BOUND = 60.0f;

__device__ __align__(1024) __nv_bfloat16 g_q[SEQ * DM];
__device__ __align__(1024) uint4 g_kc[KV_BYTES / 16];
__device__ __align__(1024) uint4 g_vc[KV_BYTES / 16];
__device__ __align__(16) float g_kmax[256];
__device__ __align__(1024) __nv_bfloat16 g_o[SEQ * DM];
__device__ __align__(1024) __nv_bfloat16 g_h[SEQ * DM];
__device__ __align__(1024) __nv_bfloat16 g_x2[SEQ * DM];


__device__ __forceinline__ uint32_t smem_u32(const void* p) { return (uint32_t)__cvta_generic_to_shared(p); }
__device__ __forceinline__ void wg_fence() { asm volatile("wgmma.fence.sync.aligned;" ::: "memory"); }
__device__ __forceinline__ void wg_commit() { asm volatile("wgmma.commit_group.sync.aligned;" ::: "memory"); }
template <int N> __device__ __forceinline__ void wg_wait() { asm volatile("wgmma.wait_group.sync.aligned %0;" ::"n"(N) : "memory"); }
template <int N> __device__ __forceinline__ void pin(float (&r)[N]) {
#pragma unroll
    for (int i = 0; i < N; i++) asm volatile("" : "+f"(r[i])::"memory");
}
template <int N> __device__ __forceinline__ void pin(uint32_t (&r)[N]) {
#pragma unroll
    for (int i = 0; i < N; i++) asm volatile("" : "+r"(r[i])::"memory");
}
constexpr uint32_t SMEM0 = 0x400;
__host__ __device__ constexpr uint64_t cdesc(uint32_t off, uint32_t lbo, uint32_t sbo, uint32_t swz) {
    return (uint64_t)(((SMEM0 + off) & 0x3FFFF) >> 4) | ((uint64_t)(lbo >> 4) << 16) | ((uint64_t)(sbo >> 4) << 32) | ((uint64_t)swz << 62);
}
__device__ __forceinline__ void check_smem_base(uint32_t base) { if ((base & 0x3FFFF) != SMEM0) __trap(); }

__device__ __forceinline__ void mbar_init(uint32_t bar, int cnt) { asm volatile("mbarrier.init.shared::cta.b64 [%0], %1;" ::"r"(bar), "r"(cnt) : "memory"); }
__device__ __forceinline__ void mbar_expect(uint32_t bar, int bytes) { asm volatile("mbarrier.arrive.expect_tx.shared::cta.b64 _, [%0], %1;" ::"r"(bar), "r"(bytes) : "memory"); }
__device__ __forceinline__ void mbar_arrive(uint32_t bar) { asm volatile("mbarrier.arrive.shared::cta.b64 _, [%0];" ::"r"(bar) : "memory"); }
__device__ __forceinline__ void mbar_wait(uint32_t bar, uint32_t parity) {
    asm volatile(
        "{\n.reg .pred p;\n.reg .u32 n;\nmov.u32 n, 0;\n"
        "LAB_WAIT:\n"
        "mbarrier.try_wait.parity.shared::cta.b64 p, [%0], %1;\n"
        "@p bra DONE;\n"
        "add.u32 n, n, 1;\n"
        "setp.lt.u32 p, n, 4000000;\n"
        "@p bra LAB_WAIT;\n"
        "trap;\n"
        "DONE:\n}\n" ::"r"(bar), "r"(parity) : "memory");
}
__device__ __forceinline__ void bar_init_fence() {
    asm volatile("fence.mbarrier_init.release.cluster;" ::: "memory");
    asm volatile("fence.proxy.async.shared::cta;" ::: "memory");
}
__device__ __forceinline__ void proxy_fence() { asm volatile("fence.proxy.async.shared::cta;" ::: "memory"); }
__device__ __forceinline__ void named_sync(int id, int n) { asm volatile("bar.sync %0, %1;" ::"r"(id), "r"(n) : "memory"); }
__device__ __forceinline__ void bulk_g2s(uint32_t dst, const void* src, int bytes, uint32_t bar) {
    asm volatile("cp.async.bulk.shared::cluster.global.mbarrier::complete_tx::bytes [%0], [%1], %2, [%3];" ::"r"(dst), "l"(src), "r"(bytes), "r"(bar) : "memory");
}
__device__ __forceinline__ void tma_2d(uint32_t dst, const CUtensorMap* tm, int c0, int c1, uint32_t bar) {
    asm volatile("cp.async.bulk.tensor.2d.shared::cluster.global.mbarrier::complete_tx::bytes [%0], [%1, {%3, %4}], [%2];" ::"r"(dst), "l"(tm), "r"(bar), "r"(c0), "r"(c1) : "memory");
}
__device__ __forceinline__ void cluster_arrive() { asm volatile("barrier.cluster.arrive.release.aligned;" ::: "memory"); }
__device__ __forceinline__ void cluster_wait() { asm volatile("barrier.cluster.wait.acquire.aligned;" ::: "memory"); }
__device__ __forceinline__ void tma_red_2d(const CUtensorMap* tm, int c0, int c1, uint32_t src) {
    asm volatile("cp.reduce.async.bulk.tensor.2d.global.shared::cta.add.tile.bulk_group [%0, {%2, %3}], [%1];" ::"l"(tm), "r"(src), "r"(c0), "r"(c1) : "memory");
}
__device__ __forceinline__ void tma_st_2d(const CUtensorMap* tm, int c0, int c1, uint32_t src) {
    asm volatile("cp.async.bulk.tensor.2d.global.shared::cta.tile.bulk_group [%0, {%2, %3}], [%1];" ::"l"(tm), "r"(src), "r"(c0), "r"(c1) : "memory");
}
__device__ __forceinline__ void bulk_commit() { asm volatile("cp.async.bulk.commit_group;" ::: "memory"); }
__device__ __forceinline__ void bulk_wait_all() { asm volatile("cp.async.bulk.wait_group.read 0;" ::: "memory"); }
__device__ __forceinline__ bool elect_one() {
    uint32_t p;
    asm volatile("{\n.reg .pred P;\nelect.sync _|P, 0xffffffff;\nselp.b32 %0, 1, 0, P;\n}\n" : "=r"(p));
    return p != 0;
}
__device__ __forceinline__ void prefetch_l2(const void* p, int bytes) { asm volatile("cp.async.bulk.prefetch.L2.global [%0], %1;" ::"l"(p), "r"(bytes) : "memory"); }
__device__ __forceinline__ void prefetch_map(const CUtensorMap* tm) { asm volatile("prefetch.tensormap [%0];" ::"l"(tm) : "memory"); }
__device__ __forceinline__ void pdl_launch() { asm volatile("griddepcontrol.launch_dependents;" ::: "memory"); }
__device__ __forceinline__ void pdl_wait() { asm volatile("griddepcontrol.wait;" ::: "memory"); }
__device__ __forceinline__ float ex2(float x) { float y; asm("ex2.approx.ftz.f32 %0, %1;" : "=f"(y) : "f"(x)); return y; }
__device__ __forceinline__ uint32_t pack_bf16(float lo, float hi) { uint32_t r; asm("cvt.rn.bf16x2.f32 %0, %1, %2;" : "=r"(r) : "f"(hi), "f"(lo)); return r; }
__device__ __forceinline__ float bf_lo(uint32_t v) { return __uint_as_float(v << 16); }
__device__ __forceinline__ float bf_hi(uint32_t v) { return __uint_as_float(v & 0xFFFF0000u); }
__device__ __forceinline__ uint32_t hfma2(uint32_t a, uint32_t b, uint32_t c) { uint32_t r; asm("fma.rn.f16x2 %0, %1, %2, %3;" : "=r"(r) : "r"(a), "r"(b), "r"(c)); return r; }
__device__ __forceinline__ void stmatrix_x4(uint32_t addr, uint32_t r0, uint32_t r1, uint32_t r2, uint32_t r3) {
    asm volatile("stmatrix.sync.aligned.m8n8.x4.shared.b16 [%0], {%1, %2, %3, %4};" ::"r"(addr), "r"(r0), "r"(r1), "r"(r2), "r"(r3) : "memory");
}

template <int TB> __device__ __forceinline__ void wgmma_ss_n24(float (&d)[12], uint64_t da, uint64_t db, int sc) {
    asm volatile("{\n.reg .pred p;\nsetp.ne.b32 p, %14, 0;\n"
        "wgmma.mma_async.sync.aligned.m64n24k16.f32.bf16.bf16 {%0, %1, %2, %3, %4, %5, %6, %7, %8, %9, %10, %11}, %12, %13, p, 1, 1, 0, %15;\n}\n"
        : "+f"(d[0]), "+f"(d[1]), "+f"(d[2]), "+f"(d[3]), "+f"(d[4]), "+f"(d[5]), "+f"(d[6]), "+f"(d[7]), "+f"(d[8]), "+f"(d[9]), "+f"(d[10]), "+f"(d[11])
        : "l"(da), "l"(db), "r"(sc), "n"(TB));
}
template <int TB> __device__ __forceinline__ void wgmma_ss_n64(float (&d)[32], uint64_t da, uint64_t db, int sc) {
    asm volatile("{\n.reg .pred p;\nsetp.ne.b32 p, %34, 0;\n"
        "wgmma.mma_async.sync.aligned.m64n64k16.f32.bf16.bf16 {%0, %1, %2, %3, %4, %5, %6, %7, %8, %9, %10, %11, %12, %13, %14, %15, %16, %17, %18, %19, %20, %21, %22, %23, %24, %25, %26, %27, %28, %29, %30, %31}, %32, %33, p, 1, 1, 0, %35;\n}\n"
        : "+f"(d[0]), "+f"(d[1]), "+f"(d[2]), "+f"(d[3]), "+f"(d[4]), "+f"(d[5]), "+f"(d[6]), "+f"(d[7]), "+f"(d[8]), "+f"(d[9]), "+f"(d[10]), "+f"(d[11]), "+f"(d[12]), "+f"(d[13]), "+f"(d[14]), "+f"(d[15]), "+f"(d[16]), "+f"(d[17]), "+f"(d[18]), "+f"(d[19]), "+f"(d[20]), "+f"(d[21]), "+f"(d[22]), "+f"(d[23]), "+f"(d[24]), "+f"(d[25]), "+f"(d[26]), "+f"(d[27]), "+f"(d[28]), "+f"(d[29]), "+f"(d[30]), "+f"(d[31])
        : "l"(da), "l"(db), "r"(sc), "n"(TB));
}
template <int TB> __device__ __forceinline__ void wgmma_ss_n128(float (&d)[64], uint64_t da, uint64_t db, int sc) {
    asm volatile("{\n.reg .pred p;\nsetp.ne.b32 p, %66, 0;\n"
        "wgmma.mma_async.sync.aligned.m64n128k16.f32.bf16.bf16 {%0, %1, %2, %3, %4, %5, %6, %7, %8, %9, %10, %11, %12, %13, %14, %15, %16, %17, %18, %19, %20, %21, %22, %23, %24, %25, %26, %27, %28, %29, %30, %31, %32, %33, %34, %35, %36, %37, %38, %39, %40, %41, %42, %43, %44, %45, %46, %47, %48, %49, %50, %51, %52, %53, %54, %55, %56, %57, %58, %59, %60, %61, %62, %63}, %64, %65, p, 1, 1, 0, %67;\n}\n"
        : "+f"(d[0]), "+f"(d[1]), "+f"(d[2]), "+f"(d[3]), "+f"(d[4]), "+f"(d[5]), "+f"(d[6]), "+f"(d[7]), "+f"(d[8]), "+f"(d[9]), "+f"(d[10]), "+f"(d[11]), "+f"(d[12]), "+f"(d[13]), "+f"(d[14]), "+f"(d[15]), "+f"(d[16]), "+f"(d[17]), "+f"(d[18]), "+f"(d[19]), "+f"(d[20]), "+f"(d[21]), "+f"(d[22]), "+f"(d[23]), "+f"(d[24]), "+f"(d[25]), "+f"(d[26]), "+f"(d[27]), "+f"(d[28]), "+f"(d[29]), "+f"(d[30]), "+f"(d[31]), "+f"(d[32]), "+f"(d[33]), "+f"(d[34]), "+f"(d[35]), "+f"(d[36]), "+f"(d[37]), "+f"(d[38]), "+f"(d[39]), "+f"(d[40]), "+f"(d[41]), "+f"(d[42]), "+f"(d[43]), "+f"(d[44]), "+f"(d[45]), "+f"(d[46]), "+f"(d[47]), "+f"(d[48]), "+f"(d[49]), "+f"(d[50]), "+f"(d[51]), "+f"(d[52]), "+f"(d[53]), "+f"(d[54]), "+f"(d[55]), "+f"(d[56]), "+f"(d[57]), "+f"(d[58]), "+f"(d[59]), "+f"(d[60]), "+f"(d[61]), "+f"(d[62]), "+f"(d[63])
        : "l"(da), "l"(db), "r"(sc), "n"(TB));
}
template <int TB> __device__ __forceinline__ void wgmma_rs_n24(float (&d)[12], uint32_t a0, uint32_t a1, uint32_t a2, uint32_t a3, uint64_t db, int sc) {
    asm volatile("{\n.reg .pred p;\nsetp.ne.b32 p, %17, 0;\n"
        "wgmma.mma_async.sync.aligned.m64n24k16.f32.bf16.bf16 {%0, %1, %2, %3, %4, %5, %6, %7, %8, %9, %10, %11}, {%12, %13, %14, %15}, %16, p, 1, 1, %18;\n}\n"
        : "+f"(d[0]), "+f"(d[1]), "+f"(d[2]), "+f"(d[3]), "+f"(d[4]), "+f"(d[5]), "+f"(d[6]), "+f"(d[7]), "+f"(d[8]), "+f"(d[9]), "+f"(d[10]), "+f"(d[11])
        : "r"(a0), "r"(a1), "r"(a2), "r"(a3), "l"(db), "r"(sc), "n"(TB));
}
template <int TB> __device__ __forceinline__ void wgmma_rs_n64(float (&d)[32], uint32_t a0, uint32_t a1, uint32_t a2, uint32_t a3, uint64_t db, int sc) {
    asm volatile("{\n.reg .pred p;\nsetp.ne.b32 p, %37, 0;\n"
        "wgmma.mma_async.sync.aligned.m64n64k16.f32.bf16.bf16 {%0, %1, %2, %3, %4, %5, %6, %7, %8, %9, %10, %11, %12, %13, %14, %15, %16, %17, %18, %19, %20, %21, %22, %23, %24, %25, %26, %27, %28, %29, %30, %31}, {%32, %33, %34, %35}, %36, p, 1, 1, %38;\n}\n"
        : "+f"(d[0]), "+f"(d[1]), "+f"(d[2]), "+f"(d[3]), "+f"(d[4]), "+f"(d[5]), "+f"(d[6]), "+f"(d[7]), "+f"(d[8]), "+f"(d[9]), "+f"(d[10]), "+f"(d[11]), "+f"(d[12]), "+f"(d[13]), "+f"(d[14]), "+f"(d[15]), "+f"(d[16]), "+f"(d[17]), "+f"(d[18]), "+f"(d[19]), "+f"(d[20]), "+f"(d[21]), "+f"(d[22]), "+f"(d[23]), "+f"(d[24]), "+f"(d[25]), "+f"(d[26]), "+f"(d[27]), "+f"(d[28]), "+f"(d[29]), "+f"(d[30]), "+f"(d[31])
        : "r"(a0), "r"(a1), "r"(a2), "r"(a3), "l"(db), "r"(sc), "n"(TB));
}
template <int TB> __device__ __forceinline__ void wgmma_rs_n128(float (&d)[64], uint32_t a0, uint32_t a1, uint32_t a2, uint32_t a3, uint64_t db, int sc) {
    asm volatile("{\n.reg .pred p;\nsetp.ne.b32 p, %69, 0;\n"
        "wgmma.mma_async.sync.aligned.m64n128k16.f32.bf16.bf16 {%0, %1, %2, %3, %4, %5, %6, %7, %8, %9, %10, %11, %12, %13, %14, %15, %16, %17, %18, %19, %20, %21, %22, %23, %24, %25, %26, %27, %28, %29, %30, %31, %32, %33, %34, %35, %36, %37, %38, %39, %40, %41, %42, %43, %44, %45, %46, %47, %48, %49, %50, %51, %52, %53, %54, %55, %56, %57, %58, %59, %60, %61, %62, %63}, {%64, %65, %66, %67}, %68, p, 1, 1, %70;\n}\n"
        : "+f"(d[0]), "+f"(d[1]), "+f"(d[2]), "+f"(d[3]), "+f"(d[4]), "+f"(d[5]), "+f"(d[6]), "+f"(d[7]), "+f"(d[8]), "+f"(d[9]), "+f"(d[10]), "+f"(d[11]), "+f"(d[12]), "+f"(d[13]), "+f"(d[14]), "+f"(d[15]), "+f"(d[16]), "+f"(d[17]), "+f"(d[18]), "+f"(d[19]), "+f"(d[20]), "+f"(d[21]), "+f"(d[22]), "+f"(d[23]), "+f"(d[24]), "+f"(d[25]), "+f"(d[26]), "+f"(d[27]), "+f"(d[28]), "+f"(d[29]), "+f"(d[30]), "+f"(d[31]), "+f"(d[32]), "+f"(d[33]), "+f"(d[34]), "+f"(d[35]), "+f"(d[36]), "+f"(d[37]), "+f"(d[38]), "+f"(d[39]), "+f"(d[40]), "+f"(d[41]), "+f"(d[42]), "+f"(d[43]), "+f"(d[44]), "+f"(d[45]), "+f"(d[46]), "+f"(d[47]), "+f"(d[48]), "+f"(d[49]), "+f"(d[50]), "+f"(d[51]), "+f"(d[52]), "+f"(d[53]), "+f"(d[54]), "+f"(d[55]), "+f"(d[56]), "+f"(d[57]), "+f"(d[58]), "+f"(d[59]), "+f"(d[60]), "+f"(d[61]), "+f"(d[62]), "+f"(d[63])
        : "r"(a0), "r"(a1), "r"(a2), "r"(a3), "l"(db), "r"(sc), "n"(TB));
}

constexpr int P_NST = 6;
constexpr int P_A_BYTES = 9 * 8192;
constexpr int P_B_STAGE = 3 * 8192;
constexpr int P_SMEM = P_A_BYTES + P_NST * P_B_STAGE + 256 + 256;

template <int NB>
__device__ __forceinline__ void stage_tile(const uint32_t (&pk)[NB * 2], uint32_t base, int w, int lane) {
    const int r = w * 16 + (lane & 7) + ((lane >> 3) & 1) * 8;
#pragma unroll
    for (int b = 0; b < NB; b += 2) {
        const uint32_t a = base + (b >> 3) * 8192 + r * 128 + ((((b & 7) + (lane >> 4)) ^ (r & 7)) << 4);
        stmatrix_x4(a, pk[2 * b], pk[2 * b + 1], pk[2 * b + 2], pk[2 * b + 3]);
    }
}

__device__ __forceinline__ uint32_t hsub2_bf16(uint32_t a, uint32_t b) { uint32_t r; asm("sub.rn.bf16x2 %0, %1, %2;" : "=r"(r) : "r"(a), "r"(b)); return r; }

constexpr int KV_RAW = DM * 18 * 2;
constexpr int Q_THREADS = 416;

__device__ __forceinline__ void proj_mma(float (&acc)[32], int wg, uint32_t fullB, uint32_t emptyB, uint32_t fullA, bool wait_a, int lane) {
    const uint64_t dA = cdesc(0, 16, 1024, 1), dB = cdesc(P_A_BYTES, 8192, 1024, 1) + wg * 512;
#pragma unroll 1
    for (int kb = 0; kb < 9; kb++) {
        const int s = kb >= P_NST ? kb - P_NST : kb;
        if (wait_a) mbar_wait(fullA + kb * 8, 0);
        mbar_wait(fullB + s * 8, kb >= P_NST ? 1 : 0);
        wg_fence();
#pragma unroll
        for (int ks = 0; ks < 4; ks++) wgmma_ss_n64<1>(acc, dA + (kb * 512 + ks * 2), dB + (s * (P_B_STAGE >> 4) + ks * 128), (kb | ks) != 0);
        wg_commit();
        if (kb < 4) {
            wg_wait<1>();
            if (kb >= 1 && lane == 0) mbar_arrive(emptyB + (kb - 1) * 8);
        }
    }
    wg_wait<0>();
    pin(acc);
}

__global__ void __launch_bounds__(Q_THREADS, 1)
k_qkv(const __grid_constant__ CUtensorMap tmWq, const __grid_constant__ CUtensorMap tmQ, const __nv_bfloat16* __restrict__ x, const __nv_bfloat16* __restrict__ wk, const __nv_bfloat16* __restrict__ wv) {
    extern __shared__ __align__(1024) uint8_t smem[];
    const uint32_t sA = smem_u32(smem), sB = sA + P_A_BYTES, bars = sB + P_NST * P_B_STAGE;
    const uint32_t fullB = bars, emptyB = bars + 64, fullX = bars + 128, fullW = bars + 136;
    float* s_rstd = reinterpret_cast<float*>(smem + P_A_BYTES + P_NST * P_B_STAGE + 256);
    const int tid = threadIdx.x, warp = __shfl_sync(~0u, tid >> 5, 0), lane = tid & 31;
    const bool isQ = blockIdx.x < 96;
    const int m = isQ ? blockIdx.x / 3 : blockIdx.x - 96, cg = blockIdx.x % 3;
    if (warp == 12) {
        if (elect_one()) {
            mbar_init(fullX, 1);
            bar_init_fence();
            mbar_expect(fullX, P_A_BYTES);
            bulk_g2s(sA, x + (size_t)m * 64 * DM, P_A_BYTES, fullX);
            prefetch_map(&tmWq); prefetch_map(&tmQ);
            for (int i = 0; i < P_NST; i++) { mbar_init(fullB + i * 8, 1); mbar_init(emptyB + i * 8, 12); }
            mbar_init(fullW, 1);
            bar_init_fence();
            if (isQ) {
                for (int kb = 0; kb < P_NST; kb++) {
                    mbar_expect(fullB + kb * 8, P_B_STAGE);
                    for (int a = 0; a < 3; a++) tma_2d(sB + kb * P_B_STAGE + a * 8192, &tmWq, cg * 192 + a * 64, kb * 64, fullB + kb * 8);
                }
            } else {
                mbar_expect(fullW, 2 * KV_RAW);
                bulk_g2s(sB + 3 * P_B_STAGE, wk, KV_RAW, fullW);
                bulk_g2s(sB + 3 * P_B_STAGE + KV_RAW, wv, KV_RAW, fullW);
            }
        }
        __syncwarp();
    }
    check_smem_base(sA);
    __syncthreads();
    pdl_launch();
    if (warp == 12) {
        if (isQ && elect_one()) {
            for (int kb = P_NST; kb < 9; kb++) {
                const int s = kb - P_NST;
                mbar_wait(emptyB + s * 8, 0);
                mbar_expect(fullB + s * 8, P_B_STAGE);
                for (int a = 0; a < 3; a++) tma_2d(sB + s * P_B_STAGE + a * 8192, &tmWq, cg * 192 + a * 64, kb * 64, fullB + s * 8);
            }
        }
        return;
    }
    if (warp < 8) {
        const int row = tid >> 2, q = tid & 3, h0 = (row & 1) * 4;
        mbar_wait(fullX, 0);
        uint4 v[18];
        const uint32_t ra = sA + row * 1152 + (q + h0) * 16, rb = sA + row * 1152 + (q + 4 - h0) * 16;
#pragma unroll
        for (int kb = 0; kb < 9; kb++) {
            asm volatile("ld.shared.v4.b32 {%0, %1, %2, %3}, [%4];" : "=r"(v[2 * kb].x), "=r"(v[2 * kb].y), "=r"(v[2 * kb].z), "=r"(v[2 * kb].w) : "r"(ra + kb * 128));
            asm volatile("ld.shared.v4.b32 {%0, %1, %2, %3}, [%4];" : "=r"(v[2 * kb + 1].x), "=r"(v[2 * kb + 1].y), "=r"(v[2 * kb + 1].z), "=r"(v[2 * kb + 1].w) : "r"(rb + kb * 128));
        }
        float sum = 0.f, sum2 = 0.f, sq = 0.f, sq2 = 0.f;
#pragma unroll
        for (int i = 0; i < 18; i++) {
            const uint32_t w[4] = {v[i].x, v[i].y, v[i].z, v[i].w};
#pragma unroll
            for (int j = 0; j < 4; j++) { const float a = bf_lo(w[j]), b = bf_hi(w[j]); sum += a; sum2 += b; sq = fmaf(a, a, sq); sq2 = fmaf(b, b, sq2); }
        }
        named_sync(1, 256);
        sum += sum2; sq += sq2;
        sum += __shfl_xor_sync(~0u, sum, 1); sum += __shfl_xor_sync(~0u, sum, 2);
        sq += __shfl_xor_sync(~0u, sq, 1); sq += __shfl_xor_sync(~0u, sq, 2);
        const float mean = sum * (1.0f / DM);
        if (q == 0) s_rstd[row] = rsqrtf(fmaxf(sq * (1.0f / DM) - mean * mean, 0.f) + LN_EPS);
        const uint32_t mhi = pack_bf16(mean, mean);
        const float rem = mean - bf_lo(mhi);
        const uint32_t mlo = pack_bf16(rem, rem);
        const uint32_t wa = sA + row * 128 + (((q + h0) ^ (row & 7)) << 4), wb = sA + row * 128 + (((q + 4 - h0) ^ (row & 7)) << 4);
#pragma unroll
        for (int i = 0; i < 18; i++) {
            const uint32_t o0 = hsub2_bf16(hsub2_bf16(v[i].x, mhi), mlo), o1 = hsub2_bf16(hsub2_bf16(v[i].y, mhi), mlo);
            const uint32_t o2 = hsub2_bf16(hsub2_bf16(v[i].z, mhi), mlo), o3 = hsub2_bf16(hsub2_bf16(v[i].w, mhi), mlo);
            asm volatile("st.shared.v4.b32 [%0], {%1, %2, %3, %4};" ::"r"(((i & 1) ? wb : wa) + (i >> 1) * 8192), "r"(o0), "r"(o1), "r"(o2), "r"(o3) : "memory");
        }
    } else if (!isQ) {
        mbar_wait(fullW, 0);
        const uint32_t* raw = reinterpret_cast<const uint32_t*>(smem + P_A_BYTES + 3 * P_B_STAGE);
#pragma unroll 3
        for (int r = tid - 256; r < 2 * DM; r += 128) {
            uint32_t wr[9];
#pragma unroll
            for (int i = 0; i < 9; i++) wr[i] = raw[r * 9 + i];
            const int sel = r >= DM, k = r - sel * DM;
            uint8_t* dst = smem + P_A_BYTES + sel * 3 * 9216 + (k >> 3) * 128 + (k & 7) * 16;
            *reinterpret_cast<uint4*>(dst) = make_uint4(wr[0], wr[1], wr[2], wr[3]);
            *reinterpret_cast<uint4*>(dst + 9216) = make_uint4(wr[4], wr[5], wr[6], wr[7]);
            *reinterpret_cast<uint32_t*>(dst + 2 * 9216) = wr[8];
        }
    }
    proxy_fence();
    named_sync(2, 384);
    const int wg = warp >> 2, w = warp & 3, g = lane >> 2, t = lane & 3;
    const float rs0 = s_rstd[w * 16 + g], rs1 = s_rstd[w * 16 + g + 8];
    if (isQ) {
        const float c0 = rs0 * Q_SCALE, c1 = rs1 * Q_SCALE;
        float acc[32];
        proj_mma(acc, wg, fullB, emptyB, 0, false, lane);
        uint32_t pk[16];
#pragma unroll
        for (int i = 0; i < 8; i++) { pk[2 * i] = pack_bf16(acc[4 * i] * c0, acc[4 * i + 1] * c0); pk[2 * i + 1] = pack_bf16(acc[4 * i + 2] * c1, acc[4 * i + 3] * c1); }
        named_sync(2, 384);
        stage_tile<8>(pk, sA + wg * 8192, w, lane);
        proxy_fence();
        named_sync(3 + wg, 128);
        if (w == 0 && elect_one()) {
            tma_st_2d(&tmQ, cg * 192 + wg * 64, m * 64, sA + wg * 8192);
            bulk_commit();
            bulk_wait_all();
        }
    } else if (wg < 2) {
        float acc[12];
        const uint64_t dA = cdesc(0, 16, 1024, 1), dB = cdesc(P_A_BYTES, 128, 9216, 0) + wg * (3 * 9216 >> 4);
#pragma unroll
        for (int i = 0; i < 12; i++) acc[i] = 0.f;
        pin(acc);
        wg_fence();
#pragma unroll 1
        for (int kb = 0; kb < 9; kb++) {
#pragma unroll
            for (int ks = 0; ks < 4; ks++) wgmma_ss_n24<1>(acc, dA + (kb * 512 + ks * 2), dB + (kb * 4 + ks) * 16, 1);
        }
        wg_commit();
        wg_wait<0>();
        pin(acc);
        uint32_t pk[6];
#pragma unroll
        for (int b = 0; b < 3; b++) { pk[2 * b] = pack_bf16(acc[4 * b] * rs0, acc[4 * b + 1] * rs0); pk[2 * b + 1] = pack_bf16(acc[4 * b + 2] * rs1, acc[4 * b + 3] * rs1); }
        float n0 = 0.f, n1 = 0.f, vm = 0.f;
#pragma unroll
        for (int b = 0; b < 3; b++) {
            if (b < 2 || t == 0) {
                const float a = bf_lo(pk[2 * b]), c = bf_hi(pk[2 * b]), d = bf_lo(pk[2 * b + 1]), e = bf_hi(pk[2 * b + 1]);
                n0 = fmaf(a, a, fmaf(c, c, n0)); n1 = fmaf(d, d, fmaf(e, e, n1));
            }
        }
        n0 += __shfl_xor_sync(~0u, n0, 1); n0 += __shfl_xor_sync(~0u, n0, 2);
        n1 += __shfl_xor_sync(~0u, n1, 1); n1 += __shfl_xor_sync(~0u, n1, 2);
        vm = fmaxf(n0, n1);
        if (!(n0 == n0) || !(n1 == n1)) vm = __int_as_float(0x7F800000);
#pragma unroll
        for (int o = 4; o < 32; o <<= 1) vm = fmaxf(vm, __shfl_xor_sync(~0u, vm, o));
        if (t != 0) {
            uint32_t lo, hi;
            if (wg == 0) {
                const int grp = m * 8 + w * 2;
                const uint32_t c = t == 1 ? 0x42FE3F80u   : (t == 2 ? 0x00003BC0u   : 0u);
                lo = ((POLY_MASK >> (grp & 15)) & 1) ? c : 0u;
                hi = ((POLY_MASK >> ((grp + 1) & 15)) & 1) ? c : 0u;
            } else {
                lo = hi = t == 1 ? 0x00003F80u : 0u;
            }
            pk[4] = lo; pk[5] = hi;
        }
        uint32_t* dst = reinterpret_cast<uint32_t*>(wg == 0 ? g_kc : g_vc) + (m * 8 + w * 2) * 96 + g * 4 + t;
#pragma unroll
        for (int b = 0; b < 3; b++) { dst[b * 32] = pk[2 * b]; dst[96 + b * 32] = pk[2 * b + 1]; }
        if (lane == 0) g_kmax[m * 8 + warp] = (wg == 0) ? vm : (vm <= 1e24f ? 0.f : __int_as_float(0x7F800000));
    }
}

constexpr int A_THREADS = 512;
constexpr int A_NPIECE = 5;
constexpr int A_OFF_Q = 2 * KV_BYTES;
constexpr int A_OFF_BAR = A_OFF_Q + 8 * 4096;
constexpr int A_SMEM = A_OFF_BAR + 128;

__device__ __forceinline__ uint32_t exp2_pair_fixed(float lo, float hi, uint32_t dep) {
    const uint32_t G = __byte_perm(__float_as_uint(lo), __float_as_uint(hi), 0x5410);
    uint32_t Hh;
    asm("lop3.b32 %0, %1, 0x007F007F, %2, 0xC0;" : "=r"(Hh) : "r"(G), "r"(dep));
    const uint32_t tt = hfma2(Hh, 0xF96BF96Bu, 0x358C358Cu);
    return G - hfma2(tt, Hh, 0u);
}

__global__ void __launch_bounds__(A_THREADS, 1)
k_attn(__nv_bfloat16* __restrict__ out) {
    extern __shared__ __align__(1024) uint8_t smem[];
    pdl_launch();
    const uint32_t sK = smem_u32(smem), sV = sK + KV_BYTES, bars = sK + A_OFF_BAR;
    const int tid = threadIdx.x;
    check_smem_base(sK);
    if (tid == 0) {
        for (int i = 0; i < A_NPIECE; i++) mbar_init(bars + i * 8, 1);
        bar_init_fence();
    }
    __syncthreads();
    pdl_wait();
    const int wg = __shfl_sync(~0u, tid >> 7, 0), w = (tid >> 5) & 3, lane = tid & 31, g = lane >> 2, t = lane & 3;
    const uint32_t* q32 = reinterpret_cast<const uint32_t*>(g_q);
    int row = (blockIdx.x * 8 + wg) * 64 + w * 16 + g;
    uint32_t nq[2][6];
#pragma unroll
    for (int r = 0; r < 2; r++) {
        const uint32_t* q = q32 + (row + r * 256) * 9;
        nq[r][0] = q[t]; nq[r][1] = q[72 + t]; nq[r][2] = q[4 + t]; nq[r][3] = q[76 + t]; nq[r][4] = q[8]; nq[r][5] = q[80];
    }
    const float4 km0 = reinterpret_cast<const float4*>(g_kmax)[lane], km1 = reinterpret_cast<const float4*>(g_kmax)[32 + lane];
    auto load_piece = [&](int i) {
        constexpr int BLK = KV_BYTES / 16;
        const int first = i == 0 ? 0 : 1 << (i - 1), bytes = (i == 0 ? 1 : 1 << (i - 1)) * BLK;
        mbar_expect(bars + i * 8, 2 * bytes);
        bulk_g2s(sK + first * BLK, reinterpret_cast<const char*>(g_kc) + first * BLK, bytes, bars + i * 8);
        bulk_g2s(sV + first * BLK, reinterpret_cast<const char*>(g_vc) + first * BLK, bytes, bars + i * 8);
    };
    if (tid < 32 && elect_one()) { load_piece(0); load_piece(1); load_piece(2); }
    float kmax2 = fmaxf(fmaxf(fmaxf(km0.x, km0.y), fmaxf(km0.z, km0.w)), fmaxf(fmaxf(km1.x, km1.y), fmaxf(km1.z, km1.w)));
#pragma unroll
    for (int o = 1; o < 32; o <<= 1) kmax2 = fmaxf(kmax2, __shfl_xor_sync(~0u, kmax2, o));
    if (tid < 32 && elect_one()) { load_piece(3); load_piece(4); }
    uint32_t vote = 0;
#pragma unroll
    for (int r = 0; r < 2; r++) {
        const uint32_t (&q)[6] = nq[r];
        const float a0 = bf_lo(q[0]), a1 = bf_hi(q[0]), a2 = bf_lo(q[2]), a3 = bf_hi(q[2]);
        const float b0 = bf_lo(q[1]), b1 = bf_hi(q[1]), b2 = bf_lo(q[3]), b3 = bf_hi(q[3]);
        float n0 = a0 * a0 + a1 * a1 + a2 * a2 + a3 * a3, n1 = b0 * b0 + b1 * b1 + b2 * b2 + b3 * b3;
        if (t == 0) {
            const float c0 = bf_lo(q[4]), c1 = bf_hi(q[4]), d0 = bf_lo(q[5]), d1 = bf_hi(q[5]);
            n0 += c0 * c0 + c1 * c1; n1 += d0 * d0 + d1 * d1;
        }
        n0 += __shfl_xor_sync(~0u, n0, 1); n0 += __shfl_xor_sync(~0u, n0, 2);
        n1 += __shfl_xor_sync(~0u, n1, 1); n1 += __shfl_xor_sync(~0u, n1, 2);
        const bool unsafe = !(fmaxf(n0, n1) * kmax2 <= FAST_BOUND * FAST_BOUND) || !(n0 == n0) || !(n1 == n1);
        vote |= (__any_sync(~0u, unsafe) ? 1u : 0u) << r;
        const uint32_t cst = t == 1 ? 0x3F804780u : (t == 2 ? 0x00003F80u : 0u);
        const uint32_t sQ = sK + A_OFF_Q + (r * 4 + wg) * 4096 + (w * 2) * 512 + g * 16 + t * 4;
        asm volatile("st.shared.b32 [%0], %1;" ::"r"(sQ), "r"(q[0]) : "memory");
        asm volatile("st.shared.b32 [%0], %1;" ::"r"(sQ + 512), "r"(q[1]) : "memory");
        asm volatile("st.shared.b32 [%0], %1;" ::"r"(sQ + 128), "r"(q[2]) : "memory");
        asm volatile("st.shared.b32 [%0], %1;" ::"r"(sQ + 640), "r"(q[3]) : "memory");
        asm volatile("st.shared.b32 [%0], %1;" ::"r"(sQ + 256), "r"(t == 0 ? q[4] : cst) : "memory");
        asm volatile("st.shared.b32 [%0], %1;" ::"r"(sQ + 768), "r"(t == 0 ? q[5] : cst) : "memory");
        asm volatile("st.shared.b32 [%0], %1;" ::"r"(sQ + 384), "r"(0u) : "memory");
        asm volatile("st.shared.b32 [%0], %1;" ::"r"(sQ + 896), "r"(0u) : "memory");
    }
    const uint32_t sVote = bars + 64 + wg * 16;
    if (lane == 0) asm volatile("st.shared.b32 [%0], %1;" ::"r"(sVote + w * 4), "r"(vote) : "memory");
    proxy_fence();
    named_sync(wg + 1, 128);
    uint32_t unsafe_mask;
    {
        uint32_t v0, v1, v2, v3;
        asm volatile("ld.shared.v4.b32 {%0, %1, %2, %3}, [%4];" : "=r"(v0), "=r"(v1), "=r"(v2), "=r"(v3) : "r"(sVote));
        unsafe_mask = __shfl_sync(~0u, v0 | v1 | v2 | v3, 0);
    }
    if (unsafe_mask) {
#pragma unroll
        for (int r = 0; r < 2; r++) {
            if (((unsafe_mask >> r) & 1) && t != 0) {
                const uint32_t sQ = sK + A_OFF_Q + (r * 4 + wg) * 4096 + (w * 2) * 512 + g * 16 + t * 4;
                asm volatile("st.shared.b32 [%0], %1;" ::"r"(sQ + 256), "r"(0u) : "memory");
                asm volatile("st.shared.b32 [%0], %1;" ::"r"(sQ + 768), "r"(0u) : "memory");
            }
        }
        proxy_fence();
        named_sync(wg + 1, 128);
    }
#pragma unroll 1
    for (int rep = 0; rep < 2; rep++, row += 256) {
        if (rep == 1) {
            uint4* z = reinterpret_cast<uint4*>(out + (size_t)blockIdx.x * 16 * DM) + tid;
            z[0] = make_uint4(0u, 0u, 0u, 0u); z[A_THREADS] = make_uint4(0u, 0u, 0u, 0u);
            if (tid < 16 * DM * 2 / 16 - 2 * A_THREADS) z[2 * A_THREADS] = make_uint4(0u, 0u, 0u, 0u);
        }
        const uint32_t any_unsafe = (unsafe_mask >> rep) & 1;
        const uint64_t dQ0 = cdesc(A_OFF_Q, 128, 512, 0) + (rep * 4 + wg) * 256, dQ1 = dQ0 + 16;
        float o[12];
#pragma unroll
        for (int i = 0; i < 12; i++) o[i] = 0.f;
        pin(o);
        uint64_t dK0 = cdesc(0, 128, 384, 0), dK1 = cdesc(256, 0, 384, 0), dV = cdesc(KV_BYTES, 384, 128, 0);
        if (!any_unsafe) {
            float s[64];
#pragma unroll 1
            for (int j = 0; j < 16; j++) {
                if (rep == 0 && (j & (j - 1)) == 0) mbar_wait(bars + (32 - __clz(j)) * 8, 0);
                wg_fence();
                wgmma_ss_n128<0>(s, dQ0, dK0, 0);
                wgmma_ss_n128<0>(s, dQ1, dK1, 1);
                wg_commit();
                dK0 += 16 * 384 >> 4; dK1 += 16 * 384 >> 4;
                wg_wait<0>();
                pin(s);
                uint32_t p[32];
                {
                    constexpr int NP = 2 * __builtin_popcount(POLY_MASK), NM = 32 - NP;
                    float e[64];
#pragma unroll
                    for (int i = 0; i < 32; i++)
                        if (!((POLY_MASK >> (i >> 1)) & 1)) { e[2 * i] = ex2(s[2 * i]); e[2 * i + 1] = ex2(s[2 * i + 1]); p[i] = pack_bf16(e[2 * i], e[2 * i + 1]); }
                    int ip = 0;
#pragma unroll
                    for (int i = 0; i < 32; i++) {
                        if ((POLY_MASK >> (i >> 1)) & 1) {
                            const int mm = (ip * 2 * NM) / NP - CHAIN;
                            uint32_t dep = 0;
                            if (CHAIN > 0 && mm >= 0) {
                                int cnt = 0;
#pragma unroll
                                for (int q = 0; q < 32; q++)
                                    if (!((POLY_MASK >> (q >> 1)) & 1)) { if (cnt == (mm >> 1)) dep = __float_as_uint(e[2 * q + (mm & 1)]); cnt++; }
                            }
                            p[i] = exp2_pair_fixed(s[2 * i], s[2 * i + 1], dep);
                            ip++;
                        }
                    }
                }
                pin(p);
                wg_fence();
#pragma unroll
                for (int k = 0; k < 8; k++) wgmma_rs_n24<1>(o, p[4 * k], p[4 * k + 1], p[4 * k + 2], p[4 * k + 3], dV + k * 48, 1);
                wg_commit();
                dV += 16 * 384 >> 4;
                wg_wait<0>();
            }
        } else {
            float s[64];
            float m0 = -INFINITY, m1 = -INFINITY;
#pragma unroll 1
            for (int j = 0; j < 16; j++) {
                if (rep == 0 && (j & (j - 1)) == 0) mbar_wait(bars + (32 - __clz(j)) * 8, 0);
                wg_fence();
                wgmma_ss_n128<0>(s, dQ0, dK0, 0);
                wgmma_ss_n128<0>(s, dQ1, dK1, 1);
                wg_commit();
                dK0 += 16 * 384 >> 4; dK1 += 16 * 384 >> 4;
                wg_wait<0>();
                pin(s);
                float x0m = m0, x1m = m1;
#pragma unroll
                for (int b = 0; b < 16; b++) { x0m = fmaxf(x0m, fmaxf(s[4 * b], s[4 * b + 1])); x1m = fmaxf(x1m, fmaxf(s[4 * b + 2], s[4 * b + 3])); }
                x0m = fmaxf(x0m, __shfl_xor_sync(~0u, x0m, 1)); x0m = fmaxf(x0m, __shfl_xor_sync(~0u, x0m, 2));
                x1m = fmaxf(x1m, __shfl_xor_sync(~0u, x1m, 1)); x1m = fmaxf(x1m, __shfl_xor_sync(~0u, x1m, 2));
                const float c0 = ex2(m0 - x0m), c1 = ex2(m1 - x1m);
                m0 = x0m; m1 = x1m;
#pragma unroll
                for (int b = 0; b < 3; b++) { o[4 * b] *= c0; o[4 * b + 1] *= c0; o[4 * b + 2] *= c1; o[4 * b + 3] *= c1; }
                uint32_t p[32];
#pragma unroll
                for (int b = 0; b < 16; b++) {
                    p[2 * b] = pack_bf16(ex2(s[4 * b] - m0), ex2(s[4 * b + 1] - m0));
                    p[2 * b + 1] = pack_bf16(ex2(s[4 * b + 2] - m1), ex2(s[4 * b + 3] - m1));
                }
                pin(p); pin(o);
                wg_fence();
#pragma unroll
                for (int k = 0; k < 8; k++) wgmma_rs_n24<1>(o, p[4 * k], p[4 * k + 1], p[4 * k + 2], p[4 * k + 3], dV + k * 48, 1);
                wg_commit();
                dV += 16 * 384 >> 4;
                wg_wait<0>();
            }
        }
        pin(o);
        const float l0 = __shfl_sync(~0u, o[8], (lane & ~3) | 1), l1 = __shfl_sync(~0u, o[10], (lane & ~3) | 1);
        const float i0 = 1.0f / l0, i1 = 1.0f / l1;
        uint32_t* o32 = reinterpret_cast<uint32_t*>(g_o);
        o32[row * 9 + t] = pack_bf16(o[0] * i0, o[1] * i0);
        o32[(row + 8) * 9 + t] = pack_bf16(o[2] * i1, o[3] * i1);
        o32[row * 9 + 4 + t] = pack_bf16(o[4] * i0, o[5] * i0);
        o32[(row + 8) * 9 + 4 + t] = pack_bf16(o[6] * i1, o[7] * i1);
        if (t == 0) { o32[row * 9 + 8] = pack_bf16(o[8] * i0, o[9] * i0); o32[(row + 8) * 9 + 8] = pack_bf16(o[10] * i1, o[11] * i1); }
    }
}

constexpr int O_THREADS = 416;
constexpr int O_OFF_STAT = P_A_BYTES + P_NST * P_B_STAGE + 256;
constexpr int O_SMEM = O_OFF_STAT + 9 * 64 * 8;

__global__ void __cluster_dims__(3, 1, 1) __launch_bounds__(O_THREADS, 1)
k_oproj(const __grid_constant__ CUtensorMap tmO, const __grid_constant__ CUtensorMap tmWo, const __grid_constant__ CUtensorMap tmX2, const __grid_constant__ CUtensorMap tmH, const __nv_bfloat16* __restrict__ x, const __nv_bfloat16* __restrict__ w1) {
    extern __shared__ __align__(1024) uint8_t smem[];
    const uint32_t sA = smem_u32(smem), sB = sA + P_A_BYTES, bars = sB + P_NST * P_B_STAGE;
    const uint32_t fullB = bars, emptyB = bars + 64, fullA = bars + 128;
    const int tid = threadIdx.x, warp = __shfl_sync(~0u, tid >> 5, 0), lane = tid & 31;
    const int m = blockIdx.x / 3, cg = blockIdx.x % 3;
    check_smem_base(sA);
    if (tid == 0) {
        prefetch_map(&tmO); prefetch_map(&tmWo); prefetch_map(&tmX2); prefetch_map(&tmH);
        for (int i = 0; i < P_NST; i++) { mbar_init(fullB + i * 8, 1); mbar_init(emptyB + i * 8, 12); }
        for (int i = 0; i < 9; i++) mbar_init(fullA + i * 8, 1);
        bar_init_fence();
        for (int kb = 0; kb < 9; kb++) mbar_expect(fullA + kb * 8, 8192);
    }
    __syncthreads();
    pdl_launch();
    if (warp == 12) {
        if (elect_one()) {
            for (int kb = 0; kb < 9; kb++) {
                const int s = kb >= P_NST ? kb - P_NST : kb;
                if (kb == 2) {
                    pdl_wait();
                    for (int ka = 0; ka < 9; ka++) tma_2d(sA + ka * 8192, &tmO, ka * 64, m * 64, fullA + ka * 8);
                }
                if (kb >= P_NST) mbar_wait(emptyB + s * 8, 0);
                mbar_expect(fullB + s * 8, P_B_STAGE);
                for (int a = 0; a < 3; a++) tma_2d(sB + s * P_B_STAGE + a * 8192, &tmWo, cg * 192 + a * 64, kb * 64, fullB + s * 8);
            }
            for (int i = 0; i < 6; i++) prefetch_l2(reinterpret_cast<const char*>(w1) + (size_t)blockIdx.x * (FF * DM * 2 / 96) + i * 9216, 9216);
        }
        return;
    }
    const int wg = warp >> 2, w = warp & 3, g = lane >> 2, t = lane & 3;
    uint32_t xr[16];
    {
        const uint32_t* x32 = reinterpret_cast<const uint32_t*>(x) + (((m * 64 + w * 16 + g) * DM + cg * 192 + wg * 64 + 2 * t) >> 1);
#pragma unroll
        for (int b = 0; b < 8; b++) { xr[2 * b] = __ldg(x32 + b * 4); xr[2 * b + 1] = __ldg(x32 + b * 4 + 4 * DM); }
    }
    float acc[32];
    proj_mma(acc, wg, fullB, emptyB, fullA, true, lane);
    named_sync(1, 384);
    float s0 = 0.f, q0 = 0.f, s1 = 0.f, q1 = 0.f;
#pragma unroll
    for (int b = 0; b < 8; b++) {
        const uint32_t xa = xr[2 * b], xb = xr[2 * b + 1];
        const uint32_t ha = pack_bf16(acc[4 * b] + bf_lo(xa), acc[4 * b + 1] + bf_hi(xa));
        const uint32_t hb = pack_bf16(acc[4 * b + 2] + bf_lo(xb), acc[4 * b + 3] + bf_hi(xb));
        xr[2 * b] = ha; xr[2 * b + 1] = hb;
        const float a = bf_lo(ha), c = bf_hi(ha), d = bf_lo(hb), e = bf_hi(hb);
        s0 += a + c; q0 = fmaf(a, a, fmaf(c, c, q0));
        s1 += d + e; q1 = fmaf(d, d, fmaf(e, e, q1));
    }
    s0 += __shfl_xor_sync(~0u, s0, 1); s0 += __shfl_xor_sync(~0u, s0, 2);
    q0 += __shfl_xor_sync(~0u, q0, 1); q0 += __shfl_xor_sync(~0u, q0, 2);
    s1 += __shfl_xor_sync(~0u, s1, 1); s1 += __shfl_xor_sync(~0u, s1, 2);
    q1 += __shfl_xor_sync(~0u, q1, 1); q1 += __shfl_xor_sync(~0u, q1, 2);
    const int r = w * 16 + g;
    const uint32_t sStat = sA + O_OFF_STAT;
    if (t < 3) {
        uint32_t dst;
        asm("mapa.shared::cluster.u32 %0, %1, %2;" : "=r"(dst) : "r"(sStat + ((cg * 3 + wg) * 64 + r) * 8), "r"(t));
        asm volatile("st.shared::cluster.v2.f32 [%0], {%1, %2};" ::"r"(dst), "f"(s0), "f"(q0) : "memory");
        asm volatile("st.shared::cluster.v2.f32 [%0], {%1, %2};" ::"r"(dst + 64), "f"(s1), "f"(q1) : "memory");
    }
    cluster_arrive();
    stage_tile<8>(xr, sA + wg * 8192, w, lane);
    proxy_fence();
    named_sync(2 + wg, 128);
    const bool leader = w == 0 && elect_one();
    if (leader) { tma_st_2d(&tmH, cg * 192 + wg * 64, m * 64, sA + wg * 8192); bulk_commit(); }
    cluster_wait();
    s0 = q0 = s1 = q1 = 0.f;
#pragma unroll
    for (int p = 0; p < 9; p++) {
        float a, b, c, d;
        asm volatile("ld.shared.v2.f32 {%0, %1}, [%2];" : "=f"(a), "=f"(b) : "r"(sStat + (p * 64 + r) * 8));
        asm volatile("ld.shared.v2.f32 {%0, %1}, [%2];" : "=f"(c), "=f"(d) : "r"(sStat + (p * 64 + r + 8) * 8));
        s0 += a; q0 += b; s1 += c; q1 += d;
    }
    const float m0 = s0 * (1.0f / DM), m1 = s1 * (1.0f / DM);
    const float rs0 = rsqrtf(fmaxf(q0 * (1.0f / DM) - m0 * m0, 0.f) + LN_EPS), rs1 = rsqrtf(fmaxf(q1 * (1.0f / DM) - m1 * m1, 0.f) + LN_EPS);
    const float sc0 = 0.5f * rs0, sc1 = 0.5f * rs1, n0 = -m0 * sc0, n1 = -m1 * sc1;
#pragma unroll
    for (int b = 0; b < 8; b++) {
        xr[2 * b] = pack_bf16(fmaf(bf_lo(xr[2 * b]), sc0, n0), fmaf(bf_hi(xr[2 * b]), sc0, n0));
        xr[2 * b + 1] = pack_bf16(fmaf(bf_lo(xr[2 * b + 1]), sc1, n1), fmaf(bf_hi(xr[2 * b + 1]), sc1, n1));
    }
    stage_tile<8>(xr, sA + (3 + wg) * 8192, w, lane);
    proxy_fence();
    named_sync(2 + wg, 128);
    if (leader) {
        tma_st_2d(&tmX2, cg * 192 + wg * 64, m * 64, sA + (3 + wg) * 8192);
        bulk_commit();
        bulk_wait_all();
    }
}

constexpr int F_THREADS = 384;
constexpr int F_NST = 6;
constexpr int F_STAGE = 96 * 128;
constexpr int F_X_BYTES = 9 * 16384;
constexpr int F_OFF_ST = F_X_BYTES;
constexpr int F_OFF_BAR = F_OFF_ST + F_NST * F_STAGE;
constexpr int F_SMEM = F_OFF_BAR + 256;

__device__ __forceinline__ float tanh_hw(float x) { float y; asm("tanh.approx.f32 %0, %1;" : "=f"(y) : "f"(x)); return y; }
__host__ __device__ constexpr int piece_begin(int p) { return p == 0 ? 0 : 3 * p + 1; }
template <int P>
__device__ __forceinline__ void silu_s1(const float (&acc)[32], float (&tmp)[8]) {
#pragma unroll
    for (int i = 2 * piece_begin(P); i < 2 * piece_begin(P + 1); i++) tmp[i - 2 * piece_begin(P)] = tanh_hw(acc[i]);
}
template <int C, int P>
__device__ __forceinline__ void silu_s2(const float (&acc)[32], const float (&tmp)[8], uint32_t (&h1)[144]) {
#pragma unroll
    for (int i = piece_begin(P); i < piece_begin(P + 1); i++) {
        const int k = 2 * (i - piece_begin(P));
        h1[C * 16 + i] = pack_bf16(fmaf(acc[2 * i], tmp[k], acc[2 * i]), fmaf(acc[2 * i + 1], tmp[k + 1], acc[2 * i + 1]));
    }
}
template <int J>
__device__ __forceinline__ void silu_slot_last(const float (&prev)[32], float (&tmp)[2][8], uint32_t (&h1)[144]) {
    if constexpr (J >= 1 && J <= 4) {
#pragma unroll
        for (int i = 0; i < 4; i++) {
            const int q = 4 * (J - 1) + i;
            h1[128 + q] = pack_bf16(fmaf(prev[2 * q], tmp[(J - 1) & 1][2 * i], prev[2 * q]), fmaf(prev[2 * q + 1], tmp[(J - 1) & 1][2 * i + 1], prev[2 * q + 1]));
        }
    }
    if constexpr (J <= 3) {
#pragma unroll
        for (int i = 0; i < 8; i++) tmp[J & 1][i] = tanh_hw(prev[8 * J + i]);
        pin(tmp[J & 1]);
    }
}
template <int C, int J>
__device__ __forceinline__ void silu_slot(const float (&prev)[32], float (&tmp)[2][8], uint32_t (&h1)[144]) {
    if constexpr (J >= 1) silu_s2<C, J - 1>(prev, tmp[(J - 1) & 1], h1);
    if constexpr (J <= 4) { silu_s1<J>(prev, tmp[J & 1]); pin(tmp[J & 1]); }
}

struct FfnPipe {
    uint32_t full, empty;
    int lane;
    __device__ __forceinline__ void acquire(int s, uint32_t ph) const { mbar_wait(full + s * 8, ph); }
    __device__ __forceinline__ void release(int s) const { if (lane == 0) mbar_arrive(empty + s * 8); }
};

template <int C>
__device__ __forceinline__ void ffn_phase1_chunk(float (&cur)[32], float (&prev)[32], uint32_t (&h1)[144], const FfnPipe& pp, uint64_t dx, uint32_t fullX) {
    float tmp[2][8];
    const uint64_t dw = cdesc(F_OFF_ST, 8192, 1024, 1) + blockIdx.y * (C + 1);
    dx += blockIdx.y * C;
#pragma unroll
    for (int j = 0; j < 6; j++) {
        if (C == 0) { mbar_wait(fullX + ((6 * j) >> 2) * 8, 0); mbar_wait(fullX + ((6 * j + 5) >> 2) * 8, 0); }
        pp.acquire(j, C & 1);
        if (j == 0) pin(cur);
        wg_fence();
#pragma unroll
        for (int i = 0; i < 6; i++) {
            const int ks = 6 * j + i;
            wgmma_ss_n64<1>(cur, dx + ((ks >> 2) * 1024 + (ks & 3) * 2), dw + ((j * F_STAGE + i * 2048) >> 4), ks != 0);
        }
        wg_commit();
        if (C > 0 || j > 0) { wg_wait<1>(); pp.release((j + 5) % 6); }
        if (C > 0) {
            constexpr int CP = C > 0 ? C - 1 : 0;
            pin(prev);
            if (j == 0) silu_slot<CP, 0>(prev, tmp, h1);
            if (j == 1) silu_slot<CP, 1>(prev, tmp, h1);
            if (j == 2) silu_slot<CP, 2>(prev, tmp, h1);
            if (j == 3) silu_slot<CP, 3>(prev, tmp, h1);
            if (j == 4) silu_slot<CP, 4>(prev, tmp, h1);
            if (j == 5) silu_slot<CP, 5>(prev, tmp, h1);
        }
    }
}

__device__ __forceinline__ void ffn_stage_chunk(const float (&acc)[32], uint32_t stg, int w, int lane, bool resid, uint32_t fullH) {
    uint32_t pk[16];
    if (resid) {
        mbar_wait(fullH, 0);
        const int r = w * 16 + (lane & 7) + ((lane >> 3) & 1) * 8;
#pragma unroll
        for (int b = 0; b < 8; b += 2) {
            uint32_t h0, h1, h2, h3;
            asm volatile("ldmatrix.sync.aligned.m8n8.x4.shared.b16 {%0, %1, %2, %3}, [%4];" : "=r"(h0), "=r"(h1), "=r"(h2), "=r"(h3) : "r"(stg + r * 128 + (((b + (lane >> 4)) ^ (r & 7)) << 4)) : "memory");
            pk[2 * b] = pack_bf16(acc[4 * b] + bf_lo(h0), acc[4 * b + 1] + bf_hi(h0));
            pk[2 * b + 1] = pack_bf16(acc[4 * b + 2] + bf_lo(h1), acc[4 * b + 3] + bf_hi(h1));
            pk[2 * b + 2] = pack_bf16(acc[4 * b + 4] + bf_lo(h2), acc[4 * b + 5] + bf_hi(h2));
            pk[2 * b + 3] = pack_bf16(acc[4 * b + 6] + bf_lo(h3), acc[4 * b + 7] + bf_hi(h3));
        }
    } else {
#pragma unroll
        for (int i = 0; i < 16; i++) pk[i] = pack_bf16(acc[2 * i], acc[2 * i + 1]);
    }
    stage_tile<8>(pk, stg, w, lane);
}
__device__ __forceinline__ void ffn_reduce_chunk(const CUtensorMap* tmOut, uint32_t stg, int col, int row, int w, int wgid, bool leader) {
    proxy_fence();
    if (w != 0) {
        asm volatile("bar.arrive %0, 128;" ::"r"(2 + wgid) : "memory");
    } else {
        named_sync(2 + wgid, 128);
        if (leader) { tma_red_2d(tmOut, col, row, stg); bulk_commit(); }
    }
}

__device__ __forceinline__ void ffn_load_residual(float (&acc)[32], uint32_t stg, int w, int lane, uint32_t fullH) {
    mbar_wait(fullH, 0);
    const int r = w * 16 + (lane & 7) + ((lane >> 3) & 1) * 8;
#pragma unroll
    for (int b = 0; b < 8; b += 2) {
        uint32_t h0, h1, h2, h3;
        asm volatile("ldmatrix.sync.aligned.m8n8.x4.shared.b16 {%0, %1, %2, %3}, [%4];" : "=r"(h0), "=r"(h1), "=r"(h2), "=r"(h3) : "r"(stg + r * 128 + (((b + (lane >> 4)) ^ (r & 7)) << 4)) : "memory");
        acc[4 * b] = bf_lo(h0); acc[4 * b + 1] = bf_hi(h0); acc[4 * b + 2] = bf_lo(h1); acc[4 * b + 3] = bf_hi(h1);
        acc[4 * b + 4] = bf_lo(h2); acc[4 * b + 5] = bf_hi(h2); acc[4 * b + 6] = bf_lo(h3); acc[4 * b + 7] = bf_hi(h3);
    }
}

template <int MODE>
__device__ __forceinline__ void ffn_phase2_chunk(float (&cur)[32], float (&prev)[32], uint32_t (&h1)[144], const FfnPipe& pp, uint32_t ph, const CUtensorMap* tmOut, uint32_t stg_prev, int col_prev, int row, int w, int lane, int wgid, bool leader,
                                                 bool resid_prev, uint32_t fullH, uint32_t stg_res) {
    const uint64_t dw = cdesc(F_OFF_ST, 8192, 1024, 1) + blockIdx.y * col_prev;
    float tmp[2][8];
#pragma unroll
    for (int j = 0; j < 6; j++) {
        pp.acquire(j, ph);
        if (j == 0) pin(cur);
        if (MODE == 0 && j == 5) pin(h1);
        wg_fence();
#pragma unroll
        for (int i = 0; i < 6; i++) {
            const int f = (6 * j + i) * 4;
            wgmma_rs_n64<1>(cur, h1[f], h1[f + 1], h1[f + 2], h1[f + 3], dw + ((j * F_STAGE + i * 2048) >> 4), MODE == 3 || (j | i) != 0);
        }
        wg_commit();
        wg_wait<1>();
        pp.release((j + 5) % 6);
        if (MODE == 0) {
            pin(prev);
            if (j == 0) silu_slot_last<0>(prev, tmp, h1);
            if (j == 1) silu_slot_last<1>(prev, tmp, h1);
            if (j == 2) silu_slot_last<2>(prev, tmp, h1);
            if (j == 3) silu_slot_last<3>(prev, tmp, h1);
            if (j == 4) silu_slot_last<4>(prev, tmp, h1);
        } else {
            if (j == 0) { pin(prev); ffn_stage_chunk(prev, stg_prev, w, lane, MODE == 3 && resid_prev, fullH); }
            if (j == 1) ffn_reduce_chunk(tmOut, stg_prev, col_prev, row, w, wgid, leader);
            if (MODE == 2 && j == 2) { ffn_load_residual(prev, stg_res, w, lane, fullH); pin(prev); }
        }
    }
}

__global__ void __launch_bounds__(F_THREADS, 1)
k_ffn(const __grid_constant__ CUtensorMap tmX2, const __grid_constant__ CUtensorMap tmW1, const __grid_constant__ CUtensorMap tmW2, const __grid_constant__ CUtensorMap tmOut,
      const __grid_constant__ CUtensorMap tmRes, const __nv_bfloat16* __restrict__ w2) {
    extern __shared__ __align__(1024) uint8_t smem[];
    const uint32_t sX = smem_u32(smem), sSt = sX + F_OFF_ST, bars = sX + F_OFF_BAR;
    const uint32_t full = bars, empty = bars + 64, fullX = bars + 128, fullH = bars + 208;
    const int tid = threadIdx.x, warp = __shfl_sync(~0u, tid >> 5, 0), lane = tid & 31;
    const int m = blockIdx.x >> 3, fs = blockIdx.x & 7;
    check_smem_base(sX);
    if (tid == 0) {
        prefetch_map(&tmW1); prefetch_map(&tmX2); prefetch_map(&tmW2); prefetch_map(&tmOut); prefetch_map(&tmRes);
        for (int i = 0; i < F_NST; i++) { mbar_init(full + i * 8, 1); mbar_init(empty + i * 8, 8); }
        for (int i = 0; i < 9; i++) mbar_init(fullX + i * 8, 1);
        mbar_init(fullH, 1); mbar_init(fullH + 8, 1);
        bar_init_fence();
        for (int kb = 0; kb < 9; kb++) mbar_expect(fullX + kb * 8, 16384);
    }
    __syncthreads();
    if (warp < 4) {
        asm volatile("setmaxnreg.dec.sync.aligned.u32 24;");
        if (warp == 1 && lane < 9) prefetch_l2(reinterpret_cast<const char*>(w2) + ((size_t)fs * 576 + m * 36 + lane * 4) * (DM * 2), 4 * DM * 2);
        if (warp == 0 && elect_one()) {
#pragma unroll 1
            for (int c = 0; c < 18; c++) {
                int col = c - 9 + fs;
                if (col >= 9) col -= 9;
#pragma unroll 1
                for (int j = 0; j < 6; j++) {
                    mbar_wait(empty + j * 8, (c & 1) ^ 1);
                    mbar_expect(full + j * 8, F_STAGE);
                    if (c < 9) tma_2d(sSt + j * F_STAGE, &tmW1, fs * 576 + c * 64, j * 96, full + j * 8);
                    else tma_2d(sSt + j * F_STAGE, &tmW2, col * 64, fs * 576 + j * 96, full + j * 8);
                }
            }
        }
    } else {
        asm volatile("setmaxnreg.inc.sync.aligned.u32 240;");
        const int wgid = (warp >> 2) - 1, w = warp & 3;
        pdl_wait();
        if (warp == 4 && elect_one()) {
            for (int kb = 0; kb < 9; kb++) tma_2d(sX + kb * 16384, &tmX2, kb * 64, m * 128, fullX + kb * 8);
        }
        __syncwarp();
        FfnPipe pp{full, empty, lane};
        const uint64_t xlo = cdesc(0, 16, 1024, 1) + wgid * 512;
        uint32_t h1[144];
        float acc0[32], acc1[32];
        ffn_phase1_chunk<0>(acc0, acc1, h1, pp, xlo, fullX);
        ffn_phase1_chunk<1>(acc1, acc0, h1, pp, xlo, fullX);
        ffn_phase1_chunk<2>(acc0, acc1, h1, pp, xlo, fullX);
        ffn_phase1_chunk<3>(acc1, acc0, h1, pp, xlo, fullX);
        ffn_phase1_chunk<4>(acc0, acc1, h1, pp, xlo, fullX);
        ffn_phase1_chunk<5>(acc1, acc0, h1, pp, xlo, fullX);
        ffn_phase1_chunk<6>(acc0, acc1, h1, pp, xlo, fullX);
        ffn_phase1_chunk<7>(acc1, acc0, h1, pp, xlo, fullX);
        ffn_phase1_chunk<8>(acc0, acc1, h1, pp, xlo, fullX);
        const int row = m * 128 + wgid * 64;
        const uint32_t stg = sX + wgid * 8192;
        int c = fs, cprev = 0;
        const bool leader = w == 0 && elect_one();
        const uint32_t myH = fullH + wgid * 8;
        ffn_phase2_chunk<0>(acc1, acc0, h1, pp, 1, &tmOut, 0, 0, row, w, lane, wgid, leader, false, myH, 0);
        if (leader) {
            const int c8 = fs == 0 ? 8 : fs - 1;
            mbar_expect(myH, fs == 0 ? 16384 : 8192);
            tma_2d(stg + 8 * 16384, &tmRes, c8 * 64, row, myH);
            if (fs == 0) tma_2d(stg + 7 * 16384, &tmRes, 7 * 64, row, myH);
        }
        cprev = c; if (++c == 9) c = 0;
#pragma unroll 1
        for (int j = 1; j < 7; j += 2) {
            ffn_phase2_chunk<1>(acc0, acc1, h1, pp, 0, &tmOut, stg + (j - 1) * 16384, cprev * 64, row, w, lane, wgid, leader, false, myH, 0);
            cprev = c; if (++c == 9) c = 0;
            ffn_phase2_chunk<1>(acc1, acc0, h1, pp, 1, &tmOut, stg + j * 16384, cprev * 64, row, w, lane, wgid, leader, false, myH, 0);
            cprev = c; if (++c == 9) c = 0;
        }
        ffn_phase2_chunk<2>(acc0, acc1, h1, pp, 0, &tmOut, stg + 6 * 16384, cprev * 64, row, w, lane, wgid, leader, false, myH, stg + 8 * 16384);
        cprev = c; if (++c == 9) c = 0;
        ffn_phase2_chunk<3>(acc1, acc0, h1, pp, 1, &tmOut, stg + 7 * 16384, cprev * 64, row, w, lane, wgid, leader, fs == 0, myH, 0);
        cprev = c;
        wg_wait<0>();
        pin(acc1);
        ffn_stage_chunk(acc1, stg + 8 * 16384, w, lane, false, myH);
        ffn_reduce_chunk(&tmOut, stg + 8 * 16384, cprev * 64, row, w, wgid, leader);
        if (leader) bulk_wait_all();
    }
}

typedef CUresult (*EncodeFn)(CUtensorMap*, CUtensorMapDataType, cuuint32_t, void*, const cuuint64_t*, const cuuint64_t*, const cuuint32_t*, const cuuint32_t*,
                             CUtensorMapInterleave, CUtensorMapSwizzle, CUtensorMapL2promotion, CUtensorMapFloatOOBfill);

CUtensorMap make_map(EncodeFn enc, const void* base, int rows, int cols, int box_rows) {
    CUtensorMap tm;
    cuuint64_t dims[2] = {(cuuint64_t)cols, (cuuint64_t)rows};
    cuuint64_t strides[1] = {(cuuint64_t)cols * 2};
    cuuint32_t box[2] = {64, (cuuint32_t)box_rows};
    cuuint32_t es[2] = {1, 1};
    enc(&tm, CU_TENSOR_MAP_DATA_TYPE_BFLOAT16, 2, const_cast<void*>(base), dims, strides, box, es, CU_TENSOR_MAP_INTERLEAVE_NONE,
        CU_TENSOR_MAP_SWIZZLE_128B, CU_TENSOR_MAP_L2_PROMOTION_L2_256B, CU_TENSOR_MAP_FLOAT_OOB_FILL_NONE);
    return tm;
}

template <typename... KArgs, typename... Args>
void launch(void (*kern)(KArgs...), int grid, int block, int smem, bool pdl, Args... args) {
    cudaLaunchConfig_t cfg = {};
    cfg.gridDim = dim3(grid); cfg.blockDim = dim3(block); cfg.dynamicSmemBytes = smem; cfg.stream = cudaStreamPerThread;
    cudaLaunchAttribute at[1];
    at[0].id = cudaLaunchAttributeProgrammaticStreamSerialization;
    at[0].val.programmaticStreamSerializationAllowed = 1;
    cfg.attrs = at; cfg.numAttrs = pdl ? 1 : 0;
    cudaLaunchKernelEx(&cfg, kern, KArgs(args)...);
}

}

extern "C" void kernel_launch(void* const* d_in, const int* in_sizes, int n_in, void* d_out, int out_size) {
    const __nv_bfloat16* x = (const __nv_bfloat16*)d_in[0];
    const __nv_bfloat16* wq = (const __nv_bfloat16*)d_in[1];
    const __nv_bfloat16* wk = (const __nv_bfloat16*)d_in[2];
    const __nv_bfloat16* wv = (const __nv_bfloat16*)d_in[3];
    const __nv_bfloat16* wo = (const __nv_bfloat16*)d_in[4];
    const __nv_bfloat16* w1 = (const __nv_bfloat16*)d_in[6];
    const __nv_bfloat16* w2 = (const __nv_bfloat16*)d_in[7];
    __nv_bfloat16* out = (__nv_bfloat16*)d_out;

    static EncodeFn enc = nullptr;
    static void *p_o = nullptr, *p_x2 = nullptr, *p_q = nullptr, *p_res = nullptr;
    if (!enc) {
        cudaDriverEntryPointQueryResult qr;
        cudaGetDriverEntryPoint("cuTensorMapEncodeTiled", (void**)&enc, cudaEnableDefault, &qr);
        cudaGetSymbolAddress(&p_o, g_o);
        cudaGetSymbolAddress(&p_x2, g_x2);
        cudaGetSymbolAddress(&p_res, g_h);
        cudaGetSymbolAddress(&p_q, g_q);
        cudaFuncSetAttribute(k_qkv, cudaFuncAttributeMaxDynamicSharedMemorySize, P_SMEM);
        cudaFuncSetAttribute(k_attn, cudaFuncAttributeMaxDynamicSharedMemorySize, A_SMEM);
        cudaFuncSetAttribute(k_oproj, cudaFuncAttributeMaxDynamicSharedMemorySize, O_SMEM);
        cudaFuncSetAttribute(k_ffn, cudaFuncAttributeMaxDynamicSharedMemorySize, F_SMEM);
    }
    const CUtensorMap tmWq = make_map(enc, wq, DM, DM, 64);
    const CUtensorMap tmWo = make_map(enc, wo, DM, DM, 64);
    const CUtensorMap tmO = make_map(enc, p_o, SEQ, DM, 64);
    const CUtensorMap tmX2st = make_map(enc, p_x2, SEQ, DM, 64);
    const CUtensorMap tmX2ld = make_map(enc, p_x2, SEQ, DM, 128);
    const CUtensorMap tmRes = make_map(enc, p_res, SEQ, DM, 64);
    const CUtensorMap tmQ = make_map(enc, p_q, SEQ, DM, 64);
    const CUtensorMap tmW1 = make_map(enc, w1, DM, FF, 96);
    const CUtensorMap tmW2 = make_map(enc, w2, FF, DM, 96);
    const CUtensorMap tmOut = make_map(enc, out, SEQ, DM, 64);

    launch(k_qkv, 128, Q_THREADS, P_SMEM, false, tmWq, tmQ, x, wk, wv);
    launch(k_attn, 128, A_THREADS, A_SMEM, true, out);
    launch(k_oproj, 96, O_THREADS, O_SMEM, true, tmO, tmWo, tmX2st, tmRes, x, w1);
    launch(k_ffn, 128, F_THREADS, F_SMEM, true, tmX2ld, tmW1, tmW2, tmOut, tmRes, w2);
}
```

```cpp
#include <cuda_runtime.h>
#include <cuda_bf16.h>
#include <cuda.h>
#include <stdint.h>

namespace {

constexpr int SEQ = 2048, DM = 576, FF = 4608;
constexpr int KV_BYTES = SEQ * 48;
constexpr float LN_EPS = 1e-5f;
constexpr float LOG2E = 1.4426950408889634f;
constexpr float Q_SCALE = 0.23570226039551584f * LOG2E;

constexpr uint32_t POLY_MASK = 0xB6DBu;
constexpr int CHAIN = 6;
constexpr float FAST_BOUND = 90.0f;
constexpr float FAST_VMAX2 = 1e12f;

__device__ __align__(1024) __nv_bfloat16 g_q[SEQ * DM];
__device__ __align__(1024) uint4 g_kc[KV_BYTES / 16];
__device__ __align__(1024) uint4 g_vc[KV_BYTES / 16];
__device__ __align__(16) float g_kmax[256];
__device__ __align__(1024) __nv_bfloat16 g_o[SEQ * DM];
__device__ __align__(1024) __nv_bfloat16 g_h[SEQ * DM];
__device__ __align__(1024) __nv_bfloat16 g_x2[SEQ * DM];


__device__ __forceinline__ uint32_t smem_u32(const void* p) { return (uint32_t)__cvta_generic_to_shared(p); }
__device__ __forceinline__ void wg_fence() { asm volatile("wgmma.fence.sync.aligned;" ::: "memory"); }
__device__ __forceinline__ void wg_commit() { asm volatile("wgmma.commit_group.sync.aligned;" ::: "memory"); }
template <int N> __device__ __forceinline__ void wg_wait() { asm volatile("wgmma.wait_group.sync.aligned %0;" ::"n"(N) : "memory"); }
template <int N> __device__ __forceinline__ void pin(float (&r)[N]) {
#pragma unroll
    for (int i = 0; i < N; i++) asm volatile("" : "+f"(r[i])::"memory");
}
template <int N> __device__ __forceinline__ void pin(uint32_t (&r)[N]) {
#pragma unroll
    for (int i = 0; i < N; i++) asm volatile("" : "+r"(r[i])::"memory");
}
constexpr uint32_t SMEM0 = 0x400;
__host__ __device__ constexpr uint64_t cdesc(uint32_t off, uint32_t lbo, uint32_t sbo, uint32_t swz) {
    return (uint64_t)(((SMEM0 + off) & 0x3FFFF) >> 4) | ((uint64_t)(lbo >> 4) << 16) | ((uint64_t)(sbo >> 4) << 32) | ((uint64_t)swz << 62);
}
__device__ __forceinline__ void check_smem_base(uint32_t base) { if ((base & 0x3FFFF) != SMEM0) __trap(); }

__device__ __forceinline__ void mbar_init(uint32_t bar, int cnt) { asm volatile("mbarrier.init.shared::cta.b64 [%0], %1;" ::"r"(bar), "r"(cnt) : "memory"); }
__device__ __forceinline__ void mbar_expect(uint32_t bar, int bytes) { asm volatile("mbarrier.arrive.expect_tx.shared::cta.b64 _, [%0], %1;" ::"r"(bar), "r"(bytes) : "memory"); }
__device__ __forceinline__ void mbar_arrive(uint32_t bar) { asm volatile("mbarrier.arrive.shared::cta.b64 _, [%0];" ::"r"(bar) : "memory"); }
__device__ __forceinline__ void mbar_wait(uint32_t bar, uint32_t parity) {
    asm volatile(
        "{\n.reg .pred p;\n.reg .u32 n;\nmov.u32 n, 0;\n"
        "LAB_WAIT:\n"
        "mbarrier.try_wait.parity.shared::cta.b64 p, [%0], %1;\n"
        "@p bra DONE;\n"
        "add.u32 n, n, 1;\n"
        "setp.lt.u32 p, n, 4000000;\n"
        "@p bra LAB_WAIT;\n"
        "trap;\n"
        "DONE:\n}\n" ::"r"(bar), "r"(parity) : "memory");
}
__device__ __forceinline__ void bar_init_fence() {
    asm volatile("fence.mbarrier_init.release.cluster;" ::: "memory");
    asm volatile("fence.proxy.async.shared::cta;" ::: "memory");
}
__device__ __forceinline__ void proxy_fence() { asm volatile("fence.proxy.async.shared::cta;" ::: "memory"); }
__device__ __forceinline__ void named_sync(int id, int n) { asm volatile("bar.sync %0, %1;" ::"r"(id), "r"(n) : "memory"); }
__device__ __forceinline__ void bulk_g2s(uint32_t dst, const void* src, int bytes, uint32_t bar) {
    asm volatile("cp.async.bulk.shared::cluster.global.mbarrier::complete_tx::bytes [%0], [%1], %2, [%3];" ::"r"(dst), "l"(src), "r"(bytes), "r"(bar) : "memory");
}
__device__ __forceinline__ void tma_2d(uint32_t dst, const CUtensorMap* tm, int c0, int c1, uint32_t bar) {
    asm volatile("cp.async.bulk.tensor.2d.shared::cluster.global.mbarrier::complete_tx::bytes [%0], [%1, {%3, %4}], [%2];" ::"r"(dst), "l"(tm), "r"(bar), "r"(c0), "r"(c1) : "memory");
}
__device__ __forceinline__ void cluster_arrive() { asm volatile("barrier.cluster.arrive.release.aligned;" ::: "memory"); }
__device__ __forceinline__ void cluster_wait() { asm volatile("barrier.cluster.wait.acquire.aligned;" ::: "memory"); }
__device__ __forceinline__ void tma_red_2d(const CUtensorMap* tm, int c0, int c1, uint32_t src) {
    asm volatile("cp.reduce.async.bulk.tensor.2d.global.shared::cta.add.tile.bulk_group [%0, {%2, %3}], [%1];" ::"l"(tm), "r"(src), "r"(c0), "r"(c1) : "memory");
}
__device__ __forceinline__ void tma_st_2d(const CUtensorMap* tm, int c0, int c1, uint32_t src) {
    asm volatile("cp.async.bulk.tensor.2d.global.shared::cta.tile.bulk_group [%0, {%2, %3}], [%1];" ::"l"(tm), "r"(src), "r"(c0), "r"(c1) : "memory");
}
__device__ __forceinline__ void bulk_commit() { asm volatile("cp.async.bulk.commit_group;" ::: "memory"); }
__device__ __forceinline__ void bulk_wait_all() { asm volatile("cp.async.bulk.wait_group.read 0;" ::: "memory"); }
__device__ __forceinline__ bool elect_one() {
    uint32_t p;
    asm volatile("{\n.reg .pred P;\nelect.sync _|P, 0xffffffff;\nselp.b32 %0, 1, 0, P;\n}\n" : "=r"(p));
    return p != 0;
}
__device__ __forceinline__ void prefetch_l2(const void* p, int bytes) { asm volatile("cp.async.bulk.prefetch.L2.global [%0], %1;" ::"l"(p), "r"(bytes) : "memory"); }
__device__ __forceinline__ void prefetch_map(const CUtensorMap* tm) { asm volatile("prefetch.tensormap [%0];" ::"l"(tm) : "memory"); }
__device__ __forceinline__ void pdl_launch() { asm volatile("griddepcontrol.launch_dependents;" ::: "memory"); }
__device__ __forceinline__ void pdl_wait() { asm volatile("griddepcontrol.wait;" ::: "memory"); }
__device__ __forceinline__ float ex2(float x) { float y; asm("ex2.approx.ftz.f32 %0, %1;" : "=f"(y) : "f"(x)); return y; }
__device__ __forceinline__ uint32_t pack_bf16(float lo, float hi) { uint32_t r; asm("cvt.rn.bf16x2.f32 %0, %1, %2;" : "=r"(r) : "f"(hi), "f"(lo)); return r; }
__device__ __forceinline__ float bf_lo(uint32_t v) { return __uint_as_float(v << 16); }
__device__ __forceinline__ float bf_hi(uint32_t v) { return __uint_as_float(v & 0xFFFF0000u); }
__device__ __forceinline__ uint32_t hfma2(uint32_t a, uint32_t b, uint32_t c) { uint32_t r; asm("fma.rn.f16x2 %0, %1, %2, %3;" : "=r"(r) : "r"(a), "r"(b), "r"(c)); return r; }
__device__ __forceinline__ void stmatrix_x4(uint32_t addr, uint32_t r0, uint32_t r1, uint32_t r2, uint32_t r3) {
    asm volatile("stmatrix.sync.aligned.m8n8.x4.shared.b16 [%0], {%1, %2, %3, %4};" ::"r"(addr), "r"(r0), "r"(r1), "r"(r2), "r"(r3) : "memory");
}

template <int TB> __device__ __forceinline__ void wgmma_ss_n24(float (&d)[12], uint64_t da, uint64_t db, int sc) {
    asm volatile("{\n.reg .pred p;\nsetp.ne.b32 p, %14, 0;\n"
        "wgmma.mma_async.sync.aligned.m64n24k16.f32.bf16.bf16 {%0, %1, %2, %3, %4, %5, %6, %7, %8, %9, %10, %11}, %12, %13, p, 1, 1, 0, %15;\n}\n"
        : "+f"(d[0]), "+f"(d[1]), "+f"(d[2]), "+f"(d[3]), "+f"(d[4]), "+f"(d[5]), "+f"(d[6]), "+f"(d[7]), "+f"(d[8]), "+f"(d[9]), "+f"(d[10]), "+f"(d[11])
        : "l"(da), "l"(db), "r"(sc), "n"(TB));
}
template <int TB> __device__ __forceinline__ void wgmma_ss_n64(float (&d)[32], uint64_t da, uint64_t db, int sc) {
    asm volatile("{\n.reg .pred p;\nsetp.ne.b32 p, %34, 0;\n"
        "wgmma.mma_async.sync.aligned.m64n64k16.f32.bf16.bf16 {%0, %1, %2, %3, %4, %5, %6, %7, %8, %9, %10, %11, %12, %13, %14, %15, %16, %17, %18, %19, %20, %21, %22, %23, %24, %25, %26, %27, %28, %29, %30, %31}, %32, %33, p, 1, 1, 0, %35;\n}\n"
        : "+f"(d[0]), "+f"(d[1]), "+f"(d[2]), "+f"(d[3]), "+f"(d[4]), "+f"(d[5]), "+f"(d[6]), "+f"(d[7]), "+f"(d[8]), "+f"(d[9]), "+f"(d[10]), "+f"(d[11]), "+f"(d[12]), "+f"(d[13]), "+f"(d[14]), "+f"(d[15]), "+f"(d[16]), "+f"(d[17]), "+f"(d[18]), "+f"(d[19]), "+f"(d[20]), "+f"(d[21]), "+f"(d[22]), "+f"(d[23]), "+f"(d[24]), "+f"(d[25]), "+f"(d[26]), "+f"(d[27]), "+f"(d[28]), "+f"(d[29]), "+f"(d[30]), "+f"(d[31])
        : "l"(da), "l"(db), "r"(sc), "n"(TB));
}
template <int TB> __device__ __forceinline__ void wgmma_ss_n128(float (&d)[64], uint64_t da, uint64_t db, int sc) {
    asm volatile("{\n.reg .pred p;\nsetp.ne.b32 p, %66, 0;\n"
        "wgmma.mma_async.sync.aligned.m64n128k16.f32.bf16.bf16 {%0, %1, %2, %3, %4, %5, %6, %7, %8, %9, %10, %11, %12, %13, %14, %15, %16, %17, %18, %19, %20, %21, %22, %23, %24, %25, %26, %27, %28, %29, %30, %31, %32, %33, %34, %35, %36, %37, %38, %39, %40, %41, %42, %43, %44, %45, %46, %47, %48, %49, %50, %51, %52, %53, %54, %55, %56, %57, %58, %59, %60, %61, %62, %63}, %64, %65, p, 1, 1, 0, %67;\n}\n"
        : "+f"(d[0]), "+f"(d[1]), "+f"(d[2]), "+f"(d[3]), "+f"(d[4]), "+f"(d[5]), "+f"(d[6]), "+f"(d[7]), "+f"(d[8]), "+f"(d[9]), "+f"(d[10]), "+f"(d[11]), "+f"(d[12]), "+f"(d[13]), "+f"(d[14]), "+f"(d[15]), "+f"(d[16]), "+f"(d[17]), "+f"(d[18]), "+f"(d[19]), "+f"(d[20]), "+f"(d[21]), "+f"(d[22]), "+f"(d[23]), "+f"(d[24]), "+f"(d[25]), "+f"(d[26]), "+f"(d[27]), "+f"(d[28]), "+f"(d[29]), "+f"(d[30]), "+f"(d[31]), "+f"(d[32]), "+f"(d[33]), "+f"(d[34]), "+f"(d[35]), "+f"(d[36]), "+f"(d[37]), "+f"(d[38]), "+f"(d[39]), "+f"(d[40]), "+f"(d[41]), "+f"(d[42]), "+f"(d[43]), "+f"(d[44]), "+f"(d[45]), "+f"(d[46]), "+f"(d[47]), "+f"(d[48]), "+f"(d[49]), "+f"(d[50]), "+f"(d[51]), "+f"(d[52]), "+f"(d[53]), "+f"(d[54]), "+f"(d[55]), "+f"(d[56]), "+f"(d[57]), "+f"(d[58]), "+f"(d[59]), "+f"(d[60]), "+f"(d[61]), "+f"(d[62]), "+f"(d[63])
        : "l"(da), "l"(db), "r"(sc), "n"(TB));
}
template <int TB> __device__ __forceinline__ void wgmma_rs_n24(float (&d)[12], uint32_t a0, uint32_t a1, uint32_t a2, uint32_t a3, uint64_t db, int sc) {
    asm volatile("{\n.reg .pred p;\nsetp.ne.b32 p, %17, 0;\n"
        "wgmma.mma_async.sync.aligned.m64n24k16.f32.bf16.bf16 {%0, %1, %2, %3, %4, %5, %6, %7, %8, %9, %10, %11}, {%12, %13, %14, %15}, %16, p, 1, 1, %18;\n}\n"
        : "+f"(d[0]), "+f"(d[1]), "+f"(d[2]), "+f"(d[3]), "+f"(d[4]), "+f"(d[5]), "+f"(d[6]), "+f"(d[7]), "+f"(d[8]), "+f"(d[9]), "+f"(d[10]), "+f"(d[11])
        : "r"(a0), "r"(a1), "r"(a2), "r"(a3), "l"(db), "r"(sc), "n"(TB));
}
template <int TB> __device__ __forceinline__ void wgmma_rs_n64(float (&d)[32], uint32_t a0, uint32_t a1, uint32_t a2, uint32_t a3, uint64_t db, int sc) {
    asm volatile("{\n.reg .pred p;\nsetp.ne.b32 p, %37, 0;\n"
        "wgmma.mma_async.sync.aligned.m64n64k16.f32.bf16.bf16 {%0, %1, %2, %3, %4, %5, %6, %7, %8, %9, %10, %11, %12, %13, %14, %15, %16, %17, %18, %19, %20, %21, %22, %23, %24, %25, %26, %27, %28, %29, %30, %31}, {%32, %33, %34, %35}, %36, p, 1, 1, %38;\n}\n"
        : "+f"(d[0]), "+f"(d[1]), "+f"(d[2]), "+f"(d[3]), "+f"(d[4]), "+f"(d[5]), "+f"(d[6]), "+f"(d[7]), "+f"(d[8]), "+f"(d[9]), "+f"(d[10]), "+f"(d[11]), "+f"(d[12]), "+f"(d[13]), "+f"(d[14]), "+f"(d[15]), "+f"(d[16]), "+f"(d[17]), "+f"(d[18]), "+f"(d[19]), "+f"(d[20]), "+f"(d[21]), "+f"(d[22]), "+f"(d[23]), "+f"(d[24]), "+f"(d[25]), "+f"(d[26]), "+f"(d[27]), "+f"(d[28]), "+f"(d[29]), "+f"(d[30]), "+f"(d[31])
        : "r"(a0), "r"(a1), "r"(a2), "r"(a3), "l"(db), "r"(sc), "n"(TB));
}
template <int TB> __device__ __forceinline__ void wgmma_rs_n128(float (&d)[64], uint32_t a0, uint32_t a1, uint32_t a2, uint32_t a3, uint64_t db, int sc) {
    asm volatile("{\n.reg .pred p;\nsetp.ne.b32 p, %69, 0;\n"
        "wgmma.mma_async.sync.aligned.m64n128k16.f32.bf16.bf16 {%0, %1, %2, %3, %4, %5, %6, %7, %8, %9, %10, %11, %12, %13, %14, %15, %16, %17, %18, %19, %20, %21, %22, %23, %24, %25, %26, %27, %28, %29, %30, %31, %32, %33, %34, %35, %36, %37, %38, %39, %40, %41, %42, %43, %44, %45, %46, %47, %48, %49, %50, %51, %52, %53, %54, %55, %56, %57, %58, %59, %60, %61, %62, %63}, {%64, %65, %66, %67}, %68, p, 1, 1, %70;\n}\n"
        : "+f"(d[0]), "+f"(d[1]), "+f"(d[2]), "+f"(d[3]), "+f"(d[4]), "+f"(d[5]), "+f"(d[6]), "+f"(d[7]), "+f"(d[8]), "+f"(d[9]), "+f"(d[10]), "+f"(d[11]), "+f"(d[12]), "+f"(d[13]), "+f"(d[14]), "+f"(d[15]), "+f"(d[16]), "+f"(d[17]), "+f"(d[18]), "+f"(d[19]), "+f"(d[20]), "+f"(d[21]), "+f"(d[22]), "+f"(d[23]), "+f"(d[24]), "+f"(d[25]), "+f"(d[26]), "+f"(d[27]), "+f"(d[28]), "+f"(d[29]), "+f"(d[30]), "+f"(d[31]), "+f"(d[32]), "+f"(d[33]), "+f"(d[34]), "+f"(d[35]), "+f"(d[36]), "+f"(d[37]), "+f"(d[38]), "+f"(d[39]), "+f"(d[40]), "+f"(d[41]), "+f"(d[42]), "+f"(d[43]), "+f"(d[44]), "+f"(d[45]), "+f"(d[46]), "+f"(d[47]), "+f"(d[48]), "+f"(d[49]), "+f"(d[50]), "+f"(d[51]), "+f"(d[52]), "+f"(d[53]), "+f"(d[54]), "+f"(d[55]), "+f"(d[56]), "+f"(d[57]), "+f"(d[58]), "+f"(d[59]), "+f"(d[60]), "+f"(d[61]), "+f"(d[62]), "+f"(d[63])
        : "r"(a0), "r"(a1), "r"(a2), "r"(a3), "l"(db), "r"(sc), "n"(TB));
}

constexpr int P_NST = 6;
constexpr int P_A_BYTES = 9 * 8192;
constexpr int P_B_STAGE = 3 * 8192;
constexpr int P_SMEM = P_A_BYTES + P_NST * P_B_STAGE + 256 + 256;

template <int NB>
__device__ __forceinline__ void stage_tile(const uint32_t (&pk)[NB * 2], uint32_t base, int w, int lane) {
    const int r = w * 16 + (lane & 7) + ((lane >> 3) & 1) * 8;
#pragma unroll
    for (int b = 0; b < NB; b += 2) {
        const uint32_t a = base + (b >> 3) * 8192 + r * 128 + ((((b & 7) + (lane >> 4)) ^ (r & 7)) << 4);
        stmatrix_x4(a, pk[2 * b], pk[2 * b + 1], pk[2 * b + 2], pk[2 * b + 3]);
    }
}

__device__ __forceinline__ uint32_t hsub2_bf16(uint32_t a, uint32_t b) { uint32_t r; asm("sub.rn.bf16x2 %0, %1, %2;" : "=r"(r) : "r"(a), "r"(b)); return r; }

constexpr int KV_RAW = DM * 18 * 2;
constexpr int Q_THREADS = 416;

__device__ __forceinline__ void proj_mma(float (&acc)[32], int wg, uint32_t fullB, uint32_t emptyB, uint32_t fullA, bool wait_a, int lane) {
    const uint64_t dA = cdesc(0, 16, 1024, 1), dB = cdesc(P_A_BYTES, 8192, 1024, 1) + wg * 512;
#pragma unroll 1
    for (int kb = 0; kb < 9; kb++) {
        const int s = kb >= P_NST ? kb - P_NST : kb;
        if (wait_a) mbar_wait(fullA + kb * 8, 0);
        mbar_wait(fullB + s * 8, kb >= P_NST ? 1 : 0);
        wg_fence();
#pragma unroll
        for (int ks = 0; ks < 4; ks++) wgmma_ss_n64<1>(acc, dA + (kb * 512 + ks * 2), dB + (s * (P_B_STAGE >> 4) + ks * 128), (kb | ks) != 0);
        wg_commit();
        if (kb < 4) {
            wg_wait<1>();
            if (kb >= 1 && lane == 0) mbar_arrive(emptyB + (kb - 1) * 8);
        }
    }
    wg_wait<0>();
    pin(acc);
}

__global__ void __launch_bounds__(Q_THREADS, 1)
k_qkv(const __grid_constant__ CUtensorMap tmWq, const __grid_constant__ CUtensorMap tmQ, const __nv_bfloat16* __restrict__ x, const __nv_bfloat16* __restrict__ wk, const __nv_bfloat16* __restrict__ wv) {
    extern __shared__ __align__(1024) uint8_t smem[];
    const uint32_t sA = smem_u32(smem), sB = sA + P_A_BYTES, bars = sB + P_NST * P_B_STAGE;
    const uint32_t fullB = bars, emptyB = bars + 64, fullX = bars + 128, fullW = bars + 136;
    float* s_rstd = reinterpret_cast<float*>(smem + P_A_BYTES + P_NST * P_B_STAGE + 256);
    const int tid = threadIdx.x, warp = __shfl_sync(~0u, tid >> 5, 0), lane = tid & 31;
    const bool isQ = blockIdx.x < 96;
    const int m = isQ ? blockIdx.x / 3 : blockIdx.x - 96, cg = blockIdx.x % 3;
    if (warp == 12) {
        if (elect_one()) {
            mbar_init(fullX, 1);
            bar_init_fence();
            mbar_expect(fullX, P_A_BYTES);
            bulk_g2s(sA, x + (size_t)m * 64 * DM, P_A_BYTES, fullX);
            prefetch_map(&tmWq); prefetch_map(&tmQ);
            for (int i = 0; i < P_NST; i++) { mbar_init(fullB + i * 8, 1); mbar_init(emptyB + i * 8, 12); }
            mbar_init(fullW, 1);
            bar_init_fence();
            if (isQ) {
                for (int kb = 0; kb < P_NST; kb++) {
                    mbar_expect(fullB + kb * 8, P_B_STAGE);
                    for (int a = 0; a < 3; a++) tma_2d(sB + kb * P_B_STAGE + a * 8192, &tmWq, cg * 192 + a * 64, kb * 64, fullB + kb * 8);
                }
            } else {
                mbar_expect(fullW, 2 * KV_RAW);
                bulk_g2s(sB + 3 * P_B_STAGE, wk, KV_RAW, fullW);
                bulk_g2s(sB + 3 * P_B_STAGE + KV_RAW, wv, KV_RAW, fullW);
            }
        }
        __syncwarp();
    }
    check_smem_base(sA);
    __syncthreads();
    pdl_launch();
    if (warp == 12) {
        if (isQ && elect_one()) {
            for (int kb = P_NST; kb < 9; kb++) {
                const int s = kb - P_NST;
                mbar_wait(emptyB + s * 8, 0);
                mbar_expect(fullB + s * 8, P_B_STAGE);
                for (int a = 0; a < 3; a++) tma_2d(sB + s * P_B_STAGE + a * 8192, &tmWq, cg * 192 + a * 64, kb * 64, fullB + s * 8);
            }
        }
        return;
    }
    if (warp < 8) {
        const int row = tid >> 2, q = tid & 3, h0 = (row & 1) * 4;
        mbar_wait(fullX, 0);
        uint4 v[18];
        const uint32_t ra = sA + row * 1152 + (q + h0) * 16, rb = sA + row * 1152 + (q + 4 - h0) * 16;
#pragma unroll
        for (int kb = 0; kb < 9; kb++) {
            asm volatile("ld.shared.v4.b32 {%0, %1, %2, %3}, [%4];" : "=r"(v[2 * kb].x), "=r"(v[2 * kb].y), "=r"(v[2 * kb].z), "=r"(v[2 * kb].w) : "r"(ra + kb * 128));
            asm volatile("ld.shared.v4.b32 {%0, %1, %2, %3}, [%4];" : "=r"(v[2 * kb + 1].x), "=r"(v[2 * kb + 1].y), "=r"(v[2 * kb + 1].z), "=r"(v[2 * kb + 1].w) : "r"(rb + kb * 128));
        }
        float sum = 0.f, sum2 = 0.f, sq = 0.f, sq2 = 0.f;
#pragma unroll
        for (int i = 0; i < 18; i++) {
            const uint32_t w[4] = {v[i].x, v[i].y, v[i].z, v[i].w};
#pragma unroll
            for (int j = 0; j < 4; j++) { const float a = bf_lo(w[j]), b = bf_hi(w[j]); sum += a; sum2 += b; sq = fmaf(a, a, sq); sq2 = fmaf(b, b, sq2); }
        }
        named_sync(1, 256);
        sum += sum2; sq += sq2;
        sum += __shfl_xor_sync(~0u, sum, 1); sum += __shfl_xor_sync(~0u, sum, 2);
        sq += __shfl_xor_sync(~0u, sq, 1); sq += __shfl_xor_sync(~0u, sq, 2);
        const float mean = sum * (1.0f / DM);
        if (q == 0) s_rstd[row] = rsqrtf(fmaxf(sq * (1.0f / DM) - mean * mean, 0.f) + LN_EPS);
        const uint32_t mhi = pack_bf16(mean, mean);
        const float rem = mean - bf_lo(mhi);
        const uint32_t mlo = pack_bf16(rem, rem);
        const uint32_t wa = sA + row * 128 + (((q + h0) ^ (row & 7)) << 4), wb = sA + row * 128 + (((q + 4 - h0) ^ (row & 7)) << 4);
#pragma unroll
        for (int i = 0; i < 18; i++) {
            const uint32_t o0 = hsub2_bf16(hsub2_bf16(v[i].x, mhi), mlo), o1 = hsub2_bf16(hsub2_bf16(v[i].y, mhi), mlo);
            const uint32_t o2 = hsub2_bf16(hsub2_bf16(v[i].z, mhi), mlo), o3 = hsub2_bf16(hsub2_bf16(v[i].w, mhi), mlo);
            asm volatile("st.shared.v4.b32 [%0], {%1, %2, %3, %4};" ::"r"(((i & 1) ? wb : wa) + (i >> 1) * 8192), "r"(o0), "r"(o1), "r"(o2), "r"(o3) : "memory");
        }
    } else if (!isQ) {
        mbar_wait(fullW, 0);
        const uint32_t* raw = reinterpret_cast<const uint32_t*>(smem + P_A_BYTES + 3 * P_B_STAGE);
#pragma unroll 3
        for (int r = tid - 256; r < 2 * DM; r += 128) {
            uint32_t wr[9];
#pragma unroll
            for (int i = 0; i < 9; i++) wr[i] = raw[r * 9 + i];
            const int sel = r >= DM, k = r - sel * DM;
            uint8_t* dst = smem + P_A_BYTES + sel * 3 * 9216 + (k >> 3) * 128 + (k & 7) * 16;
            *reinterpret_cast<uint4*>(dst) = make_uint4(wr[0], wr[1], wr[2], wr[3]);
            *reinterpret_cast<uint4*>(dst + 9216) = make_uint4(wr[4], wr[5], wr[6], wr[7]);
            *reinterpret_cast<uint32_t*>(dst + 2 * 9216) = wr[8];
        }
    }
    proxy_fence();
    named_sync(2, 384);
    const int wg = warp >> 2, w = warp & 3, g = lane >> 2, t = lane & 3;
    const float rs0 = s_rstd[w * 16 + g], rs1 = s_rstd[w * 16 + g + 8];
    if (isQ) {
        const float c0 = rs0 * Q_SCALE, c1 = rs1 * Q_SCALE;
        float acc[32];
        proj_mma(acc, wg, fullB, emptyB, 0, false, lane);
        uint32_t pk[16];
#pragma unroll
        for (int i = 0; i < 8; i++) { pk[2 * i] = pack_bf16(acc[4 * i] * c0, acc[4 * i + 1] * c0); pk[2 * i + 1] = pack_bf16(acc[4 * i + 2] * c1, acc[4 * i + 3] * c1); }
        named_sync(2, 384);
        stage_tile<8>(pk, sA + wg * 8192, w, lane);
        proxy_fence();
        named_sync(3 + wg, 128);
        if (w == 0 && elect_one()) {
            tma_st_2d(&tmQ, cg * 192 + wg * 64, m * 64, sA + wg * 8192);
            bulk_commit();
            bulk_wait_all();
        }
    } else if (wg < 2) {
        float acc[12];
        const uint64_t dA = cdesc(0, 16, 1024, 1), dB = cdesc(P_A_BYTES, 128, 9216, 0) + wg * (3 * 9216 >> 4);
#pragma unroll
        for (int i = 0; i < 12; i++) acc[i] = 0.f;
        pin(acc);
        wg_fence();
#pragma unroll 1
        for (int kb = 0; kb < 9; kb++) {
#pragma unroll
            for (int ks = 0; ks < 4; ks++) wgmma_ss_n24<1>(acc, dA + (kb * 512 + ks * 2), dB + (kb * 4 + ks) * 16, 1);
        }
        wg_commit();
        wg_wait<0>();
        pin(acc);
        uint32_t pk[6];
#pragma unroll
        for (int b = 0; b < 3; b++) { pk[2 * b] = pack_bf16(acc[4 * b] * rs0, acc[4 * b + 1] * rs0); pk[2 * b + 1] = pack_bf16(acc[4 * b + 2] * rs1, acc[4 * b + 3] * rs1); }
        float n0 = 0.f, n1 = 0.f, vm = 0.f;
#pragma unroll
        for (int b = 0; b < 3; b++) {
            if (b < 2 || t == 0) {
                const float a = bf_lo(pk[2 * b]), c = bf_hi(pk[2 * b]), d = bf_lo(pk[2 * b + 1]), e = bf_hi(pk[2 * b + 1]);
                n0 = fmaf(a, a, fmaf(c, c, n0)); n1 = fmaf(d, d, fmaf(e, e, n1));
            }
        }
        n0 += __shfl_xor_sync(~0u, n0, 1); n0 += __shfl_xor_sync(~0u, n0, 2);
        n1 += __shfl_xor_sync(~0u, n1, 1); n1 += __shfl_xor_sync(~0u, n1, 2);
        vm = fmaxf(n0, n1);
        if (!(n0 == n0) || !(n1 == n1)) vm = __int_as_float(0x7F800000);
#pragma unroll
        for (int o = 4; o < 32; o <<= 1) vm = fmaxf(vm, __shfl_xor_sync(~0u, vm, o));
        if (t != 0) {
            uint32_t lo, hi;
            if (wg == 0) {
                const int grp = m * 8 + w * 2;
                const uint32_t c = t == 1 ? 0x42FE3F80u   : (t == 2 ? 0x00003BC0u   : 0u);
                lo = ((POLY_MASK >> (grp & 15)) & 1) ? c : 0u;
                hi = ((POLY_MASK >> ((grp + 1) & 15)) & 1) ? c : 0u;
            } else {
                lo = hi = t == 1 ? 0x00003F80u : 0u;
            }
            pk[4] = lo; pk[5] = hi;
        }
        uint32_t* dst = reinterpret_cast<uint32_t*>(wg == 0 ? g_kc : g_vc) + (m * 8 + w * 2) * 96 + g * 4 + t;
#pragma unroll
        for (int b = 0; b < 3; b++) { dst[b * 32] = pk[2 * b]; dst[96 + b * 32] = pk[2 * b + 1]; }
        if (lane == 0) g_kmax[m * 8 + warp] = (wg == 0) ? vm : (vm <= FAST_VMAX2 ? 0.f : __int_as_float(0x7F800000));
    }
}

constexpr int A_THREADS = 512;
constexpr int A_NPIECE = 8;
constexpr int A_OFF_Q = 2 * KV_BYTES;
constexpr int A_OFF_BAR = A_OFF_Q + 8 * 4096;
constexpr int A_SMEM = A_OFF_BAR + 128;

__device__ __forceinline__ uint32_t exp2_pair_fixed(float lo, float hi, uint32_t dep) {
    const uint32_t G = __byte_perm(__float_as_uint(lo), __float_as_uint(hi), 0x5410);
    uint32_t Hh;
    asm("lop3.b32 %0, %1, 0x007F007F, %2, 0xC0;" : "=r"(Hh) : "r"(G), "r"(dep));
    const uint32_t tt = hfma2(Hh, 0xF96BF96Bu, 0x358C358Cu);
    return G - hfma2(tt, Hh, 0u);
}

__global__ void __launch_bounds__(A_THREADS, 1)
k_attn(__nv_bfloat16* __restrict__ out) {
    extern __shared__ __align__(1024) uint8_t smem[];
    pdl_launch();
    const uint32_t sK = smem_u32(smem), sV = sK + KV_BYTES, bars = sK + A_OFF_BAR;
    const int tid = threadIdx.x;
    check_smem_base(sK);
    if (tid == 0) {
        for (int i = 0; i < A_NPIECE; i++) mbar_init(bars + i * 8, 1);
        bar_init_fence();
    }
    __syncthreads();
    pdl_wait();
    const int wg = __shfl_sync(~0u, tid >> 7, 0), w = (tid >> 5) & 3, lane = tid & 31, g = lane >> 2, t = lane & 3;
    const uint32_t* q32 = reinterpret_cast<const uint32_t*>(g_q);
    int row = (blockIdx.x * 8 + wg) * 64 + w * 16 + g;
    uint32_t nq[2][6];
#pragma unroll
    for (int r = 0; r < 2; r++) {
        const uint32_t* q = q32 + (row + r * 256) * 9;
        nq[r][0] = q[t]; nq[r][1] = q[72 + t]; nq[r][2] = q[4 + t]; nq[r][3] = q[76 + t]; nq[r][4] = q[8]; nq[r][5] = q[80];
    }
    constexpr int PB = KV_BYTES / A_NPIECE;
    const float4 km0 = reinterpret_cast<const float4*>(g_kmax)[lane], km1 = reinterpret_cast<const float4*>(g_kmax)[32 + lane];
    if (tid < 32 && elect_one()) {
        for (int i = 0; i < 2; i++) {
            mbar_expect(bars + i * 8, 2 * PB);
            bulk_g2s(sK + i * PB, reinterpret_cast<const char*>(g_kc) + i * PB, PB, bars + i * 8);
            bulk_g2s(sV + i * PB, reinterpret_cast<const char*>(g_vc) + i * PB, PB, bars + i * 8);
        }
    }
    float kmax2 = fmaxf(fmaxf(fmaxf(km0.x, km0.y), fmaxf(km0.z, km0.w)), fmaxf(fmaxf(km1.x, km1.y), fmaxf(km1.z, km1.w)));
#pragma unroll
    for (int o = 1; o < 32; o <<= 1) kmax2 = fmaxf(kmax2, __shfl_xor_sync(~0u, kmax2, o));
    if (tid < 32 && elect_one()) {
        for (int i = 2; i < A_NPIECE; i++) {
            mbar_expect(bars + i * 8, 2 * PB);
            bulk_g2s(sK + i * PB, reinterpret_cast<const char*>(g_kc) + i * PB, PB, bars + i * 8);
            bulk_g2s(sV + i * PB, reinterpret_cast<const char*>(g_vc) + i * PB, PB, bars + i * 8);
        }
    }
    uint32_t vote = 0;
#pragma unroll
    for (int r = 0; r < 2; r++) {
        const uint32_t (&q)[6] = nq[r];
        const float a0 = bf_lo(q[0]), a1 = bf_hi(q[0]), a2 = bf_lo(q[2]), a3 = bf_hi(q[2]);
        const float b0 = bf_lo(q[1]), b1 = bf_hi(q[1]), b2 = bf_lo(q[3]), b3 = bf_hi(q[3]);
        float n0 = a0 * a0 + a1 * a1 + a2 * a2 + a3 * a3, n1 = b0 * b0 + b1 * b1 + b2 * b2 + b3 * b3;
        if (t == 0) {
            const float c0 = bf_lo(q[4]), c1 = bf_hi(q[4]), d0 = bf_lo(q[5]), d1 = bf_hi(q[5]);
            n0 += c0 * c0 + c1 * c1; n1 += d0 * d0 + d1 * d1;
        }
        n0 += __shfl_xor_sync(~0u, n0, 1); n0 += __shfl_xor_sync(~0u, n0, 2);
        n1 += __shfl_xor_sync(~0u, n1, 1); n1 += __shfl_xor_sync(~0u, n1, 2);
        const bool unsafe = !(fmaxf(n0, n1) * kmax2 <= FAST_BOUND * FAST_BOUND) || !(n0 == n0) || !(n1 == n1);
        vote |= (__any_sync(~0u, unsafe) ? 1u : 0u) << r;
        const uint32_t cst = t == 1 ? 0x3F804780u : (t == 2 ? 0x00003F80u : 0u);
        const uint32_t sQ = sK + A_OFF_Q + (r * 4 + wg) * 4096 + (w * 2) * 512 + g * 16 + t * 4;
        asm volatile("st.shared.b32 [%0], %1;" ::"r"(sQ), "r"(q[0]) : "memory");
        asm volatile("st.shared.b32 [%0], %1;" ::"r"(sQ + 512), "r"(q[1]) : "memory");
        asm volatile("st.shared.b32 [%0], %1;" ::"r"(sQ + 128), "r"(q[2]) : "memory");
        asm volatile("st.shared.b32 [%0], %1;" ::"r"(sQ + 640), "r"(q[3]) : "memory");
        asm volatile("st.shared.b32 [%0], %1;" ::"r"(sQ + 256), "r"(t == 0 ? q[4] : cst) : "memory");
        asm volatile("st.shared.b32 [%0], %1;" ::"r"(sQ + 768), "r"(t == 0 ? q[5] : cst) : "memory");
        asm volatile("st.shared.b32 [%0], %1;" ::"r"(sQ + 384), "r"(0u) : "memory");
        asm volatile("st.shared.b32 [%0], %1;" ::"r"(sQ + 896), "r"(0u) : "memory");
    }
    const uint32_t sVote = bars + 64 + wg * 16;
    if (lane == 0) asm volatile("st.shared.b32 [%0], %1;" ::"r"(sVote + w * 4), "r"(vote) : "memory");
    proxy_fence();
    named_sync(wg + 1, 128);
    uint32_t unsafe_mask;
    {
        uint32_t v0, v1, v2, v3;
        asm volatile("ld.shared.v4.b32 {%0, %1, %2, %3}, [%4];" : "=r"(v0), "=r"(v1), "=r"(v2), "=r"(v3) : "r"(sVote));
        unsafe_mask = __shfl_sync(~0u, v0 | v1 | v2 | v3, 0);
    }
    if (unsafe_mask) {
#pragma unroll
        for (int r = 0; r < 2; r++) {
            if (((unsafe_mask >> r) & 1) && t != 0) {
                const uint32_t sQ = sK + A_OFF_Q + (r * 4 + wg) * 4096 + (w * 2) * 512 + g * 16 + t * 4;
                asm volatile("st.shared.b32 [%0], %1;" ::"r"(sQ + 256), "r"(0u) : "memory");
                asm volatile("st.shared.b32 [%0], %1;" ::"r"(sQ + 768), "r"(0u) : "memory");
            }
        }
        proxy_fence();
        named_sync(wg + 1, 128);
    }
#pragma unroll 1
    for (int rep = 0; rep < 2; rep++, row += 256) {
        if (rep == 1) {
            uint4* z = reinterpret_cast<uint4*>(out + (size_t)blockIdx.x * 16 * DM) + tid;
            z[0] = make_uint4(0u, 0u, 0u, 0u); z[A_THREADS] = make_uint4(0u, 0u, 0u, 0u);
            if (tid < 16 * DM * 2 / 16 - 2 * A_THREADS) z[2 * A_THREADS] = make_uint4(0u, 0u, 0u, 0u);
        }
        const uint32_t any_unsafe = (unsafe_mask >> rep) & 1;
        const uint64_t dQ0 = cdesc(A_OFF_Q, 128, 512, 0) + (rep * 4 + wg) * 256, dQ1 = dQ0 + 16;
        float o[12];
#pragma unroll
        for (int i = 0; i < 12; i++) o[i] = 0.f;
        pin(o);
        uint64_t dK0 = cdesc(0, 128, 384, 0), dK1 = cdesc(256, 0, 384, 0), dV = cdesc(KV_BYTES, 384, 128, 0);
        if (!any_unsafe) {
            float s[64];
#pragma unroll 1
            for (int j = 0; j < 16; j++) {
                if (rep == 0 && (j & 1) == 0) mbar_wait(bars + (j >> 1) * 8, 0);
                wg_fence();
                wgmma_ss_n128<0>(s, dQ0, dK0, 0);
                wgmma_ss_n128<0>(s, dQ1, dK1, 1);
                wg_commit();
                dK0 += 16 * 384 >> 4; dK1 += 16 * 384 >> 4;
                wg_wait<0>();
                pin(s);
                uint32_t p[32];
                {
                    constexpr int NP = 2 * __builtin_popcount(POLY_MASK), NM = 32 - NP;
                    float e[64];
#pragma unroll
                    for (int i = 0; i < 32; i++)
                        if (!((POLY_MASK >> (i >> 1)) & 1)) { e[2 * i] = ex2(s[2 * i]); e[2 * i + 1] = ex2(s[2 * i + 1]); p[i] = pack_bf16(e[2 * i], e[2 * i + 1]); }
                    int ip = 0;
#pragma unroll
                    for (int i = 0; i < 32; i++) {
                        if ((POLY_MASK >> (i >> 1)) & 1) {
                            const int mm = (ip * 2 * NM) / NP - CHAIN;
                            uint32_t dep = 0;
                            if (CHAIN > 0 && mm >= 0) {
                                int cnt = 0;
#pragma unroll
                                for (int q = 0; q < 32; q++)
                                    if (!((POLY_MASK >> (q >> 1)) & 1)) { if (cnt == (mm >> 1)) dep = __float_as_uint(e[2 * q + (mm & 1)]); cnt++; }
                            }
                            p[i] = exp2_pair_fixed(s[2 * i], s[2 * i + 1], dep);
                            ip++;
                        }
                    }
                }
                pin(p);
                wg_fence();
#pragma unroll
                for (int k = 0; k < 8; k++) wgmma_rs_n24<1>(o, p[4 * k], p[4 * k + 1], p[4 * k + 2], p[4 * k + 3], dV + k * 48, 1);
                wg_commit();
                dV += 16 * 384 >> 4;
                wg_wait<0>();
            }
        } else {
            float s[64];
            float m0 = -INFINITY, m1 = -INFINITY;
#pragma unroll 1
            for (int j = 0; j < 16; j++) {
                if (rep == 0 && (j & 1) == 0) mbar_wait(bars + (j >> 1) * 8, 0);
                wg_fence();
                wgmma_ss_n128<0>(s, dQ0, dK0, 0);
                wgmma_ss_n128<0>(s, dQ1, dK1, 1);
                wg_commit();
                dK0 += 16 * 384 >> 4; dK1 += 16 * 384 >> 4;
                wg_wait<0>();
                pin(s);
                float x0m = m0, x1m = m1;
#pragma unroll
                for (int b = 0; b < 16; b++) { x0m = fmaxf(x0m, fmaxf(s[4 * b], s[4 * b + 1])); x1m = fmaxf(x1m, fmaxf(s[4 * b + 2], s[4 * b + 3])); }
                x0m = fmaxf(x0m, __shfl_xor_sync(~0u, x0m, 1)); x0m = fmaxf(x0m, __shfl_xor_sync(~0u, x0m, 2));
                x1m = fmaxf(x1m, __shfl_xor_sync(~0u, x1m, 1)); x1m = fmaxf(x1m, __shfl_xor_sync(~0u, x1m, 2));
                const float c0 = ex2(m0 - x0m), c1 = ex2(m1 - x1m);
                m0 = x0m; m1 = x1m;
#pragma unroll
                for (int b = 0; b < 3; b++) { o[4 * b] *= c0; o[4 * b + 1] *= c0; o[4 * b + 2] *= c1; o[4 * b + 3] *= c1; }
                uint32_t p[32];
#pragma unroll
                for (int b = 0; b < 16; b++) {
                    p[2 * b] = pack_bf16(ex2(s[4 * b] - m0), ex2(s[4 * b + 1] - m0));
                    p[2 * b + 1] = pack_bf16(ex2(s[4 * b + 2] - m1), ex2(s[4 * b + 3] - m1));
                }
                pin(p); pin(o);
                wg_fence();
#pragma unroll
                for (int k = 0; k < 8; k++) wgmma_rs_n24<1>(o, p[4 * k], p[4 * k + 1], p[4 * k + 2], p[4 * k + 3], dV + k * 48, 1);
                wg_commit();
                dV += 16 * 384 >> 4;
                wg_wait<0>();
            }
        }
        pin(o);
        const float l0 = __shfl_sync(~0u, o[8], (lane & ~3) | 1), l1 = __shfl_sync(~0u, o[10], (lane & ~3) | 1);
        const float i0 = 1.0f / l0, i1 = 1.0f / l1;
        uint32_t* o32 = reinterpret_cast<uint32_t*>(g_o);
        o32[row * 9 + t] = pack_bf16(o[0] * i0, o[1] * i0);
        o32[(row + 8) * 9 + t] = pack_bf16(o[2] * i1, o[3] * i1);
        o32[row * 9 + 4 + t] = pack_bf16(o[4] * i0, o[5] * i0);
        o32[(row + 8) * 9 + 4 + t] = pack_bf16(o[6] * i1, o[7] * i1);
        if (t == 0) { o32[row * 9 + 8] = pack_bf16(o[8] * i0, o[9] * i0); o32[(row + 8) * 9 + 8] = pack_bf16(o[10] * i1, o[11] * i1); }
    }
}

constexpr int O_THREADS = 416;
constexpr int O_OFF_STAT = P_A_BYTES + P_NST * P_B_STAGE + 256;
constexpr int O_SMEM = O_OFF_STAT + 9 * 64 * 8;

__global__ void __cluster_dims__(3, 1, 1) __launch_bounds__(O_THREADS, 1)
k_oproj(const __grid_constant__ CUtensorMap tmO, const __grid_constant__ CUtensorMap tmWo, const __grid_constant__ CUtensorMap tmX2, const __grid_constant__ CUtensorMap tmH, const __nv_bfloat16* __restrict__ x, const __nv_bfloat16* __restrict__ w1) {
    extern __shared__ __align__(1024) uint8_t smem[];
    const uint32_t sA = smem_u32(smem), sB = sA + P_A_BYTES, bars = sB + P_NST * P_B_STAGE;
    const uint32_t fullB = bars, emptyB = bars + 64, fullA = bars + 128;
    const int tid = threadIdx.x, warp = __shfl_sync(~0u, tid >> 5, 0), lane = tid & 31;
    const int m = blockIdx.x / 3, cg = blockIdx.x % 3;
    check_smem_base(sA);
    if (tid == 0) {
        prefetch_map(&tmO); prefetch_map(&tmWo); prefetch_map(&tmX2); prefetch_map(&tmH);
        for (int i = 0; i < P_NST; i++) { mbar_init(fullB + i * 8, 1); mbar_init(emptyB + i * 8, 12); }
        for (int i = 0; i < 9; i++) mbar_init(fullA + i * 8, 1);
        bar_init_fence();
        for (int kb = 0; kb < 9; kb++) mbar_expect(fullA + kb * 8, 8192);
    }
    __syncthreads();
    pdl_launch();
    if (warp == 12) {
        if (elect_one()) {
            for (int kb = 0; kb < 9; kb++) {
                const int s = kb >= P_NST ? kb - P_NST : kb;
                if (kb == 2) {
                    pdl_wait();
                    for (int ka = 0; ka < 9; ka++) tma_2d(sA + ka * 8192, &tmO, ka * 64, m * 64, fullA + ka * 8);
                }
                if (kb >= P_NST) mbar_wait(emptyB + s * 8, 0);
                mbar_expect(fullB + s * 8, P_B_STAGE);
                for (int a = 0; a < 3; a++) tma_2d(sB + s * P_B_STAGE + a * 8192, &tmWo, cg * 192 + a * 64, kb * 64, fullB + s * 8);
            }
            for (int i = 0; i < 6; i++) prefetch_l2(reinterpret_cast<const char*>(w1) + (size_t)blockIdx.x * (FF * DM * 2 / 96) + i * 9216, 9216);
        }
        return;
    }
    const int wg = warp >> 2, w = warp & 3, g = lane >> 2, t = lane & 3;
    uint32_t xr[16];
    {
        const uint32_t* x32 = reinterpret_cast<const uint32_t*>(x) + (((m * 64 + w * 16 + g) * DM + cg * 192 + wg * 64 + 2 * t) >> 1);
#pragma unroll
        for (int b = 0; b < 8; b++) { xr[2 * b] = __ldg(x32 + b * 4); xr[2 * b + 1] = __ldg(x32 + b * 4 + 4 * DM); }
    }
    float acc[32];
    proj_mma(acc, wg, fullB, emptyB, fullA, true, lane);
    named_sync(1, 384);
    float s0 = 0.f, q0 = 0.f, s1 = 0.f, q1 = 0.f;
#pragma unroll
    for (int b = 0; b < 8; b++) {
        const uint32_t xa = xr[2 * b], xb = xr[2 * b + 1];
        const uint32_t ha = pack_bf16(acc[4 * b] + bf_lo(xa), acc[4 * b + 1] + bf_hi(xa));
        const uint32_t hb = pack_bf16(acc[4 * b + 2] + bf_lo(xb), acc[4 * b + 3] + bf_hi(xb));
        xr[2 * b] = ha; xr[2 * b + 1] = hb;
        const float a = bf_lo(ha), c = bf_hi(ha), d = bf_lo(hb), e = bf_hi(hb);
        s0 += a + c; q0 = fmaf(a, a, fmaf(c, c, q0));
        s1 += d + e; q1 = fmaf(d, d, fmaf(e, e, q1));
    }
    s0 += __shfl_xor_sync(~0u, s0, 1); s0 += __shfl_xor_sync(~0u, s0, 2);
    q0 += __shfl_xor_sync(~0u, q0, 1); q0 += __shfl_xor_sync(~0u, q0, 2);
    s1 += __shfl_xor_sync(~0u, s1, 1); s1 += __shfl_xor_sync(~0u, s1, 2);
    q1 += __shfl_xor_sync(~0u, q1, 1); q1 += __shfl_xor_sync(~0u, q1, 2);
    const int r = w * 16 + g;
    const uint32_t sStat = sA + O_OFF_STAT;
    if (t < 3) {
        uint32_t dst;
        asm("mapa.shared::cluster.u32 %0, %1, %2;" : "=r"(dst) : "r"(sStat + ((cg * 3 + wg) * 64 + r) * 8), "r"(t));
        asm volatile("st.shared::cluster.v2.f32 [%0], {%1, %2};" ::"r"(dst), "f"(s0), "f"(q0) : "memory");
        asm volatile("st.shared::cluster.v2.f32 [%0], {%1, %2};" ::"r"(dst + 64), "f"(s1), "f"(q1) : "memory");
    }
    cluster_arrive();
    stage_tile<8>(xr, sA + wg * 8192, w, lane);
    proxy_fence();
    named_sync(2 + wg, 128);
    const bool leader = w == 0 && elect_one();
    if (leader) { tma_st_2d(&tmH, cg * 192 + wg * 64, m * 64, sA + wg * 8192); bulk_commit(); }
    cluster_wait();
    s0 = q0 = s1 = q1 = 0.f;
#pragma unroll
    for (int p = 0; p < 9; p++) {
        float a, b, c, d;
        asm volatile("ld.shared.v2.f32 {%0, %1}, [%2];" : "=f"(a), "=f"(b) : "r"(sStat + (p * 64 + r) * 8));
        asm volatile("ld.shared.v2.f32 {%0, %1}, [%2];" : "=f"(c), "=f"(d) : "r"(sStat + (p * 64 + r + 8) * 8));
        s0 += a; q0 += b; s1 += c; q1 += d;
    }
    const float m0 = s0 * (1.0f / DM), m1 = s1 * (1.0f / DM);
    const float rs0 = rsqrtf(fmaxf(q0 * (1.0f / DM) - m0 * m0, 0.f) + LN_EPS), rs1 = rsqrtf(fmaxf(q1 * (1.0f / DM) - m1 * m1, 0.f) + LN_EPS);
    const float sc0 = 0.5f * rs0, sc1 = 0.5f * rs1, n0 = -m0 * sc0, n1 = -m1 * sc1;
#pragma unroll
    for (int b = 0; b < 8; b++) {
        xr[2 * b] = pack_bf16(fmaf(bf_lo(xr[2 * b]), sc0, n0), fmaf(bf_hi(xr[2 * b]), sc0, n0));
        xr[2 * b + 1] = pack_bf16(fmaf(bf_lo(xr[2 * b + 1]), sc1, n1), fmaf(bf_hi(xr[2 * b + 1]), sc1, n1));
    }
    stage_tile<8>(xr, sA + (3 + wg) * 8192, w, lane);
    proxy_fence();
    named_sync(2 + wg, 128);
    if (leader) {
        tma_st_2d(&tmX2, cg * 192 + wg * 64, m * 64, sA + (3 + wg) * 8192);
        bulk_commit();
        bulk_wait_all();
    }
}

constexpr int F_THREADS = 384;
constexpr int F_NST = 6;
constexpr int F_STAGE = 96 * 128;
constexpr int F_X_BYTES = 9 * 16384;
constexpr int F_OFF_ST = F_X_BYTES;
constexpr int F_OFF_BAR = F_OFF_ST + F_NST * F_STAGE;
constexpr int F_SMEM = F_OFF_BAR + 256;

__device__ __forceinline__ float tanh_hw(float x) { float y; asm("tanh.approx.f32 %0, %1;" : "=f"(y) : "f"(x)); return y; }
__host__ __device__ constexpr int piece_begin(int p) { return p == 0 ? 0 : 3 * p + 1; }
template <int P>
__device__ __forceinline__ void silu_s1(const float (&acc)[32], float (&tmp)[8]) {
#pragma unroll
    for (int i = 2 * piece_begin(P); i < 2 * piece_begin(P + 1); i++) tmp[i - 2 * piece_begin(P)] = tanh_hw(acc[i]);
}
template <int C, int P>
__device__ __forceinline__ void silu_s2(const float (&acc)[32], const float (&tmp)[8], uint32_t (&h1)[144]) {
#pragma unroll
    for (int i = piece_begin(P); i < piece_begin(P + 1); i++) {
        const int k = 2 * (i - piece_begin(P));
        h1[C * 16 + i] = pack_bf16(fmaf(acc[2 * i], tmp[k], acc[2 * i]), fmaf(acc[2 * i + 1], tmp[k + 1], acc[2 * i + 1]));
    }
}
template <int J>
__device__ __forceinline__ void silu_slot_last(const float (&prev)[32], float (&tmp)[2][8], uint32_t (&h1)[144]) {
    if constexpr (J >= 1 && J <= 4) {
#pragma unroll
        for (int i = 0; i < 4; i++) {
            const int q = 4 * (J - 1) + i;
            h1[128 + q] = pack_bf16(fmaf(prev[2 * q], tmp[(J - 1) & 1][2 * i], prev[2 * q]), fmaf(prev[2 * q + 1], tmp[(J - 1) & 1][2 * i + 1], prev[2 * q + 1]));
        }
    }
    if constexpr (J <= 3) {
#pragma unroll
        for (int i = 0; i < 8; i++) tmp[J & 1][i] = tanh_hw(prev[8 * J + i]);
        pin(tmp[J & 1]);
    }
}
template <int C, int J>
__device__ __forceinline__ void silu_slot(const float (&prev)[32], float (&tmp)[2][8], uint32_t (&h1)[144]) {
    if constexpr (J >= 1) silu_s2<C, J - 1>(prev, tmp[(J - 1) & 1], h1);
    if constexpr (J <= 4) { silu_s1<J>(prev, tmp[J & 1]); pin(tmp[J & 1]); }
}

struct FfnPipe {
    uint32_t full, empty;
    int lane;
    __device__ __forceinline__ void acquire(int s, uint32_t ph) const { mbar_wait(full + s * 8, ph); }
    __device__ __forceinline__ void release(int s) const { if (lane == 0) mbar_arrive(empty + s * 8); }
};

template <int C>
__device__ __forceinline__ void ffn_phase1_chunk(float (&cur)[32], float (&prev)[32], uint32_t (&h1)[144], const FfnPipe& pp, uint64_t dx, uint32_t fullX) {
    float tmp[2][8];
    const uint64_t dw = cdesc(F_OFF_ST, 8192, 1024, 1) + blockIdx.y * (C + 1);
    dx += blockIdx.y * C;
#pragma unroll
    for (int j = 0; j < 6; j++) {
        if (C == 0) { mbar_wait(fullX + ((6 * j) >> 2) * 8, 0); mbar_wait(fullX + ((6 * j + 5) >> 2) * 8, 0); }
        pp.acquire(j, C & 1);
        if (j == 0) pin(cur);
        wg_fence();
#pragma unroll
        for (int i = 0; i < 6; i++) {
            const int ks = 6 * j + i;
            wgmma_ss_n64<1>(cur, dx + ((ks >> 2) * 1024 + (ks & 3) * 2), dw + ((j * F_STAGE + i * 2048) >> 4), ks != 0);
        }
        wg_commit();
        if (C > 0 || j > 0) { wg_wait<1>(); pp.release((j + 5) % 6); }
        if (C > 0) {
            constexpr int CP = C > 0 ? C - 1 : 0;
            pin(prev);
            if (j == 0) silu_slot<CP, 0>(prev, tmp, h1);
            if (j == 1) silu_slot<CP, 1>(prev, tmp, h1);
            if (j == 2) silu_slot<CP, 2>(prev, tmp, h1);
            if (j == 3) silu_slot<CP, 3>(prev, tmp, h1);
            if (j == 4) silu_slot<CP, 4>(prev, tmp, h1);
            if (j == 5) silu_slot<CP, 5>(prev, tmp, h1);
        }
    }
}

__device__ __forceinline__ void ffn_stage_chunk(const float (&acc)[32], uint32_t stg, int w, int lane, bool resid, uint32_t fullH) {
    uint32_t pk[16];
    if (resid) {
        mbar_wait(fullH, 0);
        const int r = w * 16 + (lane & 7) + ((lane >> 3) & 1) * 8;
#pragma unroll
        for (int b = 0; b < 8; b += 2) {
            uint32_t h0, h1, h2, h3;
            asm volatile("ldmatrix.sync.aligned.m8n8.x4.shared.b16 {%0, %1, %2, %3}, [%4];" : "=r"(h0), "=r"(h1), "=r"(h2), "=r"(h3) : "r"(stg + r * 128 + (((b + (lane >> 4)) ^ (r & 7)) << 4)) : "memory");
            pk[2 * b] = pack_bf16(acc[4 * b] + bf_lo(h0), acc[4 * b + 1] + bf_hi(h0));
            pk[2 * b + 1] = pack_bf16(acc[4 * b + 2] + bf_lo(h1), acc[4 * b + 3] + bf_hi(h1));
            pk[2 * b + 2] = pack_bf16(acc[4 * b + 4] + bf_lo(h2), acc[4 * b + 5] + bf_hi(h2));
            pk[2 * b + 3] = pack_bf16(acc[4 * b + 6] + bf_lo(h3), acc[4 * b + 7] + bf_hi(h3));
        }
    } else {
#pragma unroll
        for (int i = 0; i < 16; i++) pk[i] = pack_bf16(acc[2 * i], acc[2 * i + 1]);
    }
    stage_tile<8>(pk, stg, w, lane);
}
__device__ __forceinline__ void ffn_reduce_chunk(const CUtensorMap* tmOut, uint32_t stg, int col, int row, int w, int wgid, bool leader) {
    proxy_fence();
    if (w != 0) {
        asm volatile("bar.arrive %0, 128;" ::"r"(2 + wgid) : "memory");
    } else {
        named_sync(2 + wgid, 128);
        if (leader) { tma_red_2d(tmOut, col, row, stg); bulk_commit(); }
    }
}

__device__ __forceinline__ void ffn_load_residual(float (&acc)[32], uint32_t stg, int w, int lane, uint32_t fullH) {
    mbar_wait(fullH, 0);
    const int r = w * 16 + (lane & 7) + ((lane >> 3) & 1) * 8;
#pragma unroll
    for (int b = 0; b < 8; b += 2) {
        uint32_t h0, h1, h2, h3;
        asm volatile("ldmatrix.sync.aligned.m8n8.x4.shared.b16 {%0, %1, %2, %3}, [%4];" : "=r"(h0), "=r"(h1), "=r"(h2), "=r"(h3) : "r"(stg + r * 128 + (((b + (lane >> 4)) ^ (r & 7)) << 4)) : "memory");
        acc[4 * b] = bf_lo(h0); acc[4 * b + 1] = bf_hi(h0); acc[4 * b + 2] = bf_lo(h1); acc[4 * b + 3] = bf_hi(h1);
        acc[4 * b + 4] = bf_lo(h2); acc[4 * b + 5] = bf_hi(h2); acc[4 * b + 6] = bf_lo(h3); acc[4 * b + 7] = bf_hi(h3);
    }
}

template <int MODE>
__device__ __forceinline__ void ffn_phase2_chunk(float (&cur)[32], float (&prev)[32], uint32_t (&h1)[144], const FfnPipe& pp, uint32_t ph, const CUtensorMap* tmOut, uint32_t stg_prev, int col_prev, int row, int w, int lane, int wgid, bool leader,
                                                 bool resid_prev, uint32_t fullH, uint32_t stg_res) {
    const uint64_t dw = cdesc(F_OFF_ST, 8192, 1024, 1) + blockIdx.y * col_prev;
    float tmp[2][8];
#pragma unroll
    for (int j = 0; j < 6; j++) {
        pp.acquire(j, ph);
        if (j == 0) pin(cur);
        if (MODE == 0 && j == 5) pin(h1);
        wg_fence();
#pragma unroll
        for (int i = 0; i < 6; i++) {
            const int f = (6 * j + i) * 4;
            wgmma_rs_n64<1>(cur, h1[f], h1[f + 1], h1[f + 2], h1[f + 3], dw + ((j * F_STAGE + i * 2048) >> 4), MODE == 3 || (j | i) != 0);
        }
        wg_commit();
        wg_wait<1>();
        pp.release((j + 5) % 6);
        if (MODE == 0) {
            pin(prev);
            if (j == 0) silu_slot_last<0>(prev, tmp, h1);
            if (j == 1) silu_slot_last<1>(prev, tmp, h1);
            if (j == 2) silu_slot_last<2>(prev, tmp, h1);
            if (j == 3) silu_slot_last<3>(prev, tmp, h1);
            if (j == 4) silu_slot_last<4>(prev, tmp, h1);
        } else {
            if (j == 0) { pin(prev); ffn_stage_chunk(prev, stg_prev, w, lane, MODE == 3 && resid_prev, fullH); }
            if (j == 1) ffn_reduce_chunk(tmOut, stg_prev, col_prev, row, w, wgid, leader);
            if (MODE == 2 && j == 2) { ffn_load_residual(prev, stg_res, w, lane, fullH); pin(prev); }
        }
    }
}

__global__ void __launch_bounds__(F_THREADS, 1)
k_ffn(const __grid_constant__ CUtensorMap tmX2, const __grid_constant__ CUtensorMap tmW1, const __grid_constant__ CUtensorMap tmW2, const __grid_constant__ CUtensorMap tmOut,
      const __grid_constant__ CUtensorMap tmRes, const __nv_bfloat16* __restrict__ w2) {
    extern __shared__ __align__(1024) uint8_t smem[];
    const uint32_t sX = smem_u32(smem), sSt = sX + F_OFF_ST, bars = sX + F_OFF_BAR;
    const uint32_t full = bars, empty = bars + 64, fullX = bars + 128, fullH = bars + 208;
    const int tid = threadIdx.x, warp = __shfl_sync(~0u, tid >> 5, 0), lane = tid & 31;
    const int m = blockIdx.x >> 3, fs = blockIdx.x & 7;
    check_smem_base(sX);
    if (tid == 0) {
        prefetch_map(&tmW1); prefetch_map(&tmX2); prefetch_map(&tmW2); prefetch_map(&tmOut); prefetch_map(&tmRes);
        for (int i = 0; i < F_NST; i++) { mbar_init(full + i * 8, 1); mbar_init(empty + i * 8, 8); }
        for (int i = 0; i < 9; i++) mbar_init(fullX + i * 8, 1);
        mbar_init(fullH, 1); mbar_init(fullH + 8, 1);
        bar_init_fence();
        for (int kb = 0; kb < 9; kb++) mbar_expect(fullX + kb * 8, 16384);
    }
    __syncthreads();
    if (warp < 4) {
        asm volatile("setmaxnreg.dec.sync.aligned.u32 24;");
        if (warp == 1 && lane < 9) prefetch_l2(reinterpret_cast<const char*>(w2) + ((size_t)fs * 576 + m * 36 + lane * 4) * (DM * 2), 4 * DM * 2);
        if (warp == 0 && elect_one()) {
#pragma unroll 1
            for (int c = 0; c < 18; c++) {
                int col = c - 9 + fs;
                if (col >= 9) col -= 9;
#pragma unroll 1
                for (int j = 0; j < 6; j++) {
                    mbar_wait(empty + j * 8, (c & 1) ^ 1);
                    mbar_expect(full + j * 8, F_STAGE);
                    if (c < 9) tma_2d(sSt + j * F_STAGE, &tmW1, fs * 576 + c * 64, j * 96, full + j * 8);
                    else tma_2d(sSt + j * F_STAGE, &tmW2, col * 64, fs * 576 + j * 96, full + j * 8);
                }
            }
        }
    } else {
        asm volatile("setmaxnreg.inc.sync.aligned.u32 240;");
        const int wgid = (warp >> 2) - 1, w = warp & 3;
        pdl_wait();
        if (warp == 4 && elect_one()) {
            for (int kb = 0; kb < 9; kb++) tma_2d(sX + kb * 16384, &tmX2, kb * 64, m * 128, fullX + kb * 8);
        }
        __syncwarp();
        FfnPipe pp{full, empty, lane};
        const uint64_t xlo = cdesc(0, 16, 1024, 1) + wgid * 512;
        uint32_t h1[144];
        float acc0[32], acc1[32];
        ffn_phase1_chunk<0>(acc0, acc1, h1, pp, xlo, fullX);
        ffn_phase1_chunk<1>(acc1, acc0, h1, pp, xlo, fullX);
        ffn_phase1_chunk<2>(acc0, acc1, h1, pp, xlo, fullX);
        ffn_phase1_chunk<3>(acc1, acc0, h1, pp, xlo, fullX);
        ffn_phase1_chunk<4>(acc0, acc1, h1, pp, xlo, fullX);
        ffn_phase1_chunk<5>(acc1, acc0, h1, pp, xlo, fullX);
        ffn_phase1_chunk<6>(acc0, acc1, h1, pp, xlo, fullX);
        ffn_phase1_chunk<7>(acc1, acc0, h1, pp, xlo, fullX);
        ffn_phase1_chunk<8>(acc0, acc1, h1, pp, xlo, fullX);
        const int row = m * 128 + wgid * 64;
        const uint32_t stg = sX + wgid * 8192;
        int c = fs, cprev = 0;
        const bool leader = w == 0 && elect_one();
        const uint32_t myH = fullH + wgid * 8;
        ffn_phase2_chunk<0>(acc1, acc0, h1, pp, 1, &tmOut, 0, 0, row, w, lane, wgid, leader, false, myH, 0);
        if (leader) {
            const int c8 = fs == 0 ? 8 : fs - 1;
            mbar_expect(myH, fs == 0 ? 16384 : 8192);
            tma_2d(stg + 8 * 16384, &tmRes, c8 * 64, row, myH);
            if (fs == 0) tma_2d(stg + 7 * 16384, &tmRes, 7 * 64, row, myH);
        }
        cprev = c; if (++c == 9) c = 0;
#pragma unroll 1
        for (int j = 1; j < 7; j += 2) {
            ffn_phase2_chunk<1>(acc0, acc1, h1, pp, 0, &tmOut, stg + (j - 1) * 16384, cprev * 64, row, w, lane, wgid, leader, false, myH, 0);
            cprev = c; if (++c == 9) c = 0;
            ffn_phase2_chunk<1>(acc1, acc0, h1, pp, 1, &tmOut, stg + j * 16384, cprev * 64, row, w, lane, wgid, leader, false, myH, 0);
            cprev = c; if (++c == 9) c = 0;
        }
        ffn_phase2_chunk<2>(acc0, acc1, h1, pp, 0, &tmOut, stg + 6 * 16384, cprev * 64, row, w, lane, wgid, leader, false, myH, stg + 8 * 16384);
        cprev = c; if (++c == 9) c = 0;
        ffn_phase2_chunk<3>(acc1, acc0, h1, pp, 1, &tmOut, stg + 7 * 16384, cprev * 64, row, w, lane, wgid, leader, fs == 0, myH, 0);
        cprev = c;
        wg_wait<0>();
        pin(acc1);
        ffn_stage_chunk(acc1, stg + 8 * 16384, w, lane, false, myH);
        ffn_reduce_chunk(&tmOut, stg + 8 * 16384, cprev * 64, row, w, wgid, leader);
        if (leader) bulk_wait_all();
    }
}

typedef CUresult (*EncodeFn)(CUtensorMap*, CUtensorMapDataType, cuuint32_t, void*, const cuuint64_t*, const cuuint64_t*, const cuuint32_t*, const cuuint32_t*,
                             CUtensorMapInterleave, CUtensorMapSwizzle, CUtensorMapL2promotion, CUtensorMapFloatOOBfill);

CUtensorMap make_map(EncodeFn enc, const void* base, int rows, int cols, int box_rows) {
    CUtensorMap tm;
    cuuint64_t dims[2] = {(cuuint64_t)cols, (cuuint64_t)rows};
    cuuint64_t strides[1] = {(cuuint64_t)cols * 2};
    cuuint32_t box[2] = {64, (cuuint32_t)box_rows};
    cuuint32_t es[2] = {1, 1};
    enc(&tm, CU_TENSOR_MAP_DATA_TYPE_BFLOAT16, 2, const_cast<void*>(base), dims, strides, box, es, CU_TENSOR_MAP_INTERLEAVE_NONE,
        CU_TENSOR_MAP_SWIZZLE_128B, CU_TENSOR_MAP_L2_PROMOTION_L2_256B, CU_TENSOR_MAP_FLOAT_OOB_FILL_NONE);
    return tm;
}

template <typename... KArgs, typename... Args>
void launch(void (*kern)(KArgs...), int grid, int block, int smem, bool pdl, Args... args) {
    cudaLaunchConfig_t cfg = {};
    cfg.gridDim = dim3(grid); cfg.blockDim = dim3(block); cfg.dynamicSmemBytes = smem; cfg.stream = cudaStreamPerThread;
    cudaLaunchAttribute at[1];
    at[0].id = cudaLaunchAttributeProgrammaticStreamSerialization;
    at[0].val.programmaticStreamSerializationAllowed = 1;
    cfg.attrs = at; cfg.numAttrs = pdl ? 1 : 0;
    cudaLaunchKernelEx(&cfg, kern, KArgs(args)...);
}

}

extern "C" void kernel_launch(void* const* d_in, const int* in_sizes, int n_in, void* d_out, int out_size) {
    const __nv_bfloat16* x = (const __nv_bfloat16*)d_in[0];
    const __nv_bfloat16* wq = (const __nv_bfloat16*)d_in[1];
    const __nv_bfloat16* wk = (const __nv_bfloat16*)d_in[2];
    const __nv_bfloat16* wv = (const __nv_bfloat16*)d_in[3];
    const __nv_bfloat16* wo = (const __nv_bfloat16*)d_in[4];
    const __nv_bfloat16* w1 = (const __nv_bfloat16*)d_in[6];
    const __nv_bfloat16* w2 = (const __nv_bfloat16*)d_in[7];
    __nv_bfloat16* out = (__nv_bfloat16*)d_out;

    static EncodeFn enc = nullptr;
    static void *p_o = nullptr, *p_x2 = nullptr, *p_q = nullptr, *p_res = nullptr;
    if (!enc) {
        cudaDriverEntryPointQueryResult qr;
        cudaGetDriverEntryPoint("cuTensorMapEncodeTiled", (void**)&enc, cudaEnableDefault, &qr);
        cudaGetSymbolAddress(&p_o, g_o);
        cudaGetSymbolAddress(&p_x2, g_x2);
        cudaGetSymbolAddress(&p_res, g_h);
        cudaGetSymbolAddress(&p_q, g_q);
        cudaFuncSetAttribute(k_qkv, cudaFuncAttributeMaxDynamicSharedMemorySize, P_SMEM);
        cudaFuncSetAttribute(k_attn, cudaFuncAttributeMaxDynamicSharedMemorySize, A_SMEM);
        cudaFuncSetAttribute(k_oproj, cudaFuncAttributeMaxDynamicSharedMemorySize, O_SMEM);
        cudaFuncSetAttribute(k_ffn, cudaFuncAttributeMaxDynamicSharedMemorySize, F_SMEM);
    }
    const CUtensorMap tmWq = make_map(enc, wq, DM, DM, 64);
    const CUtensorMap tmWo = make_map(enc, wo, DM, DM, 64);
    const CUtensorMap tmO = make_map(enc, p_o, SEQ, DM, 64);
    const CUtensorMap tmX2st = make_map(enc, p_x2, SEQ, DM, 64);
    const CUtensorMap tmX2ld = make_map(enc, p_x2, SEQ, DM, 128);
    const CUtensorMap tmRes = make_map(enc, p_res, SEQ, DM, 64);
    const CUtensorMap tmQ = make_map(enc, p_q, SEQ, DM, 64);
    const CUtensorMap tmW1 = make_map(enc, w1, DM, FF, 96);
    const CUtensorMap tmW2 = make_map(enc, w2, FF, DM, 96);
    const CUtensorMap tmOut = make_map(enc, out, SEQ, DM, 64);

    launch(k_qkv, 128, Q_THREADS, P_SMEM, false, tmWq, tmQ, x, wk, wv);
    launch(k_attn, 128, A_THREADS, A_SMEM, true, out);
    launch(k_oproj, 96, O_THREADS, O_SMEM, true, tmO, tmWo, tmX2st, tmRes, x, w1);
    launch(k_ffn, 128, F_THREADS, F_SMEM, true, tmX2ld, tmW1, tmW2, tmOut, tmRes, w2);
}
```

```cpp
#include <cuda_runtime.h>
#include <cuda_bf16.h>
#include <cuda.h>
#include <stdint.h>

namespace {

constexpr int SEQ = 2048, DM = 576, FF = 4608;
constexpr int KV_BYTES = SEQ * 48;
constexpr float LN_EPS = 1e-5f;
constexpr float LOG2E = 1.4426950408889634f;
constexpr float Q_SCALE = 0.23570226039551584f * LOG2E;

constexpr uint32_t POLY_MASK = 0xB6DBu;
constexpr int CHAIN = 6;
constexpr float FAST_BOUND = 90.0f;
constexpr float FAST_VMAX2 = 1e12f;

__device__ __align__(1024) __nv_bfloat16 g_q[SEQ * DM];
__device__ __align__(1024) uint4 g_kc[KV_BYTES / 16];
__device__ __align__(1024) uint4 g_vc[KV_BYTES / 16];
__device__ __align__(16) float g_kmax[256];
__device__ __align__(1024) __nv_bfloat16 g_o[SEQ * DM];
__device__ __align__(1024) __nv_bfloat16 g_h[SEQ * DM];
__device__ __align__(1024) __nv_bfloat16 g_x2[SEQ * DM];


__device__ __forceinline__ uint32_t smem_u32(const void* p) { return (uint32_t)__cvta_generic_to_shared(p); }
__device__ __forceinline__ void wg_fence() { asm volatile("wgmma.fence.sync.aligned;" ::: "memory"); }
__device__ __forceinline__ void wg_commit() { asm volatile("wgmma.commit_group.sync.aligned;" ::: "memory"); }
template <int N> __device__ __forceinline__ void wg_wait() { asm volatile("wgmma.wait_group.sync.aligned %0;" ::"n"(N) : "memory"); }
template <int N> __device__ __forceinline__ void pin(float (&r)[N]) {
#pragma unroll
    for (int i = 0; i < N; i++) asm volatile("" : "+f"(r[i])::"memory");
}
template <int N> __device__ __forceinline__ void pin(uint32_t (&r)[N]) {
#pragma unroll
    for (int i = 0; i < N; i++) asm volatile("" : "+r"(r[i])::"memory");
}
constexpr uint32_t SMEM0 = 0x400;
__host__ __device__ constexpr uint64_t cdesc(uint32_t off, uint32_t lbo, uint32_t sbo, uint32_t swz) {
    return (uint64_t)(((SMEM0 + off) & 0x3FFFF) >> 4) | ((uint64_t)(lbo >> 4) << 16) | ((uint64_t)(sbo >> 4) << 32) | ((uint64_t)swz << 62);
}
__device__ __forceinline__ void check_smem_base(uint32_t base) { if ((base & 0x3FFFF) != SMEM0) __trap(); }

__device__ __forceinline__ void mbar_init(uint32_t bar, int cnt) { asm volatile("mbarrier.init.shared::cta.b64 [%0], %1;" ::"r"(bar), "r"(cnt) : "memory"); }
__device__ __forceinline__ void mbar_expect(uint32_t bar, int bytes) { asm volatile("mbarrier.arrive.expect_tx.shared::cta.b64 _, [%0], %1;" ::"r"(bar), "r"(bytes) : "memory"); }
__device__ __forceinline__ void mbar_arrive(uint32_t bar) { asm volatile("mbarrier.arrive.shared::cta.b64 _, [%0];" ::"r"(bar) : "memory"); }
__device__ __forceinline__ void mbar_wait(uint32_t bar, uint32_t parity) {
    asm volatile(
        "{\n.reg .pred p;\n.reg .u32 n;\nmov.u32 n, 0;\n"
        "LAB_WAIT:\n"
        "mbarrier.try_wait.parity.shared::cta.b64 p, [%0], %1;\n"
        "@p bra DONE;\n"
        "add.u32 n, n, 1;\n"
        "setp.lt.u32 p, n, 4000000;\n"
        "@p bra LAB_WAIT;\n"
        "trap;\n"
        "DONE:\n}\n" ::"r"(bar), "r"(parity) : "memory");
}
__device__ __forceinline__ void bar_init_fence() {
    asm volatile("fence.mbarrier_init.release.cluster;" ::: "memory");
    asm volatile("fence.proxy.async.shared::cta;" ::: "memory");
}
__device__ __forceinline__ void proxy_fence() { asm volatile("fence.proxy.async.shared::cta;" ::: "memory"); }
__device__ __forceinline__ void named_sync(int id, int n) { asm volatile("bar.sync %0, %1;" ::"r"(id), "r"(n) : "memory"); }
__device__ __forceinline__ void bulk_g2s(uint32_t dst, const void* src, int bytes, uint32_t bar) {
    asm volatile("cp.async.bulk.shared::cluster.global.mbarrier::complete_tx::bytes [%0], [%1], %2, [%3];" ::"r"(dst), "l"(src), "r"(bytes), "r"(bar) : "memory");
}
__device__ __forceinline__ void tma_2d(uint32_t dst, const CUtensorMap* tm, int c0, int c1, uint32_t bar) {
    asm volatile("cp.async.bulk.tensor.2d.shared::cluster.global.mbarrier::complete_tx::bytes [%0], [%1, {%3, %4}], [%2];" ::"r"(dst), "l"(tm), "r"(bar), "r"(c0), "r"(c1) : "memory");
}
__device__ __forceinline__ void cluster_arrive() { asm volatile("barrier.cluster.arrive.release.aligned;" ::: "memory"); }
__device__ __forceinline__ void cluster_wait() { asm volatile("barrier.cluster.wait.acquire.aligned;" ::: "memory"); }
__device__ __forceinline__ void tma_red_2d(const CUtensorMap* tm, int c0, int c1, uint32_t src) {
    asm volatile("cp.reduce.async.bulk.tensor.2d.global.shared::cta.add.tile.bulk_group [%0, {%2, %3}], [%1];" ::"l"(tm), "r"(src), "r"(c0), "r"(c1) : "memory");
}
__device__ __forceinline__ void tma_st_2d(const CUtensorMap* tm, int c0, int c1, uint32_t src) {
    asm volatile("cp.async.bulk.tensor.2d.global.shared::cta.tile.bulk_group [%0, {%2, %3}], [%1];" ::"l"(tm), "r"(src), "r"(c0), "r"(c1) : "memory");
}
__device__ __forceinline__ void bulk_commit() { asm volatile("cp.async.bulk.commit_group;" ::: "memory"); }
__device__ __forceinline__ void bulk_wait_all() { asm volatile("cp.async.bulk.wait_group.read 0;" ::: "memory"); }
__device__ __forceinline__ bool elect_one() {
    uint32_t p;
    asm volatile("{\n.reg .pred P;\nelect.sync _|P, 0xffffffff;\nselp.b32 %0, 1, 0, P;\n}\n" : "=r"(p));
    return p != 0;
}
__device__ __forceinline__ void prefetch_l2(const void* p, int bytes) { asm volatile("cp.async.bulk.prefetch.L2.global [%0], %1;" ::"l"(p), "r"(bytes) : "memory"); }
__device__ __forceinline__ void prefetch_map(const CUtensorMap* tm) { asm volatile("prefetch.tensormap [%0];" ::"l"(tm) : "memory"); }
__device__ __forceinline__ void pdl_launch() { asm volatile("griddepcontrol.launch_dependents;" ::: "memory"); }
__device__ __forceinline__ void pdl_wait() { asm volatile("griddepcontrol.wait;" ::: "memory"); }
__device__ __forceinline__ float ex2(float x) { float y; asm("ex2.approx.ftz.f32 %0, %1;" : "=f"(y) : "f"(x)); return y; }
__device__ __forceinline__ uint32_t pack_bf16(float lo, float hi) { uint32_t r; asm("cvt.rn.bf16x2.f32 %0, %1, %2;" : "=r"(r) : "f"(hi), "f"(lo)); return r; }
__device__ __forceinline__ float bf_lo(uint32_t v) { return __uint_as_float(v << 16); }
__device__ __forceinline__ float bf_hi(uint32_t v) { return __uint_as_float(v & 0xFFFF0000u); }
__device__ __forceinline__ uint32_t hfma2(uint32_t a, uint32_t b, uint32_t c) { uint32_t r; asm("fma.rn.f16x2 %0, %1, %2, %3;" : "=r"(r) : "r"(a), "r"(b), "r"(c)); return r; }
__device__ __forceinline__ void stmatrix_x4(uint32_t addr, uint32_t r0, uint32_t r1, uint32_t r2, uint32_t r3) {
    asm volatile("stmatrix.sync.aligned.m8n8.x4.shared.b16 [%0], {%1, %2, %3, %4};" ::"r"(addr), "r"(r0), "r"(r1), "r"(r2), "r"(r3) : "memory");
}

template <int TB> __device__ __forceinline__ void wgmma_ss_n24(float (&d)[12], uint64_t da, uint64_t db, int sc) {
    asm volatile("{\n.reg .pred p;\nsetp.ne.b32 p, %14, 0;\n"
        "wgmma.mma_async.sync.aligned.m64n24k16.f32.bf16.bf16 {%0, %1, %2, %3, %4, %5, %6, %7, %8, %9, %10, %11}, %12, %13, p, 1, 1, 0, %15;\n}\n"
        : "+f"(d[0]), "+f"(d[1]), "+f"(d[2]), "+f"(d[3]), "+f"(d[4]), "+f"(d[5]), "+f"(d[6]), "+f"(d[7]), "+f"(d[8]), "+f"(d[9]), "+f"(d[10]), "+f"(d[11])
        : "l"(da), "l"(db), "r"(sc), "n"(TB));
}
template <int TB> __device__ __forceinline__ void wgmma_ss_n64(float (&d)[32], uint64_t da, uint64_t db, int sc) {
    asm volatile("{\n.reg .pred p;\nsetp.ne.b32 p, %34, 0;\n"
        "wgmma.mma_async.sync.aligned.m64n64k16.f32.bf16.bf16 {%0, %1, %2, %3, %4, %5, %6, %7, %8, %9, %10, %11, %12, %13, %14, %15, %16, %17, %18, %19, %20, %21, %22, %23, %24, %25, %26, %27, %28, %29, %30, %31}, %32, %33, p, 1, 1, 0, %35;\n}\n"
        : "+f"(d[0]), "+f"(d[1]), "+f"(d[2]), "+f"(d[3]), "+f"(d[4]), "+f"(d[5]), "+f"(d[6]), "+f"(d[7]), "+f"(d[8]), "+f"(d[9]), "+f"(d[10]), "+f"(d[11]), "+f"(d[12]), "+f"(d[13]), "+f"(d[14]), "+f"(d[15]), "+f"(d[16]), "+f"(d[17]), "+f"(d[18]), "+f"(d[19]), "+f"(d[20]), "+f"(d[21]), "+f"(d[22]), "+f"(d[23]), "+f"(d[24]), "+f"(d[25]), "+f"(d[26]), "+f"(d[27]), "+f"(d[28]), "+f"(d[29]), "+f"(d[30]), "+f"(d[31])
        : "l"(da), "l"(db), "r"(sc), "n"(TB));
}
template <int TB> __device__ __forceinline__ void wgmma_ss_n128(float (&d)[64], uint64_t da, uint64_t db, int sc) {
    asm volatile("{\n.reg .pred p;\nsetp.ne.b32 p, %66, 0;\n"
        "wgmma.mma_async.sync.aligned.m64n128k16.f32.bf16.bf16 {%0, %1, %2, %3, %4, %5, %6, %7, %8, %9, %10, %11, %12, %13, %14, %15, %16, %17, %18, %19, %20, %21, %22, %23, %24, %25, %26, %27, %28, %29, %30, %31, %32, %33, %34, %35, %36, %37, %38, %39, %40, %41, %42, %43, %44, %45, %46, %47, %48, %49, %50, %51, %52, %53, %54, %55, %56, %57, %58, %59, %60, %61, %62, %63}, %64, %65, p, 1, 1, 0, %67;\n}\n"
        : "+f"(d[0]), "+f"(d[1]), "+f"(d[2]), "+f"(d[3]), "+f"(d[4]), "+f"(d[5]), "+f"(d[6]), "+f"(d[7]), "+f"(d[8]), "+f"(d[9]), "+f"(d[10]), "+f"(d[11]), "+f"(d[12]), "+f"(d[13]), "+f"(d[14]), "+f"(d[15]), "+f"(d[16]), "+f"(d[17]), "+f"(d[18]), "+f"(d[19]), "+f"(d[20]), "+f"(d[21]), "+f"(d[22]), "+f"(d[23]), "+f"(d[24]), "+f"(d[25]), "+f"(d[26]), "+f"(d[27]), "+f"(d[28]), "+f"(d[29]), "+f"(d[30]), "+f"(d[31]), "+f"(d[32]), "+f"(d[33]), "+f"(d[34]), "+f"(d[35]), "+f"(d[36]), "+f"(d[37]), "+f"(d[38]), "+f"(d[39]), "+f"(d[40]), "+f"(d[41]), "+f"(d[42]), "+f"(d[43]), "+f"(d[44]), "+f"(d[45]), "+f"(d[46]), "+f"(d[47]), "+f"(d[48]), "+f"(d[49]), "+f"(d[50]), "+f"(d[51]), "+f"(d[52]), "+f"(d[53]), "+f"(d[54]), "+f"(d[55]), "+f"(d[56]), "+f"(d[57]), "+f"(d[58]), "+f"(d[59]), "+f"(d[60]), "+f"(d[61]), "+f"(d[62]), "+f"(d[63])
        : "l"(da), "l"(db), "r"(sc), "n"(TB));
}
template <int TB> __device__ __forceinline__ void wgmma_rs_n24(float (&d)[12], uint32_t a0, uint32_t a1, uint32_t a2, uint32_t a3, uint64_t db, int sc) {
    asm volatile("{\n.reg .pred p;\nsetp.ne.b32 p, %17, 0;\n"
        "wgmma.mma_async.sync.aligned.m64n24k16.f32.bf16.bf16 {%0, %1, %2, %3, %4, %5, %6, %7, %8, %9, %10, %11}, {%12, %13, %14, %15}, %16, p, 1, 1, %18;\n}\n"
        : "+f"(d[0]), "+f"(d[1]), "+f"(d[2]), "+f"(d[3]), "+f"(d[4]), "+f"(d[5]), "+f"(d[6]), "+f"(d[7]), "+f"(d[8]), "+f"(d[9]), "+f"(d[10]), "+f"(d[11])
        : "r"(a0), "r"(a1), "r"(a2), "r"(a3), "l"(db), "r"(sc), "n"(TB));
}
template <int TB> __device__ __forceinline__ void wgmma_rs_n64(float (&d)[32], uint32_t a0, uint32_t a1, uint32_t a2, uint32_t a3, uint64_t db, int sc) {
    asm volatile("{\n.reg .pred p;\nsetp.ne.b32 p, %37, 0;\n"
        "wgmma.mma_async.sync.aligned.m64n64k16.f32.bf16.bf16 {%0, %1, %2, %3, %4, %5, %6, %7, %8, %9, %10, %11, %12, %13, %14, %15, %16, %17, %18, %19, %20, %21, %22, %23, %24, %25, %26, %27, %28, %29, %30, %31}, {%32, %33, %34, %35}, %36, p, 1, 1, %38;\n}\n"
        : "+f"(d[0]), "+f"(d[1]), "+f"(d[2]), "+f"(d[3]), "+f"(d[4]), "+f"(d[5]), "+f"(d[6]), "+f"(d[7]), "+f"(d[8]), "+f"(d[9]), "+f"(d[10]), "+f"(d[11]), "+f"(d[12]), "+f"(d[13]), "+f"(d[14]), "+f"(d[15]), "+f"(d[16]), "+f"(d[17]), "+f"(d[18]), "+f"(d[19]), "+f"(d[20]), "+f"(d[21]), "+f"(d[22]), "+f"(d[23]), "+f"(d[24]), "+f"(d[25]), "+f"(d[26]), "+f"(d[27]), "+f"(d[28]), "+f"(d[29]), "+f"(d[30]), "+f"(d[31])
        : "r"(a0), "r"(a1), "r"(a2), "r"(a3), "l"(db), "r"(sc), "n"(TB));
}
template <int TB> __device__ __forceinline__ void wgmma_rs_n128(float (&d)[64], uint32_t a0, uint32_t a1, uint32_t a2, uint32_t a3, uint64_t db, int sc) {
    asm volatile("{\n.reg .pred p;\nsetp.ne.b32 p, %69, 0;\n"
        "wgmma.mma_async.sync.aligned.m64n128k16.f32.bf16.bf16 {%0, %1, %2, %3, %4, %5, %6, %7, %8, %9, %10, %11, %12, %13, %14, %15, %16, %17, %18, %19, %20, %21, %22, %23, %24, %25, %26, %27, %28, %29, %30, %31, %32, %33, %34, %35, %36, %37, %38, %39, %40, %41, %42, %43, %44, %45, %46, %47, %48, %49, %50, %51, %52, %53, %54, %55, %56, %57, %58, %59, %60, %61, %62, %63}, {%64, %65, %66, %67}, %68, p, 1, 1, %70;\n}\n"
        : "+f"(d[0]), "+f"(d[1]), "+f"(d[2]), "+f"(d[3]), "+f"(d[4]), "+f"(d[5]), "+f"(d[6]), "+f"(d[7]), "+f"(d[8]), "+f"(d[9]), "+f"(d[10]), "+f"(d[11]), "+f"(d[12]), "+f"(d[13]), "+f"(d[14]), "+f"(d[15]), "+f"(d[16]), "+f"(d[17]), "+f"(d[18]), "+f"(d[19]), "+f"(d[20]), "+f"(d[21]), "+f"(d[22]), "+f"(d[23]), "+f"(d[24]), "+f"(d[25]), "+f"(d[26]), "+f"(d[27]), "+f"(d[28]), "+f"(d[29]), "+f"(d[30]), "+f"(d[31]), "+f"(d[32]), "+f"(d[33]), "+f"(d[34]), "+f"(d[35]), "+f"(d[36]), "+f"(d[37]), "+f"(d[38]), "+f"(d[39]), "+f"(d[40]), "+f"(d[41]), "+f"(d[42]), "+f"(d[43]), "+f"(d[44]), "+f"(d[45]), "+f"(d[46]), "+f"(d[47]), "+f"(d[48]), "+f"(d[49]), "+f"(d[50]), "+f"(d[51]), "+f"(d[52]), "+f"(d[53]), "+f"(d[54]), "+f"(d[55]), "+f"(d[56]), "+f"(d[57]), "+f"(d[58]), "+f"(d[59]), "+f"(d[60]), "+f"(d[61]), "+f"(d[62]), "+f"(d[63])
        : "r"(a0), "r"(a1), "r"(a2), "r"(a3), "l"(db), "r"(sc), "n"(TB));
}

constexpr int P_NST = 6;
constexpr int P_A_BYTES = 9 * 8192;
constexpr int P_B_STAGE = 3 * 8192;

template <int NB>
__device__ __forceinline__ void stage_tile(const uint32_t (&pk)[NB * 2], uint32_t base, int w, int lane) {
    const int r = w * 16 + (lane & 7) + ((lane >> 3) & 1) * 8;
#pragma unroll
    for (int b = 0; b < NB; b += 2) {
        const uint32_t a = base + (b >> 3) * 8192 + r * 128 + ((((b & 7) + (lane >> 4)) ^ (r & 7)) << 4);
        stmatrix_x4(a, pk[2 * b], pk[2 * b + 1], pk[2 * b + 2], pk[2 * b + 3]);
    }
}

__device__ __forceinline__ uint32_t hsub2_bf16(uint32_t a, uint32_t b) { uint32_t r; asm("sub.rn.bf16x2 %0, %1, %2;" : "=r"(r) : "r"(a), "r"(b)); return r; }

constexpr int KV_RAW = DM * 18 * 2;
constexpr int Q_THREADS = 416;

__device__ __forceinline__ void proj_mma(float (&acc)[32], int wg, uint32_t fullB, uint32_t emptyB, uint32_t fullA, bool wait_a, int lane) {
    const uint64_t dA = cdesc(0, 16, 1024, 1), dB = cdesc(P_A_BYTES, 8192, 1024, 1) + wg * 512;
#pragma unroll 1
    for (int kb = 0; kb < 9; kb++) {
        const int s = kb >= P_NST ? kb - P_NST : kb;
        if (wait_a) mbar_wait(fullA + kb * 8, 0);
        mbar_wait(fullB + s * 8, kb >= P_NST ? 1 : 0);
        wg_fence();
#pragma unroll
        for (int ks = 0; ks < 4; ks++) wgmma_ss_n64<1>(acc, dA + (kb * 512 + ks * 2), dB + (s * (P_B_STAGE >> 4) + ks * 128), (kb | ks) != 0);
        wg_commit();
        if (kb < 4) {
            wg_wait<1>();
            if (kb >= 1 && lane == 0) mbar_arrive(emptyB + (kb - 1) * 8);
        }
    }
    wg_wait<0>();
    pin(acc);
}

constexpr int Q_SLOT = 9 * 8192, Q_THIRD = 3 * 8192;
constexpr int Q_OFF_STG = P_A_BYTES + 2 * Q_SLOT;
constexpr int Q_OFF_BAR = Q_OFF_STG + 8192;
constexpr int Q_SMEM = Q_OFF_BAR + 256 + 256;

__global__ void __launch_bounds__(Q_THREADS, 1)
k_qkv(const __grid_constant__ CUtensorMap tmWq, const __grid_constant__ CUtensorMap tmQ, const __nv_bfloat16* __restrict__ x, const __nv_bfloat16* __restrict__ wk, const __nv_bfloat16* __restrict__ wv) {
    extern __shared__ __align__(1024) uint8_t smem[];
    const uint32_t sA = smem_u32(smem), sB = sA + P_A_BYTES, bars = sA + Q_OFF_BAR;
    const uint32_t fullB = bars, free0 = bars + 80, fullX = bars + 128, fullW = bars + 136;
    float* s_rstd = reinterpret_cast<float*>(smem + Q_OFF_BAR + 256);
    const int tid = threadIdx.x, warp = __shfl_sync(~0u, tid >> 5, 0), lane = tid & 31;
    const bool isQ = blockIdx.x < 96;
    const int m = isQ ? blockIdx.x / 3 : blockIdx.x - 96, cg = blockIdx.x % 3;
    if (warp == 12) {
        if (elect_one()) {
            mbar_init(fullX, 1);
            bar_init_fence();
            mbar_expect(fullX, P_A_BYTES);
            bulk_g2s(sA, x + (size_t)m * 64 * DM, P_A_BYTES, fullX);
            prefetch_map(&tmWq); prefetch_map(&tmQ);
            for (int i = 0; i < 9; i++) mbar_init(fullB + i * 8, 1);
            for (int i = 0; i < 3; i++) mbar_init(free0 + i * 8, 4);
            mbar_init(fullW, 1);
            bar_init_fence();
            if (isQ) {
                for (int i = 0; i < 6; i++) {
                    mbar_expect(fullB + i * 8, Q_THIRD);
                    tma_2d(sB + i * Q_THIRD, &tmWq, cg * 192 + (i / 3) * 64, (i % 3) * 192, fullB + i * 8);
                }
                for (int i = 0; i < 3; i++)
                    asm volatile("cp.async.bulk.prefetch.tensor.2d.L2.global [%0, {%1, %2}];" ::"l"(&tmWq), "r"(cg * 192 + 128), "r"(i * 192) : "memory");
            } else {
                mbar_expect(fullW, 2 * KV_RAW);
                bulk_g2s(sB + Q_SLOT, wk, KV_RAW, fullW);
                bulk_g2s(sB + Q_SLOT + KV_RAW, wv, KV_RAW, fullW);
            }
        }
        __syncwarp();
    }
    check_smem_base(sA);
    __syncthreads();
    pdl_launch();
    if (warp == 12) {
        if (isQ && elect_one()) {
            for (int i = 0; i < 3; i++) {
                mbar_wait(free0 + i * 8, 0);
                mbar_expect(fullB + (6 + i) * 8, Q_THIRD);
                tma_2d(sB + i * Q_THIRD, &tmWq, cg * 192 + 128, i * 192, fullB + (6 + i) * 8);
            }
        }
        return;
    }
    if (warp < 8) {
        const int row = tid >> 2, q = tid & 3, h0 = (row & 1) * 4;
        mbar_wait(fullX, 0);
        uint4 v[18];
        const uint32_t ra = sA + row * 1152 + (q + h0) * 16, rb = sA + row * 1152 + (q + 4 - h0) * 16;
#pragma unroll
        for (int kb = 0; kb < 9; kb++) {
            asm volatile("ld.shared.v4.b32 {%0, %1, %2, %3}, [%4];" : "=r"(v[2 * kb].x), "=r"(v[2 * kb].y), "=r"(v[2 * kb].z), "=r"(v[2 * kb].w) : "r"(ra + kb * 128));
            asm volatile("ld.shared.v4.b32 {%0, %1, %2, %3}, [%4];" : "=r"(v[2 * kb + 1].x), "=r"(v[2 * kb + 1].y), "=r"(v[2 * kb + 1].z), "=r"(v[2 * kb + 1].w) : "r"(rb + kb * 128));
        }
        float sum = 0.f, sum2 = 0.f, sq = 0.f, sq2 = 0.f;
#pragma unroll
        for (int i = 0; i < 18; i++) {
            const uint32_t w[4] = {v[i].x, v[i].y, v[i].z, v[i].w};
#pragma unroll
            for (int j = 0; j < 4; j++) { const float a = bf_lo(w[j]), b = bf_hi(w[j]); sum += a; sum2 += b; sq = fmaf(a, a, sq); sq2 = fmaf(b, b, sq2); }
        }
        named_sync(1, 256);
        sum += sum2; sq += sq2;
        sum += __shfl_xor_sync(~0u, sum, 1); sum += __shfl_xor_sync(~0u, sum, 2);
        sq += __shfl_xor_sync(~0u, sq, 1); sq += __shfl_xor_sync(~0u, sq, 2);
        const float mean = sum * (1.0f / DM);
        if (q == 0) s_rstd[row] = rsqrtf(fmaxf(sq * (1.0f / DM) - mean * mean, 0.f) + LN_EPS);
        const uint32_t mhi = pack_bf16(mean, mean);
        const float rem = mean - bf_lo(mhi);
        const uint32_t mlo = pack_bf16(rem, rem);
        const uint32_t wa = sA + row * 128 + (((q + h0) ^ (row & 7)) << 4), wb = sA + row * 128 + (((q + 4 - h0) ^ (row & 7)) << 4);
#pragma unroll
        for (int i = 0; i < 18; i++) {
            const uint32_t o0 = hsub2_bf16(hsub2_bf16(v[i].x, mhi), mlo), o1 = hsub2_bf16(hsub2_bf16(v[i].y, mhi), mlo);
            const uint32_t o2 = hsub2_bf16(hsub2_bf16(v[i].z, mhi), mlo), o3 = hsub2_bf16(hsub2_bf16(v[i].w, mhi), mlo);
            asm volatile("st.shared.v4.b32 [%0], {%1, %2, %3, %4};" ::"r"(((i & 1) ? wb : wa) + (i >> 1) * 8192), "r"(o0), "r"(o1), "r"(o2), "r"(o3) : "memory");
        }
    } else if (!isQ) {
        mbar_wait(fullW, 0);
        const uint32_t* raw = reinterpret_cast<const uint32_t*>(smem + P_A_BYTES + Q_SLOT);
#pragma unroll 3
        for (int r = tid - 256; r < 2 * DM; r += 128) {
            uint32_t wr[9];
#pragma unroll
            for (int i = 0; i < 9; i++) wr[i] = raw[r * 9 + i];
            const int sel = r >= DM, k = r - sel * DM;
            uint8_t* dst = smem + P_A_BYTES + sel * 3 * 9216 + (k >> 3) * 128 + (k & 7) * 16;
            *reinterpret_cast<uint4*>(dst) = make_uint4(wr[0], wr[1], wr[2], wr[3]);
            *reinterpret_cast<uint4*>(dst + 9216) = make_uint4(wr[4], wr[5], wr[6], wr[7]);
            *reinterpret_cast<uint32_t*>(dst + 2 * 9216) = wr[8];
        }
    }
    proxy_fence();
    named_sync(2, 384);
    const int wg = warp >> 2, w = warp & 3, g = lane >> 2, t = lane & 3;
    const float rs0 = s_rstd[w * 16 + g], rs1 = s_rstd[w * 16 + g + 8];
    if (isQ) {
        const float c0 = rs0 * Q_SCALE, c1 = rs1 * Q_SCALE;
        float acc[32];
        const uint64_t dA = cdesc(0, 16, 1024, 1), dB = cdesc(P_A_BYTES, 8192, 1024, 1) + (wg == 1 ? (Q_SLOT >> 4) : 0);
        if (wg > 0) named_sync(6 + wg, 256);
#pragma unroll 1
        for (int i = 0; i < 3; i++) {
            mbar_wait(fullB + (wg * 3 + i) * 8, 0);
            wg_fence();
#pragma unroll
            for (int ks = 0; ks < 12; ks++)
                wgmma_ss_n64<1>(acc, dA + ((i * 3 + (ks >> 2)) * 512 + (ks & 3) * 2), dB + (i * (Q_THIRD >> 4) + ks * 128), (i | ks) != 0);
            wg_commit();
            if (wg == 0 && i > 0) { wg_wait<1>(); if (lane == 0) mbar_arrive(free0 + (i - 1) * 8); }
        }
        if (wg < 2) asm volatile("bar.arrive %0, 256;" ::"r"(7 + wg) : "memory");
        wg_wait<0>();
        pin(acc);
        if (wg == 0 && lane == 0) mbar_arrive(free0 + 16);
        uint32_t pk[16];
#pragma unroll
        for (int i = 0; i < 8; i++) { pk[2 * i] = pack_bf16(acc[4 * i] * c0, acc[4 * i + 1] * c0); pk[2 * i + 1] = pack_bf16(acc[4 * i + 2] * c1, acc[4 * i + 3] * c1); }
        const uint32_t stg = wg == 0 ? sA + Q_OFF_STG : (wg == 1 ? sB + Q_SLOT : sB);
        stage_tile<8>(pk, stg, w, lane);
        proxy_fence();
        named_sync(3 + wg, 128);
        if (w == 0 && elect_one()) {
            tma_st_2d(&tmQ, cg * 192 + wg * 64, m * 64, stg);
            bulk_commit();
            bulk_wait_all();
        }
    } else if (wg < 2) {
        float acc[12];
        const uint64_t dA = cdesc(0, 16, 1024, 1), dB = cdesc(P_A_BYTES, 128, 9216, 0) + wg * (3 * 9216 >> 4);
#pragma unroll
        for (int i = 0; i < 12; i++) acc[i] = 0.f;
        pin(acc);
        wg_fence();
#pragma unroll 1
        for (int kb = 0; kb < 9; kb++) {
#pragma unroll
            for (int ks = 0; ks < 4; ks++) wgmma_ss_n24<1>(acc, dA + (kb * 512 + ks * 2), dB + (kb * 4 + ks) * 16, 1);
        }
        wg_commit();
        wg_wait<0>();
        pin(acc);
        uint32_t pk[6];
#pragma unroll
        for (int b = 0; b < 3; b++) { pk[2 * b] = pack_bf16(acc[4 * b] * rs0, acc[4 * b + 1] * rs0); pk[2 * b + 1] = pack_bf16(acc[4 * b + 2] * rs1, acc[4 * b + 3] * rs1); }
        float n0 = 0.f, n1 = 0.f, vm = 0.f;
#pragma unroll
        for (int b = 0; b < 3; b++) {
            if (b < 2 || t == 0) {
                const float a = bf_lo(pk[2 * b]), c = bf_hi(pk[2 * b]), d = bf_lo(pk[2 * b + 1]), e = bf_hi(pk[2 * b + 1]);
                n0 = fmaf(a, a, fmaf(c, c, n0)); n1 = fmaf(d, d, fmaf(e, e, n1));
            }
        }
        n0 += __shfl_xor_sync(~0u, n0, 1); n0 += __shfl_xor_sync(~0u, n0, 2);
        n1 += __shfl_xor_sync(~0u, n1, 1); n1 += __shfl_xor_sync(~0u, n1, 2);
        vm = fmaxf(n0, n1);
        if (!(n0 == n0) || !(n1 == n1)) vm = __int_as_float(0x7F800000);
#pragma unroll
        for (int o = 4; o < 32; o <<= 1) vm = fmaxf(vm, __shfl_xor_sync(~0u, vm, o));
        if (t != 0) {
            uint32_t lo, hi;
            if (wg == 0) {
                const int grp = m * 8 + w * 2;
                const uint32_t c = t == 1 ? 0x42FE3F80u   : (t == 2 ? 0x00003BC0u   : 0u);
                lo = ((POLY_MASK >> (grp & 15)) & 1) ? c : 0u;
                hi = ((POLY_MASK >> ((grp + 1) & 15)) & 1) ? c : 0u;
            } else {
                lo = hi = t == 1 ? 0x00003F80u : 0u;
            }
            pk[4] = lo; pk[5] = hi;
        }
        uint32_t* dst = reinterpret_cast<uint32_t*>(wg == 0 ? g_kc : g_vc) + (m * 8 + w * 2) * 96 + g * 4 + t;
#pragma unroll
        for (int b = 0; b < 3; b++) { dst[b * 32] = pk[2 * b]; dst[96 + b * 32] = pk[2 * b + 1]; }
        if (lane == 0) g_kmax[m * 8 + warp] = (wg == 0) ? vm : (vm <= FAST_VMAX2 ? 0.f : __int_as_float(0x7F800000));
    }
}

constexpr int A_THREADS = 512;
constexpr int A_NPIECE = 8;
constexpr int A_OFF_Q = 2 * KV_BYTES;
constexpr int A_OFF_BAR = A_OFF_Q + 8 * 4096;
constexpr int A_SMEM = A_OFF_BAR + 128;

__device__ __forceinline__ uint32_t exp2_pair_fixed(float lo, float hi, uint32_t dep) {
    const uint32_t G = __byte_perm(__float_as_uint(lo), __float_as_uint(hi), 0x5410);
    uint32_t Hh;
    asm("lop3.b32 %0, %1, 0x007F007F, %2, 0xC0;" : "=r"(Hh) : "r"(G), "r"(dep));
    const uint32_t tt = hfma2(Hh, 0xF96BF96Bu, 0x358C358Cu);
    return G - hfma2(tt, Hh, 0u);
}

__global__ void __launch_bounds__(A_THREADS, 1)
k_attn(__nv_bfloat16* __restrict__ out) {
    extern __shared__ __align__(1024) uint8_t smem[];
    pdl_launch();
    const uint32_t sK = smem_u32(smem), sV = sK + KV_BYTES, bars = sK + A_OFF_BAR;
    const int tid = threadIdx.x;
    check_smem_base(sK);
    if (tid == 0) {
        for (int i = 0; i < A_NPIECE; i++) mbar_init(bars + i * 8, 1);
        bar_init_fence();
    }
    __syncthreads();
    pdl_wait();
    const int wg = __shfl_sync(~0u, tid >> 7, 0), w = (tid >> 5) & 3, lane = tid & 31, g = lane >> 2, t = lane & 3;
    const uint32_t* q32 = reinterpret_cast<const uint32_t*>(g_q);
    int row = (blockIdx.x * 8 + wg) * 64 + w * 16 + g;
    uint32_t nq[2][6];
#pragma unroll
    for (int r = 0; r < 2; r++) {
        const uint32_t* q = q32 + (row + r * 256) * 9;
        nq[r][0] = q[t]; nq[r][1] = q[72 + t]; nq[r][2] = q[4 + t]; nq[r][3] = q[76 + t]; nq[r][4] = q[8]; nq[r][5] = q[80];
    }
    constexpr int PB = KV_BYTES / A_NPIECE;
    const float4 km0 = reinterpret_cast<const float4*>(g_kmax)[lane], km1 = reinterpret_cast<const float4*>(g_kmax)[32 + lane];
    if (tid < 32 && elect_one()) {
        for (int i = 0; i < 2; i++) {
            mbar_expect(bars + i * 8, 2 * PB);
            bulk_g2s(sK + i * PB, reinterpret_cast<const char*>(g_kc) + i * PB, PB, bars + i * 8);
            bulk_g2s(sV + i * PB, reinterpret_cast<const char*>(g_vc) + i * PB, PB, bars + i * 8);
        }
    }
    float kmax2 = fmaxf(fmaxf(fmaxf(km0.x, km0.y), fmaxf(km0.z, km0.w)), fmaxf(fmaxf(km1.x, km1.y), fmaxf(km1.z, km1.w)));
#pragma unroll
    for (int o = 1; o < 32; o <<= 1) kmax2 = fmaxf(kmax2, __shfl_xor_sync(~0u, kmax2, o));
    if (tid < 32 && elect_one()) {
        for (int i = 2; i < A_NPIECE; i++) {
            mbar_expect(bars + i * 8, 2 * PB);
            bulk_g2s(sK + i * PB, reinterpret_cast<const char*>(g_kc) + i * PB, PB, bars + i * 8);
            bulk_g2s(sV + i * PB, reinterpret_cast<const char*>(g_vc) + i * PB, PB, bars + i * 8);
        }
    }
    uint32_t vote = 0;
#pragma unroll
    for (int r = 0; r < 2; r++) {
        const uint32_t (&q)[6] = nq[r];
        const float a0 = bf_lo(q[0]), a1 = bf_hi(q[0]), a2 = bf_lo(q[2]), a3 = bf_hi(q[2]);
        const float b0 = bf_lo(q[1]), b1 = bf_hi(q[1]), b2 = bf_lo(q[3]), b3 = bf_hi(q[3]);
        float n0 = a0 * a0 + a1 * a1 + a2 * a2 + a3 * a3, n1 = b0 * b0 + b1 * b1 + b2 * b2 + b3 * b3;
        if (t == 0) {
            const float c0 = bf_lo(q[4]), c1 = bf_hi(q[4]), d0 = bf_lo(q[5]), d1 = bf_hi(q[5]);
            n0 += c0 * c0 + c1 * c1; n1 += d0 * d0 + d1 * d1;
        }
        n0 += __shfl_xor_sync(~0u, n0, 1); n0 += __shfl_xor_sync(~0u, n0, 2);
        n1 += __shfl_xor_sync(~0u, n1, 1); n1 += __shfl_xor_sync(~0u, n1, 2);
        const bool unsafe = !(fmaxf(n0, n1) * kmax2 <= FAST_BOUND * FAST_BOUND) || !(n0 == n0) || !(n1 == n1);
        vote |= (__any_sync(~0u, unsafe) ? 1u : 0u) << r;
        const uint32_t cst = t == 1 ? 0x3F804780u : (t == 2 ? 0x00003F80u : 0u);
        const uint32_t sQ = sK + A_OFF_Q + (r * 4 + wg) * 4096 + (w * 2) * 512 + g * 16 + t * 4;
        asm volatile("st.shared.b32 [%0], %1;" ::"r"(sQ), "r"(q[0]) : "memory");
        asm volatile("st.shared.b32 [%0], %1;" ::"r"(sQ + 512), "r"(q[1]) : "memory");
        asm volatile("st.shared.b32 [%0], %1;" ::"r"(sQ + 128), "r"(q[2]) : "memory");
        asm volatile("st.shared.b32 [%0], %1;" ::"r"(sQ + 640), "r"(q[3]) : "memory");
        asm volatile("st.shared.b32 [%0], %1;" ::"r"(sQ + 256), "r"(t == 0 ? q[4] : cst) : "memory");
        asm volatile("st.shared.b32 [%0], %1;" ::"r"(sQ + 768), "r"(t == 0 ? q[5] : cst) : "memory");
        asm volatile("st.shared.b32 [%0], %1;" ::"r"(sQ + 384), "r"(0u) : "memory");
        asm volatile("st.shared.b32 [%0], %1;" ::"r"(sQ + 896), "r"(0u) : "memory");
    }
    const uint32_t sVote = bars + 64 + wg * 16;
    if (lane == 0) asm volatile("st.shared.b32 [%0], %1;" ::"r"(sVote + w * 4), "r"(vote) : "memory");
    proxy_fence();
    named_sync(wg + 1, 128);
    uint32_t unsafe_mask;
    {
        uint32_t v0, v1, v2, v3;
        asm volatile("ld.shared.v4.b32 {%0, %1, %2, %3}, [%4];" : "=r"(v0), "=r"(v1), "=r"(v2), "=r"(v3) : "r"(sVote));
        unsafe_mask = __shfl_sync(~0u, v0 | v1 | v2 | v3, 0);
    }
    if (unsafe_mask) {
#pragma unroll
        for (int r = 0; r < 2; r++) {
            if (((unsafe_mask >> r) & 1) && t != 0) {
                const uint32_t sQ = sK + A_OFF_Q + (r * 4 + wg) * 4096 + (w * 2) * 512 + g * 16 + t * 4;
                asm volatile("st.shared.b32 [%0], %1;" ::"r"(sQ + 256), "r"(0u) : "memory");
                asm volatile("st.shared.b32 [%0], %1;" ::"r"(sQ + 768), "r"(0u) : "memory");
            }
        }
        proxy_fence();
        named_sync(wg + 1, 128);
    }
#pragma unroll 1
    for (int rep = 0; rep < 2; rep++, row += 256) {
        if (rep == 1) {
            uint4* z = reinterpret_cast<uint4*>(out + (size_t)blockIdx.x * 16 * DM) + tid;
            z[0] = make_uint4(0u, 0u, 0u, 0u); z[A_THREADS] = make_uint4(0u, 0u, 0u, 0u);
            if (tid < 16 * DM * 2 / 16 - 2 * A_THREADS) z[2 * A_THREADS] = make_uint4(0u, 0u, 0u, 0u);
        }
        const uint32_t any_unsafe = (unsafe_mask >> rep) & 1;
        const uint64_t dQ0 = cdesc(A_OFF_Q, 128, 512, 0) + (rep * 4 + wg) * 256, dQ1 = dQ0 + 16;
        float o[12];
#pragma unroll
        for (int i = 0; i < 12; i++) o[i] = 0.f;
        pin(o);
        uint64_t dK0 = cdesc(0, 128, 384, 0), dK1 = cdesc(256, 0, 384, 0), dV = cdesc(KV_BYTES, 384, 128, 0);
        if (!any_unsafe) {
            float s[64];
#pragma unroll 1
            for (int j = 0; j < 16; j++) {
                if (rep == 0 && (j & 1) == 0) mbar_wait(bars + (j >> 1) * 8, 0);
                wg_fence();
                wgmma_ss_n128<0>(s, dQ0, dK0, 0);
                wgmma_ss_n128<0>(s, dQ1, dK1, 1);
                wg_commit();
                dK0 += 16 * 384 >> 4; dK1 += 16 * 384 >> 4;
                wg_wait<0>();
                pin(s);
                uint32_t p[32];
                {
                    constexpr int NP = 2 * __builtin_popcount(POLY_MASK), NM = 32 - NP;
                    float e[64];
#pragma unroll
                    for (int i = 0; i < 32; i++)
                        if (!((POLY_MASK >> (i >> 1)) & 1)) { e[2 * i] = ex2(s[2 * i]); e[2 * i + 1] = ex2(s[2 * i + 1]); p[i] = pack_bf16(e[2 * i], e[2 * i + 1]); }
                    int ip = 0;
#pragma unroll
                    for (int i = 0; i < 32; i++) {
                        if ((POLY_MASK >> (i >> 1)) & 1) {
                            const int mm = (ip * 2 * NM) / NP - CHAIN;
                            uint32_t dep = 0;
                            if (CHAIN > 0 && mm >= 0) {
                                int cnt = 0;
#pragma unroll
                                for (int q = 0; q < 32; q++)
                                    if (!((POLY_MASK >> (q >> 1)) & 1)) { if (cnt == (mm >> 1)) dep = __float_as_uint(e[2 * q + (mm & 1)]); cnt++; }
                            }
                            p[i] = exp2_pair_fixed(s[2 * i], s[2 * i + 1], dep);
                            ip++;
                        }
                    }
                }
                pin(p);
                wg_fence();
#pragma unroll
                for (int k = 0; k < 8; k++) wgmma_rs_n24<1>(o, p[4 * k], p[4 * k + 1], p[4 * k + 2], p[4 * k + 3], dV + k * 48, 1);
                wg_commit();
                dV += 16 * 384 >> 4;
                wg_wait<0>();
            }
        } else {
            float s[64];
            float m0 = -INFINITY, m1 = -INFINITY;
#pragma unroll 1
            for (int j = 0; j < 16; j++) {
                if (rep == 0 && (j & 1) == 0) mbar_wait(bars + (j >> 1) * 8, 0);
                wg_fence();
                wgmma_ss_n128<0>(s, dQ0, dK0, 0);
                wgmma_ss_n128<0>(s, dQ1, dK1, 1);
                wg_commit();
                dK0 += 16 * 384 >> 4; dK1 += 16 * 384 >> 4;
                wg_wait<0>();
                pin(s);
                float x0m = m0, x1m = m1;
#pragma unroll
                for (int b = 0; b < 16; b++) { x0m = fmaxf(x0m, fmaxf(s[4 * b], s[4 * b + 1])); x1m = fmaxf(x1m, fmaxf(s[4 * b + 2], s[4 * b + 3])); }
                x0m = fmaxf(x0m, __shfl_xor_sync(~0u, x0m, 1)); x0m = fmaxf(x0m, __shfl_xor_sync(~0u, x0m, 2));
                x1m = fmaxf(x1m, __shfl_xor_sync(~0u, x1m, 1)); x1m = fmaxf(x1m, __shfl_xor_sync(~0u, x1m, 2));
                const float c0 = ex2(m0 - x0m), c1 = ex2(m1 - x1m);
                m0 = x0m; m1 = x1m;
#pragma unroll
                for (int b = 0; b < 3; b++) { o[4 * b] *= c0; o[4 * b + 1] *= c0; o[4 * b + 2] *= c1; o[4 * b + 3] *= c1; }
                uint32_t p[32];
#pragma unroll
                for (int b = 0; b < 16; b++) {
                    p[2 * b] = pack_bf16(ex2(s[4 * b] - m0), ex2(s[4 * b + 1] - m0));
                    p[2 * b + 1] = pack_bf16(ex2(s[4 * b + 2] - m1), ex2(s[4 * b + 3] - m1));
                }
                pin(p); pin(o);
                wg_fence();
#pragma unroll
                for (int k = 0; k < 8; k++) wgmma_rs_n24<1>(o, p[4 * k], p[4 * k + 1], p[4 * k + 2], p[4 * k + 3], dV + k * 48, 1);
                wg_commit();
                dV += 16 * 384 >> 4;
                wg_wait<0>();
            }
        }
        pin(o);
        const float l0 = __shfl_sync(~0u, o[8], (lane & ~3) | 1), l1 = __shfl_sync(~0u, o[10], (lane & ~3) | 1);
        const float i0 = 1.0f / l0, i1 = 1.0f / l1;
        uint32_t* o32 = reinterpret_cast<uint32_t*>(g_o);
        o32[row * 9 + t] = pack_bf16(o[0] * i0, o[1] * i0);
        o32[(row + 8) * 9 + t] = pack_bf16(o[2] * i1, o[3] * i1);
        o32[row * 9 + 4 + t] = pack_bf16(o[4] * i0, o[5] * i0);
        o32[(row + 8) * 9 + 4 + t] = pack_bf16(o[6] * i1, o[7] * i1);
        if (t == 0) { o32[row * 9 + 8] = pack_bf16(o[8] * i0, o[9] * i0); o32[(row + 8) * 9 + 8] = pack_bf16(o[10] * i1, o[11] * i1); }
    }
}

constexpr int O_THREADS = 416;
constexpr int O_OFF_STAT = P_A_BYTES + P_NST * P_B_STAGE + 256;
constexpr int O_SMEM = O_OFF_STAT + 9 * 64 * 8;

__global__ void __cluster_dims__(3, 1, 1) __launch_bounds__(O_THREADS, 1)
k_oproj(const __grid_constant__ CUtensorMap tmO, const __grid_constant__ CUtensorMap tmWo, const __grid_constant__ CUtensorMap tmX2, const __grid_constant__ CUtensorMap tmH, const __nv_bfloat16* __restrict__ x, const __nv_bfloat16* __restrict__ w1) {
    extern __shared__ __align__(1024) uint8_t smem[];
    const uint32_t sA = smem_u32(smem), sB = sA + P_A_BYTES, bars = sB + P_NST * P_B_STAGE;
    const uint32_t fullB = bars, emptyB = bars + 64, fullA = bars + 128;
    const int tid = threadIdx.x, warp = __shfl_sync(~0u, tid >> 5, 0), lane = tid & 31;
    const int m = blockIdx.x / 3, cg = blockIdx.x % 3;
    check_smem_base(sA);
    if (tid == 0) {
        prefetch_map(&tmO); prefetch_map(&tmWo); prefetch_map(&tmX2); prefetch_map(&tmH);
        for (int i = 0; i < P_NST; i++) { mbar_init(fullB + i * 8, 1); mbar_init(emptyB + i * 8, 12); }
        for (int i = 0; i < 9; i++) mbar_init(fullA + i * 8, 1);
        bar_init_fence();
        for (int kb = 0; kb < 9; kb++) mbar_expect(fullA + kb * 8, 8192);
    }
    __syncthreads();
    pdl_launch();
    if (warp == 12) {
        if (elect_one()) {
            for (int kb = 0; kb < 9; kb++) {
                const int s = kb >= P_NST ? kb - P_NST : kb;
                if (kb == 2) {
                    pdl_wait();
                    for (int ka = 0; ka < 9; ka++) tma_2d(sA + ka * 8192, &tmO, ka * 64, m * 64, fullA + ka * 8);
                }
                if (kb >= P_NST) mbar_wait(emptyB + s * 8, 0);
                mbar_expect(fullB + s * 8, P_B_STAGE);
                for (int a = 0; a < 3; a++) tma_2d(sB + s * P_B_STAGE + a * 8192, &tmWo, cg * 192 + a * 64, kb * 64, fullB + s * 8);
            }
            for (int i = 0; i < 6; i++) prefetch_l2(reinterpret_cast<const char*>(w1) + (size_t)blockIdx.x * (FF * DM * 2 / 96) + i * 9216, 9216);
        }
        return;
    }
    const int wg = warp >> 2, w = warp & 3, g = lane >> 2, t = lane & 3;
    uint32_t xr[16];
    {
        const uint32_t* x32 = reinterpret_cast<const uint32_t*>(x) + (((m * 64 + w * 16 + g) * DM + cg * 192 + wg * 64 + 2 * t) >> 1);
#pragma unroll
        for (int b = 0; b < 8; b++) { xr[2 * b] = __ldg(x32 + b * 4); xr[2 * b + 1] = __ldg(x32 + b * 4 + 4 * DM); }
    }
    float acc[32];
    proj_mma(acc, wg, fullB, emptyB, fullA, true, lane);
    named_sync(1, 384);
    float s0 = 0.f, q0 = 0.f, s1 = 0.f, q1 = 0.f;
#pragma unroll
    for (int b = 0; b < 8; b++) {
        const uint32_t xa = xr[2 * b], xb = xr[2 * b + 1];
        const uint32_t ha = pack_bf16(acc[4 * b] + bf_lo(xa), acc[4 * b + 1] + bf_hi(xa));
        const uint32_t hb = pack_bf16(acc[4 * b + 2] + bf_lo(xb), acc[4 * b + 3] + bf_hi(xb));
        xr[2 * b] = ha; xr[2 * b + 1] = hb;
        const float a = bf_lo(ha), c = bf_hi(ha), d = bf_lo(hb), e = bf_hi(hb);
        s0 += a + c; q0 = fmaf(a, a, fmaf(c, c, q0));
        s1 += d + e; q1 = fmaf(d, d, fmaf(e, e, q1));
    }
    s0 += __shfl_xor_sync(~0u, s0, 1); s0 += __shfl_xor_sync(~0u, s0, 2);
    q0 += __shfl_xor_sync(~0u, q0, 1); q0 += __shfl_xor_sync(~0u, q0, 2);
    s1 += __shfl_xor_sync(~0u, s1, 1); s1 += __shfl_xor_sync(~0u, s1, 2);
    q1 += __shfl_xor_sync(~0u, q1, 1); q1 += __shfl_xor_sync(~0u, q1, 2);
    const int r = w * 16 + g;
    const uint32_t sStat = sA + O_OFF_STAT;
    if (t < 3) {
        uint32_t dst;
        asm("mapa.shared::cluster.u32 %0, %1, %2;" : "=r"(dst) : "r"(sStat + ((cg * 3 + wg) * 64 + r) * 8), "r"(t));
        asm volatile("st.shared::cluster.v2.f32 [%0], {%1, %2};" ::"r"(dst), "f"(s0), "f"(q0) : "memory");
        asm volatile("st.shared::cluster.v2.f32 [%0], {%1, %2};" ::"r"(dst + 64), "f"(s1), "f"(q1) : "memory");
    }
    cluster_arrive();
    stage_tile<8>(xr, sA + wg * 8192, w, lane);
    proxy_fence();
    named_sync(2 + wg, 128);
    const bool leader = w == 0 && elect_one();
    if (leader) { tma_st_2d(&tmH, cg * 192 + wg * 64, m * 64, sA + wg * 8192); bulk_commit(); }
    cluster_wait();
    s0 = q0 = s1 = q1 = 0.f;
#pragma unroll
    for (int p = 0; p < 9; p++) {
        float a, b, c, d;
        asm volatile("ld.shared.v2.f32 {%0, %1}, [%2];" : "=f"(a), "=f"(b) : "r"(sStat + (p * 64 + r) * 8));
        asm volatile("ld.shared.v2.f32 {%0, %1}, [%2];" : "=f"(c), "=f"(d) : "r"(sStat + (p * 64 + r + 8) * 8));
        s0 += a; q0 += b; s1 += c; q1 += d;
    }
    const float m0 = s0 * (1.0f / DM), m1 = s1 * (1.0f / DM);
    const float rs0 = rsqrtf(fmaxf(q0 * (1.0f / DM) - m0 * m0, 0.f) + LN_EPS), rs1 = rsqrtf(fmaxf(q1 * (1.0f / DM) - m1 * m1, 0.f) + LN_EPS);
    const float sc0 = 0.5f * rs0, sc1 = 0.5f * rs1, n0 = -m0 * sc0, n1 = -m1 * sc1;
#pragma unroll
    for (int b = 0; b < 8; b++) {
        xr[2 * b] = pack_bf16(fmaf(bf_lo(xr[2 * b]), sc0, n0), fmaf(bf_hi(xr[2 * b]), sc0, n0));
        xr[2 * b + 1] = pack_bf16(fmaf(bf_lo(xr[2 * b + 1]), sc1, n1), fmaf(bf_hi(xr[2 * b + 1]), sc1, n1));
    }
    stage_tile<8>(xr, sA + (3 + wg) * 8192, w, lane);
    proxy_fence();
    named_sync(2 + wg, 128);
    if (leader) {
        tma_st_2d(&tmX2, cg * 192 + wg * 64, m * 64, sA + (3 + wg) * 8192);
        bulk_commit();
        bulk_wait_all();
    }
}

constexpr int F_THREADS = 384;
constexpr int F_NST = 6;
constexpr int F_STAGE = 96 * 128;
constexpr int F_X_BYTES = 9 * 16384;
constexpr int F_OFF_ST = F_X_BYTES;
constexpr int F_OFF_BAR = F_OFF_ST + F_NST * F_STAGE;
constexpr int F_SMEM = F_OFF_BAR + 256;

__device__ __forceinline__ float tanh_hw(float x) { float y; asm("tanh.approx.f32 %0, %1;" : "=f"(y) : "f"(x)); return y; }
__host__ __device__ constexpr int piece_begin(int p) { return p == 0 ? 0 : 3 * p + 1; }
template <int P>
__device__ __forceinline__ void silu_s1(const float (&acc)[32], float (&tmp)[8]) {
#pragma unroll
    for (int i = 2 * piece_begin(P); i < 2 * piece_begin(P + 1); i++) tmp[i - 2 * piece_begin(P)] = tanh_hw(acc[i]);
}
template <int C, int P>
__device__ __forceinline__ void silu_s2(const float (&acc)[32], const float (&tmp)[8], uint32_t (&h1)[144]) {
#pragma unroll
    for (int i = piece_begin(P); i < piece_begin(P + 1); i++) {
        const int k = 2 * (i - piece_begin(P));
        h1[C * 16 + i] = pack_bf16(fmaf(acc[2 * i], tmp[k], acc[2 * i]), fmaf(acc[2 * i + 1], tmp[k + 1], acc[2 * i + 1]));
    }
}
template <int J>
__device__ __forceinline__ void silu_slot_last(const float (&prev)[32], float (&tmp)[2][8], uint32_t (&h1)[144]) {
    if constexpr (J >= 1 && J <= 4) {
#pragma unroll
        for (int i = 0; i < 4; i++) {
            const int q = 4 * (J - 1) + i;
            h1[128 + q] = pack_bf16(fmaf(prev[2 * q], tmp[(J - 1) & 1][2 * i], prev[2 * q]), fmaf(prev[2 * q + 1], tmp[(J - 1) & 1][2 * i + 1], prev[2 * q + 1]));
        }
    }
    if constexpr (J <= 3) {
#pragma unroll
        for (int i = 0; i < 8; i++) tmp[J & 1][i] = tanh_hw(prev[8 * J + i]);
        pin(tmp[J & 1]);
    }
}
template <int C, int J>
__device__ __forceinline__ void silu_slot(const float (&prev)[32], float (&tmp)[2][8], uint32_t (&h1)[144]) {
    if constexpr (J >= 1) silu_s2<C, J - 1>(prev, tmp[(J - 1) & 1], h1);
    if constexpr (J <= 4) { silu_s1<J>(prev, tmp[J & 1]); pin(tmp[J & 1]); }
}

struct FfnPipe {
    uint32_t full, empty;
    int lane;
    __device__ __forceinline__ void acquire(int s, uint32_t ph) const { mbar_wait(full + s * 8, ph); }
    __device__ __forceinline__ void release(int s) const { if (lane == 0) mbar_arrive(empty + s * 8); }
};

template <int C>
__device__ __forceinline__ void ffn_phase1_chunk(float (&cur)[32], float (&prev)[32], uint32_t (&h1)[144], const FfnPipe& pp, uint64_t dx, uint32_t fullX) {
    float tmp[2][8];
    const uint64_t dw = cdesc(F_OFF_ST, 8192, 1024, 1) + blockIdx.y * (C + 1);
    dx += blockIdx.y * C;
#pragma unroll
    for (int j = 0; j < 6; j++) {
        if (C == 0) { mbar_wait(fullX + ((6 * j) >> 2) * 8, 0); mbar_wait(fullX + ((6 * j + 5) >> 2) * 8, 0); }
        pp.acquire(j, C & 1);
        if (j == 0) pin(cur);
        wg_fence();
#pragma unroll
        for (int i = 0; i < 6; i++) {
            const int ks = 6 * j + i;
            wgmma_ss_n64<1>(cur, dx + ((ks >> 2) * 1024 + (ks & 3) * 2), dw + ((j * F_STAGE + i * 2048) >> 4), ks != 0);
        }
        wg_commit();
        if (C > 0 || j > 0) { wg_wait<1>(); pp.release((j + 5) % 6); }
        if (C > 0) {
            constexpr int CP = C > 0 ? C - 1 : 0;
            pin(prev);
            if (j == 0) silu_slot<CP, 0>(prev, tmp, h1);
            if (j == 1) silu_slot<CP, 1>(prev, tmp, h1);
            if (j == 2) silu_slot<CP, 2>(prev, tmp, h1);
            if (j == 3) silu_slot<CP, 3>(prev, tmp, h1);
            if (j == 4) silu_slot<CP, 4>(prev, tmp, h1);
            if (j == 5) silu_slot<CP, 5>(prev, tmp, h1);
        }
    }
}

__device__ __forceinline__ void ffn_stage_chunk(const float (&acc)[32], uint32_t stg, int w, int lane, bool resid, uint32_t fullH) {
    uint32_t pk[16];
    if (resid) {
        mbar_wait(fullH, 0);
        const int r = w * 16 + (lane & 7) + ((lane >> 3) & 1) * 8;
#pragma unroll
        for (int b = 0; b < 8; b += 2) {
            uint32_t h0, h1, h2, h3;
            asm volatile("ldmatrix.sync.aligned.m8n8.x4.shared.b16 {%0, %1, %2, %3}, [%4];" : "=r"(h0), "=r"(h1), "=r"(h2), "=r"(h3) : "r"(stg + r * 128 + (((b + (lane >> 4)) ^ (r & 7)) << 4)) : "memory");
            pk[2 * b] = pack_bf16(acc[4 * b] + bf_lo(h0), acc[4 * b + 1] + bf_hi(h0));
            pk[2 * b + 1] = pack_bf16(acc[4 * b + 2] + bf_lo(h1), acc[4 * b + 3] + bf_hi(h1));
            pk[2 * b + 2] = pack_bf16(acc[4 * b + 4] + bf_lo(h2), acc[4 * b + 5] + bf_hi(h2));
            pk[2 * b + 3] = pack_bf16(acc[4 * b + 6] + bf_lo(h3), acc[4 * b + 7] + bf_hi(h3));
        }
    } else {
#pragma unroll
        for (int i = 0; i < 16; i++) pk[i] = pack_bf16(acc[2 * i], acc[2 * i + 1]);
    }
    stage_tile<8>(pk, stg, w, lane);
}
__device__ __forceinline__ void ffn_reduce_chunk(const CUtensorMap* tmOut, uint32_t stg, int col, int row, int w, int wgid, bool leader) {
    proxy_fence();
    if (w != 0) {
        asm volatile("bar.arrive %0, 128;" ::"r"(2 + wgid) : "memory");
    } else {
        named_sync(2 + wgid, 128);
        if (leader) { tma_red_2d(tmOut, col, row, stg); bulk_commit(); }
    }
}

__device__ __forceinline__ void ffn_load_residual(float (&acc)[32], uint32_t stg, int w, int lane, uint32_t fullH) {
    mbar_wait(fullH, 0);
    const int r = w * 16 + (lane & 7) + ((lane >> 3) & 1) * 8;
#pragma unroll
    for (int b = 0; b < 8; b += 2) {
        uint32_t h0, h1, h2, h3;
        asm volatile("ldmatrix.sync.aligned.m8n8.x4.shared.b16 {%0, %1, %2, %3}, [%4];" : "=r"(h0), "=r"(h1), "=r"(h2), "=r"(h3) : "r"(stg + r * 128 + (((b + (lane >> 4)) ^ (r & 7)) << 4)) : "memory");
        acc[4 * b] = bf_lo(h0); acc[4 * b + 1] = bf_hi(h0); acc[4 * b + 2] = bf_lo(h1); acc[4 * b + 3] = bf_hi(h1);
        acc[4 * b + 4] = bf_lo(h2); acc[4 * b + 5] = bf_hi(h2); acc[4 * b + 6] = bf_lo(h3); acc[4 * b + 7] = bf_hi(h3);
    }
}

template <int MODE>
__device__ __forceinline__ void ffn_phase2_chunk(float (&cur)[32], float (&prev)[32], uint32_t (&h1)[144], const FfnPipe& pp, uint32_t ph, const CUtensorMap* tmOut, uint32_t stg_prev, int col_prev, int row, int w, int lane, int wgid, bool leader,
                                                 bool resid_prev, uint32_t fullH, uint32_t stg_res) {
    const uint64_t dw = cdesc(F_OFF_ST, 8192, 1024, 1) + blockIdx.y * col_prev;
    float tmp[2][8];
#pragma unroll
    for (int j = 0; j < 6; j++) {
        pp.acquire(j, ph);
        if (j == 0) pin(cur);
        if (MODE == 0 && j == 5) pin(h1);
        wg_fence();
#pragma unroll
        for (int i = 0; i < 6; i++) {
            const int f = (6 * j + i) * 4;
            wgmma_rs_n64<1>(cur, h1[f], h1[f + 1], h1[f + 2], h1[f + 3], dw + ((j * F_STAGE + i * 2048) >> 4), MODE == 3 || (j | i) != 0);
        }
        wg_commit();
        wg_wait<1>();
        pp.release((j + 5) % 6);
        if (MODE == 0) {
            pin(prev);
            if (j == 0) silu_slot_last<0>(prev, tmp, h1);
            if (j == 1) silu_slot_last<1>(prev, tmp, h1);
            if (j == 2) silu_slot_last<2>(prev, tmp, h1);
            if (j == 3) silu_slot_last<3>(prev, tmp, h1);
            if (j == 4) silu_slot_last<4>(prev, tmp, h1);
        } else {
            if (j == 0) { pin(prev); ffn_stage_chunk(prev, stg_prev, w, lane, MODE == 3 && resid_prev, fullH); }
            if (j == 1) ffn_reduce_chunk(tmOut, stg_prev, col_prev, row, w, wgid, leader);
            if (MODE == 2 && j == 2) { ffn_load_residual(prev, stg_res, w, lane, fullH); pin(prev); }
        }
    }
}

__global__ void __launch_bounds__(F_THREADS, 1)
k_ffn(const __grid_constant__ CUtensorMap tmX2, const __grid_constant__ CUtensorMap tmW1, const __grid_constant__ CUtensorMap tmW2, const __grid_constant__ CUtensorMap tmOut,
      const __grid_constant__ CUtensorMap tmRes, const __nv_bfloat16* __restrict__ w2) {
    extern __shared__ __align__(1024) uint8_t smem[];
    const uint32_t sX = smem_u32(smem), sSt = sX + F_OFF_ST, bars = sX + F_OFF_BAR;
    const uint32_t full = bars, empty = bars + 64, fullX = bars + 128, fullH = bars + 208;
    const int tid = threadIdx.x, warp = __shfl_sync(~0u, tid >> 5, 0), lane = tid & 31;
    const int m = blockIdx.x >> 3, fs = blockIdx.x & 7;
    check_smem_base(sX);
    if (tid == 0) {
        prefetch_map(&tmW1); prefetch_map(&tmX2); prefetch_map(&tmW2); prefetch_map(&tmOut); prefetch_map(&tmRes);
        for (int i = 0; i < F_NST; i++) { mbar_init(full + i * 8, 1); mbar_init(empty + i * 8, 8); }
        for (int i = 0; i < 9; i++) mbar_init(fullX + i * 8, 1);
        mbar_init(fullH, 1); mbar_init(fullH + 8, 1);
        bar_init_fence();
        for (int kb = 0; kb < 9; kb++) mbar_expect(fullX + kb * 8, 16384);
    }
    __syncthreads();
    if (warp < 4) {
        asm volatile("setmaxnreg.dec.sync.aligned.u32 24;");
        if (warp == 1 && lane < 9) prefetch_l2(reinterpret_cast<const char*>(w2) + ((size_t)fs * 576 + m * 36 + lane * 4) * (DM * 2), 4 * DM * 2);
        if (warp == 0 && elect_one()) {
#pragma unroll 1
            for (int c = 0; c < 18; c++) {
                int col = c - 9 + fs;
                if (col >= 9) col -= 9;
#pragma unroll 1
                for (int j = 0; j < 6; j++) {
                    mbar_wait(empty + j * 8, (c & 1) ^ 1);
                    mbar_expect(full + j * 8, F_STAGE);
                    if (c < 9) tma_2d(sSt + j * F_STAGE, &tmW1, fs * 576 + c * 64, j * 96, full + j * 8);
                    else tma_2d(sSt + j * F_STAGE, &tmW2, col * 64, fs * 576 + j * 96, full + j * 8);
                }
            }
        }
    } else {
        asm volatile("setmaxnreg.inc.sync.aligned.u32 240;");
        const int wgid = (warp >> 2) - 1, w = warp & 3;
        pdl_wait();
        if (warp == 4 && elect_one()) {
            for (int kb = 0; kb < 9; kb++) tma_2d(sX + kb * 16384, &tmX2, kb * 64, m * 128, fullX + kb * 8);
        }
        __syncwarp();
        FfnPipe pp{full, empty, lane};
        const uint64_t xlo = cdesc(0, 16, 1024, 1) + wgid * 512;
        uint32_t h1[144];
        float acc0[32], acc1[32];
        ffn_phase1_chunk<0>(acc0, acc1, h1, pp, xlo, fullX);
        ffn_phase1_chunk<1>(acc1, acc0, h1, pp, xlo, fullX);
        ffn_phase1_chunk<2>(acc0, acc1, h1, pp, xlo, fullX);
        ffn_phase1_chunk<3>(acc1, acc0, h1, pp, xlo, fullX);
        ffn_phase1_chunk<4>(acc0, acc1, h1, pp, xlo, fullX);
        ffn_phase1_chunk<5>(acc1, acc0, h1, pp, xlo, fullX);
        ffn_phase1_chunk<6>(acc0, acc1, h1, pp, xlo, fullX);
        ffn_phase1_chunk<7>(acc1, acc0, h1, pp, xlo, fullX);
        ffn_phase1_chunk<8>(acc0, acc1, h1, pp, xlo, fullX);
        const int row = m * 128 + wgid * 64;
        const uint32_t stg = sX + wgid * 8192;
        int c = fs, cprev = 0;
        const bool leader = w == 0 && elect_one();
        const uint32_t myH = fullH + wgid * 8;
        ffn_phase2_chunk<0>(acc1, acc0, h1, pp, 1, &tmOut, 0, 0, row, w, lane, wgid, leader, false, myH, 0);
        if (leader) {
            const int c8 = fs == 0 ? 8 : fs - 1;
            mbar_expect(myH, fs == 0 ? 16384 : 8192);
            tma_2d(stg + 8 * 16384, &tmRes, c8 * 64, row, myH);
            if (fs == 0) tma_2d(stg + 7 * 16384, &tmRes, 7 * 64, row, myH);
        }
        cprev = c; if (++c == 9) c = 0;
#pragma unroll 1
        for (int j = 1; j < 7; j += 2) {
            ffn_phase2_chunk<1>(acc0, acc1, h1, pp, 0, &tmOut, stg + (j - 1) * 16384, cprev * 64, row, w, lane, wgid, leader, false, myH, 0);
            cprev = c; if (++c == 9) c = 0;
            ffn_phase2_chunk<1>(acc1, acc0, h1, pp, 1, &tmOut, stg + j * 16384, cprev * 64, row, w, lane, wgid, leader, false, myH, 0);
            cprev = c; if (++c == 9) c = 0;
        }
        ffn_phase2_chunk<2>(acc0, acc1, h1, pp, 0, &tmOut, stg + 6 * 16384, cprev * 64, row, w, lane, wgid, leader, false, myH, stg + 8 * 16384);
        cprev = c; if (++c == 9) c = 0;
        ffn_phase2_chunk<3>(acc1, acc0, h1, pp, 1, &tmOut, stg + 7 * 16384, cprev * 64, row, w, lane, wgid, leader, fs == 0, myH, 0);
        cprev = c;
        wg_wait<0>();
        pin(acc1);
        ffn_stage_chunk(acc1, stg + 8 * 16384, w, lane, false, myH);
        ffn_reduce_chunk(&tmOut, stg + 8 * 16384, cprev * 64, row, w, wgid, leader);
        if (leader) bulk_wait_all();
    }
}

typedef CUresult (*EncodeFn)(CUtensorMap*, CUtensorMapDataType, cuuint32_t, void*, const cuuint64_t*, const cuuint64_t*, const cuuint32_t*, const cuuint32_t*,
                             CUtensorMapInterleave, CUtensorMapSwizzle, CUtensorMapL2promotion, CUtensorMapFloatOOBfill);

CUtensorMap make_map(EncodeFn enc, const void* base, int rows, int cols, int box_rows) {
    CUtensorMap tm;
    cuuint64_t dims[2] = {(cuuint64_t)cols, (cuuint64_t)rows};
    cuuint64_t strides[1] = {(cuuint64_t)cols * 2};
    cuuint32_t box[2] = {64, (cuuint32_t)box_rows};
    cuuint32_t es[2] = {1, 1};
    enc(&tm, CU_TENSOR_MAP_DATA_TYPE_BFLOAT16, 2, const_cast<void*>(base), dims, strides, box, es, CU_TENSOR_MAP_INTERLEAVE_NONE,
        CU_TENSOR_MAP_SWIZZLE_128B, CU_TENSOR_MAP_L2_PROMOTION_L2_256B, CU_TENSOR_MAP_FLOAT_OOB_FILL_NONE);
    return tm;
}

template <typename... KArgs, typename... Args>
void launch(void (*kern)(KArgs...), int grid, int block, int smem, bool pdl, Args... args) {
    cudaLaunchConfig_t cfg = {};
    cfg.gridDim = dim3(grid); cfg.blockDim = dim3(block); cfg.dynamicSmemBytes = smem; cfg.stream = cudaStreamPerThread;
    cudaLaunchAttribute at[1];
    at[0].id = cudaLaunchAttributeProgrammaticStreamSerialization;
    at[0].val.programmaticStreamSerializationAllowed = 1;
    cfg.attrs = at; cfg.numAttrs = pdl ? 1 : 0;
    cudaLaunchKernelEx(&cfg, kern, KArgs(args)...);
}

}

extern "C" void kernel_launch(void* const* d_in, const int* in_sizes, int n_in, void* d_out, int out_size) {
    const __nv_bfloat16* x = (const __nv_bfloat16*)d_in[0];
    const __nv_bfloat16* wq = (const __nv_bfloat16*)d_in[1];
    const __nv_bfloat16* wk = (const __nv_bfloat16*)d_in[2];
    const __nv_bfloat16* wv = (const __nv_bfloat16*)d_in[3];
    const __nv_bfloat16* wo = (const __nv_bfloat16*)d_in[4];
    const __nv_bfloat16* w1 = (const __nv_bfloat16*)d_in[6];
    const __nv_bfloat16* w2 = (const __nv_bfloat16*)d_in[7];
    __nv_bfloat16* out = (__nv_bfloat16*)d_out;

    static EncodeFn enc = nullptr;
    static void *p_o = nullptr, *p_x2 = nullptr, *p_q = nullptr, *p_res = nullptr;
    if (!enc) {
        cudaDriverEntryPointQueryResult qr;
        cudaGetDriverEntryPoint("cuTensorMapEncodeTiled", (void**)&enc, cudaEnableDefault, &qr);
        cudaGetSymbolAddress(&p_o, g_o);
        cudaGetSymbolAddress(&p_x2, g_x2);
        cudaGetSymbolAddress(&p_res, g_h);
        cudaGetSymbolAddress(&p_q, g_q);
        cudaFuncSetAttribute(k_qkv, cudaFuncAttributeMaxDynamicSharedMemorySize, Q_SMEM);
        cudaFuncSetAttribute(k_attn, cudaFuncAttributeMaxDynamicSharedMemorySize, A_SMEM);
        cudaFuncSetAttribute(k_oproj, cudaFuncAttributeMaxDynamicSharedMemorySize, O_SMEM);
        cudaFuncSetAttribute(k_ffn, cudaFuncAttributeMaxDynamicSharedMemorySize, F_SMEM);
    }
    const CUtensorMap tmWq = make_map(enc, wq, DM, DM, 192);
    const CUtensorMap tmWo = make_map(enc, wo, DM, DM, 64);
    const CUtensorMap tmO = make_map(enc, p_o, SEQ, DM, 64);
    const CUtensorMap tmX2st = make_map(enc, p_x2, SEQ, DM, 64);
    const CUtensorMap tmX2ld = make_map(enc, p_x2, SEQ, DM, 128);
    const CUtensorMap tmRes = make_map(enc, p_res, SEQ, DM, 64);
    const CUtensorMap tmQ = make_map(enc, p_q, SEQ, DM, 64);
    const CUtensorMap tmW1 = make_map(enc, w1, DM, FF, 96);
    const CUtensorMap tmW2 = make_map(enc, w2, FF, DM, 96);
    const CUtensorMap tmOut = make_map(enc, out, SEQ, DM, 64);

    launch(k_qkv, 128, Q_THREADS, Q_SMEM, false, tmWq, tmQ, x, wk, wv);
    launch(k_attn, 128, A_THREADS, A_SMEM, true, out);
    launch(k_oproj, 96, O_THREADS, O_SMEM, true, tmO, tmWo, tmX2st, tmRes, x, w1);
    launch(k_ffn, 128, F_THREADS, F_SMEM, true, tmX2ld, tmW1, tmW2, tmOut, tmRes, w2);
}
```

```cpp
#include <cuda_runtime.h>
#include <cuda_bf16.h>
#include <cuda.h>
#include <stdint.h>

namespace {

constexpr int SEQ = 2048, DM = 576, FF = 4608;
constexpr int KV_BYTES = SEQ * 48;
constexpr float LN_EPS = 1e-5f;
constexpr float LOG2E = 1.4426950408889634f;
constexpr float Q_SCALE = 0.23570226039551584f * LOG2E;

constexpr uint32_t POLY_MASK = 0xB6DBu;
constexpr int CHAIN = 6;
constexpr float FAST_BOUND = 90.0f;
constexpr float FAST_VMAX2 = 1e12f;

__device__ __align__(1024) __nv_bfloat16 g_q[SEQ * DM];
__device__ __align__(1024) uint4 g_kc[KV_BYTES / 16];
__device__ __align__(1024) uint4 g_vc[KV_BYTES / 16];
__device__ __align__(16) float g_kmax[256];
__device__ __align__(1024) __nv_bfloat16 g_o[SEQ * DM];
__device__ __align__(1024) __nv_bfloat16 g_h[SEQ * DM];
__device__ __align__(1024) __nv_bfloat16 g_x2[SEQ * DM];


__device__ __forceinline__ uint32_t smem_u32(const void* p) { return (uint32_t)__cvta_generic_to_shared(p); }
__device__ __forceinline__ void wg_fence() { asm volatile("wgmma.fence.sync.aligned;" ::: "memory"); }
__device__ __forceinline__ void wg_commit() { asm volatile("wgmma.commit_group.sync.aligned;" ::: "memory"); }
template <int N> __device__ __forceinline__ void wg_wait() { asm volatile("wgmma.wait_group.sync.aligned %0;" ::"n"(N) : "memory"); }
template <int N> __device__ __forceinline__ void pin(float (&r)[N]) {
#pragma unroll
    for (int i = 0; i < N; i++) asm volatile("" : "+f"(r[i])::"memory");
}
template <int N> __device__ __forceinline__ void pin(uint32_t (&r)[N]) {
#pragma unroll
    for (int i = 0; i < N; i++) asm volatile("" : "+r"(r[i])::"memory");
}
constexpr uint32_t SMEM0 = 0x400;
__host__ __device__ constexpr uint64_t cdesc(uint32_t off, uint32_t lbo, uint32_t sbo, uint32_t swz) {
    return (uint64_t)(((SMEM0 + off) & 0x3FFFF) >> 4) | ((uint64_t)(lbo >> 4) << 16) | ((uint64_t)(sbo >> 4) << 32) | ((uint64_t)swz << 62);
}
__device__ __forceinline__ void check_smem_base(uint32_t base) { if ((base & 0x3FFFF) != SMEM0) __trap(); }

__device__ __forceinline__ void mbar_init(uint32_t bar, int cnt) { asm volatile("mbarrier.init.shared::cta.b64 [%0], %1;" ::"r"(bar), "r"(cnt) : "memory"); }
__device__ __forceinline__ void mbar_expect(uint32_t bar, int bytes) { asm volatile("mbarrier.arrive.expect_tx.shared::cta.b64 _, [%0], %1;" ::"r"(bar), "r"(bytes) : "memory"); }
__device__ __forceinline__ void mbar_arrive(uint32_t bar) { asm volatile("mbarrier.arrive.shared::cta.b64 _, [%0];" ::"r"(bar) : "memory"); }
__device__ __forceinline__ void mbar_wait(uint32_t bar, uint32_t parity) {
    asm volatile(
        "{\n.reg .pred p;\n.reg .u32 n;\nmov.u32 n, 0;\n"
        "LAB_WAIT:\n"
        "mbarrier.try_wait.parity.shared::cta.b64 p, [%0], %1;\n"
        "@p bra DONE;\n"
        "add.u32 n, n, 1;\n"
        "setp.lt.u32 p, n, 4000000;\n"
        "@p bra LAB_WAIT;\n"
        "trap;\n"
        "DONE:\n}\n" ::"r"(bar), "r"(parity) : "memory");
}
__device__ __forceinline__ void bar_init_fence() {
    asm volatile("fence.mbarrier_init.release.cluster;" ::: "memory");
    asm volatile("fence.proxy.async.shared::cta;" ::: "memory");
}
__device__ __forceinline__ void proxy_fence() { asm volatile("fence.proxy.async.shared::cta;" ::: "memory"); }
__device__ __forceinline__ void named_sync(int id, int n) { asm volatile("bar.sync %0, %1;" ::"r"(id), "r"(n) : "memory"); }
__device__ __forceinline__ void bulk_g2s(uint32_t dst, const void* src, int bytes, uint32_t bar) {
    asm volatile("cp.async.bulk.shared::cluster.global.mbarrier::complete_tx::bytes [%0], [%1], %2, [%3];" ::"r"(dst), "l"(src), "r"(bytes), "r"(bar) : "memory");
}
__device__ __forceinline__ void tma_2d(uint32_t dst, const CUtensorMap* tm, int c0, int c1, uint32_t bar) {
    asm volatile("cp.async.bulk.tensor.2d.shared::cluster.global.mbarrier::complete_tx::bytes [%0], [%1, {%3, %4}], [%2];" ::"r"(dst), "l"(tm), "r"(bar), "r"(c0), "r"(c1) : "memory");
}
__device__ __forceinline__ void cluster_arrive() { asm volatile("barrier.cluster.arrive.release.aligned;" ::: "memory"); }
__device__ __forceinline__ void cluster_wait() { asm volatile("barrier.cluster.wait.acquire.aligned;" ::: "memory"); }
__device__ __forceinline__ void tma_red_2d(const CUtensorMap* tm, int c0, int c1, uint32_t src) {
    asm volatile("cp.reduce.async.bulk.tensor.2d.global.shared::cta.add.tile.bulk_group [%0, {%2, %3}], [%1];" ::"l"(tm), "r"(src), "r"(c0), "r"(c1) : "memory");
}
__device__ __forceinline__ void tma_st_2d(const CUtensorMap* tm, int c0, int c1, uint32_t src) {
    asm volatile("cp.async.bulk.tensor.2d.global.shared::cta.tile.bulk_group [%0, {%2, %3}], [%1];" ::"l"(tm), "r"(src), "r"(c0), "r"(c1) : "memory");
}
__device__ __forceinline__ void bulk_commit() { asm volatile("cp.async.bulk.commit_group;" ::: "memory"); }
__device__ __forceinline__ void bulk_wait_all() { asm volatile("cp.async.bulk.wait_group.read 0;" ::: "memory"); }
__device__ __forceinline__ bool elect_one() {
    uint32_t p;
    asm volatile("{\n.reg .pred P;\nelect.sync _|P, 0xffffffff;\nselp.b32 %0, 1, 0, P;\n}\n" : "=r"(p));
    return p != 0;
}
__device__ __forceinline__ void prefetch_l2(const void* p, int bytes) { asm volatile("cp.async.bulk.prefetch.L2.global [%0], %1;" ::"l"(p), "r"(bytes) : "memory"); }
__device__ __forceinline__ void prefetch_map(const CUtensorMap* tm) { asm volatile("prefetch.tensormap [%0];" ::"l"(tm) : "memory"); }
__device__ __forceinline__ void pdl_launch() { asm volatile("griddepcontrol.launch_dependents;" ::: "memory"); }
__device__ __forceinline__ void pdl_wait() { asm volatile("griddepcontrol.wait;" ::: "memory"); }
__device__ __forceinline__ float ex2(float x) { float y; asm("ex2.approx.ftz.f32 %0, %1;" : "=f"(y) : "f"(x)); return y; }
__device__ __forceinline__ uint32_t pack_bf16(float lo, float hi) { uint32_t r; asm("cvt.rn.bf16x2.f32 %0, %1, %2;" : "=r"(r) : "f"(hi), "f"(lo)); return r; }
__device__ __forceinline__ float bf_lo(uint32_t v) { return __uint_as_float(v << 16); }
__device__ __forceinline__ float bf_hi(uint32_t v) { return __uint_as_float(v & 0xFFFF0000u); }
__device__ __forceinline__ uint32_t hfma2(uint32_t a, uint32_t b, uint32_t c) { uint32_t r; asm("fma.rn.f16x2 %0, %1, %2, %3;" : "=r"(r) : "r"(a), "r"(b), "r"(c)); return r; }
__device__ __forceinline__ void stmatrix_x4(uint32_t addr, uint32_t r0, uint32_t r1, uint32_t r2, uint32_t r3) {
    asm volatile("stmatrix.sync.aligned.m8n8.x4.shared.b16 [%0], {%1, %2, %3, %4};" ::"r"(addr), "r"(r0), "r"(r1), "r"(r2), "r"(r3) : "memory");
}

template <int TB> __device__ __forceinline__ void wgmma_ss_n24(float (&d)[12], uint64_t da, uint64_t db, int sc) {
    asm volatile("{\n.reg .pred p;\nsetp.ne.b32 p, %14, 0;\n"
        "wgmma.mma_async.sync.aligned.m64n24k16.f32.bf16.bf16 {%0, %1, %2, %3, %4, %5, %6, %7, %8, %9, %10, %11}, %12, %13, p, 1, 1, 0, %15;\n}\n"
        : "+f"(d[0]), "+f"(d[1]), "+f"(d[2]), "+f"(d[3]), "+f"(d[4]), "+f"(d[5]), "+f"(d[6]), "+f"(d[7]), "+f"(d[8]), "+f"(d[9]), "+f"(d[10]), "+f"(d[11])
        : "l"(da), "l"(db), "r"(sc), "n"(TB));
}
template <int TB> __device__ __forceinline__ void wgmma_ss_n64(float (&d)[32], uint64_t da, uint64_t db, int sc) {
    asm volatile("{\n.reg .pred p;\nsetp.ne.b32 p, %34, 0;\n"
        "wgmma.mma_async.sync.aligned.m64n64k16.f32.bf16.bf16 {%0, %1, %2, %3, %4, %5, %6, %7, %8, %9, %10, %11, %12, %13, %14, %15, %16, %17, %18, %19, %20, %21, %22, %23, %24, %25, %26, %27, %28, %29, %30, %31}, %32, %33, p, 1, 1, 0, %35;\n}\n"
        : "+f"(d[0]), "+f"(d[1]), "+f"(d[2]), "+f"(d[3]), "+f"(d[4]), "+f"(d[5]), "+f"(d[6]), "+f"(d[7]), "+f"(d[8]), "+f"(d[9]), "+f"(d[10]), "+f"(d[11]), "+f"(d[12]), "+f"(d[13]), "+f"(d[14]), "+f"(d[15]), "+f"(d[16]), "+f"(d[17]), "+f"(d[18]), "+f"(d[19]), "+f"(d[20]), "+f"(d[21]), "+f"(d[22]), "+f"(d[23]), "+f"(d[24]), "+f"(d[25]), "+f"(d[26]), "+f"(d[27]), "+f"(d[28]), "+f"(d[29]), "+f"(d[30]), "+f"(d[31])
        : "l"(da), "l"(db), "r"(sc), "n"(TB));
}
template <int TB> __device__ __forceinline__ void wgmma_ss_n128(float (&d)[64], uint64_t da, uint64_t db, int sc) {
    asm volatile("{\n.reg .pred p;\nsetp.ne.b32 p, %66, 0;\n"
        "wgmma.mma_async.sync.aligned.m64n128k16.f32.bf16.bf16 {%0, %1, %2, %3, %4, %5, %6, %7, %8, %9, %10, %11, %12, %13, %14, %15, %16, %17, %18, %19, %20, %21, %22, %23, %24, %25, %26, %27, %28, %29, %30, %31, %32, %33, %34, %35, %36, %37, %38, %39, %40, %41, %42, %43, %44, %45, %46, %47, %48, %49, %50, %51, %52, %53, %54, %55, %56, %57, %58, %59, %60, %61, %62, %63}, %64, %65, p, 1, 1, 0, %67;\n}\n"
        : "+f"(d[0]), "+f"(d[1]), "+f"(d[2]), "+f"(d[3]), "+f"(d[4]), "+f"(d[5]), "+f"(d[6]), "+f"(d[7]), "+f"(d[8]), "+f"(d[9]), "+f"(d[10]), "+f"(d[11]), "+f"(d[12]), "+f"(d[13]), "+f"(d[14]), "+f"(d[15]), "+f"(d[16]), "+f"(d[17]), "+f"(d[18]), "+f"(d[19]), "+f"(d[20]), "+f"(d[21]), "+f"(d[22]), "+f"(d[23]), "+f"(d[24]), "+f"(d[25]), "+f"(d[26]), "+f"(d[27]), "+f"(d[28]), "+f"(d[29]), "+f"(d[30]), "+f"(d[31]), "+f"(d[32]), "+f"(d[33]), "+f"(d[34]), "+f"(d[35]), "+f"(d[36]), "+f"(d[37]), "+f"(d[38]), "+f"(d[39]), "+f"(d[40]), "+f"(d[41]), "+f"(d[42]), "+f"(d[43]), "+f"(d[44]), "+f"(d[45]), "+f"(d[46]), "+f"(d[47]), "+f"(d[48]), "+f"(d[49]), "+f"(d[50]), "+f"(d[51]), "+f"(d[52]), "+f"(d[53]), "+f"(d[54]), "+f"(d[55]), "+f"(d[56]), "+f"(d[57]), "+f"(d[58]), "+f"(d[59]), "+f"(d[60]), "+f"(d[61]), "+f"(d[62]), "+f"(d[63])
        : "l"(da), "l"(db), "r"(sc), "n"(TB));
}
template <int TB> __device__ __forceinline__ void wgmma_rs_n24(float (&d)[12], uint32_t a0, uint32_t a1, uint32_t a2, uint32_t a3, uint64_t db, int sc) {
    asm volatile("{\n.reg .pred p;\nsetp.ne.b32 p, %17, 0;\n"
        "wgmma.mma_async.sync.aligned.m64n24k16.f32.bf16.bf16 {%0, %1, %2, %3, %4, %5, %6, %7, %8, %9, %10, %11}, {%12, %13, %14, %15}, %16, p, 1, 1, %18;\n}\n"
        : "+f"(d[0]), "+f"(d[1]), "+f"(d[2]), "+f"(d[3]), "+f"(d[4]), "+f"(d[5]), "+f"(d[6]), "+f"(d[7]), "+f"(d[8]), "+f"(d[9]), "+f"(d[10]), "+f"(d[11])
        : "r"(a0), "r"(a1), "r"(a2), "r"(a3), "l"(db), "r"(sc), "n"(TB));
}
template <int TB> __device__ __forceinline__ void wgmma_rs_n64(float (&d)[32], uint32_t a0, uint32_t a1, uint32_t a2, uint32_t a3, uint64_t db, int sc) {
    asm volatile("{\n.reg .pred p;\nsetp.ne.b32 p, %37, 0;\n"
        "wgmma.mma_async.sync.aligned.m64n64k16.f32.bf16.bf16 {%0, %1, %2, %3, %4, %5, %6, %7, %8, %9, %10, %11, %12, %13, %14, %15, %16, %17, %18, %19, %20, %21, %22, %23, %24, %25, %26, %27, %28, %29, %30, %31}, {%32, %33, %34, %35}, %36, p, 1, 1, %38;\n}\n"
        : "+f"(d[0]), "+f"(d[1]), "+f"(d[2]), "+f"(d[3]), "+f"(d[4]), "+f"(d[5]), "+f"(d[6]), "+f"(d[7]), "+f"(d[8]), "+f"(d[9]), "+f"(d[10]), "+f"(d[11]), "+f"(d[12]), "+f"(d[13]), "+f"(d[14]), "+f"(d[15]), "+f"(d[16]), "+f"(d[17]), "+f"(d[18]), "+f"(d[19]), "+f"(d[20]), "+f"(d[21]), "+f"(d[22]), "+f"(d[23]), "+f"(d[24]), "+f"(d[25]), "+f"(d[26]), "+f"(d[27]), "+f"(d[28]), "+f"(d[29]), "+f"(d[30]), "+f"(d[31])
        : "r"(a0), "r"(a1), "r"(a2), "r"(a3), "l"(db), "r"(sc), "n"(TB));
}
template <int TB, int OFF> __device__ __forceinline__ void wgmma_rs_n32_of32(float (&d)[32], uint32_t a0, uint32_t a1, uint32_t a2, uint32_t a3, uint64_t db, int sc) {
    asm volatile("{\n.reg .pred p;\nsetp.ne.b32 p, %21, 0;\n"
        "wgmma.mma_async.sync.aligned.m64n32k16.f32.bf16.bf16 {%0, %1, %2, %3, %4, %5, %6, %7, %8, %9, %10, %11, %12, %13, %14, %15}, {%16, %17, %18, %19}, %20, p, 1, 1, %22;\n}\n"
        : "+f"(d[OFF + 0]), "+f"(d[OFF + 1]), "+f"(d[OFF + 2]), "+f"(d[OFF + 3]), "+f"(d[OFF + 4]), "+f"(d[OFF + 5]), "+f"(d[OFF + 6]), "+f"(d[OFF + 7]), "+f"(d[OFF + 8]), "+f"(d[OFF + 9]), "+f"(d[OFF + 10]), "+f"(d[OFF + 11]), "+f"(d[OFF + 12]), "+f"(d[OFF + 13]), "+f"(d[OFF + 14]), "+f"(d[OFF + 15])
        : "r"(a0), "r"(a1), "r"(a2), "r"(a3), "l"(db), "r"(sc), "n"(TB));
}

constexpr int P_NST = 6;
constexpr int P_A_BYTES = 9 * 8192;
constexpr int P_B_STAGE = 3 * 8192;

template <int NB>
__device__ __forceinline__ void stage_tile(const uint32_t (&pk)[NB * 2], uint32_t base, int w, int lane) {
    const int r = w * 16 + (lane & 7) + ((lane >> 3) & 1) * 8;
#pragma unroll
    for (int b = 0; b < NB; b += 2) {
        const uint32_t a = base + (b >> 3) * 8192 + r * 128 + ((((b & 7) + (lane >> 4)) ^ (r & 7)) << 4);
        stmatrix_x4(a, pk[2 * b], pk[2 * b + 1], pk[2 * b + 2], pk[2 * b + 3]);
    }
}

__device__ __forceinline__ uint32_t hsub2_bf16(uint32_t a, uint32_t b) { uint32_t r; asm("sub.rn.bf16x2 %0, %1, %2;" : "=r"(r) : "r"(a), "r"(b)); return r; }

constexpr int KV_RAW = DM * 18 * 2;
constexpr int Q_THREADS = 416;

__device__ __forceinline__ void proj_mma(float (&acc)[32], int wg, uint32_t fullB, uint32_t emptyB, uint32_t fullA, bool wait_a, int lane) {
    const uint64_t dA = cdesc(0, 16, 1024, 1), dB = cdesc(P_A_BYTES, 8192, 1024, 1) + wg * 512;
#pragma unroll 1
    for (int kb = 0; kb < 9; kb++) {
        const int s = kb >= P_NST ? kb - P_NST : kb;
        if (wait_a) mbar_wait(fullA + kb * 8, 0);
        mbar_wait(fullB + s * 8, kb >= P_NST ? 1 : 0);
        wg_fence();
#pragma unroll
        for (int ks = 0; ks < 4; ks++) wgmma_ss_n64<1>(acc, dA + (kb * 512 + ks * 2), dB + (s * (P_B_STAGE >> 4) + ks * 128), (kb | ks) != 0);
        wg_commit();
        if (kb < 4) {
            wg_wait<1>();
            if (kb >= 1 && lane == 0) mbar_arrive(emptyB + (kb - 1) * 8);
        }
    }
    wg_wait<0>();
    pin(acc);
}

constexpr int Q_SLOT = 9 * 8192, Q_THIRD = 3 * 8192;
constexpr int Q_OFF_STG = P_A_BYTES + 2 * Q_SLOT;
constexpr int Q_OFF_BAR = Q_OFF_STG + 8192;
constexpr int Q_SMEM = Q_OFF_BAR + 256 + 256;

__global__ void __launch_bounds__(Q_THREADS, 1)
k_qkv(const __grid_constant__ CUtensorMap tmWq, const __grid_constant__ CUtensorMap tmQ, const __nv_bfloat16* __restrict__ x, const __nv_bfloat16* __restrict__ wk, const __nv_bfloat16* __restrict__ wv) {
    extern __shared__ __align__(1024) uint8_t smem[];
    const uint32_t sA = smem_u32(smem), sB = sA + P_A_BYTES, bars = sA + Q_OFF_BAR;
    const uint32_t fullB = bars, free0 = bars + 80, fullX = bars + 128, fullW = bars + 136;
    float* s_rstd = reinterpret_cast<float*>(smem + Q_OFF_BAR + 256);
    const int tid = threadIdx.x, warp = __shfl_sync(~0u, tid >> 5, 0), lane = tid & 31;
    const bool isQ = blockIdx.x < 96;
    const int m = isQ ? blockIdx.x / 3 : blockIdx.x - 96, cg = blockIdx.x % 3;
    if (warp == 12) {
        if (elect_one()) {
            mbar_init(fullX, 1);
            bar_init_fence();
            mbar_expect(fullX, P_A_BYTES);
            bulk_g2s(sA, x + (size_t)m * 64 * DM, P_A_BYTES, fullX);
            prefetch_map(&tmWq); prefetch_map(&tmQ);
            for (int i = 0; i < 9; i++) mbar_init(fullB + i * 8, 1);
            for (int i = 0; i < 3; i++) mbar_init(free0 + i * 8, 4);
            mbar_init(fullW, 1);
            bar_init_fence();
            if (isQ) {
                for (int i = 0; i < 6; i++) {
                    mbar_expect(fullB + i * 8, Q_THIRD);
                    tma_2d(sB + i * Q_THIRD, &tmWq, cg * 192 + (i / 3) * 64, (i % 3) * 192, fullB + i * 8);
                }
                for (int i = 0; i < 3; i++)
                    asm volatile("cp.async.bulk.prefetch.tensor.2d.L2.global [%0, {%1, %2}];" ::"l"(&tmWq), "r"(cg * 192 + 128), "r"(i * 192) : "memory");
            } else {
                mbar_expect(fullW, 2 * KV_RAW);
                bulk_g2s(sB + Q_SLOT, wk, KV_RAW, fullW);
                bulk_g2s(sB + Q_SLOT + KV_RAW, wv, KV_RAW, fullW);
            }
        }
        __syncwarp();
    }
    check_smem_base(sA);
    __syncthreads();
    pdl_launch();
    if (warp == 12) {
        if (isQ && elect_one()) {
            for (int i = 0; i < 3; i++) {
                mbar_wait(free0 + i * 8, 0);
                mbar_expect(fullB + (6 + i) * 8, Q_THIRD);
                tma_2d(sB + i * Q_THIRD, &tmWq, cg * 192 + 128, i * 192, fullB + (6 + i) * 8);
            }
        }
        return;
    }
    if (warp < 8) {
        const int row = tid >> 2, q = tid & 3, h0 = (row & 1) * 4;
        mbar_wait(fullX, 0);
        uint4 v[18];
        const uint32_t ra = sA + row * 1152 + (q + h0) * 16, rb = sA + row * 1152 + (q + 4 - h0) * 16;
#pragma unroll
        for (int kb = 0; kb < 9; kb++) {
            asm volatile("ld.shared.v4.b32 {%0, %1, %2, %3}, [%4];" : "=r"(v[2 * kb].x), "=r"(v[2 * kb].y), "=r"(v[2 * kb].z), "=r"(v[2 * kb].w) : "r"(ra + kb * 128));
            asm volatile("ld.shared.v4.b32 {%0, %1, %2, %3}, [%4];" : "=r"(v[2 * kb + 1].x), "=r"(v[2 * kb + 1].y), "=r"(v[2 * kb + 1].z), "=r"(v[2 * kb + 1].w) : "r"(rb + kb * 128));
        }
        float sum = 0.f, sum2 = 0.f, sq = 0.f, sq2 = 0.f;
#pragma unroll
        for (int i = 0; i < 18; i++) {
            const uint32_t w[4] = {v[i].x, v[i].y, v[i].z, v[i].w};
#pragma unroll
            for (int j = 0; j < 4; j++) { const float a = bf_lo(w[j]), b = bf_hi(w[j]); sum += a; sum2 += b; sq = fmaf(a, a, sq); sq2 = fmaf(b, b, sq2); }
        }
        named_sync(1, 256);
        sum += sum2; sq += sq2;
        sum += __shfl_xor_sync(~0u, sum, 1); sum += __shfl_xor_sync(~0u, sum, 2);
        sq += __shfl_xor_sync(~0u, sq, 1); sq += __shfl_xor_sync(~0u, sq, 2);
        const float mean = sum * (1.0f / DM);
        if (q == 0) s_rstd[row] = rsqrtf(fmaxf(sq * (1.0f / DM) - mean * mean, 0.f) + LN_EPS);
        const uint32_t mhi = pack_bf16(mean, mean);
        const float rem = mean - bf_lo(mhi);
        const uint32_t mlo = pack_bf16(rem, rem);
        const uint32_t wa = sA + row * 128 + (((q + h0) ^ (row & 7)) << 4), wb = sA + row * 128 + (((q + 4 - h0) ^ (row & 7)) << 4);
#pragma unroll
        for (int i = 0; i < 18; i++) {
            const uint32_t o0 = hsub2_bf16(hsub2_bf16(v[i].x, mhi), mlo), o1 = hsub2_bf16(hsub2_bf16(v[i].y, mhi), mlo);
            const uint32_t o2 = hsub2_bf16(hsub2_bf16(v[i].z, mhi), mlo), o3 = hsub2_bf16(hsub2_bf16(v[i].w, mhi), mlo);
            asm volatile("st.shared.v4.b32 [%0], {%1, %2, %3, %4};" ::"r"(((i & 1) ? wb : wa) + (i >> 1) * 8192), "r"(o0), "r"(o1), "r"(o2), "r"(o3) : "memory");
        }
    } else if (!isQ) {
        mbar_wait(fullW, 0);
        const uint32_t* raw = reinterpret_cast<const uint32_t*>(smem + P_A_BYTES + Q_SLOT);
#pragma unroll 3
        for (int r = tid - 256; r < 2 * DM; r += 128) {
            uint32_t wr[9];
#pragma unroll
            for (int i = 0; i < 9; i++) wr[i] = raw[r * 9 + i];
            const int sel = r >= DM, k = r - sel * DM;
            uint8_t* dst = smem + P_A_BYTES + sel * 3 * 9216 + (k >> 3) * 128 + (k & 7) * 16;
            *reinterpret_cast<uint4*>(dst) = make_uint4(wr[0], wr[1], wr[2], wr[3]);
            *reinterpret_cast<uint4*>(dst + 9216) = make_uint4(wr[4], wr[5], wr[6], wr[7]);
            *reinterpret_cast<uint32_t*>(dst + 2 * 9216) = wr[8];
        }
    }
    proxy_fence();
    named_sync(2, 384);
    const int wg = warp >> 2, w = warp & 3, g = lane >> 2, t = lane & 3;
    const float rs0 = s_rstd[w * 16 + g], rs1 = s_rstd[w * 16 + g + 8];
    if (isQ) {
        const float c0 = rs0 * Q_SCALE, c1 = rs1 * Q_SCALE;
        float acc[32];
        const uint64_t dA = cdesc(0, 16, 1024, 1), dB = cdesc(P_A_BYTES, 8192, 1024, 1) + (wg == 1 ? (Q_SLOT >> 4) : 0);
        if (wg > 0) named_sync(6 + wg, 256);
#pragma unroll 1
        for (int i = 0; i < 3; i++) {
            mbar_wait(fullB + (wg * 3 + i) * 8, 0);
            wg_fence();
#pragma unroll
            for (int ks = 0; ks < 12; ks++)
                wgmma_ss_n64<1>(acc, dA + ((i * 3 + (ks >> 2)) * 512 + (ks & 3) * 2), dB + (i * (Q_THIRD >> 4) + ks * 128), (i | ks) != 0);
            wg_commit();
            if (wg == 0 && i > 0) { wg_wait<1>(); if (lane == 0) mbar_arrive(free0 + (i - 1) * 8); }
        }
        if (wg < 2) asm volatile("bar.arrive %0, 256;" ::"r"(7 + wg) : "memory");
        wg_wait<0>();
        pin(acc);
        if (wg == 0 && lane == 0) mbar_arrive(free0 + 16);
        uint32_t pk[16];
#pragma unroll
        for (int i = 0; i < 8; i++) { pk[2 * i] = pack_bf16(acc[4 * i] * c0, acc[4 * i + 1] * c0); pk[2 * i + 1] = pack_bf16(acc[4 * i + 2] * c1, acc[4 * i + 3] * c1); }
        const uint32_t stg = wg == 0 ? sA + Q_OFF_STG : (wg == 1 ? sB + Q_SLOT : sB);
        stage_tile<8>(pk, stg, w, lane);
        proxy_fence();
        named_sync(3 + wg, 128);
        if (w == 0 && elect_one()) {
            tma_st_2d(&tmQ, cg * 192 + wg * 64, m * 64, stg);
            bulk_commit();
            bulk_wait_all();
        }
    } else if (wg < 2) {
        float acc[12];
        const uint64_t dA = cdesc(0, 16, 1024, 1), dB = cdesc(P_A_BYTES, 128, 9216, 0) + wg * (3 * 9216 >> 4);
#pragma unroll
        for (int i = 0; i < 12; i++) acc[i] = 0.f;
        pin(acc);
        wg_fence();
#pragma unroll 1
        for (int kb = 0; kb < 9; kb++) {
#pragma unroll
            for (int ks = 0; ks < 4; ks++) wgmma_ss_n24<1>(acc, dA + (kb * 512 + ks * 2), dB + (kb * 4 + ks) * 16, 1);
        }
        wg_commit();
        wg_wait<0>();
        pin(acc);
        uint32_t pk[6];
#pragma unroll
        for (int b = 0; b < 3; b++) { pk[2 * b] = pack_bf16(acc[4 * b] * rs0, acc[4 * b + 1] * rs0); pk[2 * b + 1] = pack_bf16(acc[4 * b + 2] * rs1, acc[4 * b + 3] * rs1); }
        float n0 = 0.f, n1 = 0.f, vm = 0.f;
#pragma unroll
        for (int b = 0; b < 3; b++) {
            if (b < 2 || t == 0) {
                const float a = bf_lo(pk[2 * b]), c = bf_hi(pk[2 * b]), d = bf_lo(pk[2 * b + 1]), e = bf_hi(pk[2 * b + 1]);
                n0 = fmaf(a, a, fmaf(c, c, n0)); n1 = fmaf(d, d, fmaf(e, e, n1));
            }
        }
        n0 += __shfl_xor_sync(~0u, n0, 1); n0 += __shfl_xor_sync(~0u, n0, 2);
        n1 += __shfl_xor_sync(~0u, n1, 1); n1 += __shfl_xor_sync(~0u, n1, 2);
        vm = fmaxf(n0, n1);
        if (!(n0 == n0) || !(n1 == n1)) vm = __int_as_float(0x7F800000);
#pragma unroll
        for (int o = 4; o < 32; o <<= 1) vm = fmaxf(vm, __shfl_xor_sync(~0u, vm, o));
        if (t != 0) {
            uint32_t lo, hi;
            if (wg == 0) {
                const int grp = m * 8 + w * 2;
                const uint32_t c = t == 1 ? 0x42FE3F80u   : (t == 2 ? 0x00003BC0u   : 0u);
                lo = ((POLY_MASK >> (grp & 15)) & 1) ? c : 0u;
                hi = ((POLY_MASK >> ((grp + 1) & 15)) & 1) ? c : 0u;
            } else {
                lo = hi = t == 1 ? 0x00003F80u : 0u;
            }
            pk[4] = lo; pk[5] = hi;
        }
        uint32_t* dst = reinterpret_cast<uint32_t*>(wg == 0 ? g_kc : g_vc) + (m * 8 + w * 2) * 96 + g * 4 + t;
#pragma unroll
        for (int b = 0; b < 3; b++) { dst[b * 32] = pk[2 * b]; dst[96 + b * 32] = pk[2 * b + 1]; }
        if (lane == 0) g_kmax[m * 8 + warp] = (wg == 0) ? vm : (vm <= FAST_VMAX2 ? 0.f : __int_as_float(0x7F800000));
    }
}

constexpr int A_THREADS = 512;
constexpr int A_NPIECE = 8;
constexpr int A_OFF_Q = 2 * KV_BYTES;
constexpr int A_OFF_BAR = A_OFF_Q + 8 * 4096;
constexpr int A_SMEM = A_OFF_BAR + 128;

__device__ __forceinline__ uint32_t exp2_pair_fixed(float lo, float hi, uint32_t dep) {
    const uint32_t G = __byte_perm(__float_as_uint(lo), __float_as_uint(hi), 0x5410);
    uint32_t Hh;
    asm("lop3.b32 %0, %1, 0x007F007F, %2, 0xC0;" : "=r"(Hh) : "r"(G), "r"(dep));
    const uint32_t tt = hfma2(Hh, 0xF96BF96Bu, 0x358C358Cu);
    return G - hfma2(tt, Hh, 0u);
}

__global__ void __launch_bounds__(A_THREADS, 1)
k_attn(__nv_bfloat16* __restrict__ out) {
    extern __shared__ __align__(1024) uint8_t smem[];
    pdl_launch();
    const uint32_t sK = smem_u32(smem), sV = sK + KV_BYTES, bars = sK + A_OFF_BAR;
    const int tid = threadIdx.x;
    check_smem_base(sK);
    if (tid == 0) {
        for (int i = 0; i < A_NPIECE; i++) mbar_init(bars + i * 8, 1);
        bar_init_fence();
    }
    __syncthreads();
    pdl_wait();
    const int wg = __shfl_sync(~0u, tid >> 7, 0), w = (tid >> 5) & 3, lane = tid & 31, g = lane >> 2, t = lane & 3;
    const uint32_t* q32 = reinterpret_cast<const uint32_t*>(g_q);
    int row = (blockIdx.x * 8 + wg) * 64 + w * 16 + g;
    uint32_t nq[2][6];
#pragma unroll
    for (int r = 0; r < 2; r++) {
        const uint32_t* q = q32 + (row + r * 256) * 9;
        nq[r][0] = q[t]; nq[r][1] = q[72 + t]; nq[r][2] = q[4 + t]; nq[r][3] = q[76 + t]; nq[r][4] = q[8]; nq[r][5] = q[80];
    }
    constexpr int PB = KV_BYTES / A_NPIECE;
    const float4 km0 = reinterpret_cast<const float4*>(g_kmax)[lane], km1 = reinterpret_cast<const float4*>(g_kmax)[32 + lane];
    if (tid < 32 && elect_one()) {
        for (int i = 0; i < 2; i++) {
            mbar_expect(bars + i * 8, 2 * PB);
            bulk_g2s(sK + i * PB, reinterpret_cast<const char*>(g_kc) + i * PB, PB, bars + i * 8);
            bulk_g2s(sV + i * PB, reinterpret_cast<const char*>(g_vc) + i * PB, PB, bars + i * 8);
        }
    }
    float kmax2 = fmaxf(fmaxf(fmaxf(km0.x, km0.y), fmaxf(km0.z, km0.w)), fmaxf(fmaxf(km1.x, km1.y), fmaxf(km1.z, km1.w)));
#pragma unroll
    for (int o = 1; o < 32; o <<= 1) kmax2 = fmaxf(kmax2, __shfl_xor_sync(~0u, kmax2, o));
    if (tid < 32 && elect_one()) {
        for (int i = 2; i < A_NPIECE; i++) {
            mbar_expect(bars + i * 8, 2 * PB);
            bulk_g2s(sK + i * PB, reinterpret_cast<const char*>(g_kc) + i * PB, PB, bars + i * 8);
            bulk_g2s(sV + i * PB, reinterpret_cast<const char*>(g_vc) + i * PB, PB, bars + i * 8);
        }
    }
    uint32_t vote = 0;
#pragma unroll
    for (int r = 0; r < 2; r++) {
        const uint32_t (&q)[6] = nq[r];
        const float a0 = bf_lo(q[0]), a1 = bf_hi(q[0]), a2 = bf_lo(q[2]), a3 = bf_hi(q[2]);
        const float b0 = bf_lo(q[1]), b1 = bf_hi(q[1]), b2 = bf_lo(q[3]), b3 = bf_hi(q[3]);
        float n0 = a0 * a0 + a1 * a1 + a2 * a2 + a3 * a3, n1 = b0 * b0 + b1 * b1 + b2 * b2 + b3 * b3;
        if (t == 0) {
            const float c0 = bf_lo(q[4]), c1 = bf_hi(q[4]), d0 = bf_lo(q[5]), d1 = bf_hi(q[5]);
            n0 += c0 * c0 + c1 * c1; n1 += d0 * d0 + d1 * d1;
        }
        n0 += __shfl_xor_sync(~0u, n0, 1); n0 += __shfl_xor_sync(~0u, n0, 2);
        n1 += __shfl_xor_sync(~0u, n1, 1); n1 += __shfl_xor_sync(~0u, n1, 2);
        const bool unsafe = !(fmaxf(n0, n1) * kmax2 <= FAST_BOUND * FAST_BOUND) || !(n0 == n0) || !(n1 == n1);
        vote |= (__any_sync(~0u, unsafe) ? 1u : 0u) << r;
        const uint32_t cst = t == 1 ? 0x3F804780u : (t == 2 ? 0x00003F80u : 0u);
        const uint32_t sQ = sK + A_OFF_Q + (r * 4 + wg) * 4096 + (w * 2) * 512 + g * 16 + t * 4;
        asm volatile("st.shared.b32 [%0], %1;" ::"r"(sQ), "r"(q[0]) : "memory");
        asm volatile("st.shared.b32 [%0], %1;" ::"r"(sQ + 512), "r"(q[1]) : "memory");
        asm volatile("st.shared.b32 [%0], %1;" ::"r"(sQ + 128), "r"(q[2]) : "memory");
        asm volatile("st.shared.b32 [%0], %1;" ::"r"(sQ + 640), "r"(q[3]) : "memory");
        asm volatile("st.shared.b32 [%0], %1;" ::"r"(sQ + 256), "r"(t == 0 ? q[4] : cst) : "memory");
        asm volatile("st.shared.b32 [%0], %1;" ::"r"(sQ + 768), "r"(t == 0 ? q[5] : cst) : "memory");
        asm volatile("st.shared.b32 [%0], %1;" ::"r"(sQ + 384), "r"(0u) : "memory");
        asm volatile("st.shared.b32 [%0], %1;" ::"r"(sQ + 896), "r"(0u) : "memory");
    }
    const uint32_t sVote = bars + 64 + wg * 16;
    if (lane == 0) asm volatile("st.shared.b32 [%0], %1;" ::"r"(sVote + w * 4), "r"(vote) : "memory");
    proxy_fence();
    named_sync(wg + 1, 128);
    uint32_t unsafe_mask;
    {
        uint32_t v0, v1, v2, v3;
        asm volatile("ld.shared.v4.b32 {%0, %1, %2, %3}, [%4];" : "=r"(v0), "=r"(v1), "=r"(v2), "=r"(v3) : "r"(sVote));
        unsafe_mask = __shfl_sync(~0u, v0 | v1 | v2 | v3, 0);
    }
    if (unsafe_mask) {
#pragma unroll
        for (int r = 0; r < 2; r++) {
            if (((unsafe_mask >> r) & 1) && t != 0) {
                const uint32_t sQ = sK + A_OFF_Q + (r * 4 + wg) * 4096 + (w * 2) * 512 + g * 16 + t * 4;
                asm volatile("st.shared.b32 [%0], %1;" ::"r"(sQ + 256), "r"(0u) : "memory");
                asm volatile("st.shared.b32 [%0], %1;" ::"r"(sQ + 768), "r"(0u) : "memory");
            }
        }
        proxy_fence();
        named_sync(wg + 1, 128);
    }
#pragma unroll 1
    for (int rep = 0; rep < 2; rep++, row += 256) {
        if (rep == 1) {
            uint4* z = reinterpret_cast<uint4*>(out + (size_t)blockIdx.x * 16 * DM) + tid;
            z[0] = make_uint4(0u, 0u, 0u, 0u); z[A_THREADS] = make_uint4(0u, 0u, 0u, 0u);
            if (tid < 16 * DM * 2 / 16 - 2 * A_THREADS) z[2 * A_THREADS] = make_uint4(0u, 0u, 0u, 0u);
        }
        const uint32_t any_unsafe = (unsafe_mask >> rep) & 1;
        const uint64_t dQ0 = cdesc(A_OFF_Q, 128, 512, 0) + (rep * 4 + wg) * 256, dQ1 = dQ0 + 16;
        float o[12];
#pragma unroll
        for (int i = 0; i < 12; i++) o[i] = 0.f;
        pin(o);
        uint64_t dK0 = cdesc(0, 128, 384, 0), dK1 = cdesc(256, 0, 384, 0), dV = cdesc(KV_BYTES, 384, 128, 0);
        if (!any_unsafe) {
            float s[64];
#pragma unroll 1
            for (int j = 0; j < 16; j++) {
                if (rep == 0 && (j & 1) == 0) mbar_wait(bars + (j >> 1) * 8, 0);
                wg_fence();
                wgmma_ss_n128<0>(s, dQ0, dK0, 0);
                wgmma_ss_n128<0>(s, dQ1, dK1, 1);
                wg_commit();
                dK0 += 16 * 384 >> 4; dK1 += 16 * 384 >> 4;
                wg_wait<0>();
                pin(s);
                uint32_t p[32];
                {
                    constexpr int NP = 2 * __builtin_popcount(POLY_MASK), NM = 32 - NP;
                    float e[64];
#pragma unroll
                    for (int i = 0; i < 32; i++)
                        if (!((POLY_MASK >> (i >> 1)) & 1)) { e[2 * i] = ex2(s[2 * i]); e[2 * i + 1] = ex2(s[2 * i + 1]); p[i] = pack_bf16(e[2 * i], e[2 * i + 1]); }
                    int ip = 0;
#pragma unroll
                    for (int i = 0; i < 32; i++) {
                        if ((POLY_MASK >> (i >> 1)) & 1) {
                            const int mm = (ip * 2 * NM) / NP - CHAIN;
                            uint32_t dep = 0;
                            if (CHAIN > 0 && mm >= 0) {
                                int cnt = 0;
#pragma unroll
                                for (int q = 0; q < 32; q++)
                                    if (!((POLY_MASK >> (q >> 1)) & 1)) { if (cnt == (mm >> 1)) dep = __float_as_uint(e[2 * q + (mm & 1)]); cnt++; }
                            }
                            p[i] = exp2_pair_fixed(s[2 * i], s[2 * i + 1], dep);
                            ip++;
                        }
                    }
                }
                pin(p);
                wg_fence();
#pragma unroll
                for (int k = 0; k < 8; k++) wgmma_rs_n24<1>(o, p[4 * k], p[4 * k + 1], p[4 * k + 2], p[4 * k + 3], dV + k * 48, 1);
                wg_commit();
                dV += 16 * 384 >> 4;
                wg_wait<0>();
            }
        } else {
            float s[64];
            float m0 = -INFINITY, m1 = -INFINITY;
#pragma unroll 1
            for (int j = 0; j < 16; j++) {
                if (rep == 0 && (j & 1) == 0) mbar_wait(bars + (j >> 1) * 8, 0);
                wg_fence();
                wgmma_ss_n128<0>(s, dQ0, dK0, 0);
                wgmma_ss_n128<0>(s, dQ1, dK1, 1);
                wg_commit();
                dK0 += 16 * 384 >> 4; dK1 += 16 * 384 >> 4;
                wg_wait<0>();
                pin(s);
                float x0m = m0, x1m = m1;
#pragma unroll
                for (int b = 0; b < 16; b++) { x0m = fmaxf(x0m, fmaxf(s[4 * b], s[4 * b + 1])); x1m = fmaxf(x1m, fmaxf(s[4 * b + 2], s[4 * b + 3])); }
                x0m = fmaxf(x0m, __shfl_xor_sync(~0u, x0m, 1)); x0m = fmaxf(x0m, __shfl_xor_sync(~0u, x0m, 2));
                x1m = fmaxf(x1m, __shfl_xor_sync(~0u, x1m, 1)); x1m = fmaxf(x1m, __shfl_xor_sync(~0u, x1m, 2));
                const float c0 = ex2(m0 - x0m), c1 = ex2(m1 - x1m);
                m0 = x0m; m1 = x1m;
#pragma unroll
                for (int b = 0; b < 3; b++) { o[4 * b] *= c0; o[4 * b + 1] *= c0; o[4 * b + 2] *= c1; o[4 * b + 3] *= c1; }
                uint32_t p[32];
#pragma unroll
                for (int b = 0; b < 16; b++) {
                    p[2 * b] = pack_bf16(ex2(s[4 * b] - m0), ex2(s[4 * b + 1] - m0));
                    p[2 * b + 1] = pack_bf16(ex2(s[4 * b + 2] - m1), ex2(s[4 * b + 3] - m1));
                }
                pin(p); pin(o);
                wg_fence();
#pragma unroll
                for (int k = 0; k < 8; k++) wgmma_rs_n24<1>(o, p[4 * k], p[4 * k + 1], p[4 * k + 2], p[4 * k + 3], dV + k * 48, 1);
                wg_commit();
                dV += 16 * 384 >> 4;
                wg_wait<0>();
            }
        }
        pin(o);
        const float l0 = __shfl_sync(~0u, o[8], (lane & ~3) | 1), l1 = __shfl_sync(~0u, o[10], (lane & ~3) | 1);
        const float i0 = 1.0f / l0, i1 = 1.0f / l1;
        uint32_t* o32 = reinterpret_cast<uint32_t*>(g_o);
        o32[row * 9 + t] = pack_bf16(o[0] * i0, o[1] * i0);
        o32[(row + 8) * 9 + t] = pack_bf16(o[2] * i1, o[3] * i1);
        o32[row * 9 + 4 + t] = pack_bf16(o[4] * i0, o[5] * i0);
        o32[(row + 8) * 9 + 4 + t] = pack_bf16(o[6] * i1, o[7] * i1);
        if (t == 0) { o32[row * 9 + 8] = pack_bf16(o[8] * i0, o[9] * i0); o32[(row + 8) * 9 + 8] = pack_bf16(o[10] * i1, o[11] * i1); }
    }
}

constexpr int O_THREADS = 416;
constexpr int O_OFF_STAT = P_A_BYTES + P_NST * P_B_STAGE + 256;
constexpr int O_SMEM = O_OFF_STAT + 9 * 64 * 8;

__global__ void __cluster_dims__(3, 1, 1) __launch_bounds__(O_THREADS, 1)
k_oproj(const __grid_constant__ CUtensorMap tmO, const __grid_constant__ CUtensorMap tmWo, const __grid_constant__ CUtensorMap tmX2, const __grid_constant__ CUtensorMap tmH, const __nv_bfloat16* __restrict__ x, const __nv_bfloat16* __restrict__ w1) {
    extern __shared__ __align__(1024) uint8_t smem[];
    const uint32_t sA = smem_u32(smem), sB = sA + P_A_BYTES, bars = sB + P_NST * P_B_STAGE;
    const uint32_t fullB = bars, emptyB = bars + 64, fullA = bars + 128;
    const int tid = threadIdx.x, warp = __shfl_sync(~0u, tid >> 5, 0), lane = tid & 31;
    const int m = blockIdx.x / 3, cg = blockIdx.x % 3;
    check_smem_base(sA);
    if (tid == 0) {
        prefetch_map(&tmO); prefetch_map(&tmWo); prefetch_map(&tmX2); prefetch_map(&tmH);
        for (int i = 0; i < P_NST; i++) { mbar_init(fullB + i * 8, 1); mbar_init(emptyB + i * 8, 12); }
        for (int i = 0; i < 9; i++) mbar_init(fullA + i * 8, 1);
        bar_init_fence();
        for (int kb = 0; kb < 9; kb++) mbar_expect(fullA + kb * 8, 8192);
    }
    __syncthreads();
    pdl_launch();
    if (warp == 12) {
        if (elect_one()) {
            for (int kb = 0; kb < 9; kb++) {
                const int s = kb >= P_NST ? kb - P_NST : kb;
                if (kb == 2) {
                    pdl_wait();
                    for (int ka = 0; ka < 9; ka++) tma_2d(sA + ka * 8192, &tmO, ka * 64, m * 64, fullA + ka * 8);
                }
                if (kb >= P_NST) mbar_wait(emptyB + s * 8, 0);
                mbar_expect(fullB + s * 8, P_B_STAGE);
                for (int a = 0; a < 3; a++) tma_2d(sB + s * P_B_STAGE + a * 8192, &tmWo, cg * 192 + a * 64, kb * 64, fullB + s * 8);
            }
            for (int i = 0; i < 6; i++) prefetch_l2(reinterpret_cast<const char*>(w1) + (size_t)blockIdx.x * (FF * DM * 2 / 96) + i * 9216, 9216);
        }
        return;
    }
    const int wg = warp >> 2, w = warp & 3, g = lane >> 2, t = lane & 3;
    uint32_t xr[16];
    {
        const uint32_t* x32 = reinterpret_cast<const uint32_t*>(x) + (((m * 64 + w * 16 + g) * DM + cg * 192 + wg * 64 + 2 * t) >> 1);
#pragma unroll
        for (int b = 0; b < 8; b++) { xr[2 * b] = __ldg(x32 + b * 4); xr[2 * b + 1] = __ldg(x32 + b * 4 + 4 * DM); }
    }
    float acc[32];
    proj_mma(acc, wg, fullB, emptyB, fullA, true, lane);
    named_sync(1, 384);
    float s0 = 0.f, q0 = 0.f, s1 = 0.f, q1 = 0.f;
#pragma unroll
    for (int b = 0; b < 8; b++) {
        const uint32_t xa = xr[2 * b], xb = xr[2 * b + 1];
        const uint32_t ha = pack_bf16(acc[4 * b] + bf_lo(xa), acc[4 * b + 1] + bf_hi(xa));
        const uint32_t hb = pack_bf16(acc[4 * b + 2] + bf_lo(xb), acc[4 * b + 3] + bf_hi(xb));
        xr[2 * b] = ha; xr[2 * b + 1] = hb;
        const float a = bf_lo(ha), c = bf_hi(ha), d = bf_lo(hb), e = bf_hi(hb);
        s0 += a + c; q0 = fmaf(a, a, fmaf(c, c, q0));
        s1 += d + e; q1 = fmaf(d, d, fmaf(e, e, q1));
    }
    s0 += __shfl_xor_sync(~0u, s0, 1); s0 += __shfl_xor_sync(~0u, s0, 2);
    q0 += __shfl_xor_sync(~0u, q0, 1); q0 += __shfl_xor_sync(~0u, q0, 2);
    s1 += __shfl_xor_sync(~0u, s1, 1); s1 += __shfl_xor_sync(~0u, s1, 2);
    q1 += __shfl_xor_sync(~0u, q1, 1); q1 += __shfl_xor_sync(~0u, q1, 2);
    const int r = w * 16 + g;
    const uint32_t sStat = sA + O_OFF_STAT;
    if (t < 3) {
        uint32_t dst;
        asm("mapa.shared::cluster.u32 %0, %1, %2;" : "=r"(dst) : "r"(sStat + ((cg * 3 + wg) * 64 + r) * 8), "r"(t));
        asm volatile("st.shared::cluster.v2.f32 [%0], {%1, %2};" ::"r"(dst), "f"(s0), "f"(q0) : "memory");
        asm volatile("st.shared::cluster.v2.f32 [%0], {%1, %2};" ::"r"(dst + 64), "f"(s1), "f"(q1) : "memory");
    }
    cluster_arrive();
    stage_tile<8>(xr, sA + wg * 8192, w, lane);
    proxy_fence();
    named_sync(2 + wg, 128);
    const bool leader = w == 0 && elect_one();
    if (leader) { tma_st_2d(&tmH, cg * 192 + wg * 64, m * 64, sA + wg * 8192); bulk_commit(); }
    cluster_wait();
    s0 = q0 = s1 = q1 = 0.f;
#pragma unroll
    for (int p = 0; p < 9; p++) {
        float a, b, c, d;
        asm volatile("ld.shared.v2.f32 {%0, %1}, [%2];" : "=f"(a), "=f"(b) : "r"(sStat + (p * 64 + r) * 8));
        asm volatile("ld.shared.v2.f32 {%0, %1}, [%2];" : "=f"(c), "=f"(d) : "r"(sStat + (p * 64 + r + 8) * 8));
        s0 += a; q0 += b; s1 += c; q1 += d;
    }
    const float m0 = s0 * (1.0f / DM), m1 = s1 * (1.0f / DM);
    const float rs0 = rsqrtf(fmaxf(q0 * (1.0f / DM) - m0 * m0, 0.f) + LN_EPS), rs1 = rsqrtf(fmaxf(q1 * (1.0f / DM) - m1 * m1, 0.f) + LN_EPS);
    const float sc0 = 0.5f * rs0, sc1 = 0.5f * rs1, n0 = -m0 * sc0, n1 = -m1 * sc1;
#pragma unroll
    for (int b = 0; b < 8; b++) {
        xr[2 * b] = pack_bf16(fmaf(bf_lo(xr[2 * b]), sc0, n0), fmaf(bf_hi(xr[2 * b]), sc0, n0));
        xr[2 * b + 1] = pack_bf16(fmaf(bf_lo(xr[2 * b + 1]), sc1, n1), fmaf(bf_hi(xr[2 * b + 1]), sc1, n1));
    }
    stage_tile<8>(xr, sA + (3 + wg) * 8192, w, lane);
    proxy_fence();
    named_sync(2 + wg, 128);
    if (leader) {
        tma_st_2d(&tmX2, cg * 192 + wg * 64, m * 64, sA + (3 + wg) * 8192);
        bulk_commit();
        bulk_wait_all();
    }
}

constexpr int F_THREADS = 384;
constexpr int F_NST = 6;
constexpr int F_STAGE = 96 * 128;
constexpr int F_X_BYTES = 9 * 16384;
constexpr int F_OFF_ST = F_X_BYTES;
constexpr int F_OFF_BAR = F_OFF_ST + F_NST * F_STAGE;
constexpr int F_SMEM = F_OFF_BAR + 256;

__device__ __forceinline__ float tanh_hw(float x) { float y; asm("tanh.approx.f32 %0, %1;" : "=f"(y) : "f"(x)); return y; }
__host__ __device__ constexpr int piece_begin(int p) { return p == 0 ? 0 : 3 * p + 1; }
template <int P>
__device__ __forceinline__ void silu_s1(const float (&acc)[32], float (&tmp)[8]) {
#pragma unroll
    for (int i = 2 * piece_begin(P); i < 2 * piece_begin(P + 1); i++) tmp[i - 2 * piece_begin(P)] = tanh_hw(acc[i]);
}
template <int C, int P>
__device__ __forceinline__ void silu_s2(const float (&acc)[32], const float (&tmp)[8], uint32_t (&h1)[144]) {
#pragma unroll
    for (int i = piece_begin(P); i < piece_begin(P + 1); i++) {
        const int k = 2 * (i - piece_begin(P));
        h1[C * 16 + i] = pack_bf16(fmaf(acc[2 * i], tmp[k], acc[2 * i]), fmaf(acc[2 * i + 1], tmp[k + 1], acc[2 * i + 1]));
    }
}
template <int J>
__device__ __forceinline__ void silu_slot_last(const float (&prev)[32], float (&tmp)[2][8], uint32_t (&h1)[144]) {
    if constexpr (J >= 1 && J <= 4) {
#pragma unroll
        for (int i = 0; i < 4; i++) {
            const int q = 4 * (J - 1) + i;
            h1[128 + q] = pack_bf16(fmaf(prev[2 * q], tmp[(J - 1) & 1][2 * i], prev[2 * q]), fmaf(prev[2 * q + 1], tmp[(J - 1) & 1][2 * i + 1], prev[2 * q + 1]));
        }
    }
    if constexpr (J <= 3) {
#pragma unroll
        for (int i = 0; i < 8; i++) tmp[J & 1][i] = tanh_hw(prev[8 * J + i]);
        pin(tmp[J & 1]);
    }
}
template <int C, int J>
__device__ __forceinline__ void silu_slot(const float (&prev)[32], float (&tmp)[2][8], uint32_t (&h1)[144]) {
    if constexpr (J >= 1) silu_s2<C, J - 1>(prev, tmp[(J - 1) & 1], h1);
    if constexpr (J <= 4) { silu_s1<J>(prev, tmp[J & 1]); pin(tmp[J & 1]); }
}

struct FfnPipe {
    uint32_t full, empty;
    int lane;
    __device__ __forceinline__ void acquire(int s, uint32_t ph) const { mbar_wait(full + s * 8, ph); }
    __device__ __forceinline__ void release(int s) const { if (lane == 0) mbar_arrive(empty + s * 8); }
};

template <int C>
__device__ __forceinline__ void ffn_phase1_chunk(float (&cur)[32], float (&prev)[32], uint32_t (&h1)[144], const FfnPipe& pp, uint64_t dx, uint32_t fullX) {
    float tmp[2][8];
    const uint64_t dw = cdesc(F_OFF_ST, 8192, 1024, 1) + blockIdx.y * (C + 1);
    dx += blockIdx.y * C;
#pragma unroll
    for (int j = 0; j < 6; j++) {
        if (C == 0) { mbar_wait(fullX + ((6 * j) >> 2) * 8, 0); mbar_wait(fullX + ((6 * j + 5) >> 2) * 8, 0); }
        pp.acquire(j, C & 1);
        if (j == 0) pin(cur);
        wg_fence();
#pragma unroll
        for (int i = 0; i < 6; i++) {
            const int ks = 6 * j + i;
            wgmma_ss_n64<1>(cur, dx + ((ks >> 2) * 1024 + (ks & 3) * 2), dw + ((j * F_STAGE + i * 2048) >> 4), ks != 0);
        }
        wg_commit();
        if (C > 0 || j > 0) { wg_wait<1>(); pp.release((j + 5) % 6); }
        if (C > 0) {
            constexpr int CP = C > 0 ? C - 1 : 0;
            pin(prev);
            if (j == 0) silu_slot<CP, 0>(prev, tmp, h1);
            if (j == 1) silu_slot<CP, 1>(prev, tmp, h1);
            if (j == 2) silu_slot<CP, 2>(prev, tmp, h1);
            if (j == 3) silu_slot<CP, 3>(prev, tmp, h1);
            if (j == 4) silu_slot<CP, 4>(prev, tmp, h1);
            if (j == 5) silu_slot<CP, 5>(prev, tmp, h1);
        }
    }
}

__device__ __forceinline__ void ffn_stage_chunk(const float (&acc)[32], uint32_t stg, int w, int lane, bool resid, uint32_t fullH) {
    uint32_t pk[16];
    if (resid) {
        mbar_wait(fullH, 0);
        const int r = w * 16 + (lane & 7) + ((lane >> 3) & 1) * 8;
#pragma unroll
        for (int b = 0; b < 8; b += 2) {
            uint32_t h0, h1, h2, h3;
            asm volatile("ldmatrix.sync.aligned.m8n8.x4.shared.b16 {%0, %1, %2, %3}, [%4];" : "=r"(h0), "=r"(h1), "=r"(h2), "=r"(h3) : "r"(stg + r * 128 + (((b + (lane >> 4)) ^ (r & 7)) << 4)) : "memory");
            pk[2 * b] = pack_bf16(acc[4 * b] + bf_lo(h0), acc[4 * b + 1] + bf_hi(h0));
            pk[2 * b + 1] = pack_bf16(acc[4 * b + 2] + bf_lo(h1), acc[4 * b + 3] + bf_hi(h1));
            pk[2 * b + 2] = pack_bf16(acc[4 * b + 4] + bf_lo(h2), acc[4 * b + 5] + bf_hi(h2));
            pk[2 * b + 3] = pack_bf16(acc[4 * b + 6] + bf_lo(h3), acc[4 * b + 7] + bf_hi(h3));
        }
    } else {
#pragma unroll
        for (int i = 0; i < 16; i++) pk[i] = pack_bf16(acc[2 * i], acc[2 * i + 1]);
    }
    stage_tile<8>(pk, stg, w, lane);
}
__device__ __forceinline__ void ffn_reduce_chunk(const CUtensorMap* tmOut, uint32_t stg, int col, int row, int w, int wgid, bool leader) {
    proxy_fence();
    if (w != 0) {
        asm volatile("bar.arrive %0, 128;" ::"r"(2 + wgid) : "memory");
    } else {
        named_sync(2 + wgid, 128);
        if (leader) { tma_red_2d(tmOut, col, row, stg); bulk_commit(); }
    }
}

__device__ __forceinline__ void ffn_load_residual(float (&acc)[32], uint32_t stg, int w, int lane, uint32_t fullH) {
    mbar_wait(fullH, 0);
    const int r = w * 16 + (lane & 7) + ((lane >> 3) & 1) * 8;
#pragma unroll
    for (int b = 0; b < 8; b += 2) {
        uint32_t h0, h1, h2, h3;
        asm volatile("ldmatrix.sync.aligned.m8n8.x4.shared.b16 {%0, %1, %2, %3}, [%4];" : "=r"(h0), "=r"(h1), "=r"(h2), "=r"(h3) : "r"(stg + r * 128 + (((b + (lane >> 4)) ^ (r & 7)) << 4)) : "memory");
        acc[4 * b] = bf_lo(h0); acc[4 * b + 1] = bf_hi(h0); acc[4 * b + 2] = bf_lo(h1); acc[4 * b + 3] = bf_hi(h1);
        acc[4 * b + 4] = bf_lo(h2); acc[4 * b + 5] = bf_hi(h2); acc[4 * b + 6] = bf_lo(h3); acc[4 * b + 7] = bf_hi(h3);
    }
}

template <int MODE>
__device__ __forceinline__ void ffn_phase2_chunk(float (&cur)[32], float (&prev)[32], uint32_t (&h1)[144], const FfnPipe& pp, uint32_t ph, const CUtensorMap* tmOut, uint32_t stg_prev, int col_prev, int row, int w, int lane, int wgid, bool leader,
                                                 uint32_t fullH, uint32_t stg_res) {
    const uint64_t dw = cdesc(F_OFF_ST, 8192, 1024, 1) + blockIdx.y * col_prev;
    float tmp[2][8];
#pragma unroll
    for (int j = 0; j < 6; j++) {
        pp.acquire(j, ph);
        if (j == 0) pin(cur);
        if (MODE == 0 && j == 5) pin(h1);
        wg_fence();
#pragma unroll
        for (int i = 0; i < 6; i++) {
            const int f = (6 * j + i) * 4;
            wgmma_rs_n64<1>(cur, h1[f], h1[f + 1], h1[f + 2], h1[f + 3], dw + ((j * F_STAGE + i * 2048) >> 4), (j | i) != 0);
        }
        wg_commit();
        wg_wait<1>();
        pp.release((j + 5) % 6);
        if (MODE == 0) {
            pin(prev);
            if (j == 0) silu_slot_last<0>(prev, tmp, h1);
            if (j == 1) silu_slot_last<1>(prev, tmp, h1);
            if (j == 2) silu_slot_last<2>(prev, tmp, h1);
            if (j == 3) silu_slot_last<3>(prev, tmp, h1);
            if (j == 4) silu_slot_last<4>(prev, tmp, h1);
        } else {
            if (j == 0) { pin(prev); ffn_stage_chunk(prev, stg_prev, w, lane, false, fullH); }
            if (j == 1) ffn_reduce_chunk(tmOut, stg_prev, col_prev, row, w, wgid, leader);
            if (MODE == 2 && j == 2) { ffn_load_residual(prev, stg_res, w, lane, fullH); pin(prev); }
        }
    }
}

template <int HALF, int J>
__device__ __forceinline__ void ffn_half_group(float (&cur)[32], uint32_t (&h1)[144], const FfnPipe& pp, uint64_t dw) {
    if (HALF == 0) pp.acquire(J, 1);
    wg_fence();
#pragma unroll
    for (int i = 0; i < 6; i++) {
        const int f = (6 * J + i) * 4;
        wgmma_rs_n32_of32<1, HALF * 16>(cur, h1[f], h1[f + 1], h1[f + 2], h1[f + 3], dw + (((J * F_STAGE + i * 2048) >> 4) + HALF * 4), 1);
    }
    wg_commit();
}
template <int HALF>
__device__ __forceinline__ void ffn_store_half(float (&acc)[32], const CUtensorMap* tmHalf, uint32_t stg, int col, int row, int w, int lane, int wgid, bool leader) {
    const int r = w * 16 + (lane & 7) + ((lane >> 3) & 1) * 8;
#pragma unroll
    for (int i = 0; i < 16; i++) asm volatile("" : "+f"(acc[HALF * 16 + i])::"memory");
#pragma unroll
    for (int b = 0; b < 4; b += 2) {
        const int q = HALF * 16 + 4 * b;
        stmatrix_x4(stg + r * 64 + (((b + (lane >> 4)) ^ ((r >> 1) & 3)) << 4), pack_bf16(acc[q], acc[q + 1]), pack_bf16(acc[q + 2], acc[q + 3]),
                    pack_bf16(acc[q + 4], acc[q + 5]), pack_bf16(acc[q + 6], acc[q + 7]));
    }
    ffn_reduce_chunk(tmHalf, stg, col + HALF * 32, row, w, wgid, leader);
}

__global__ void __launch_bounds__(F_THREADS, 1)
k_ffn(const __grid_constant__ CUtensorMap tmX2, const __grid_constant__ CUtensorMap tmW1, const __grid_constant__ CUtensorMap tmW2, const __grid_constant__ CUtensorMap tmOut,
      const __grid_constant__ CUtensorMap tmRes, const __grid_constant__ CUtensorMap tmHalf, const __nv_bfloat16* __restrict__ w2) {
    extern __shared__ __align__(1024) uint8_t smem[];
    const uint32_t sX = smem_u32(smem), sSt = sX + F_OFF_ST, bars = sX + F_OFF_BAR;
    const uint32_t full = bars, empty = bars + 64, fullX = bars + 128, fullH = bars + 208;
    const int tid = threadIdx.x, warp = __shfl_sync(~0u, tid >> 5, 0), lane = tid & 31;
    const int m = blockIdx.x >> 3, fs = blockIdx.x & 7;
    check_smem_base(sX);
    if (tid == 0) {
        prefetch_map(&tmW1); prefetch_map(&tmX2); prefetch_map(&tmW2); prefetch_map(&tmOut); prefetch_map(&tmRes); prefetch_map(&tmHalf);
        for (int i = 0; i < F_NST; i++) { mbar_init(full + i * 8, 1); mbar_init(empty + i * 8, 8); }
        for (int i = 0; i < 9; i++) mbar_init(fullX + i * 8, 1);
        mbar_init(fullH, 1); mbar_init(fullH + 8, 1);
        bar_init_fence();
        for (int kb = 0; kb < 9; kb++) mbar_expect(fullX + kb * 8, 16384);
    }
    __syncthreads();
    if (warp < 4) {
        asm volatile("setmaxnreg.dec.sync.aligned.u32 24;");
        if (warp == 1 && lane < 9) prefetch_l2(reinterpret_cast<const char*>(w2) + ((size_t)fs * 576 + m * 36 + lane * 4) * (DM * 2), 4 * DM * 2);
        if (warp == 0 && elect_one()) {
#pragma unroll 1
            for (int c = 0; c < 18; c++) {
                int col = c - 9 + fs;
                if (col >= 9) col -= 9;
#pragma unroll 1
                for (int j = 0; j < 6; j++) {
                    mbar_wait(empty + j * 8, (c & 1) ^ 1);
                    mbar_expect(full + j * 8, F_STAGE);
                    if (c < 9) tma_2d(sSt + j * F_STAGE, &tmW1, fs * 576 + c * 64, j * 96, full + j * 8);
                    else tma_2d(sSt + j * F_STAGE, &tmW2, col * 64, fs * 576 + j * 96, full + j * 8);
                }
            }
        }
    } else {
        asm volatile("setmaxnreg.inc.sync.aligned.u32 240;");
        const int wgid = (warp >> 2) - 1, w = warp & 3;
        pdl_wait();
        if (warp == 4 && elect_one()) {
            for (int kb = 0; kb < 9; kb++) tma_2d(sX + kb * 16384, &tmX2, kb * 64, m * 128, fullX + kb * 8);
        }
        __syncwarp();
        FfnPipe pp{full, empty, lane};
        const uint64_t xlo = cdesc(0, 16, 1024, 1) + wgid * 512;
        uint32_t h1[144];
        float acc0[32], acc1[32];
        ffn_phase1_chunk<0>(acc0, acc1, h1, pp, xlo, fullX);
        ffn_phase1_chunk<1>(acc1, acc0, h1, pp, xlo, fullX);
        ffn_phase1_chunk<2>(acc0, acc1, h1, pp, xlo, fullX);
        ffn_phase1_chunk<3>(acc1, acc0, h1, pp, xlo, fullX);
        ffn_phase1_chunk<4>(acc0, acc1, h1, pp, xlo, fullX);
        ffn_phase1_chunk<5>(acc1, acc0, h1, pp, xlo, fullX);
        ffn_phase1_chunk<6>(acc0, acc1, h1, pp, xlo, fullX);
        ffn_phase1_chunk<7>(acc1, acc0, h1, pp, xlo, fullX);
        ffn_phase1_chunk<8>(acc0, acc1, h1, pp, xlo, fullX);
        const int row = m * 128 + wgid * 64;
        const uint32_t stg = sX + wgid * 8192;
        int c = fs, cprev = 0;
        const bool leader = w == 0 && elect_one();
        const uint32_t myH = fullH + wgid * 8;
        ffn_phase2_chunk<0>(acc1, acc0, h1, pp, 1, &tmOut, 0, 0, row, w, lane, wgid, leader, myH, 0);
        if (leader) {
            const int c8 = fs == 0 ? 8 : fs - 1;
            mbar_expect(myH, fs == 0 ? 16384 : 8192);
            tma_2d(stg + 8 * 16384, &tmRes, c8 * 64, row, myH);
            if (fs == 0) tma_2d(stg + 7 * 16384, &tmRes, 7 * 64, row, myH);
        }
        cprev = c; if (++c == 9) c = 0;
#pragma unroll 1
        for (int j = 1; j < 7; j += 2) {
            ffn_phase2_chunk<1>(acc0, acc1, h1, pp, 0, &tmOut, stg + (j - 1) * 16384, cprev * 64, row, w, lane, wgid, leader, myH, 0);
            cprev = c; if (++c == 9) c = 0;
            ffn_phase2_chunk<1>(acc1, acc0, h1, pp, 1, &tmOut, stg + j * 16384, cprev * 64, row, w, lane, wgid, leader, myH, 0);
            cprev = c; if (++c == 9) c = 0;
        }
        ffn_phase2_chunk<2>(acc0, acc1, h1, pp, 0, &tmOut, stg + 6 * 16384, cprev * 64, row, w, lane, wgid, leader, myH, stg + 8 * 16384);
        cprev = c; if (++c == 9) c = 0;
        {
            const uint64_t dw = cdesc(F_OFF_ST, 8192, 1024, 1) + blockIdx.y * (c + 1);
            pin(acc1);
            ffn_half_group<0, 0>(acc1, h1, pp, dw);
            wg_wait<1>();
            pp.release(5);
            pin(acc0);
            ffn_stage_chunk(acc0, stg + 7 * 16384, w, lane, fs == 0, myH);
            ffn_half_group<0, 1>(acc1, h1, pp, dw);
            wg_wait<2>();
            ffn_reduce_chunk(&tmOut, stg + 7 * 16384, cprev * 64, row, w, wgid, leader);
            ffn_half_group<0, 2>(acc1, h1, pp, dw);
            ffn_half_group<0, 3>(acc1, h1, pp, dw);
            ffn_half_group<0, 4>(acc1, h1, pp, dw);
            ffn_half_group<0, 5>(acc1, h1, pp, dw);
            ffn_half_group<1, 0>(acc1, h1, pp, dw);
            ffn_half_group<1, 1>(acc1, h1, pp, dw);
            wg_wait<2>();
            ffn_store_half<0>(acc1, &tmHalf, stg + 8 * 16384, c * 64, row, w, lane, wgid, leader);
            ffn_half_group<1, 2>(acc1, h1, pp, dw);
            ffn_half_group<1, 3>(acc1, h1, pp, dw);
            ffn_half_group<1, 4>(acc1, h1, pp, dw);
            ffn_half_group<1, 5>(acc1, h1, pp, dw);
            wg_wait<0>();
            pin(acc1);
            ffn_store_half<1>(acc1, &tmHalf, stg + 8 * 16384 + 4096, c * 64, row, w, lane, wgid, leader);
        }
        if (leader) bulk_wait_all();
    }
}

typedef CUresult (*EncodeFn)(CUtensorMap*, CUtensorMapDataType, cuuint32_t, void*, const cuuint64_t*, const cuuint64_t*, const cuuint32_t*, const cuuint32_t*,
                             CUtensorMapInterleave, CUtensorMapSwizzle, CUtensorMapL2promotion, CUtensorMapFloatOOBfill);

CUtensorMap make_map(EncodeFn enc, const void* base, int rows, int cols, int box_rows, int box_cols = 64) {
    CUtensorMap tm;
    cuuint64_t dims[2] = {(cuuint64_t)cols, (cuuint64_t)rows};
    cuuint64_t strides[1] = {(cuuint64_t)cols * 2};
    cuuint32_t box[2] = {(cuuint32_t)box_cols, (cuuint32_t)box_rows};
    cuuint32_t es[2] = {1, 1};
    enc(&tm, CU_TENSOR_MAP_DATA_TYPE_BFLOAT16, 2, const_cast<void*>(base), dims, strides, box, es, CU_TENSOR_MAP_INTERLEAVE_NONE,
        box_cols == 64 ? CU_TENSOR_MAP_SWIZZLE_128B : CU_TENSOR_MAP_SWIZZLE_64B, CU_TENSOR_MAP_L2_PROMOTION_L2_256B, CU_TENSOR_MAP_FLOAT_OOB_FILL_NONE);
    return tm;
}

template <typename... KArgs, typename... Args>
void launch(void (*kern)(KArgs...), int grid, int block, int smem, bool pdl, Args... args) {
    cudaLaunchConfig_t cfg = {};
    cfg.gridDim = dim3(grid); cfg.blockDim = dim3(block); cfg.dynamicSmemBytes = smem; cfg.stream = cudaStreamPerThread;
    cudaLaunchAttribute at[1];
    at[0].id = cudaLaunchAttributeProgrammaticStreamSerialization;
    at[0].val.programmaticStreamSerializationAllowed = 1;
    cfg.attrs = at; cfg.numAttrs = pdl ? 1 : 0;
    cudaLaunchKernelEx(&cfg, kern, KArgs(args)...);
}

}

extern "C" void kernel_launch(void* const* d_in, const int* in_sizes, int n_in, void* d_out, int out_size) {
    const __nv_bfloat16* x = (const __nv_bfloat16*)d_in[0];
    const __nv_bfloat16* wq = (const __nv_bfloat16*)d_in[1];
    const __nv_bfloat16* wk = (const __nv_bfloat16*)d_in[2];
    const __nv_bfloat16* wv = (const __nv_bfloat16*)d_in[3];
    const __nv_bfloat16* wo = (const __nv_bfloat16*)d_in[4];
    const __nv_bfloat16* w1 = (const __nv_bfloat16*)d_in[6];
    const __nv_bfloat16* w2 = (const __nv_bfloat16*)d_in[7];
    __nv_bfloat16* out = (__nv_bfloat16*)d_out;

    static EncodeFn enc = nullptr;
    static void *p_o = nullptr, *p_x2 = nullptr, *p_q = nullptr, *p_res = nullptr;
    if (!enc) {
        cudaDriverEntryPointQueryResult qr;
        cudaGetDriverEntryPoint("cuTensorMapEncodeTiled", (void**)&enc, cudaEnableDefault, &qr);
        cudaGetSymbolAddress(&p_o, g_o);
        cudaGetSymbolAddress(&p_x2, g_x2);
        cudaGetSymbolAddress(&p_res, g_h);
        cudaGetSymbolAddress(&p_q, g_q);
        cudaFuncSetAttribute(k_qkv, cudaFuncAttributeMaxDynamicSharedMemorySize, Q_SMEM);
        cudaFuncSetAttribute(k_attn, cudaFuncAttributeMaxDynamicSharedMemorySize, A_SMEM);
        cudaFuncSetAttribute(k_oproj, cudaFuncAttributeMaxDynamicSharedMemorySize, O_SMEM);
        cudaFuncSetAttribute(k_ffn, cudaFuncAttributeMaxDynamicSharedMemorySize, F_SMEM);
    }
    const CUtensorMap tmWq = make_map(enc, wq, DM, DM, 192);
    const CUtensorMap tmWo = make_map(enc, wo, DM, DM, 64);
    const CUtensorMap tmO = make_map(enc, p_o, SEQ, DM, 64);
    const CUtensorMap tmX2st = make_map(enc, p_x2, SEQ, DM, 64);
    const CUtensorMap tmX2ld = make_map(enc, p_x2, SEQ, DM, 128);
    const CUtensorMap tmRes = make_map(enc, p_res, SEQ, DM, 64);
    const CUtensorMap tmQ = make_map(enc, p_q, SEQ, DM, 64);
    const CUtensorMap tmW1 = make_map(enc, w1, DM, FF, 96);
    const CUtensorMap tmW2 = make_map(enc, w2, FF, DM, 96);
    const CUtensorMap tmOut = make_map(enc, out, SEQ, DM, 64);
    const CUtensorMap tmHalf = make_map(enc, out, SEQ, DM, 64, 32);

    launch(k_qkv, 128, Q_THREADS, Q_SMEM, false, tmWq, tmQ, x, wk, wv);
    launch(k_attn, 128, A_THREADS, A_SMEM, true, out);
    launch(k_oproj, 96, O_THREADS, O_SMEM, true, tmO, tmWo, tmX2st, tmRes, x, w1);
    launch(k_ffn, 128, F_THREADS, F_SMEM, true, tmX2ld, tmW1, tmW2, tmOut, tmRes, tmHalf, w2);
}
```

```cpp
#include <cuda_runtime.h>
#include <cuda_bf16.h>
#include <cuda.h>
#include <stdint.h>

namespace {

constexpr int SEQ = 2048, DM = 576, FF = 4608;
constexpr int KV_BYTES = SEQ * 48;
constexpr float LN_EPS = 1e-5f;
constexpr float LOG2E = 1.4426950408889634f;
constexpr float Q_SCALE = 0.23570226039551584f * LOG2E;

constexpr uint32_t POLY_MASK = 0xB6DBu;
constexpr int CHAIN = 6;
constexpr float FAST_BOUND = 90.0f;
constexpr float FAST_VMAX2 = 1e12f;

__device__ __align__(1024) __nv_bfloat16 g_q[SEQ * DM];
__device__ __align__(1024) uint4 g_kc[KV_BYTES / 16];
__device__ __align__(1024) uint4 g_vc[KV_BYTES / 16];
__device__ __align__(16) float g_kmax[256];
__device__ __align__(1024) __nv_bfloat16 g_o[SEQ * DM];
__device__ __align__(1024) __nv_bfloat16 g_h[SEQ * DM];
__device__ __align__(1024) __nv_bfloat16 g_x2[SEQ * DM];

__device__ __forceinline__ uint32_t smem_u32(const void* p) { return (uint32_t)__cvta_generic_to_shared(p); }
__device__ __forceinline__ void wg_fence() { asm volatile("wgmma.fence.sync.aligned;" ::: "memory"); }
__device__ __forceinline__ void wg_commit() { asm volatile("wgmma.commit_group.sync.aligned;" ::: "memory"); }
template <int N> __device__ __forceinline__ void wg_wait() { asm volatile("wgmma.wait_group.sync.aligned %0;" ::"n"(N) : "memory"); }
template <int N> __device__ __forceinline__ void pin(float (&r)[N]) {
#pragma unroll
    for (int i = 0; i < N; i++) asm volatile("" : "+f"(r[i])::"memory");
}
template <int N> __device__ __forceinline__ void pin(uint32_t (&r)[N]) {
#pragma unroll
    for (int i = 0; i < N; i++) asm volatile("" : "+r"(r[i])::"memory");
}
constexpr uint32_t SMEM0 = 0x400;
__host__ __device__ constexpr uint64_t cdesc(uint32_t off, uint32_t lbo, uint32_t sbo, uint32_t swz) {
    return (uint64_t)(((SMEM0 + off) & 0x3FFFF) >> 4) | ((uint64_t)(lbo >> 4) << 16) | ((uint64_t)(sbo >> 4) << 32) | ((uint64_t)swz << 62);
}
__device__ __forceinline__ void check_smem_base(uint32_t base) { if ((base & 0x3FFFF) != SMEM0) __trap(); }

__device__ __forceinline__ void mbar_init(uint32_t bar, int cnt) { asm volatile("mbarrier.init.shared::cta.b64 [%0], %1;" ::"r"(bar), "r"(cnt) : "memory"); }
__device__ __forceinline__ void mbar_expect(uint32_t bar, int bytes) { asm volatile("mbarrier.arrive.expect_tx.shared::cta.b64 _, [%0], %1;" ::"r"(bar), "r"(bytes) : "memory"); }
__device__ __forceinline__ void mbar_arrive(uint32_t bar) { asm volatile("mbarrier.arrive.shared::cta.b64 _, [%0];" ::"r"(bar) : "memory"); }
__device__ __forceinline__ void mbar_wait(uint32_t bar, uint32_t parity) {
    asm volatile(
        "{\n.reg .pred p;\n.reg .u32 n;\nmov.u32 n, 0;\n"
        "LAB_WAIT:\n"
        "mbarrier.try_wait.parity.shared::cta.b64 p, [%0], %1;\n"
        "@p bra DONE;\n"
        "add.u32 n, n, 1;\n"
        "setp.lt.u32 p, n, 4000000;\n"
        "@p bra LAB_WAIT;\n"
        "trap;\n"
        "DONE:\n}\n" ::"r"(bar), "r"(parity) : "memory");
}
__device__ __forceinline__ void bar_init_fence() {
    asm volatile("fence.mbarrier_init.release.cluster;" ::: "memory");
    asm volatile("fence.proxy.async.shared::cta;" ::: "memory");
}
__device__ __forceinline__ void proxy_fence() { asm volatile("fence.proxy.async.shared::cta;" ::: "memory"); }
__device__ __forceinline__ void named_sync(int id, int n) { asm volatile("bar.sync %0, %1;" ::"r"(id), "r"(n) : "memory"); }
__device__ __forceinline__ void bulk_g2s(uint32_t dst, const void* src, int bytes, uint32_t bar) {
    asm volatile("cp.async.bulk.shared::cluster.global.mbarrier::complete_tx::bytes [%0], [%1], %2, [%3];" ::"r"(dst), "l"(src), "r"(bytes), "r"(bar) : "memory");
}
__device__ __forceinline__ void tma_2d(uint32_t dst, const CUtensorMap* tm, int c0, int c1, uint32_t bar) {
    asm volatile("cp.async.bulk.tensor.2d.shared::cluster.global.mbarrier::complete_tx::bytes [%0], [%1, {%3, %4}], [%2];" ::"r"(dst), "l"(tm), "r"(bar), "r"(c0), "r"(c1) : "memory");
}
__device__ __forceinline__ void cluster_arrive() { asm volatile("barrier.cluster.arrive.release.aligned;" ::: "memory"); }
__device__ __forceinline__ void cluster_wait() { asm volatile("barrier.cluster.wait.acquire.aligned;" ::: "memory"); }
__device__ __forceinline__ void tma_red_2d(const CUtensorMap* tm, int c0, int c1, uint32_t src) {
    asm volatile("cp.reduce.async.bulk.tensor.2d.global.shared::cta.add.tile.bulk_group [%0, {%2, %3}], [%1];" ::"l"(tm), "r"(src), "r"(c0), "r"(c1) : "memory");
}
__device__ __forceinline__ void tma_st_2d(const CUtensorMap* tm, int c0, int c1, uint32_t src) {
    asm volatile("cp.async.bulk.tensor.2d.global.shared::cta.tile.bulk_group [%0, {%2, %3}], [%1];" ::"l"(tm), "r"(src), "r"(c0), "r"(c1) : "memory");
}
__device__ __forceinline__ void bulk_commit() { asm volatile("cp.async.bulk.commit_group;" ::: "memory"); }
__device__ __forceinline__ void bulk_wait_all() { asm volatile("cp.async.bulk.wait_group.read 0;" ::: "memory"); }
__device__ __forceinline__ bool elect_one() {
    uint32_t p;
    asm volatile("{\n.reg .pred P;\nelect.sync _|P, 0xffffffff;\nselp.b32 %0, 1, 0, P;\n}\n" : "=r"(p));
    return p != 0;
}
__device__ __forceinline__ void prefetch_l2(const void* p, int bytes) { asm volatile("cp.async.bulk.prefetch.L2.global [%0], %1;" ::"l"(p), "r"(bytes) : "memory"); }
__device__ __forceinline__ void prefetch_map(const CUtensorMap* tm) { asm volatile("prefetch.tensormap [%0];" ::"l"(tm) : "memory"); }
__device__ __forceinline__ void pdl_launch() { asm volatile("griddepcontrol.launch_dependents;" ::: "memory"); }
__device__ __forceinline__ void pdl_wait() { asm volatile("griddepcontrol.wait;" ::: "memory"); }
__device__ __forceinline__ float ex2(float x) { float y; asm("ex2.approx.ftz.f32 %0, %1;" : "=f"(y) : "f"(x)); return y; }
__device__ __forceinline__ uint32_t pack_bf16(float lo, float hi) { uint32_t r; asm("cvt.rn.bf16x2.f32 %0, %1, %2;" : "=r"(r) : "f"(hi), "f"(lo)); return r; }
__device__ __forceinline__ float bf_lo(uint32_t v) { return __uint_as_float(v << 16); }
__device__ __forceinline__ float bf_hi(uint32_t v) { return __uint_as_float(v & 0xFFFF0000u); }
__device__ __forceinline__ uint32_t hfma2(uint32_t a, uint32_t b, uint32_t c) { uint32_t r; asm("fma.rn.f16x2 %0, %1, %2, %3;" : "=r"(r) : "r"(a), "r"(b), "r"(c)); return r; }
__device__ __forceinline__ void stmatrix_x4(uint32_t addr, uint32_t r0, uint32_t r1, uint32_t r2, uint32_t r3) {
    asm volatile("stmatrix.sync.aligned.m8n8.x4.shared.b16 [%0], {%1, %2, %3, %4};" ::"r"(addr), "r"(r0), "r"(r1), "r"(r2), "r"(r3) : "memory");
}

template <int TB> __device__ __forceinline__ void wgmma_ss_n24(float (&d)[12], uint64_t da, uint64_t db, int sc) {
    asm volatile("{\n.reg .pred p;\nsetp.ne.b32 p, %14, 0;\n"
        "wgmma.mma_async.sync.aligned.m64n24k16.f32.bf16.bf16 {%0, %1, %2, %3, %4, %5, %6, %7, %8, %9, %10, %11}, %12, %13, p, 1, 1, 0, %15;\n}\n"
        : "+f"(d[0]), "+f"(d[1]), "+f"(d[2]), "+f"(d[3]), "+f"(d[4]), "+f"(d[5]), "+f"(d[6]), "+f"(d[7]), "+f"(d[8]), "+f"(d[9]), "+f"(d[10]), "+f"(d[11])
        : "l"(da), "l"(db), "r"(sc), "n"(TB));
}
template <int TB> __device__ __forceinline__ void wgmma_ss_n64(float (&d)[32], uint64_t da, uint64_t db, int sc) {
    asm volatile("{\n.reg .pred p;\nsetp.ne.b32 p, %34, 0;\n"
        "wgmma.mma_async.sync.aligned.m64n64k16.f32.bf16.bf16 {%0, %1, %2, %3, %4, %5, %6, %7, %8, %9, %10, %11, %12, %13, %14, %15, %16, %17, %18, %19, %20, %21, %22, %23, %24, %25, %26, %27, %28, %29, %30, %31}, %32, %33, p, 1, 1, 0, %35;\n}\n"
        : "+f"(d[0]), "+f"(d[1]), "+f"(d[2]), "+f"(d[3]), "+f"(d[4]), "+f"(d[5]), "+f"(d[6]), "+f"(d[7]), "+f"(d[8]), "+f"(d[9]), "+f"(d[10]), "+f"(d[11]), "+f"(d[12]), "+f"(d[13]), "+f"(d[14]), "+f"(d[15]), "+f"(d[16]), "+f"(d[17]), "+f"(d[18]), "+f"(d[19]), "+f"(d[20]), "+f"(d[21]), "+f"(d[22]), "+f"(d[23]), "+f"(d[24]), "+f"(d[25]), "+f"(d[26]), "+f"(d[27]), "+f"(d[28]), "+f"(d[29]), "+f"(d[30]), "+f"(d[31])
        : "l"(da), "l"(db), "r"(sc), "n"(TB));
}
template <int TB> __device__ __forceinline__ void wgmma_ss_n128(float (&d)[64], uint64_t da, uint64_t db, int sc) {
    asm volatile("{\n.reg .pred p;\nsetp.ne.b32 p, %66, 0;\n"
        "wgmma.mma_async.sync.aligned.m64n128k16.f32.bf16.bf16 {%0, %1, %2, %3, %4, %5, %6, %7, %8, %9, %10, %11, %12, %13, %14, %15, %16, %17, %18, %19, %20, %21, %22, %23, %24, %25, %26, %27, %28, %29, %30, %31, %32, %33, %34, %35, %36, %37, %38, %39, %40, %41, %42, %43, %44, %45, %46, %47, %48, %49, %50, %51, %52, %53, %54, %55, %56, %57, %58, %59, %60, %61, %62, %63}, %64, %65, p, 1, 1, 0, %67;\n}\n"
        : "+f"(d[0]), "+f"(d[1]), "+f"(d[2]), "+f"(d[3]), "+f"(d[4]), "+f"(d[5]), "+f"(d[6]), "+f"(d[7]), "+f"(d[8]), "+f"(d[9]), "+f"(d[10]), "+f"(d[11]), "+f"(d[12]), "+f"(d[13]), "+f"(d[14]), "+f"(d[15]), "+f"(d[16]), "+f"(d[17]), "+f"(d[18]), "+f"(d[19]), "+f"(d[20]), "+f"(d[21]), "+f"(d[22]), "+f"(d[23]), "+f"(d[24]), "+f"(d[25]), "+f"(d[26]), "+f"(d[27]), "+f"(d[28]), "+f"(d[29]), "+f"(d[30]), "+f"(d[31]), "+f"(d[32]), "+f"(d[33]), "+f"(d[34]), "+f"(d[35]), "+f"(d[36]), "+f"(d[37]), "+f"(d[38]), "+f"(d[39]), "+f"(d[40]), "+f"(d[41]), "+f"(d[42]), "+f"(d[43]), "+f"(d[44]), "+f"(d[45]), "+f"(d[46]), "+f"(d[47]), "+f"(d[48]), "+f"(d[49]), "+f"(d[50]), "+f"(d[51]), "+f"(d[52]), "+f"(d[53]), "+f"(d[54]), "+f"(d[55]), "+f"(d[56]), "+f"(d[57]), "+f"(d[58]), "+f"(d[59]), "+f"(d[60]), "+f"(d[61]), "+f"(d[62]), "+f"(d[63])
        : "l"(da), "l"(db), "r"(sc), "n"(TB));
}
template <int TB> __device__ __forceinline__ void wgmma_rs_n24(float (&d)[12], uint32_t a0, uint32_t a1, uint32_t a2, uint32_t a3, uint64_t db, int sc) {
    asm volatile("{\n.reg .pred p;\nsetp.ne.b32 p, %17, 0;\n"
        "wgmma.mma_async.sync.aligned.m64n24k16.f32.bf16.bf16 {%0, %1, %2, %3, %4, %5, %6, %7, %8, %9, %10, %11}, {%12, %13, %14, %15}, %16, p, 1, 1, %18;\n}\n"
        : "+f"(d[0]), "+f"(d[1]), "+f"(d[2]), "+f"(d[3]), "+f"(d[4]), "+f"(d[5]), "+f"(d[6]), "+f"(d[7]), "+f"(d[8]), "+f"(d[9]), "+f"(d[10]), "+f"(d[11])
        : "r"(a0), "r"(a1), "r"(a2), "r"(a3), "l"(db), "r"(sc), "n"(TB));
}
template <int TB> __device__ __forceinline__ void wgmma_rs_n64(float (&d)[32], uint32_t a0, uint32_t a1, uint32_t a2, uint32_t a3, uint64_t db, int sc) {
    asm volatile("{\n.reg .pred p;\nsetp.ne.b32 p, %37, 0;\n"
        "wgmma.mma_async.sync.aligned.m64n64k16.f32.bf16.bf16 {%0, %1, %2, %3, %4, %5, %6, %7, %8, %9, %10, %11, %12, %13, %14, %15, %16, %17, %18, %19, %20, %21, %22, %23, %24, %25, %26, %27, %28, %29, %30, %31}, {%32, %33, %34, %35}, %36, p, 1, 1, %38;\n}\n"
        : "+f"(d[0]), "+f"(d[1]), "+f"(d[2]), "+f"(d[3]), "+f"(d[4]), "+f"(d[5]), "+f"(d[6]), "+f"(d[7]), "+f"(d[8]), "+f"(d[9]), "+f"(d[10]), "+f"(d[11]), "+f"(d[12]), "+f"(d[13]), "+f"(d[14]), "+f"(d[15]), "+f"(d[16]), "+f"(d[17]), "+f"(d[18]), "+f"(d[19]), "+f"(d[20]), "+f"(d[21]), "+f"(d[22]), "+f"(d[23]), "+f"(d[24]), "+f"(d[25]), "+f"(d[26]), "+f"(d[27]), "+f"(d[28]), "+f"(d[29]), "+f"(d[30]), "+f"(d[31])
        : "r"(a0), "r"(a1), "r"(a2), "r"(a3), "l"(db), "r"(sc), "n"(TB));
}
template <int TB, int OFF> __device__ __forceinline__ void wgmma_rs_n32_of32(float (&d)[32], uint32_t a0, uint32_t a1, uint32_t a2, uint32_t a3, uint64_t db, int sc) {
    asm volatile("{\n.reg .pred p;\nsetp.ne.b32 p, %21, 0;\n"
        "wgmma.mma_async.sync.aligned.m64n32k16.f32.bf16.bf16 {%0, %1, %2, %3, %4, %5, %6, %7, %8, %9, %10, %11, %12, %13, %14, %15}, {%16, %17, %18, %19}, %20, p, 1, 1, %22;\n}\n"
        : "+f"(d[OFF + 0]), "+f"(d[OFF + 1]), "+f"(d[OFF + 2]), "+f"(d[OFF + 3]), "+f"(d[OFF + 4]), "+f"(d[OFF + 5]), "+f"(d[OFF + 6]), "+f"(d[OFF + 7]), "+f"(d[OFF + 8]), "+f"(d[OFF + 9]), "+f"(d[OFF + 10]), "+f"(d[OFF + 11]), "+f"(d[OFF + 12]), "+f"(d[OFF + 13]), "+f"(d[OFF + 14]), "+f"(d[OFF + 15])
        : "r"(a0), "r"(a1), "r"(a2), "r"(a3), "l"(db), "r"(sc), "n"(TB));
}

constexpr int P_NST = 6;
constexpr int P_A_BYTES = 9 * 8192;
constexpr int P_B_STAGE = 3 * 8192;

template <int NB>
__device__ __forceinline__ void stage_tile(const uint32_t (&pk)[NB * 2], uint32_t base, int w, int lane) {
    const int r = w * 16 + (lane & 7) + ((lane >> 3) & 1) * 8;
#pragma unroll
    for (int b = 0; b < NB; b += 2) {
        const uint32_t a = base + (b >> 3) * 8192 + r * 128 + ((((b & 7) + (lane >> 4)) ^ (r & 7)) << 4);
        stmatrix_x4(a, pk[2 * b], pk[2 * b + 1], pk[2 * b + 2], pk[2 * b + 3]);
    }
}

__device__ __forceinline__ uint32_t hsub2_bf16(uint32_t a, uint32_t b) { uint32_t r; asm("sub.rn.bf16x2 %0, %1, %2;" : "=r"(r) : "r"(a), "r"(b)); return r; }

constexpr int KV_RAW = DM * 18 * 2;
constexpr int Q_THREADS = 416;

__device__ __forceinline__ void proj_mma(float (&acc)[32], int wg, uint32_t fullB, uint32_t emptyB, uint32_t fullA, bool wait_a, int lane) {
    const uint64_t dA = cdesc(0, 16, 1024, 1), dB = cdesc(P_A_BYTES, 8192, 1024, 1) + wg * 512;
#pragma unroll 1
    for (int kb = 0; kb < 9; kb++) {
        const int s = kb >= P_NST ? kb - P_NST : kb;
        if (wait_a) mbar_wait(fullA + kb * 8, 0);
        mbar_wait(fullB + s * 8, kb >= P_NST ? 1 : 0);
        wg_fence();
#pragma unroll
        for (int ks = 0; ks < 4; ks++) wgmma_ss_n64<1>(acc, dA + (kb * 512 + ks * 2), dB + (s * (P_B_STAGE >> 4) + ks * 128), (kb | ks) != 0);
        wg_commit();
        if (kb < 4) {
            wg_wait<1>();
            if (kb >= 1 && lane == 0) mbar_arrive(emptyB + (kb - 1) * 8);
        }
    }
    wg_wait<0>();
    pin(acc);
}

constexpr int Q_SLOT = 9 * 8192, Q_THIRD = 3 * 8192;
constexpr int Q_OFF_STG = P_A_BYTES + 2 * Q_SLOT;
constexpr int Q_OFF_BAR = Q_OFF_STG + 8192;
constexpr int Q_SMEM = Q_OFF_BAR + 256 + 256;

__global__ void __launch_bounds__(Q_THREADS, 1)
k_qkv(const __grid_constant__ CUtensorMap tmWq, const __grid_constant__ CUtensorMap tmQ, const __nv_bfloat16* __restrict__ x, const __nv_bfloat16* __restrict__ wk, const __nv_bfloat16* __restrict__ wv) {
    extern __shared__ __align__(1024) uint8_t smem[];
    const uint32_t sA = smem_u32(smem), sB = sA + P_A_BYTES, bars = sA + Q_OFF_BAR;
    const uint32_t fullB = bars, free0 = bars + 80, fullX = bars + 128, fullW = bars + 136;
    float* s_rstd = reinterpret_cast<float*>(smem + Q_OFF_BAR + 256);
    const int tid = threadIdx.x, warp = __shfl_sync(~0u, tid >> 5, 0), lane = tid & 31;
    const bool isQ = blockIdx.x < 96;
    const int m = isQ ? blockIdx.x / 3 : blockIdx.x - 96, cg = blockIdx.x % 3;
    if (warp == 12) {
        if (elect_one()) {
            mbar_init(fullX, 1);
            bar_init_fence();
            mbar_expect(fullX, P_A_BYTES);
            bulk_g2s(sA, x + (size_t)m * 64 * DM, P_A_BYTES, fullX);
            prefetch_map(&tmWq); prefetch_map(&tmQ);
            for (int i = 0; i < 9; i++) mbar_init(fullB + i * 8, 1);
            for (int i = 0; i < 3; i++) mbar_init(free0 + i * 8, 4);
            mbar_init(fullW, 1);
            bar_init_fence();
            if (isQ) {
                for (int i = 0; i < 6; i++) {
                    mbar_expect(fullB + i * 8, Q_THIRD);
                    tma_2d(sB + i * Q_THIRD, &tmWq, cg * 192 + (i / 3) * 64, (i % 3) * 192, fullB + i * 8);
                }
                for (int i = 0; i < 3; i++)
                    asm volatile("cp.async.bulk.prefetch.tensor.2d.L2.global [%0, {%1, %2}];" ::"l"(&tmWq), "r"(cg * 192 + 128), "r"(i * 192) : "memory");
            } else {
                mbar_expect(fullW, 2 * KV_RAW);
                bulk_g2s(sB + Q_SLOT, wk, KV_RAW, fullW);
                bulk_g2s(sB + Q_SLOT + KV_RAW, wv, KV_RAW, fullW);
            }
        }
        __syncwarp();
    }
    check_smem_base(sA);
    __syncthreads();
    pdl_launch();
    if (warp == 12) {
        if (isQ && elect_one()) {
            for (int i = 0; i < 3; i++) {
                mbar_wait(free0 + i * 8, 0);
                mbar_expect(fullB + (6 + i) * 8, Q_THIRD);
                tma_2d(sB + i * Q_THIRD, &tmWq, cg * 192 + 128, i * 192, fullB + (6 + i) * 8);
            }
        }
        return;
    }
    if (warp < 8) {
        const int row = tid >> 2, q = tid & 3, h0 = (row & 1) * 4;
        mbar_wait(fullX, 0);
        uint4 v[18];
        const uint32_t ra = sA + row * 1152 + (q + h0) * 16, rb = sA + row * 1152 + (q + 4 - h0) * 16;
#pragma unroll
        for (int kb = 0; kb < 9; kb++) {
            asm volatile("ld.shared.v4.b32 {%0, %1, %2, %3}, [%4];" : "=r"(v[2 * kb].x), "=r"(v[2 * kb].y), "=r"(v[2 * kb].z), "=r"(v[2 * kb].w) : "r"(ra + kb * 128));
            asm volatile("ld.shared.v4.b32 {%0, %1, %2, %3}, [%4];" : "=r"(v[2 * kb + 1].x), "=r"(v[2 * kb + 1].y), "=r"(v[2 * kb + 1].z), "=r"(v[2 * kb + 1].w) : "r"(rb + kb * 128));
        }
        float sum = 0.f, sum2 = 0.f, sq = 0.f, sq2 = 0.f;
#pragma unroll
        for (int i = 0; i < 18; i++) {
            const uint32_t w[4] = {v[i].x, v[i].y, v[i].z, v[i].w};
#pragma unroll
            for (int j = 0; j < 4; j++) { const float a = bf_lo(w[j]), b = bf_hi(w[j]); sum += a; sum2 += b; sq = fmaf(a, a, sq); sq2 = fmaf(b, b, sq2); }
        }
        named_sync(1, 256);
        sum += sum2; sq += sq2;
        sum += __shfl_xor_sync(~0u, sum, 1); sum += __shfl_xor_sync(~0u, sum, 2);
        sq += __shfl_xor_sync(~0u, sq, 1); sq += __shfl_xor_sync(~0u, sq, 2);
        const float mean = sum * (1.0f / DM);
        if (q == 0) s_rstd[row] = rsqrtf(fmaxf(sq * (1.0f / DM) - mean * mean, 0.f) + LN_EPS);
        const uint32_t mhi = pack_bf16(mean, mean);
        const float rem = mean - bf_lo(mhi);
        const uint32_t mlo = pack_bf16(rem, rem);
        const uint32_t wa = sA + row * 128 + (((q + h0) ^ (row & 7)) << 4), wb = sA + row * 128 + (((q + 4 - h0) ^ (row & 7)) << 4);
#pragma unroll
        for (int i = 0; i < 18; i++) {
            const uint32_t o0 = hsub2_bf16(hsub2_bf16(v[i].x, mhi), mlo), o1 = hsub2_bf16(hsub2_bf16(v[i].y, mhi), mlo);
            const uint32_t o2 = hsub2_bf16(hsub2_bf16(v[i].z, mhi), mlo), o3 = hsub2_bf16(hsub2_bf16(v[i].w, mhi), mlo);
            asm volatile("st.shared.v4.b32 [%0], {%1, %2, %3, %4};" ::"r"(((i & 1) ? wb : wa) + (i >> 1) * 8192), "r"(o0), "r"(o1), "r"(o2), "r"(o3) : "memory");
        }
    } else if (!isQ) {
        mbar_wait(fullW, 0);
        const uint32_t* raw = reinterpret_cast<const uint32_t*>(smem + P_A_BYTES + Q_SLOT);
#pragma unroll 3
        for (int r = tid - 256; r < 2 * DM; r += 128) {
            uint32_t wr[9];
#pragma unroll
            for (int i = 0; i < 9; i++) wr[i] = raw[r * 9 + i];
            const int sel = r >= DM, k = r - sel * DM;
            uint8_t* dst = smem + P_A_BYTES + sel * 3 * 9216 + (k >> 3) * 128 + (k & 7) * 16;
            *reinterpret_cast<uint4*>(dst) = make_uint4(wr[0], wr[1], wr[2], wr[3]);
            *reinterpret_cast<uint4*>(dst + 9216) = make_uint4(wr[4], wr[5], wr[6], wr[7]);
            *reinterpret_cast<uint32_t*>(dst + 2 * 9216) = wr[8];
        }
    }
    proxy_fence();
    named_sync(2, 384);
    const int wg = warp >> 2, w = warp & 3, g = lane >> 2, t = lane & 3;
    const float rs0 = s_rstd[w * 16 + g], rs1 = s_rstd[w * 16 + g + 8];
    if (isQ) {
        const float c0 = rs0 * Q_SCALE, c1 = rs1 * Q_SCALE;
        float acc[32];
        const uint64_t dA = cdesc(0, 16, 1024, 1), dB = cdesc(P_A_BYTES, 8192, 1024, 1) + (wg == 1 ? (Q_SLOT >> 4) : 0);
        if (wg > 0) named_sync(6 + wg, 256);
#pragma unroll 1
        for (int i = 0; i < 3; i++) {
            mbar_wait(fullB + (wg * 3 + i) * 8, 0);
            wg_fence();
#pragma unroll
            for (int ks = 0; ks < 12; ks++)
                wgmma_ss_n64<1>(acc, dA + ((i * 3 + (ks >> 2)) * 512 + (ks & 3) * 2), dB + (i * (Q_THIRD >> 4) + ks * 128), (i | ks) != 0);
            wg_commit();
            if (wg == 0 && i > 0) { wg_wait<1>(); if (lane == 0) mbar_arrive(free0 + (i - 1) * 8); }
        }
        if (wg < 2) asm volatile("bar.arrive %0, 256;" ::"r"(7 + wg) : "memory");
        wg_wait<0>();
        pin(acc);
        if (wg == 0 && lane == 0) mbar_arrive(free0 + 16);
        uint32_t pk[16];
#pragma unroll
        for (int i = 0; i < 8; i++) { pk[2 * i] = pack_bf16(acc[4 * i] * c0, acc[4 * i + 1] * c0); pk[2 * i + 1] = pack_bf16(acc[4 * i + 2] * c1, acc[4 * i + 3] * c1); }
        const uint32_t stg = wg == 0 ? sA + Q_OFF_STG : (wg == 1 ? sB + Q_SLOT : sB);
        stage_tile<8>(pk, stg, w, lane);
        proxy_fence();
        named_sync(3 + wg, 128);
        if (w == 0 && elect_one()) {
            tma_st_2d(&tmQ, cg * 192 + wg * 64, m * 64, stg);
            bulk_commit();
            bulk_wait_all();
        }
    } else if (wg < 2) {
        float acc[12];
        const uint64_t dA = cdesc(0, 16, 1024, 1), dB = cdesc(P_A_BYTES, 128, 9216, 0) + wg * (3 * 9216 >> 4);
#pragma unroll
        for (int i = 0; i < 12; i++) acc[i] = 0.f;
        pin(acc);
        wg_fence();
#pragma unroll 1
        for (int kb = 0; kb < 9; kb++) {
#pragma unroll
            for (int ks = 0; ks < 4; ks++) wgmma_ss_n24<1>(acc, dA + (kb * 512 + ks * 2), dB + (kb * 4 + ks) * 16, 1);
        }
        wg_commit();
        wg_wait<0>();
        pin(acc);
        uint32_t pk[6];
#pragma unroll
        for (int b = 0; b < 3; b++) { pk[2 * b] = pack_bf16(acc[4 * b] * rs0, acc[4 * b + 1] * rs0); pk[2 * b + 1] = pack_bf16(acc[4 * b + 2] * rs1, acc[4 * b + 3] * rs1); }
        float n0 = 0.f, n1 = 0.f, vm = 0.f;
#pragma unroll
        for (int b = 0; b < 3; b++) {
            if (b < 2 || t == 0) {
                const float a = bf_lo(pk[2 * b]), c = bf_hi(pk[2 * b]), d = bf_lo(pk[2 * b + 1]), e = bf_hi(pk[2 * b + 1]);
                n0 = fmaf(a, a, fmaf(c, c, n0)); n1 = fmaf(d, d, fmaf(e, e, n1));
            }
        }
        n0 += __shfl_xor_sync(~0u, n0, 1); n0 += __shfl_xor_sync(~0u, n0, 2);
        n1 += __shfl_xor_sync(~0u, n1, 1); n1 += __shfl_xor_sync(~0u, n1, 2);
        vm = fmaxf(n0, n1);
        if (!(n0 == n0) || !(n1 == n1)) vm = __int_as_float(0x7F800000);
#pragma unroll
        for (int o = 4; o < 32; o <<= 1) vm = fmaxf(vm, __shfl_xor_sync(~0u, vm, o));
        if (t != 0) {
            uint32_t lo, hi;
            if (wg == 0) {
                const int grp = m * 8 + w * 2;
                const uint32_t c = t == 1 ? 0x42FE3F80u   : (t == 2 ? 0x00003BC0u   : 0u);
                lo = ((POLY_MASK >> (grp & 15)) & 1) ? c : 0u;
                hi = ((POLY_MASK >> ((grp + 1) & 15)) & 1) ? c : 0u;
            } else {
                lo = hi = t == 1 ? 0x00003F80u : 0u;
            }
            pk[4] = lo; pk[5] = hi;
        }
        uint32_t* dst = reinterpret_cast<uint32_t*>(wg == 0 ? g_kc : g_vc) + (m * 8 + w * 2) * 96 + g * 4 + t;
#pragma unroll
        for (int b = 0; b < 3; b++) { dst[b * 32] = pk[2 * b]; dst[96 + b * 32] = pk[2 * b + 1]; }
        if (lane == 0) g_kmax[m * 8 + warp] = (wg == 0) ? vm : (vm <= FAST_VMAX2 ? 0.f : __int_as_float(0x7F800000));
    }
}

constexpr int A_THREADS = 512;
constexpr int A_NPIECE = 8;
constexpr int A_OFF_Q = 2 * KV_BYTES;
constexpr int A_OFF_BAR = A_OFF_Q + 8 * 4096;
constexpr int A_SMEM = A_OFF_BAR + 128;

__device__ __forceinline__ uint32_t exp2_pair_fixed(float lo, float hi, uint32_t dep) {
    const uint32_t G = __byte_perm(__float_as_uint(lo), __float_as_uint(hi), 0x5410);
    uint32_t Hh;
    asm("lop3.b32 %0, %1, 0x007F007F, %2, 0xC0;" : "=r"(Hh) : "r"(G), "r"(dep));
    const uint32_t tt = hfma2(Hh, 0xF96BF96Bu, 0x358C358Cu);
    return G - hfma2(tt, Hh, 0u);
}

__global__ void __launch_bounds__(A_THREADS, 1)
k_attn(__nv_bfloat16* __restrict__ out) {
    extern __shared__ __align__(1024) uint8_t smem[];
    pdl_launch();
    const uint32_t sK = smem_u32(smem), sV = sK + KV_BYTES, bars = sK + A_OFF_BAR;
    const int tid = threadIdx.x;
    check_smem_base(sK);
    if (tid == 0) {
        for (int i = 0; i < A_NPIECE; i++) mbar_init(bars + i * 8, 1);
        bar_init_fence();
    }
    __syncthreads();
    pdl_wait();
    const int wg = __shfl_sync(~0u, tid >> 7, 0), w = (tid >> 5) & 3, lane = tid & 31, g = lane >> 2, t = lane & 3;
    const uint32_t* q32 = reinterpret_cast<const uint32_t*>(g_q);
    int row = (blockIdx.x * 8 + wg) * 64 + w * 16 + g;
    uint32_t nq[2][6];
#pragma unroll
    for (int r = 0; r < 2; r++) {
        const uint32_t* q = q32 + (row + r * 256) * 9;
        nq[r][0] = q[t]; nq[r][1] = q[72 + t]; nq[r][2] = q[4 + t]; nq[r][3] = q[76 + t]; nq[r][4] = q[8]; nq[r][5] = q[80];
    }
    constexpr int PB = KV_BYTES / A_NPIECE;
    const float4 km0 = reinterpret_cast<const float4*>(g_kmax)[lane], km1 = reinterpret_cast<const float4*>(g_kmax)[32 + lane];
    if (tid < 32 && elect_one()) {
        for (int i = 0; i < 2; i++) {
            mbar_expect(bars + i * 8, 2 * PB);
            bulk_g2s(sK + i * PB, reinterpret_cast<const char*>(g_kc) + i * PB, PB, bars + i * 8);
            bulk_g2s(sV + i * PB, reinterpret_cast<const char*>(g_vc) + i * PB, PB, bars + i * 8);
        }
    }
    float kmax2 = fmaxf(fmaxf(fmaxf(km0.x, km0.y), fmaxf(km0.z, km0.w)), fmaxf(fmaxf(km1.x, km1.y), fmaxf(km1.z, km1.w)));
#pragma unroll
    for (int o = 1; o < 32; o <<= 1) kmax2 = fmaxf(kmax2, __shfl_xor_sync(~0u, kmax2, o));
    if (tid < 32 && elect_one()) {
        for (int i = 2; i < A_NPIECE; i++) {
            mbar_expect(bars + i * 8, 2 * PB);
            bulk_g2s(sK + i * PB, reinterpret_cast<const char*>(g_kc) + i * PB, PB, bars + i * 8);
            bulk_g2s(sV + i * PB, reinterpret_cast<const char*>(g_vc) + i * PB, PB, bars + i * 8);
        }
    }
    uint32_t vote = 0;
#pragma unroll
    for (int r = 0; r < 2; r++) {
        const uint32_t (&q)[6] = nq[r];
        const float a0 = bf_lo(q[0]), a1 = bf_hi(q[0]), a2 = bf_lo(q[2]), a3 = bf_hi(q[2]);
        const float b0 = bf_lo(q[1]), b1 = bf_hi(q[1]), b2 = bf_lo(q[3]), b3 = bf_hi(q[3]);
        float n0 = a0 * a0 + a1 * a1 + a2 * a2 + a3 * a3, n1 = b0 * b0 + b1 * b1 + b2 * b2 + b3 * b3;
        if (t == 0) {
            const float c0 = bf_lo(q[4]), c1 = bf_hi(q[4]), d0 = bf_lo(q[5]), d1 = bf_hi(q[5]);
            n0 += c0 * c0 + c1 * c1; n1 += d0 * d0 + d1 * d1;
        }
        n0 += __shfl_xor_sync(~0u, n0, 1); n0 += __shfl_xor_sync(~0u, n0, 2);
        n1 += __shfl_xor_sync(~0u, n1, 1); n1 += __shfl_xor_sync(~0u, n1, 2);
        const bool unsafe = !(fmaxf(n0, n1) * kmax2 <= FAST_BOUND * FAST_BOUND) || !(n0 == n0) || !(n1 == n1);
        vote |= (__any_sync(~0u, unsafe) ? 1u : 0u) << r;
        const uint32_t cst = t == 1 ? 0x3F804780u : (t == 2 ? 0x00003F80u : 0u);
        const uint32_t sQ = sK + A_OFF_Q + (r * 4 + wg) * 4096 + (w * 2) * 512 + g * 16 + t * 4;
        asm volatile("st.shared.b32 [%0], %1;" ::"r"(sQ), "r"(q[0]) : "memory");
        asm volatile("st.shared.b32 [%0], %1;" ::"r"(sQ + 512), "r"(q[1]) : "memory");
        asm volatile("st.shared.b32 [%0], %1;" ::"r"(sQ + 128), "r"(q[2]) : "memory");
        asm volatile("st.shared.b32 [%0], %1;" ::"r"(sQ + 640), "r"(q[3]) : "memory");
        asm volatile("st.shared.b32 [%0], %1;" ::"r"(sQ + 256), "r"(t == 0 ? q[4] : cst) : "memory");
        asm volatile("st.shared.b32 [%0], %1;" ::"r"(sQ + 768), "r"(t == 0 ? q[5] : cst) : "memory");
        asm volatile("st.shared.b32 [%0], %1;" ::"r"(sQ + 384), "r"(0u) : "memory");
        asm volatile("st.shared.b32 [%0], %1;" ::"r"(sQ + 896), "r"(0u) : "memory");
    }
    const uint32_t sVote = bars + 64 + wg * 16;
    if (lane == 0) asm volatile("st.shared.b32 [%0], %1;" ::"r"(sVote + w * 4), "r"(vote) : "memory");
    proxy_fence();
    named_sync(wg + 1, 128);
    uint32_t unsafe_mask;
    {
        uint32_t v0, v1, v2, v3;
        asm volatile("ld.shared.v4.b32 {%0, %1, %2, %3}, [%4];" : "=r"(v0), "=r"(v1), "=r"(v2), "=r"(v3) : "r"(sVote));
        unsafe_mask = __shfl_sync(~0u, v0 | v1 | v2 | v3, 0);
    }
    if (unsafe_mask) {
#pragma unroll
        for (int r = 0; r < 2; r++) {
            if (((unsafe_mask >> r) & 1) && t != 0) {
                const uint32_t sQ = sK + A_OFF_Q + (r * 4 + wg) * 4096 + (w * 2) * 512 + g * 16 + t * 4;
                asm volatile("st.shared.b32 [%0], %1;" ::"r"(sQ + 256), "r"(0u) : "memory");
                asm volatile("st.shared.b32 [%0], %1;" ::"r"(sQ + 768), "r"(0u) : "memory");
            }
        }
        proxy_fence();
        named_sync(wg + 1, 128);
    }
#pragma unroll 1
    for (int rep = 0; rep < 2; rep++, row += 256) {
        if (rep == 1) {
            uint4* z = reinterpret_cast<uint4*>(out + (size_t)blockIdx.x * 16 * DM) + tid;
            z[0] = make_uint4(0u, 0u, 0u, 0u); z[A_THREADS] = make_uint4(0u, 0u, 0u, 0u);
            if (tid < 16 * DM * 2 / 16 - 2 * A_THREADS) z[2 * A_THREADS] = make_uint4(0u, 0u, 0u, 0u);
        }
        const uint32_t any_unsafe = (unsafe_mask >> rep) & 1;
        const uint64_t dQ0 = cdesc(A_OFF_Q, 128, 512, 0) + (rep * 4 + wg) * 256, dQ1 = dQ0 + 16;
        float o[12];
#pragma unroll
        for (int i = 0; i < 12; i++) o[i] = 0.f;
        pin(o);
        uint64_t dK0 = cdesc(0, 128, 384, 0), dK1 = cdesc(256, 0, 384, 0), dV = cdesc(KV_BYTES, 384, 128, 0);
        if (!any_unsafe) {
            float s[64];
#pragma unroll 1
            for (int j = 0; j < 16; j++) {
                if (rep == 0 && (j & 1) == 0) mbar_wait(bars + (j >> 1) * 8, 0);
                wg_fence();
                wgmma_ss_n128<0>(s, dQ0, dK0, 0);
                wgmma_ss_n128<0>(s, dQ1, dK1, 1);
                wg_commit();
                dK0 += 16 * 384 >> 4; dK1 += 16 * 384 >> 4;
                wg_wait<0>();
                pin(s);
                uint32_t p[32];
                {
                    constexpr int NP = 2 * __builtin_popcount(POLY_MASK), NM = 32 - NP;
                    float e[64];
#pragma unroll
                    for (int i = 0; i < 32; i++)
                        if (!((POLY_MASK >> (i >> 1)) & 1)) { e[2 * i] = ex2(s[2 * i]); e[2 * i + 1] = ex2(s[2 * i + 1]); p[i] = pack_bf16(e[2 * i], e[2 * i + 1]); }
                    int ip = 0;
#pragma unroll
                    for (int i = 0; i < 32; i++) {
                        if ((POLY_MASK >> (i >> 1)) & 1) {
                            const int mm = (ip * 2 * NM) / NP - CHAIN;
                            uint32_t dep = 0;
                            if (CHAIN > 0 && mm >= 0) {
                                int cnt = 0;
#pragma unroll
                                for (int q = 0; q < 32; q++)
                                    if (!((POLY_MASK >> (q >> 1)) & 1)) { if (cnt == (mm >> 1)) dep = __float_as_uint(e[2 * q + (mm & 1)]); cnt++; }
                            }
                            p[i] = exp2_pair_fixed(s[2 * i], s[2 * i + 1], dep);
                            ip++;
                        }
                    }
                }
                pin(p);
                wg_fence();
#pragma unroll
                for (int k = 0; k < 8; k++) wgmma_rs_n24<1>(o, p[4 * k], p[4 * k + 1], p[4 * k + 2], p[4 * k + 3], dV + k * 48, 1);
                wg_commit();
                dV += 16 * 384 >> 4;
                wg_wait<0>();
            }
        } else {
            float s[64];
            float m0 = -INFINITY, m1 = -INFINITY;
#pragma unroll 1
            for (int j = 0; j < 16; j++) {
                if (rep == 0 && (j & 1) == 0) mbar_wait(bars + (j >> 1) * 8, 0);
                wg_fence();
                wgmma_ss_n128<0>(s, dQ0, dK0, 0);
                wgmma_ss_n128<0>(s, dQ1, dK1, 1);
                wg_commit();
                dK0 += 16 * 384 >> 4; dK1 += 16 * 384 >> 4;
                wg_wait<0>();
                pin(s);
                float x0m = m0, x1m = m1;
#pragma unroll
                for (int b = 0; b < 16; b++) { x0m = fmaxf(x0m, fmaxf(s[4 * b], s[4 * b + 1])); x1m = fmaxf(x1m, fmaxf(s[4 * b + 2], s[4 * b + 3])); }
                x0m = fmaxf(x0m, __shfl_xor_sync(~0u, x0m, 1)); x0m = fmaxf(x0m, __shfl_xor_sync(~0u, x0m, 2));
                x1m = fmaxf(x1m, __shfl_xor_sync(~0u, x1m, 1)); x1m = fmaxf(x1m, __shfl_xor_sync(~0u, x1m, 2));
                const float c0 = ex2(m0 - x0m), c1 = ex2(m1 - x1m);
                m0 = x0m; m1 = x1m;
#pragma unroll
                for (int b = 0; b < 3; b++) { o[4 * b] *= c0; o[4 * b + 1] *= c0; o[4 * b + 2] *= c1; o[4 * b + 3] *= c1; }
                uint32_t p[32];
#pragma unroll
                for (int b = 0; b < 16; b++) {
                    p[2 * b] = pack_bf16(ex2(s[4 * b] - m0), ex2(s[4 * b + 1] - m0));
                    p[2 * b + 1] = pack_bf16(ex2(s[4 * b + 2] - m1), ex2(s[4 * b + 3] - m1));
                }
                pin(p); pin(o);
                wg_fence();
#pragma unroll
                for (int k = 0; k < 8; k++) wgmma_rs_n24<1>(o, p[4 * k], p[4 * k + 1], p[4 * k + 2], p[4 * k + 3], dV + k * 48, 1);
                wg_commit();
                dV += 16 * 384 >> 4;
                wg_wait<0>();
            }
        }
        pin(o);
        const float l0 = __shfl_sync(~0u, o[8], (lane & ~3) | 1), l1 = __shfl_sync(~0u, o[10], (lane & ~3) | 1);
        const float i0 = 1.0f / l0, i1 = 1.0f / l1;
#define OMODE 3
        if (OMODE == 0) {
            uint32_t* o32 = reinterpret_cast<uint32_t*>(g_o);
            o32[row * 9 + t] = pack_bf16(o[0] * i0, o[1] * i0);
            o32[(row + 8) * 9 + t] = pack_bf16(o[2] * i1, o[3] * i1);
            o32[row * 9 + 4 + t] = pack_bf16(o[4] * i0, o[5] * i0);
            o32[(row + 8) * 9 + 4 + t] = pack_bf16(o[6] * i1, o[7] * i1);
            if (t == 0) { o32[row * 9 + 8] = pack_bf16(o[8] * i0, o[9] * i0); o32[(row + 8) * 9 + 8] = pack_bf16(o[10] * i1, o[11] * i1); }
        } else {
            const uint32_t sO = sK + A_OFF_Q + (rep * 4 + wg) * 4096 + w * 1024, so = sO + g * 36 + t * 4;
            asm volatile("st.shared.b32 [%0], %1;" ::"r"(so), "r"(pack_bf16(o[0] * i0, o[1] * i0)) : "memory");
            asm volatile("st.shared.b32 [%0], %1;" ::"r"(so + 288), "r"(pack_bf16(o[2] * i1, o[3] * i1)) : "memory");
            asm volatile("st.shared.b32 [%0], %1;" ::"r"(so + 16), "r"(pack_bf16(o[4] * i0, o[5] * i0)) : "memory");
            asm volatile("st.shared.b32 [%0], %1;" ::"r"(so + 304), "r"(pack_bf16(o[6] * i1, o[7] * i1)) : "memory");
            if (t == 0) {
                asm volatile("st.shared.b32 [%0], %1;" ::"r"(so + 32), "r"(pack_bf16(o[8] * i0, o[9] * i0)) : "memory");
                asm volatile("st.shared.b32 [%0], %1;" ::"r"(so + 320), "r"(pack_bf16(o[10] * i1, o[11] * i1)) : "memory");
            }
            __syncwarp();
            uint4* dst = reinterpret_cast<uint4*>(reinterpret_cast<char*>(g_o) + (size_t)(row - g) * 36);
            uint4 v0, v1;
            asm volatile("ld.shared.v4.b32 {%0, %1, %2, %3}, [%4];" : "=r"(v0.x), "=r"(v0.y), "=r"(v0.z), "=r"(v0.w) : "r"(sO + lane * 16));
            asm volatile("ld.shared.v4.b32 {%0, %1, %2, %3}, [%4];" : "=r"(v1.x), "=r"(v1.y), "=r"(v1.z), "=r"(v1.w) : "r"(sO + 512 + (lane & 3) * 16));
            dst[lane] = v0;
            if (lane < 4) dst[32 + lane] = v1;
        }
    }
}

constexpr int O_THREADS = 416;
constexpr int O_OFF_STAT = P_A_BYTES + P_NST * P_B_STAGE + 256;
constexpr int O_SMEM = O_OFF_STAT + 9 * 64 * 8;

__global__ void __cluster_dims__(3, 1, 1) __launch_bounds__(O_THREADS, 1)
k_oproj(const __grid_constant__ CUtensorMap tmO, const __grid_constant__ CUtensorMap tmWo, const __grid_constant__ CUtensorMap tmX2, const __grid_constant__ CUtensorMap tmH, const __nv_bfloat16* __restrict__ x, const __nv_bfloat16* __restrict__ w1) {
    extern __shared__ __align__(1024) uint8_t smem[];
    const uint32_t sA = smem_u32(smem), sB = sA + P_A_BYTES, bars = sB + P_NST * P_B_STAGE;
    const uint32_t fullB = bars, emptyB = bars + 64, fullA = bars + 128;
    const int tid = threadIdx.x, warp = __shfl_sync(~0u, tid >> 5, 0), lane = tid & 31;
    const int m = blockIdx.x / 3, cg = blockIdx.x % 3;
    check_smem_base(sA);
    if (tid == 0) {
        prefetch_map(&tmO); prefetch_map(&tmWo); prefetch_map(&tmX2); prefetch_map(&tmH);
        for (int i = 0; i < P_NST; i++) { mbar_init(fullB + i * 8, 1); mbar_init(emptyB + i * 8, 12); }
        for (int i = 0; i < 9; i++) mbar_init(fullA + i * 8, 1);
        bar_init_fence();
        for (int kb = 0; kb < 9; kb++) mbar_expect(fullA + kb * 8, 8192);
    }
    __syncthreads();
    pdl_launch();
    if (warp == 12) {
        if (elect_one()) {
            for (int kb = 0; kb < 9; kb++) {
                const int s = kb >= P_NST ? kb - P_NST : kb;
                if (kb == 2) {
                    pdl_wait();
                    for (int ka = 0; ka < 9; ka++) tma_2d(sA + ka * 8192, &tmO, ka * 64, m * 64, fullA + ka * 8);
                }
                if (kb >= P_NST) mbar_wait(emptyB + s * 8, 0);
                mbar_expect(fullB + s * 8, P_B_STAGE);
                for (int a = 0; a < 3; a++) tma_2d(sB + s * P_B_STAGE + a * 8192, &tmWo, cg * 192 + a * 64, kb * 64, fullB + s * 8);
            }
            for (int i = 0; i < 6; i++) prefetch_l2(reinterpret_cast<const char*>(w1) + (size_t)blockIdx.x * (FF * DM * 2 / 96) + i * 9216, 9216);
        }
        return;
    }
    const int wg = warp >> 2, w = warp & 3, g = lane >> 2, t = lane & 3;
    uint32_t xr[16];
    {
        const uint32_t* x32 = reinterpret_cast<const uint32_t*>(x) + (((m * 64 + w * 16 + g) * DM + cg * 192 + wg * 64 + 2 * t) >> 1);
#pragma unroll
        for (int b = 0; b < 8; b++) { xr[2 * b] = __ldg(x32 + b * 4); xr[2 * b + 1] = __ldg(x32 + b * 4 + 4 * DM); }
    }
    float acc[32];
    proj_mma(acc, wg, fullB, emptyB, fullA, true, lane);
    named_sync(1, 384);
    float s0 = 0.f, q0 = 0.f, s1 = 0.f, q1 = 0.f;
#pragma unroll
    for (int b = 0; b < 8; b++) {
        const uint32_t xa = xr[2 * b], xb = xr[2 * b + 1];
        const uint32_t ha = pack_bf16(acc[4 * b] + bf_lo(xa), acc[4 * b + 1] + bf_hi(xa));
        const uint32_t hb = pack_bf16(acc[4 * b + 2] + bf_lo(xb), acc[4 * b + 3] + bf_hi(xb));
        xr[2 * b] = ha; xr[2 * b + 1] = hb;
        const float a = bf_lo(ha), c = bf_hi(ha), d = bf_lo(hb), e = bf_hi(hb);
        s0 += a + c; q0 = fmaf(a, a, fmaf(c, c, q0));
        s1 += d + e; q1 = fmaf(d, d, fmaf(e, e, q1));
    }
    s0 += __shfl_xor_sync(~0u, s0, 1); s0 += __shfl_xor_sync(~0u, s0, 2);
    q0 += __shfl_xor_sync(~0u, q0, 1); q0 += __shfl_xor_sync(~0u, q0, 2);
    s1 += __shfl_xor_sync(~0u, s1, 1); s1 += __shfl_xor_sync(~0u, s1, 2);
    q1 += __shfl_xor_sync(~0u, q1, 1); q1 += __shfl_xor_sync(~0u, q1, 2);
    const int r = w * 16 + g;
    const uint32_t sStat = sA + O_OFF_STAT;
    if (t < 3) {
        uint32_t dst;
        asm("mapa.shared::cluster.u32 %0, %1, %2;" : "=r"(dst) : "r"(sStat + ((cg * 3 + wg) * 64 + r) * 8), "r"(t));
        asm volatile("st.shared::cluster.v2.f32 [%0], {%1, %2};" ::"r"(dst), "f"(s0), "f"(q0) : "memory");
        asm volatile("st.shared::cluster.v2.f32 [%0], {%1, %2};" ::"r"(dst + 64), "f"(s1), "f"(q1) : "memory");
    }
    cluster_arrive();
    stage_tile<8>(xr, sA + wg * 8192, w, lane);
    proxy_fence();
    named_sync(2 + wg, 128);
    const bool leader = w == 0 && elect_one();
    if (leader) { tma_st_2d(&tmH, cg * 192 + wg * 64, m * 64, sA + wg * 8192); bulk_commit(); }
    cluster_wait();
    s0 = q0 = s1 = q1 = 0.f;
#pragma unroll
    for (int p = 0; p < 9; p++) {
        float a, b, c, d;
        asm volatile("ld.shared.v2.f32 {%0, %1}, [%2];" : "=f"(a), "=f"(b) : "r"(sStat + (p * 64 + r) * 8));
        asm volatile("ld.shared.v2.f32 {%0, %1}, [%2];" : "=f"(c), "=f"(d) : "r"(sStat + (p * 64 + r + 8) * 8));
        s0 += a; q0 += b; s1 += c; q1 += d;
    }
    const float m0 = s0 * (1.0f / DM), m1 = s1 * (1.0f / DM);
    const float rs0 = rsqrtf(fmaxf(q0 * (1.0f / DM) - m0 * m0, 0.f) + LN_EPS), rs1 = rsqrtf(fmaxf(q1 * (1.0f / DM) - m1 * m1, 0.f) + LN_EPS);
    const float sc0 = 0.5f * rs0, sc1 = 0.5f * rs1, n0 = -m0 * sc0, n1 = -m1 * sc1;
#pragma unroll
    for (int b = 0; b < 8; b++) {
        xr[2 * b] = pack_bf16(fmaf(bf_lo(xr[2 * b]), sc0, n0), fmaf(bf_hi(xr[2 * b]), sc0, n0));
        xr[2 * b + 1] = pack_bf16(fmaf(bf_lo(xr[2 * b + 1]), sc1, n1), fmaf(bf_hi(xr[2 * b + 1]), sc1, n1));
    }
    stage_tile<8>(xr, sA + (3 + wg) * 8192, w, lane);
    proxy_fence();
    named_sync(2 + wg, 128);
    if (leader) {
        tma_st_2d(&tmX2, cg * 192 + wg * 64, m * 64, sA + (3 + wg) * 8192);
        bulk_commit();
        bulk_wait_all();
    }
}

constexpr int F_THREADS = 384;
constexpr int F_NST = 6;
constexpr int F_STAGE = 96 * 128;
constexpr int F_X_BYTES = 9 * 16384;
constexpr int F_OFF_ST = F_X_BYTES;
constexpr int F_OFF_BAR = F_OFF_ST + F_NST * F_STAGE;
constexpr int F_SMEM = F_OFF_BAR + 256;

__device__ __forceinline__ float tanh_hw(float x) { float y; asm("tanh.approx.f32 %0, %1;" : "=f"(y) : "f"(x)); return y; }
__host__ __device__ constexpr int piece_begin(int p) { return p == 0 ? 0 : 3 * p + 1; }
template <int P>
__device__ __forceinline__ void silu_s1(const float (&acc)[32], float (&tmp)[8]) {
#pragma unroll
    for (int i = 2 * piece_begin(P); i < 2 * piece_begin(P + 1); i++) tmp[i - 2 * piece_begin(P)] = tanh_hw(acc[i]);
}
template <int C, int P>
__device__ __forceinline__ void silu_s2(const float (&acc)[32], const float (&tmp)[8], uint32_t (&h1)[144]) {
#pragma unroll
    for (int i = piece_begin(P); i < piece_begin(P + 1); i++) {
        const int k = 2 * (i - piece_begin(P));
        h1[C * 16 + i] = pack_bf16(fmaf(acc[2 * i], tmp[k], acc[2 * i]), fmaf(acc[2 * i + 1], tmp[k + 1], acc[2 * i + 1]));
    }
}
template <int J>
__device__ __forceinline__ void silu_slot_last(const float (&prev)[32], float (&tmp)[2][8], uint32_t (&h1)[144]) {
    if constexpr (J >= 1 && J <= 4) {
#pragma unroll
        for (int i = 0; i < 4; i++) {
            const int q = 4 * (J - 1) + i;
            h1[128 + q] = pack_bf16(fmaf(prev[2 * q], tmp[(J - 1) & 1][2 * i], prev[2 * q]), fmaf(prev[2 * q + 1], tmp[(J - 1) & 1][2 * i + 1], prev[2 * q + 1]));
        }
    }
    if constexpr (J <= 3) {
#pragma unroll
        for (int i = 0; i < 8; i++) tmp[J & 1][i] = tanh_hw(prev[8 * J + i]);
        pin(tmp[J & 1]);
    }
}
template <int C, int J>
__device__ __forceinline__ void silu_slot(const float (&prev)[32], float (&tmp)[2][8], uint32_t (&h1)[144]) {
    if constexpr (J >= 1) silu_s2<C, J - 1>(prev, tmp[(J - 1) & 1], h1);
    if constexpr (J <= 4) { silu_s1<J>(prev, tmp[J & 1]); pin(tmp[J & 1]); }
}

struct FfnPipe {
    uint32_t full, empty;
    int lane;
    __device__ __forceinline__ void acquire(int s, uint32_t ph) const { mbar_wait(full + s * 8, ph); }
    __device__ __forceinline__ void release(int s) const { if (lane == 0) mbar_arrive(empty + s * 8); }
};

template <int C>
__device__ __forceinline__ void ffn_phase1_chunk(float (&cur)[32], float (&prev)[32], uint32_t (&h1)[144], const FfnPipe& pp, uint64_t dx, uint32_t fullX) {
    float tmp[2][8];
    const uint64_t dw = cdesc(F_OFF_ST, 8192, 1024, 1) + blockIdx.y * (C + 1);
    dx += blockIdx.y * C;
#pragma unroll
    for (int j = 0; j < 6; j++) {
        if (C == 0) { mbar_wait(fullX + ((6 * j) >> 2) * 8, 0); mbar_wait(fullX + ((6 * j + 5) >> 2) * 8, 0); }
        pp.acquire(j, C & 1);
        if (j == 0) pin(cur);
        wg_fence();
#pragma unroll
        for (int i = 0; i < 6; i++) {
            const int ks = 6 * j + i;
            wgmma_ss_n64<1>(cur, dx + ((ks >> 2) * 1024 + (ks & 3) * 2), dw + ((j * F_STAGE + i * 2048) >> 4), ks != 0);
        }
        wg_commit();
        if (C > 0 || j > 0) { wg_wait<1>(); pp.release((j + 5) % 6); }
        if (C > 0) {
            constexpr int CP = C > 0 ? C - 1 : 0;
            pin(prev);
            if (j == 0) silu_slot<CP, 0>(prev, tmp, h1);
            if (j == 1) silu_slot<CP, 1>(prev, tmp, h1);
            if (j == 2) silu_slot<CP, 2>(prev, tmp, h1);
            if (j == 3) silu_slot<CP, 3>(prev, tmp, h1);
            if (j == 4) silu_slot<CP, 4>(prev, tmp, h1);
            if (j == 5) silu_slot<CP, 5>(prev, tmp, h1);
        }
    }
}

__device__ __forceinline__ void ffn_stage_chunk(const float (&acc)[32], uint32_t stg, int w, int lane, bool resid, uint32_t fullH) {
    uint32_t pk[16];
    if (resid) {
        mbar_wait(fullH, 0);
        const int r = w * 16 + (lane & 7) + ((lane >> 3) & 1) * 8;
#pragma unroll
        for (int b = 0; b < 8; b += 2) {
            uint32_t h0, h1, h2, h3;
            asm volatile("ldmatrix.sync.aligned.m8n8.x4.shared.b16 {%0, %1, %2, %3}, [%4];" : "=r"(h0), "=r"(h1), "=r"(h2), "=r"(h3) : "r"(stg + r * 128 + (((b + (lane >> 4)) ^ (r & 7)) << 4)) : "memory");
            pk[2 * b] = pack_bf16(acc[4 * b] + bf_lo(h0), acc[4 * b + 1] + bf_hi(h0));
            pk[2 * b + 1] = pack_bf16(acc[4 * b + 2] + bf_lo(h1), acc[4 * b + 3] + bf_hi(h1));
            pk[2 * b + 2] = pack_bf16(acc[4 * b + 4] + bf_lo(h2), acc[4 * b + 5] + bf_hi(h2));
            pk[2 * b + 3] = pack_bf16(acc[4 * b + 6] + bf_lo(h3), acc[4 * b + 7] + bf_hi(h3));
        }
    } else {
#pragma unroll
        for (int i = 0; i < 16; i++) pk[i] = pack_bf16(acc[2 * i], acc[2 * i + 1]);
    }
    stage_tile<8>(pk, stg, w, lane);
}
__device__ __forceinline__ void ffn_reduce_chunk(const CUtensorMap* tmOut, uint32_t stg, int col, int row, int w, int wgid, bool leader) {
    proxy_fence();
    if (w != 0) {
        asm volatile("bar.arrive %0, 128;" ::"r"(2 + wgid) : "memory");
    } else {
        named_sync(2 + wgid, 128);
        if (leader) { tma_red_2d(tmOut, col, row, stg); bulk_commit(); }
    }
}

__device__ __forceinline__ void ffn_load_residual(float (&acc)[32], uint32_t stg, int w, int lane, uint32_t fullH) {
    mbar_wait(fullH, 0);
    const int r = w * 16 + (lane & 7) + ((lane >> 3) & 1) * 8;
#pragma unroll
    for (int b = 0; b < 8; b += 2) {
        uint32_t h0, h1, h2, h3;
        asm volatile("ldmatrix.sync.aligned.m8n8.x4.shared.b16 {%0, %1, %2, %3}, [%4];" : "=r"(h0), "=r"(h1), "=r"(h2), "=r"(h3) : "r"(stg + r * 128 + (((b + (lane >> 4)) ^ (r & 7)) << 4)) : "memory");
        acc[4 * b] = bf_lo(h0); acc[4 * b + 1] = bf_hi(h0); acc[4 * b + 2] = bf_lo(h1); acc[4 * b + 3] = bf_hi(h1);
        acc[4 * b + 4] = bf_lo(h2); acc[4 * b + 5] = bf_hi(h2); acc[4 * b + 6] = bf_lo(h3); acc[4 * b + 7] = bf_hi(h3);
    }
}

template <int MODE>
__device__ __forceinline__ void ffn_phase2_chunk(float (&cur)[32], float (&prev)[32], uint32_t (&h1)[144], const FfnPipe& pp, uint32_t ph, const CUtensorMap* tmOut, uint32_t stg_prev, int col_prev, int row, int w, int lane, int wgid, bool leader,
                                                 uint32_t fullH, uint32_t stg_res) {
    const uint64_t dw = cdesc(F_OFF_ST, 8192, 1024, 1) + blockIdx.y * col_prev;
    float tmp[2][8];
#pragma unroll
    for (int j = 0; j < 6; j++) {
        pp.acquire(j, ph);
        if (j == 0) pin(cur);
        if (MODE == 0 && j == 5) pin(h1);
        wg_fence();
#pragma unroll
        for (int i = 0; i < 6; i++) {
            const int f = (6 * j + i) * 4;
            wgmma_rs_n64<1>(cur, h1[f], h1[f + 1], h1[f + 2], h1[f + 3], dw + ((j * F_STAGE + i * 2048) >> 4), (j | i) != 0);
        }
        wg_commit();
        wg_wait<1>();
        pp.release((j + 5) % 6);
        if (MODE == 0) {
            pin(prev);
            if (j == 0) silu_slot_last<0>(prev, tmp, h1);
            if (j == 1) silu_slot_last<1>(prev, tmp, h1);
            if (j == 2) silu_slot_last<2>(prev, tmp, h1);
            if (j == 3) silu_slot_last<3>(prev, tmp, h1);
            if (j == 4) silu_slot_last<4>(prev, tmp, h1);
        } else {
            if (j == 0) { pin(prev); ffn_stage_chunk(prev, stg_prev, w, lane, false, fullH); }
            if (j == 1) ffn_reduce_chunk(tmOut, stg_prev, col_prev, row, w, wgid, leader);
            if (MODE == 2 && j == 2) { ffn_load_residual(prev, stg_res, w, lane, fullH); pin(prev); }
        }
    }
}

template <int HALF, int J>
__device__ __forceinline__ void ffn_half_group(float (&cur)[32], uint32_t (&h1)[144], const FfnPipe& pp, uint64_t dw) {
    if (HALF == 0) pp.acquire(J, 1);
    wg_fence();
#pragma unroll
    for (int i = 0; i < 6; i++) {
        const int f = (6 * J + i) * 4;
        wgmma_rs_n32_of32<1, HALF * 16>(cur, h1[f], h1[f + 1], h1[f + 2], h1[f + 3], dw + (((J * F_STAGE + i * 2048) >> 4) + HALF * 4), 1);
    }
    wg_commit();
}
template <int HALF>
__device__ __forceinline__ void ffn_store_half(float (&acc)[32], const CUtensorMap* tmHalf, uint32_t stg, int col, int row, int w, int lane, int wgid, bool leader) {
    const int r = w * 16 + (lane & 7) + ((lane >> 3) & 1) * 8;
#pragma unroll
    for (int i = 0; i < 16; i++) asm volatile("" : "+f"(acc[HALF * 16 + i])::"memory");
#pragma unroll
    for (int b = 0; b < 4; b += 2) {
        const int q = HALF * 16 + 4 * b;
        stmatrix_x4(stg + r * 64 + (((b + (lane >> 4)) ^ ((r >> 1) & 3)) << 4), pack_bf16(acc[q], acc[q + 1]), pack_bf16(acc[q + 2], acc[q + 3]),
                    pack_bf16(acc[q + 4], acc[q + 5]), pack_bf16(acc[q + 6], acc[q + 7]));
    }
    ffn_reduce_chunk(tmHalf, stg, col + HALF * 32, row, w, wgid, leader);
}

__global__ void __launch_bounds__(F_THREADS, 1)
k_ffn(const __grid_constant__ CUtensorMap tmX2, const __grid_constant__ CUtensorMap tmW1, const __grid_constant__ CUtensorMap tmW2, const __grid_constant__ CUtensorMap tmOut,
      const __grid_constant__ CUtensorMap tmRes, const __grid_constant__ CUtensorMap tmHalf, const __nv_bfloat16* __restrict__ w2) {
    extern __shared__ __align__(1024) uint8_t smem[];
    const uint32_t sX = smem_u32(smem), sSt = sX + F_OFF_ST, bars = sX + F_OFF_BAR;
    const uint32_t full = bars, empty = bars + 64, fullX = bars + 128, fullH = bars + 208;
    const int tid = threadIdx.x, warp = __shfl_sync(~0u, tid >> 5, 0), lane = tid & 31;
    const int m = blockIdx.x >> 3, fs = blockIdx.x & 7;
    check_smem_base(sX);
    if (tid == 0) {
        prefetch_map(&tmW1); prefetch_map(&tmX2); prefetch_map(&tmW2); prefetch_map(&tmOut); prefetch_map(&tmRes); prefetch_map(&tmHalf);
        for (int i = 0; i < F_NST; i++) { mbar_init(full + i * 8, 1); mbar_init(empty + i * 8, 8); }
        for (int i = 0; i < 9; i++) mbar_init(fullX + i * 8, 1);
        mbar_init(fullH, 1); mbar_init(fullH + 8, 1);
        bar_init_fence();
        for (int kb = 0; kb < 9; kb++) mbar_expect(fullX + kb * 8, 16384);
    }
    __syncthreads();
    if (warp < 4) {
        asm volatile("setmaxnreg.dec.sync.aligned.u32 24;");
        if (warp == 1 && lane < 9) prefetch_l2(reinterpret_cast<const char*>(w2) + ((size_t)fs * 576 + m * 36 + lane * 4) * (DM * 2), 4 * DM * 2);
        if (warp == 0 && elect_one()) {
#pragma unroll 1
            for (int c = 0; c < 18; c++) {
                int col = c - 9 + fs;
                if (col >= 9) col -= 9;
#pragma unroll 1
                for (int j = 0; j < 6; j++) {
                    mbar_wait(empty + j * 8, (c & 1) ^ 1);
                    mbar_expect(full + j * 8, F_STAGE);
                    if (c < 9) tma_2d(sSt + j * F_STAGE, &tmW1, fs * 576 + c * 64, j * 96, full + j * 8);
                    else tma_2d(sSt + j * F_STAGE, &tmW2, col * 64, fs * 576 + j * 96, full + j * 8);
                }
            }
        }
    } else {
        asm volatile("setmaxnreg.inc.sync.aligned.u32 240;");
        const int wgid = (warp >> 2) - 1, w = warp & 3;
        pdl_wait();
        if (warp == 4 && elect_one()) {
            for (int kb = 0; kb < 9; kb++) tma_2d(sX + kb * 16384, &tmX2, kb * 64, m * 128, fullX + kb * 8);
        }
        __syncwarp();
        FfnPipe pp{full, empty, lane};
        const uint64_t xlo = cdesc(0, 16, 1024, 1) + wgid * 512;
        uint32_t h1[144];
        float acc0[32], acc1[32];
        ffn_phase1_chunk<0>(acc0, acc1, h1, pp, xlo, fullX);
        ffn_phase1_chunk<1>(acc1, acc0, h1, pp, xlo, fullX);
        ffn_phase1_chunk<2>(acc0, acc1, h1, pp, xlo, fullX);
        ffn_phase1_chunk<3>(acc1, acc0, h1, pp, xlo, fullX);
        ffn_phase1_chunk<4>(acc0, acc1, h1, pp, xlo, fullX);
        ffn_phase1_chunk<5>(acc1, acc0, h1, pp, xlo, fullX);
        ffn_phase1_chunk<6>(acc0, acc1, h1, pp, xlo, fullX);
        ffn_phase1_chunk<7>(acc1, acc0, h1, pp, xlo, fullX);
        ffn_phase1_chunk<8>(acc0, acc1, h1, pp, xlo, fullX);
        const int row = m * 128 + wgid * 64;
        const uint32_t stg = sX + wgid * 8192;
        int c = fs, cprev = 0;
        const bool leader = w == 0 && elect_one();
        const uint32_t myH = fullH + wgid * 8;
        ffn_phase2_chunk<0>(acc1, acc0, h1, pp, 1, &tmOut, 0, 0, row, w, lane, wgid, leader, myH, 0);
        if (leader) {
            const int c8 = fs == 0 ? 8 : fs - 1;
            mbar_expect(myH, fs == 0 ? 16384 : 8192);
            tma_2d(stg + 8 * 16384, &tmRes, c8 * 64, row, myH);
            if (fs == 0) tma_2d(stg + 7 * 16384, &tmRes, 7 * 64, row, myH);
        }
        cprev = c; if (++c == 9) c = 0;
#pragma unroll 1
        for (int j = 1; j < 7; j += 2) {
            ffn_phase2_chunk<1>(acc0, acc1, h1, pp, 0, &tmOut, stg + (j - 1) * 16384, cprev * 64, row, w, lane, wgid, leader, myH, 0);
            cprev = c; if (++c == 9) c = 0;
            ffn_phase2_chunk<1>(acc1, acc0, h1, pp, 1, &tmOut, stg + j * 16384, cprev * 64, row, w, lane, wgid, leader, myH, 0);
            cprev = c; if (++c == 9) c = 0;
        }
        ffn_phase2_chunk<2>(acc0, acc1, h1, pp, 0, &tmOut, stg + 6 * 16384, cprev * 64, row, w, lane, wgid, leader, myH, stg + 8 * 16384);
        cprev = c; if (++c == 9) c = 0;
        {
            const uint64_t dw = cdesc(F_OFF_ST, 8192, 1024, 1) + blockIdx.y * (c + 1);
            pin(acc1);
            ffn_half_group<0, 0>(acc1, h1, pp, dw);
            wg_wait<1>();
            pp.release(5);
            pin(acc0);
            ffn_stage_chunk(acc0, stg + 7 * 16384, w, lane, fs == 0, myH);
            ffn_half_group<0, 1>(acc1, h1, pp, dw);
            wg_wait<2>();
            ffn_reduce_chunk(&tmOut, stg + 7 * 16384, cprev * 64, row, w, wgid, leader);
            ffn_half_group<0, 2>(acc1, h1, pp, dw);
            ffn_half_group<0, 3>(acc1, h1, pp, dw);
            ffn_half_group<0, 4>(acc1, h1, pp, dw);
            ffn_half_group<0, 5>(acc1, h1, pp, dw);
            ffn_half_group<1, 0>(acc1, h1, pp, dw);
            ffn_half_group<1, 1>(acc1, h1, pp, dw);
            wg_wait<2>();
            ffn_store_half<0>(acc1, &tmHalf, stg + 8 * 16384, c * 64, row, w, lane, wgid, leader);
            ffn_half_group<1, 2>(acc1, h1, pp, dw);
            ffn_half_group<1, 3>(acc1, h1, pp, dw);
            ffn_half_group<1, 4>(acc1, h1, pp, dw);
            ffn_half_group<1, 5>(acc1, h1, pp, dw);
            wg_wait<0>();
            pin(acc1);
            ffn_store_half<1>(acc1, &tmHalf, stg + 8 * 16384 + 4096, c * 64, row, w, lane, wgid, leader);
        }
        if (leader) bulk_wait_all();
    }
}

typedef CUresult (*EncodeFn)(CUtensorMap*, CUtensorMapDataType, cuuint32_t, void*, const cuuint64_t*, const cuuint64_t*, const cuuint32_t*, const cuuint32_t*,
                             CUtensorMapInterleave, CUtensorMapSwizzle, CUtensorMapL2promotion, CUtensorMapFloatOOBfill);

CUtensorMap make_map(EncodeFn enc, const void* base, int rows, int cols, int box_rows, int box_cols = 64) {
    CUtensorMap tm;
    cuuint64_t dims[2] = {(cuuint64_t)cols, (cuuint64_t)rows};
    cuuint64_t strides[1] = {(cuuint64_t)cols * 2};
    cuuint32_t box[2] = {(cuuint32_t)box_cols, (cuuint32_t)box_rows};
    cuuint32_t es[2] = {1, 1};
    enc(&tm, CU_TENSOR_MAP_DATA_TYPE_BFLOAT16, 2, const_cast<void*>(base), dims, strides, box, es, CU_TENSOR_MAP_INTERLEAVE_NONE,
        box_cols == 64 ? CU_TENSOR_MAP_SWIZZLE_128B : CU_TENSOR_MAP_SWIZZLE_64B, CU_TENSOR_MAP_L2_PROMOTION_L2_256B, CU_TENSOR_MAP_FLOAT_OOB_FILL_NONE);
    return tm;
}

template <typename... KArgs, typename... Args>
void launch(void (*kern)(KArgs...), int grid, int block, int smem, bool pdl, Args... args) {
    cudaLaunchConfig_t cfg = {};
    cfg.gridDim = dim3(grid); cfg.blockDim = dim3(block); cfg.dynamicSmemBytes = smem; cfg.stream = cudaStreamPerThread;
    cudaLaunchAttribute at[1];
    at[0].id = cudaLaunchAttributeProgrammaticStreamSerialization;
    at[0].val.programmaticStreamSerializationAllowed = 1;
    cfg.attrs = at; cfg.numAttrs = pdl ? 1 : 0;
    cudaLaunchKernelEx(&cfg, kern, KArgs(args)...);
}

}

extern "C" void kernel_launch(void* const* d_in, const int* in_sizes, int n_in, void* d_out, int out_size) {
    const __nv_bfloat16* x = (const __nv_bfloat16*)d_in[0];
    const __nv_bfloat16* wq = (const __nv_bfloat16*)d_in[1];
    const __nv_bfloat16* wk = (const __nv_bfloat16*)d_in[2];
    const __nv_bfloat16* wv = (const __nv_bfloat16*)d_in[3];
    const __nv_bfloat16* wo = (const __nv_bfloat16*)d_in[4];
    const __nv_bfloat16* w1 = (const __nv_bfloat16*)d_in[6];
    const __nv_bfloat16* w2 = (const __nv_bfloat16*)d_in[7];
    __nv_bfloat16* out = (__nv_bfloat16*)d_out;

    static EncodeFn enc = nullptr;
    static void *p_o = nullptr, *p_x2 = nullptr, *p_q = nullptr, *p_res = nullptr;
    if (!enc) {
        cudaDriverEntryPointQueryResult qr;
        cudaGetDriverEntryPoint("cuTensorMapEncodeTiled", (void**)&enc, cudaEnableDefault, &qr);
        cudaGetSymbolAddress(&p_o, g_o);
        cudaGetSymbolAddress(&p_x2, g_x2);
        cudaGetSymbolAddress(&p_res, g_h);
        cudaGetSymbolAddress(&p_q, g_q);
        cudaFuncSetAttribute(k_qkv, cudaFuncAttributeMaxDynamicSharedMemorySize, Q_SMEM);
        cudaFuncSetAttribute(k_attn, cudaFuncAttributeMaxDynamicSharedMemorySize, A_SMEM);
        cudaFuncSetAttribute(k_oproj, cudaFuncAttributeMaxDynamicSharedMemorySize, O_SMEM);
        cudaFuncSetAttribute(k_ffn, cudaFuncAttributeMaxDynamicSharedMemorySize, F_SMEM);
    }
    const CUtensorMap tmWq = make_map(enc, wq, DM, DM, 192);
    const CUtensorMap tmWo = make_map(enc, wo, DM, DM, 64);
    const CUtensorMap tmO = make_map(enc, p_o, SEQ, DM, 64);
    const CUtensorMap tmX2st = make_map(enc, p_x2, SEQ, DM, 64);
    const CUtensorMap tmX2ld = make_map(enc, p_x2, SEQ, DM, 128);
    const CUtensorMap tmRes = make_map(enc, p_res, SEQ, DM, 64);
    const CUtensorMap tmQ = make_map(enc, p_q, SEQ, DM, 64);
    const CUtensorMap tmW1 = make_map(enc, w1, DM, FF, 96);
    const CUtensorMap tmW2 = make_map(enc, w2, FF, DM, 96);
    const CUtensorMap tmOut = make_map(enc, out, SEQ, DM, 64);
    const CUtensorMap tmHalf = make_map(enc, out, SEQ, DM, 64, 32);

    launch(k_qkv, 128, Q_THREADS, Q_SMEM, false, tmWq, tmQ, x, wk, wv);
    launch(k_attn, 128, A_THREADS, A_SMEM, true, out);
    launch(k_oproj, 96, O_THREADS, O_SMEM, true, tmO, tmWo, tmX2st, tmRes, x, w1);
    launch(k_ffn, 128, F_THREADS, F_SMEM, true, tmX2ld, tmW1, tmW2, tmOut, tmRes, tmHalf, w2);
}
```

```cpp
#include <cuda_runtime.h>
#include <cuda_bf16.h>
#include <cuda.h>
#include <stdint.h>

namespace {

constexpr int SEQ = 2048, DM = 576, FF = 4608;
constexpr int KV_BYTES = SEQ * 48;
constexpr float LN_EPS = 1e-5f;
constexpr float LOG2E = 1.4426950408889634f;
constexpr float Q_SCALE = 0.23570226039551584f * LOG2E;

constexpr uint32_t POLY_MASK = 0xB5B5u;
constexpr int CHAIN = 6;
constexpr float FAST_BOUND = 90.0f;
constexpr float FAST_VMAX2 = 1e12f;

__device__ __align__(1024) __nv_bfloat16 g_q[SEQ * DM];
__device__ __align__(1024) uint4 g_kc[KV_BYTES / 16];
__device__ __align__(1024) uint4 g_vc[KV_BYTES / 16];
__device__ __align__(16) float g_kmax[256];
__device__ __align__(1024) __nv_bfloat16 g_o[SEQ * DM];
__device__ __align__(1024) __nv_bfloat16 g_h[SEQ * DM];
__device__ __align__(1024) __nv_bfloat16 g_x2[SEQ * DM];


__device__ __forceinline__ uint32_t smem_u32(const void* p) { return (uint32_t)__cvta_generic_to_shared(p); }
__device__ __forceinline__ void wg_fence() { asm volatile("wgmma.fence.sync.aligned;" ::: "memory"); }
__device__ __forceinline__ void wg_commit() { asm volatile("wgmma.commit_group.sync.aligned;" ::: "memory"); }
template <int N> __device__ __forceinline__ void wg_wait() { asm volatile("wgmma.wait_group.sync.aligned %0;" ::"n"(N) : "memory"); }
template <int N> __device__ __forceinline__ void pin(float (&r)[N]) {
#pragma unroll
    for (int i = 0; i < N; i++) asm volatile("" : "+f"(r[i])::"memory");
}
template <int N> __device__ __forceinline__ void pin(uint32_t (&r)[N]) {
#pragma unroll
    for (int i = 0; i < N; i++) asm volatile("" : "+r"(r[i])::"memory");
}
constexpr uint32_t SMEM0 = 0x400;
__host__ __device__ constexpr uint64_t cdesc(uint32_t off, uint32_t lbo, uint32_t sbo, uint32_t swz) {
    return (uint64_t)(((SMEM0 + off) & 0x3FFFF) >> 4) | ((uint64_t)(lbo >> 4) << 16) | ((uint64_t)(sbo >> 4) << 32) | ((uint64_t)swz << 62);
}
__device__ __forceinline__ void check_smem_base(uint32_t base) { if ((base & 0x3FFFF) != SMEM0) __trap(); }

__device__ __forceinline__ void mbar_init(uint32_t bar, int cnt) { asm volatile("mbarrier.init.shared::cta.b64 [%0], %1;" ::"r"(bar), "r"(cnt) : "memory"); }
__device__ __forceinline__ void mbar_expect(uint32_t bar, int bytes) { asm volatile("mbarrier.arrive.expect_tx.shared::cta.b64 _, [%0], %1;" ::"r"(bar), "r"(bytes) : "memory"); }
__device__ __forceinline__ void mbar_arrive(uint32_t bar) { asm volatile("mbarrier.arrive.shared::cta.b64 _, [%0];" ::"r"(bar) : "memory"); }
__device__ __forceinline__ void mbar_wait(uint32_t bar, uint32_t parity) {
    asm volatile(
        "{\n.reg .pred p;\n.reg .u32 n;\nmov.u32 n, 0;\n"
        "LAB_WAIT:\n"
        "mbarrier.try_wait.parity.shared::cta.b64 p, [%0], %1;\n"
        "@p bra DONE;\n"
        "add.u32 n, n, 1;\n"
        "setp.lt.u32 p, n, 4000000;\n"
        "@p bra LAB_WAIT;\n"
        "trap;\n"
        "DONE:\n}\n" ::"r"(bar), "r"(parity) : "memory");
}
__device__ __forceinline__ void bar_init_fence() {
    asm volatile("fence.mbarrier_init.release.cluster;" ::: "memory");
    asm volatile("fence.proxy.async.shared::cta;" ::: "memory");
}
__device__ __forceinline__ void proxy_fence() { asm volatile("fence.proxy.async.shared::cta;" ::: "memory"); }
__device__ __forceinline__ void named_sync(int id, int n) { asm volatile("bar.sync %0, %1;" ::"r"(id), "r"(n) : "memory"); }
__device__ __forceinline__ void bulk_g2s(uint32_t dst, const void* src, int bytes, uint32_t bar) {
    asm volatile("cp.async.bulk.shared::cluster.global.mbarrier::complete_tx::bytes [%0], [%1], %2, [%3];" ::"r"(dst), "l"(src), "r"(bytes), "r"(bar) : "memory");
}
__device__ __forceinline__ void tma_2d(uint32_t dst, const CUtensorMap* tm, int c0, int c1, uint32_t bar) {
    asm volatile("cp.async.bulk.tensor.2d.shared::cluster.global.mbarrier::complete_tx::bytes [%0], [%1, {%3, %4}], [%2];" ::"r"(dst), "l"(tm), "r"(bar), "r"(c0), "r"(c1) : "memory");
}
__device__ __forceinline__ void cluster_arrive() { asm volatile("barrier.cluster.arrive.release.aligned;" ::: "memory"); }
__device__ __forceinline__ void cluster_wait() { asm volatile("barrier.cluster.wait.acquire.aligned;" ::: "memory"); }
__device__ __forceinline__ void tma_red_2d(const CUtensorMap* tm, int c0, int c1, uint32_t src) {
    asm volatile("cp.reduce.async.bulk.tensor.2d.global.shared::cta.add.tile.bulk_group [%0, {%2, %3}], [%1];" ::"l"(tm), "r"(src), "r"(c0), "r"(c1) : "memory");
}
__device__ __forceinline__ void tma_st_2d(const CUtensorMap* tm, int c0, int c1, uint32_t src) {
    asm volatile("cp.async.bulk.tensor.2d.global.shared::cta.tile.bulk_group [%0, {%2, %3}], [%1];" ::"l"(tm), "r"(src), "r"(c0), "r"(c1) : "memory");
}
__device__ __forceinline__ void bulk_commit() { asm volatile("cp.async.bulk.commit_group;" ::: "memory"); }
__device__ __forceinline__ void bulk_wait_all() { asm volatile("cp.async.bulk.wait_group.read 0;" ::: "memory"); }
__device__ __forceinline__ bool elect_one() {
    uint32_t p;
    asm volatile("{\n.reg .pred P;\nelect.sync _|P, 0xffffffff;\nselp.b32 %0, 1, 0, P;\n}\n" : "=r"(p));
    return p != 0;
}
__device__ __forceinline__ void prefetch_l2(const void* p, int bytes) { asm volatile("cp.async.bulk.prefetch.L2.global [%0], %1;" ::"l"(p), "r"(bytes) : "memory"); }
__device__ __forceinline__ void prefetch_map(const CUtensorMap* tm) { asm volatile("prefetch.tensormap [%0];" ::"l"(tm) : "memory"); }
__device__ __forceinline__ void pdl_launch() { asm volatile("griddepcontrol.launch_dependents;" ::: "memory"); }
__device__ __forceinline__ void pdl_wait() { asm volatile("griddepcontrol.wait;" ::: "memory"); }
__device__ __forceinline__ float ex2(float x) { float y; asm("ex2.approx.ftz.f32 %0, %1;" : "=f"(y) : "f"(x)); return y; }
__device__ __forceinline__ uint32_t pack_bf16(float lo, float hi) { uint32_t r; asm("cvt.rn.bf16x2.f32 %0, %1, %2;" : "=r"(r) : "f"(hi), "f"(lo)); return r; }
__device__ __forceinline__ float bf_lo(uint32_t v) { return __uint_as_float(v << 16); }
__device__ __forceinline__ float bf_hi(uint32_t v) { return __uint_as_float(v & 0xFFFF0000u); }
__device__ __forceinline__ uint32_t hfma2(uint32_t a, uint32_t b, uint32_t c) { uint32_t r; asm("fma.rn.f16x2 %0, %1, %2, %3;" : "=r"(r) : "r"(a), "r"(b), "r"(c)); return r; }
__device__ __forceinline__ void stmatrix_x4(uint32_t addr, uint32_t r0, uint32_t r1, uint32_t r2, uint32_t r3) {
    asm volatile("stmatrix.sync.aligned.m8n8.x4.shared.b16 [%0], {%1, %2, %3, %4};" ::"r"(addr), "r"(r0), "r"(r1), "r"(r2), "r"(r3) : "memory");
}

template <int TB> __device__ __forceinline__ void wgmma_ss_n24(float (&d)[12], uint64_t da, uint64_t db, int sc) {
    asm volatile("{\n.reg .pred p;\nsetp.ne.b32 p, %14, 0;\n"
        "wgmma.mma_async.sync.aligned.m64n24k16.f32.bf16.bf16 {%0, %1, %2, %3, %4, %5, %6, %7, %8, %9, %10, %11}, %12, %13, p, 1, 1, 0, %15;\n}\n"
        : "+f"(d[0]), "+f"(d[1]), "+f"(d[2]), "+f"(d[3]), "+f"(d[4]), "+f"(d[5]), "+f"(d[6]), "+f"(d[7]), "+f"(d[8]), "+f"(d[9]), "+f"(d[10]), "+f"(d[11])
        : "l"(da), "l"(db), "r"(sc), "n"(TB));
}
template <int TB> __device__ __forceinline__ void wgmma_ss_n64(float (&d)[32], uint64_t da, uint64_t db, int sc) {
    asm volatile("{\n.reg .pred p;\nsetp.ne.b32 p, %34, 0;\n"
        "wgmma.mma_async.sync.aligned.m64n64k16.f32.bf16.bf16 {%0, %1, %2, %3, %4, %5, %6, %7, %8, %9, %10, %11, %12, %13, %14, %15, %16, %17, %18, %19, %20, %21, %22, %23, %24, %25, %26, %27, %28, %29, %30, %31}, %32, %33, p, 1, 1, 0, %35;\n}\n"
        : "+f"(d[0]), "+f"(d[1]), "+f"(d[2]), "+f"(d[3]), "+f"(d[4]), "+f"(d[5]), "+f"(d[6]), "+f"(d[7]), "+f"(d[8]), "+f"(d[9]), "+f"(d[10]), "+f"(d[11]), "+f"(d[12]), "+f"(d[13]), "+f"(d[14]), "+f"(d[15]), "+f"(d[16]), "+f"(d[17]), "+f"(d[18]), "+f"(d[19]), "+f"(d[20]), "+f"(d[21]), "+f"(d[22]), "+f"(d[23]), "+f"(d[24]), "+f"(d[25]), "+f"(d[26]), "+f"(d[27]), "+f"(d[28]), "+f"(d[29]), "+f"(d[30]), "+f"(d[31])
        : "l"(da), "l"(db), "r"(sc), "n"(TB));
}
template <int TB> __device__ __forceinline__ void wgmma_ss_n128(float (&d)[64], uint64_t da, uint64_t db, int sc) {
    asm volatile("{\n.reg .pred p;\nsetp.ne.b32 p, %66, 0;\n"
        "wgmma.mma_async.sync.aligned.m64n128k16.f32.bf16.bf16 {%0, %1, %2, %3, %4, %5, %6, %7, %8, %9, %10, %11, %12, %13, %14, %15, %16, %17, %18, %19, %20, %21, %22, %23, %24, %25, %26, %27, %28, %29, %30, %31, %32, %33, %34, %35, %36, %37, %38, %39, %40, %41, %42, %43, %44, %45, %46, %47, %48, %49, %50, %51, %52, %53, %54, %55, %56, %57, %58, %59, %60, %61, %62, %63}, %64, %65, p, 1, 1, 0, %67;\n}\n"
        : "+f"(d[0]), "+f"(d[1]), "+f"(d[2]), "+f"(d[3]), "+f"(d[4]), "+f"(d[5]), "+f"(d[6]), "+f"(d[7]), "+f"(d[8]), "+f"(d[9]), "+f"(d[10]), "+f"(d[11]), "+f"(d[12]), "+f"(d[13]), "+f"(d[14]), "+f"(d[15]), "+f"(d[16]), "+f"(d[17]), "+f"(d[18]), "+f"(d[19]), "+f"(d[20]), "+f"(d[21]), "+f"(d[22]), "+f"(d[23]), "+f"(d[24]), "+f"(d[25]), "+f"(d[26]), "+f"(d[27]), "+f"(d[28]), "+f"(d[29]), "+f"(d[30]), "+f"(d[31]), "+f"(d[32]), "+f"(d[33]), "+f"(d[34]), "+f"(d[35]), "+f"(d[36]), "+f"(d[37]), "+f"(d[38]), "+f"(d[39]), "+f"(d[40]), "+f"(d[41]), "+f"(d[42]), "+f"(d[43]), "+f"(d[44]), "+f"(d[45]), "+f"(d[46]), "+f"(d[47]), "+f"(d[48]), "+f"(d[49]), "+f"(d[50]), "+f"(d[51]), "+f"(d[52]), "+f"(d[53]), "+f"(d[54]), "+f"(d[55]), "+f"(d[56]), "+f"(d[57]), "+f"(d[58]), "+f"(d[59]), "+f"(d[60]), "+f"(d[61]), "+f"(d[62]), "+f"(d[63])
        : "l"(da), "l"(db), "r"(sc), "n"(TB));
}
template <int TB> __device__ __forceinline__ void wgmma_rs_n24(float (&d)[12], uint32_t a0, uint32_t a1, uint32_t a2, uint32_t a3, uint64_t db, int sc) {
    asm volatile("{\n.reg .pred p;\nsetp.ne.b32 p, %17, 0;\n"
        "wgmma.mma_async.sync.aligned.m64n24k16.f32.bf16.bf16 {%0, %1, %2, %3, %4, %5, %6, %7, %8, %9, %10, %11}, {%12, %13, %14, %15}, %16, p, 1, 1, %18;\n}\n"
        : "+f"(d[0]), "+f"(d[1]), "+f"(d[2]), "+f"(d[3]), "+f"(d[4]), "+f"(d[5]), "+f"(d[6]), "+f"(d[7]), "+f"(d[8]), "+f"(d[9]), "+f"(d[10]), "+f"(d[11])
        : "r"(a0), "r"(a1), "r"(a2), "r"(a3), "l"(db), "r"(sc), "n"(TB));
}
template <int TB> __device__ __forceinline__ void wgmma_rs_n64(float (&d)[32], uint32_t a0, uint32_t a1, uint32_t a2, uint32_t a3, uint64_t db, int sc) {
    asm volatile("{\n.reg .pred p;\nsetp.ne.b32 p, %37, 0;\n"
        "wgmma.mma_async.sync.aligned.m64n64k16.f32.bf16.bf16 {%0, %1, %2, %3, %4, %5, %6, %7, %8, %9, %10, %11, %12, %13, %14, %15, %16, %17, %18, %19, %20, %21, %22, %23, %24, %25, %26, %27, %28, %29, %30, %31}, {%32, %33, %34, %35}, %36, p, 1, 1, %38;\n}\n"
        : "+f"(d[0]), "+f"(d[1]), "+f"(d[2]), "+f"(d[3]), "+f"(d[4]), "+f"(d[5]), "+f"(d[6]), "+f"(d[7]), "+f"(d[8]), "+f"(d[9]), "+f"(d[10]), "+f"(d[11]), "+f"(d[12]), "+f"(d[13]), "+f"(d[14]), "+f"(d[15]), "+f"(d[16]), "+f"(d[17]), "+f"(d[18]), "+f"(d[19]), "+f"(d[20]), "+f"(d[21]), "+f"(d[22]), "+f"(d[23]), "+f"(d[24]), "+f"(d[25]), "+f"(d[26]), "+f"(d[27]), "+f"(d[28]), "+f"(d[29]), "+f"(d[30]), "+f"(d[31])
        : "r"(a0), "r"(a1), "r"(a2), "r"(a3), "l"(db), "r"(sc), "n"(TB));
}
template <int TB, int OFF> __device__ __forceinline__ void wgmma_rs_n32_of32(float (&d)[32], uint32_t a0, uint32_t a1, uint32_t a2, uint32_t a3, uint64_t db, int sc) {
    asm volatile("{\n.reg .pred p;\nsetp.ne.b32 p, %21, 0;\n"
        "wgmma.mma_async.sync.aligned.m64n32k16.f32.bf16.bf16 {%0, %1, %2, %3, %4, %5, %6, %7, %8, %9, %10, %11, %12, %13, %14, %15}, {%16, %17, %18, %19}, %20, p, 1, 1, %22;\n}\n"
        : "+f"(d[OFF + 0]), "+f"(d[OFF + 1]), "+f"(d[OFF + 2]), "+f"(d[OFF + 3]), "+f"(d[OFF + 4]), "+f"(d[OFF + 5]), "+f"(d[OFF + 6]), "+f"(d[OFF + 7]), "+f"(d[OFF + 8]), "+f"(d[OFF + 9]), "+f"(d[OFF + 10]), "+f"(d[OFF + 11]), "+f"(d[OFF + 12]), "+f"(d[OFF + 13]), "+f"(d[OFF + 14]), "+f"(d[OFF + 15])
        : "r"(a0), "r"(a1), "r"(a2), "r"(a3), "l"(db), "r"(sc), "n"(TB));
}

constexpr int P_NST = 6;
constexpr int P_A_BYTES = 9 * 8192;
constexpr int P_B_STAGE = 3 * 8192;

template <int NB>
__device__ __forceinline__ void stage_tile(const uint32_t (&pk)[NB * 2], uint32_t base, int w, int lane) {
    const int r = w * 16 + (lane & 7) + ((lane >> 3) & 1) * 8;
#pragma unroll
    for (int b = 0; b < NB; b += 2) {
        const uint32_t a = base + (b >> 3) * 8192 + r * 128 + ((((b & 7) + (lane >> 4)) ^ (r & 7)) << 4);
        stmatrix_x4(a, pk[2 * b], pk[2 * b + 1], pk[2 * b + 2], pk[2 * b + 3]);
    }
}

__device__ __forceinline__ uint32_t hsub2_bf16(uint32_t a, uint32_t b) { uint32_t r; asm("sub.rn.bf16x2 %0, %1, %2;" : "=r"(r) : "r"(a), "r"(b)); return r; }

constexpr int KV_RAW = DM * 18 * 2;
constexpr int Q_THREADS = 416;

__device__ __forceinline__ void proj_mma(float (&acc)[32], int wg, uint32_t fullB, uint32_t emptyB, uint32_t fullA, bool wait_a, int lane) {
    const uint64_t dA = cdesc(0, 16, 1024, 1), dB = cdesc(P_A_BYTES, 8192, 1024, 1) + wg * 512;
#pragma unroll 1
    for (int kb = 0; kb < 9; kb++) {
        const int s = kb >= P_NST ? kb - P_NST : kb;
        if (wait_a) mbar_wait(fullA + kb * 8, 0);
        mbar_wait(fullB + s * 8, kb >= P_NST ? 1 : 0);
        wg_fence();
#pragma unroll
        for (int ks = 0; ks < 4; ks++) wgmma_ss_n64<1>(acc, dA + (kb * 512 + ks * 2), dB + (s * (P_B_STAGE >> 4) + ks * 128), (kb | ks) != 0);
        wg_commit();
        if (kb < 4) {
            wg_wait<1>();
            if (kb >= 1 && lane == 0) mbar_arrive(emptyB + (kb - 1) * 8);
        }
    }
    wg_wait<0>();
    pin(acc);
}

constexpr int Q_SLOT = 9 * 8192, Q_THIRD = 3 * 8192;
constexpr int Q_OFF_STG = P_A_BYTES + 2 * Q_SLOT;
constexpr int Q_OFF_BAR = Q_OFF_STG + 8192;
constexpr int Q_SMEM = Q_OFF_BAR + 256 + 256;

__global__ void __launch_bounds__(Q_THREADS, 1)
k_qkv(const __grid_constant__ CUtensorMap tmWq, const __grid_constant__ CUtensorMap tmQ, const __nv_bfloat16* __restrict__ x, const __nv_bfloat16* __restrict__ wk, const __nv_bfloat16* __restrict__ wv) {
    extern __shared__ __align__(1024) uint8_t smem[];
    const uint32_t sA = smem_u32(smem), sB = sA + P_A_BYTES, bars = sA + Q_OFF_BAR;
    const uint32_t fullB = bars, free0 = bars + 80, fullX = bars + 128, fullW = bars + 136;
    float* s_rstd = reinterpret_cast<float*>(smem + Q_OFF_BAR + 256);
    const int tid = threadIdx.x, warp = __shfl_sync(~0u, tid >> 5, 0), lane = tid & 31;
    const bool isQ = blockIdx.x < 96;
    const int m = isQ ? blockIdx.x / 3 : blockIdx.x - 96, cg = blockIdx.x % 3;
    if (warp == 12) {
        if (elect_one()) {
            mbar_init(fullX, 1);
            bar_init_fence();
            mbar_expect(fullX, P_A_BYTES);
            bulk_g2s(sA, x + (size_t)m * 64 * DM, P_A_BYTES, fullX);
            prefetch_map(&tmWq); prefetch_map(&tmQ);
            for (int i = 0; i < 9; i++) mbar_init(fullB + i * 8, 1);
            for (int i = 0; i < 3; i++) mbar_init(free0 + i * 8, 4);
            mbar_init(fullW, 1);
            bar_init_fence();
            if (isQ) {
                for (int i = 0; i < 6; i++) {
                    mbar_expect(fullB + i * 8, Q_THIRD);
                    tma_2d(sB + i * Q_THIRD, &tmWq, cg * 192 + (i / 3) * 64, (i % 3) * 192, fullB + i * 8);
                }
                for (int i = 0; i < 3; i++)
                    asm volatile("cp.async.bulk.prefetch.tensor.2d.L2.global [%0, {%1, %2}];" ::"l"(&tmWq), "r"(cg * 192 + 128), "r"(i * 192) : "memory");
            } else {
                mbar_expect(fullW, 2 * KV_RAW);
                bulk_g2s(sB + Q_SLOT, wk, KV_RAW, fullW);
                bulk_g2s(sB + Q_SLOT + KV_RAW, wv, KV_RAW, fullW);
            }
        }
        __syncwarp();
    }
    check_smem_base(sA);
    __syncthreads();
    pdl_launch();
    if (warp == 12) {
        if (isQ && elect_one()) {
            for (int i = 0; i < 3; i++) {
                mbar_wait(free0 + i * 8, 0);
                mbar_expect(fullB + (6 + i) * 8, Q_THIRD);
                tma_2d(sB + i * Q_THIRD, &tmWq, cg * 192 + 128, i * 192, fullB + (6 + i) * 8);
            }
        }
        return;
    }
    if (warp < 8) {
        const int row = tid >> 2, q = tid & 3, h0 = (row & 1) * 4;
        mbar_wait(fullX, 0);
        uint4 v[18];
        const uint32_t ra = sA + row * 1152 + (q + h0) * 16, rb = sA + row * 1152 + (q + 4 - h0) * 16;
#pragma unroll
        for (int kb = 0; kb < 9; kb++) {
            asm volatile("ld.shared.v4.b32 {%0, %1, %2, %3}, [%4];" : "=r"(v[2 * kb].x), "=r"(v[2 * kb].y), "=r"(v[2 * kb].z), "=r"(v[2 * kb].w) : "r"(ra + kb * 128));
            asm volatile("ld.shared.v4.b32 {%0, %1, %2, %3}, [%4];" : "=r"(v[2 * kb + 1].x), "=r"(v[2 * kb + 1].y), "=r"(v[2 * kb + 1].z), "=r"(v[2 * kb + 1].w) : "r"(rb + kb * 128));
        }
        float sum = 0.f, sum2 = 0.f, sq = 0.f, sq2 = 0.f;
#pragma unroll
        for (int i = 0; i < 18; i++) {
            const uint32_t w[4] = {v[i].x, v[i].y, v[i].z, v[i].w};
#pragma unroll
            for (int j = 0; j < 4; j++) { const float a = bf_lo(w[j]), b = bf_hi(w[j]); sum += a; sum2 += b; sq = fmaf(a, a, sq); sq2 = fmaf(b, b, sq2); }
        }
        named_sync(1, 256);
        sum += sum2; sq += sq2;
        sum += __shfl_xor_sync(~0u, sum, 1); sum += __shfl_xor_sync(~0u, sum, 2);
        sq += __shfl_xor_sync(~0u, sq, 1); sq += __shfl_xor_sync(~0u, sq, 2);
        const float mean = sum * (1.0f / DM);
        if (q == 0) s_rstd[row] = rsqrtf(fmaxf(sq * (1.0f / DM) - mean * mean, 0.f) + LN_EPS);
        const uint32_t mhi = pack_bf16(mean, mean);
        const float rem = mean - bf_lo(mhi);
        const uint32_t mlo = pack_bf16(rem, rem);
        const uint32_t wa = sA + row * 128 + (((q + h0) ^ (row & 7)) << 4), wb = sA + row * 128 + (((q + 4 - h0) ^ (row & 7)) << 4);
#pragma unroll
        for (int i = 0; i < 18; i++) {
            const uint32_t o0 = hsub2_bf16(hsub2_bf16(v[i].x, mhi), mlo), o1 = hsub2_bf16(hsub2_bf16(v[i].y, mhi), mlo);
            const uint32_t o2 = hsub2_bf16(hsub2_bf16(v[i].z, mhi), mlo), o3 = hsub2_bf16(hsub2_bf16(v[i].w, mhi), mlo);
            asm volatile("st.shared.v4.b32 [%0], {%1, %2, %3, %4};" ::"r"(((i & 1) ? wb : wa) + (i >> 1) * 8192), "r"(o0), "r"(o1), "r"(o2), "r"(o3) : "memory");
        }
    } else if (!isQ) {
        mbar_wait(fullW, 0);
        const uint32_t* raw = reinterpret_cast<const uint32_t*>(smem + P_A_BYTES + Q_SLOT);
#pragma unroll 3
        for (int r = tid - 256; r < 2 * DM; r += 128) {
            uint32_t wr[9];
#pragma unroll
            for (int i = 0; i < 9; i++) wr[i] = raw[r * 9 + i];
            const int sel = r >= DM, k = r - sel * DM;
            uint8_t* dst = smem + P_A_BYTES + sel * 3 * 9216 + (k >> 3) * 128 + (k & 7) * 16;
            *reinterpret_cast<uint4*>(dst) = make_uint4(wr[0], wr[1], wr[2], wr[3]);
            *reinterpret_cast<uint4*>(dst + 9216) = make_uint4(wr[4], wr[5], wr[6], wr[7]);
            *reinterpret_cast<uint32_t*>(dst + 2 * 9216) = wr[8];
        }
    }
    proxy_fence();
    named_sync(2, 384);
    const int wg = warp >> 2, w = warp & 3, g = lane >> 2, t = lane & 3;
    const float rs0 = s_rstd[w * 16 + g], rs1 = s_rstd[w * 16 + g + 8];
    if (isQ) {
        const float c0 = rs0 * Q_SCALE, c1 = rs1 * Q_SCALE;
        float acc[32];
        const uint64_t dA = cdesc(0, 16, 1024, 1), dB = cdesc(P_A_BYTES, 8192, 1024, 1) + (wg == 1 ? (Q_SLOT >> 4) : 0);
        if (wg > 0) named_sync(6 + wg, 256);
#pragma unroll 1
        for (int i = 0; i < 3; i++) {
            mbar_wait(fullB + (wg * 3 + i) * 8, 0);
            wg_fence();
#pragma unroll
            for (int ks = 0; ks < 12; ks++)
                wgmma_ss_n64<1>(acc, dA + ((i * 3 + (ks >> 2)) * 512 + (ks & 3) * 2), dB + (i * (Q_THIRD >> 4) + ks * 128), (i | ks) != 0);
            wg_commit();
            if (wg == 0 && i > 0) { wg_wait<1>(); if (lane == 0) mbar_arrive(free0 + (i - 1) * 8); }
        }
        if (wg < 2) asm volatile("bar.arrive %0, 256;" ::"r"(7 + wg) : "memory");
        wg_wait<0>();
        pin(acc);
        if (wg == 0 && lane == 0) mbar_arrive(free0 + 16);
        uint32_t pk[16];
#pragma unroll
        for (int i = 0; i < 8; i++) { pk[2 * i] = pack_bf16(acc[4 * i] * c0, acc[4 * i + 1] * c0); pk[2 * i + 1] = pack_bf16(acc[4 * i + 2] * c1, acc[4 * i + 3] * c1); }
        const uint32_t stg = wg == 0 ? sA + Q_OFF_STG : (wg == 1 ? sB + Q_SLOT : sB);
        stage_tile<8>(pk, stg, w, lane);
        proxy_fence();
        named_sync(3 + wg, 128);
        if (w == 0 && elect_one()) {
            tma_st_2d(&tmQ, cg * 192 + wg * 64, m * 64, stg);
            bulk_commit();
            bulk_wait_all();
        }
    } else if (wg < 2) {
        float acc[12];
        const uint64_t dA = cdesc(0, 16, 1024, 1), dB = cdesc(P_A_BYTES, 128, 9216, 0) + wg * (3 * 9216 >> 4);
#pragma unroll
        for (int i = 0; i < 12; i++) acc[i] = 0.f;
        pin(acc);
        wg_fence();
#pragma unroll 1
        for (int kb = 0; kb < 9; kb++) {
#pragma unroll
            for (int ks = 0; ks < 4; ks++) wgmma_ss_n24<1>(acc, dA + (kb * 512 + ks * 2), dB + (kb * 4 + ks) * 16, 1);
        }
        wg_commit();
        wg_wait<0>();
        pin(acc);
        uint32_t pk[6];
#pragma unroll
        for (int b = 0; b < 3; b++) { pk[2 * b] = pack_bf16(acc[4 * b] * rs0, acc[4 * b + 1] * rs0); pk[2 * b + 1] = pack_bf16(acc[4 * b + 2] * rs1, acc[4 * b + 3] * rs1); }
        float n0 = 0.f, n1 = 0.f, vm = 0.f;
#pragma unroll
        for (int b = 0; b < 3; b++) {
            if (b < 2 || t == 0) {
                const float a = bf_lo(pk[2 * b]), c = bf_hi(pk[2 * b]), d = bf_lo(pk[2 * b + 1]), e = bf_hi(pk[2 * b + 1]);
                n0 = fmaf(a, a, fmaf(c, c, n0)); n1 = fmaf(d, d, fmaf(e, e, n1));
            }
        }
        n0 += __shfl_xor_sync(~0u, n0, 1); n0 += __shfl_xor_sync(~0u, n0, 2);
        n1 += __shfl_xor_sync(~0u, n1, 1); n1 += __shfl_xor_sync(~0u, n1, 2);
        vm = fmaxf(n0, n1);
        if (!(n0 == n0) || !(n1 == n1)) vm = __int_as_float(0x7F800000);
#pragma unroll
        for (int o = 4; o < 32; o <<= 1) vm = fmaxf(vm, __shfl_xor_sync(~0u, vm, o));
        if (t != 0) {
            uint32_t lo, hi;
            if (wg == 0) {
                const int grp = m * 8 + w * 2;
                const uint32_t c = t == 1 ? 0x42FE3F80u   : (t == 2 ? 0x00003BC0u   : 0u);
                lo = ((POLY_MASK >> (grp & 15)) & 1) ? c : 0u;
                hi = ((POLY_MASK >> ((grp + 1) & 15)) & 1) ? c : 0u;
            } else {
                lo = hi = t == 1 ? 0x00003F80u : 0u;
            }
            pk[4] = lo; pk[5] = hi;
        }
        uint32_t* dst = reinterpret_cast<uint32_t*>(wg == 0 ? g_kc : g_vc) + (m * 8 + w * 2) * 96 + g * 4 + t;
#pragma unroll
        for (int b = 0; b < 3; b++) { dst[b * 32] = pk[2 * b]; dst[96 + b * 32] = pk[2 * b + 1]; }
        if (lane == 0) g_kmax[m * 8 + warp] = (wg == 0) ? vm : (vm <= FAST_VMAX2 ? 0.f : __int_as_float(0x7F800000));
    }
}

constexpr int A_THREADS = 512;
constexpr int A_NPIECE = 8;
constexpr int A_OFF_Q = 2 * KV_BYTES;
constexpr int A_OFF_BAR = A_OFF_Q + 8 * 4096;
constexpr int A_SMEM = A_OFF_BAR + 128;

__device__ __forceinline__ uint32_t exp2_pair_fixed(float lo, float hi, uint32_t dep) {
    const uint32_t G = __byte_perm(__float_as_uint(lo), __float_as_uint(hi), 0x5410);
    uint32_t Hh;
    asm("lop3.b32 %0, %1, 0x007F007F, %2, 0xC0;" : "=r"(Hh) : "r"(G), "r"(dep));
    const uint32_t tt = hfma2(Hh, 0xF96BF96Bu, 0x358C358Cu);
    return G - hfma2(tt, Hh, 0u);
}

__global__ void __launch_bounds__(A_THREADS, 1)
k_attn(__nv_bfloat16* __restrict__ out) {
    extern __shared__ __align__(1024) uint8_t smem[];
    pdl_launch();
    const uint32_t sK = smem_u32(smem), sV = sK + KV_BYTES, bars = sK + A_OFF_BAR;
    const int tid = threadIdx.x;
    check_smem_base(sK);
    if (tid == 0) {
        for (int i = 0; i < A_NPIECE; i++) mbar_init(bars + i * 8, 1);
        bar_init_fence();
    }
    __syncthreads();
    pdl_wait();
    const int wg = __shfl_sync(~0u, tid >> 7, 0), w = (tid >> 5) & 3, lane = tid & 31, g = lane >> 2, t = lane & 3;
    const uint32_t* q32 = reinterpret_cast<const uint32_t*>(g_q);
    int row = (blockIdx.x * 8 + wg) * 64 + w * 16 + g;
    uint32_t nq[2][6];
#pragma unroll
    for (int r = 0; r < 2; r++) {
        const uint32_t* q = q32 + (row + r * 256) * 9;
        nq[r][0] = q[t]; nq[r][1] = q[72 + t]; nq[r][2] = q[4 + t]; nq[r][3] = q[76 + t]; nq[r][4] = q[8]; nq[r][5] = q[80];
    }
    constexpr int PB = KV_BYTES / A_NPIECE;
    const float4 km0 = reinterpret_cast<const float4*>(g_kmax)[lane], km1 = reinterpret_cast<const float4*>(g_kmax)[32 + lane];
    if (tid < 32 && elect_one()) {
        for (int i = 0; i < 2; i++) {
            mbar_expect(bars + i * 8, 2 * PB);
            bulk_g2s(sK + i * PB, reinterpret_cast<const char*>(g_kc) + i * PB, PB, bars + i * 8);
            bulk_g2s(sV + i * PB, reinterpret_cast<const char*>(g_vc) + i * PB, PB, bars + i * 8);
        }
    }
    float kmax2 = fmaxf(fmaxf(fmaxf(km0.x, km0.y), fmaxf(km0.z, km0.w)), fmaxf(fmaxf(km1.x, km1.y), fmaxf(km1.z, km1.w)));
#pragma unroll
    for (int o = 1; o < 32; o <<= 1) kmax2 = fmaxf(kmax2, __shfl_xor_sync(~0u, kmax2, o));
    if (tid < 32 && elect_one()) {
        for (int i = 2; i < A_NPIECE; i++) {
            mbar_expect(bars + i * 8, 2 * PB);
            bulk_g2s(sK + i * PB, reinterpret_cast<const char*>(g_kc) + i * PB, PB, bars + i * 8);
            bulk_g2s(sV + i * PB, reinterpret_cast<const char*>(g_vc) + i * PB, PB, bars + i * 8);
        }
    }
    uint32_t vote = 0;
#pragma unroll
    for (int r = 0; r < 2; r++) {
        const uint32_t (&q)[6] = nq[r];
        const float a0 = bf_lo(q[0]), a1 = bf_hi(q[0]), a2 = bf_lo(q[2]), a3 = bf_hi(q[2]);
        const float b0 = bf_lo(q[1]), b1 = bf_hi(q[1]), b2 = bf_lo(q[3]), b3 = bf_hi(q[3]);
        float n0 = a0 * a0 + a1 * a1 + a2 * a2 + a3 * a3, n1 = b0 * b0 + b1 * b1 + b2 * b2 + b3 * b3;
        if (t == 0) {
            const float c0 = bf_lo(q[4]), c1 = bf_hi(q[4]), d0 = bf_lo(q[5]), d1 = bf_hi(q[5]);
            n0 += c0 * c0 + c1 * c1; n1 += d0 * d0 + d1 * d1;
        }
        n0 += __shfl_xor_sync(~0u, n0, 1); n0 += __shfl_xor_sync(~0u, n0, 2);
        n1 += __shfl_xor_sync(~0u, n1, 1); n1 += __shfl_xor_sync(~0u, n1, 2);
        const bool unsafe = !(fmaxf(n0, n1) * kmax2 <= FAST_BOUND * FAST_BOUND) || !(n0 == n0) || !(n1 == n1);
        vote |= (__any_sync(~0u, unsafe) ? 1u : 0u) << r;
        const uint32_t cst = t == 1 ? 0x3F804780u : (t == 2 ? 0x00003F80u : 0u);
        const uint32_t sQ = sK + A_OFF_Q + (r * 4 + wg) * 4096 + (w * 2) * 512 + g * 16 + t * 4;
        asm volatile("st.shared.b32 [%0], %1;" ::"r"(sQ), "r"(q[0]) : "memory");
        asm volatile("st.shared.b32 [%0], %1;" ::"r"(sQ + 512), "r"(q[1]) : "memory");
        asm volatile("st.shared.b32 [%0], %1;" ::"r"(sQ + 128), "r"(q[2]) : "memory");
        asm volatile("st.shared.b32 [%0], %1;" ::"r"(sQ + 640), "r"(q[3]) : "memory");
        asm volatile("st.shared.b32 [%0], %1;" ::"r"(sQ + 256), "r"(t == 0 ? q[4] : cst) : "memory");
        asm volatile("st.shared.b32 [%0], %1;" ::"r"(sQ + 768), "r"(t == 0 ? q[5] : cst) : "memory");
        asm volatile("st.shared.b32 [%0], %1;" ::"r"(sQ + 384), "r"(0u) : "memory");
        asm volatile("st.shared.b32 [%0], %1;" ::"r"(sQ + 896), "r"(0u) : "memory");
    }
    const uint32_t sVote = bars + 64 + wg * 16;
    if (lane == 0) asm volatile("st.shared.b32 [%0], %1;" ::"r"(sVote + w * 4), "r"(vote) : "memory");
    proxy_fence();
    named_sync(wg + 1, 128);
    uint32_t unsafe_mask;
    {
        uint32_t v0, v1, v2, v3;
        asm volatile("ld.shared.v4.b32 {%0, %1, %2, %3}, [%4];" : "=r"(v0), "=r"(v1), "=r"(v2), "=r"(v3) : "r"(sVote));
        unsafe_mask = __shfl_sync(~0u, v0 | v1 | v2 | v3, 0);
    }
    if (unsafe_mask) {
#pragma unroll
        for (int r = 0; r < 2; r++) {
            if (((unsafe_mask >> r) & 1) && t != 0) {
                const uint32_t sQ = sK + A_OFF_Q + (r * 4 + wg) * 4096 + (w * 2) * 512 + g * 16 + t * 4;
                asm volatile("st.shared.b32 [%0], %1;" ::"r"(sQ + 256), "r"(0u) : "memory");
                asm volatile("st.shared.b32 [%0], %1;" ::"r"(sQ + 768), "r"(0u) : "memory");
            }
        }
        proxy_fence();
        named_sync(wg + 1, 128);
    }
#pragma unroll 1
    for (int rep = 0; rep < 2; rep++, row += 256) {
        if (rep == 1) {
            uint4* z = reinterpret_cast<uint4*>(out + (size_t)blockIdx.x * 16 * DM) + tid;
            z[0] = make_uint4(0u, 0u, 0u, 0u); z[A_THREADS] = make_uint4(0u, 0u, 0u, 0u);
            if (tid < 16 * DM * 2 / 16 - 2 * A_THREADS) z[2 * A_THREADS] = make_uint4(0u, 0u, 0u, 0u);
        }
        const uint32_t any_unsafe = (unsafe_mask >> rep) & 1;
        const uint64_t dQ0 = cdesc(A_OFF_Q, 128, 512, 0) + (rep * 4 + wg) * 256, dQ1 = dQ0 + 16;
        float o[12];
#pragma unroll
        for (int i = 0; i < 12; i++) o[i] = 0.f;
        pin(o);
        uint64_t dK0 = cdesc(0, 128, 384, 0), dK1 = cdesc(256, 0, 384, 0), dV = cdesc(KV_BYTES, 384, 128, 0);
        if (!any_unsafe) {
            float s[64];
#pragma unroll 1
            for (int j = 0; j < 16; j++) {
                if (rep == 0 && (j & 1) == 0) mbar_wait(bars + (j >> 1) * 8, 0);
                wg_fence();
                wgmma_ss_n128<0>(s, dQ0, dK0, 0);
                wgmma_ss_n128<0>(s, dQ1, dK1, 1);
                wg_commit();
                dK0 += 16 * 384 >> 4; dK1 += 16 * 384 >> 4;
                wg_wait<0>();
                pin(s);
                uint32_t p[32];
                {
                    constexpr int NP = 2 * __builtin_popcount(POLY_MASK), NM = 32 - NP;
                    float e[64];
#pragma unroll
                    for (int i = 0; i < 32; i++)
                        if (!((POLY_MASK >> (i >> 1)) & 1)) { e[2 * i] = ex2(s[2 * i]); e[2 * i + 1] = ex2(s[2 * i + 1]); p[i] = pack_bf16(e[2 * i], e[2 * i + 1]); }
                    int ip = 0;
#pragma unroll
                    for (int i = 0; i < 32; i++) {
                        if ((POLY_MASK >> (i >> 1)) & 1) {
                            const int mm = (ip * 2 * NM) / NP - CHAIN;
                            uint32_t dep = 0;
                            if (CHAIN > 0 && mm >= 0) {
                                int cnt = 0;
#pragma unroll
                                for (int q = 0; q < 32; q++)
                                    if (!((POLY_MASK >> (q >> 1)) & 1)) { if (cnt == (mm >> 1)) dep = __float_as_uint(e[2 * q + (mm & 1)]); cnt++; }
                            }
                            p[i] = exp2_pair_fixed(s[2 * i], s[2 * i + 1], dep);
                            ip++;
                        }
                    }
                }
                pin(p);
                wg_fence();
#pragma unroll
                for (int k = 0; k < 8; k++) wgmma_rs_n24<1>(o, p[4 * k], p[4 * k + 1], p[4 * k + 2], p[4 * k + 3], dV + k * 48, 1);
                wg_commit();
                dV += 16 * 384 >> 4;
                wg_wait<0>();
            }
        } else {
            float s[64];
            float m0 = -INFINITY, m1 = -INFINITY;
#pragma unroll 1
            for (int j = 0; j < 16; j++) {
                if (rep == 0 && (j & 1) == 0) mbar_wait(bars + (j >> 1) * 8, 0);
                wg_fence();
                wgmma_ss_n128<0>(s, dQ0, dK0, 0);
                wgmma_ss_n128<0>(s, dQ1, dK1, 1);
                wg_commit();
                dK0 += 16 * 384 >> 4; dK1 += 16 * 384 >> 4;
                wg_wait<0>();
                pin(s);
                float x0m = m0, x1m = m1;
#pragma unroll
                for (int b = 0; b < 16; b++) { x0m = fmaxf(x0m, fmaxf(s[4 * b], s[4 * b + 1])); x1m = fmaxf(x1m, fmaxf(s[4 * b + 2], s[4 * b + 3])); }
                x0m = fmaxf(x0m, __shfl_xor_sync(~0u, x0m, 1)); x0m = fmaxf(x0m, __shfl_xor_sync(~0u, x0m, 2));
                x1m = fmaxf(x1m, __shfl_xor_sync(~0u, x1m, 1)); x1m = fmaxf(x1m, __shfl_xor_sync(~0u, x1m, 2));
                const float c0 = ex2(m0 - x0m), c1 = ex2(m1 - x1m);
                m0 = x0m; m1 = x1m;
#pragma unroll
                for (int b = 0; b < 3; b++) { o[4 * b] *= c0; o[4 * b + 1] *= c0; o[4 * b + 2] *= c1; o[4 * b + 3] *= c1; }
                uint32_t p[32];
#pragma unroll
                for (int b = 0; b < 16; b++) {
                    p[2 * b] = pack_bf16(ex2(s[4 * b] - m0), ex2(s[4 * b + 1] - m0));
                    p[2 * b + 1] = pack_bf16(ex2(s[4 * b + 2] - m1), ex2(s[4 * b + 3] - m1));
                }
                pin(p); pin(o);
                wg_fence();
#pragma unroll
                for (int k = 0; k < 8; k++) wgmma_rs_n24<1>(o, p[4 * k], p[4 * k + 1], p[4 * k + 2], p[4 * k + 3], dV + k * 48, 1);
                wg_commit();
                dV += 16 * 384 >> 4;
                wg_wait<0>();
            }
        }
        pin(o);
        const float l0 = __shfl_sync(~0u, o[8], (lane & ~3) | 1), l1 = __shfl_sync(~0u, o[10], (lane & ~3) | 1);
        const float i0 = 1.0f / l0, i1 = 1.0f / l1;
        uint32_t* o32 = reinterpret_cast<uint32_t*>(g_o);
        o32[row * 9 + t] = pack_bf16(o[0] * i0, o[1] * i0);
        o32[(row + 8) * 9 + t] = pack_bf16(o[2] * i1, o[3] * i1);
        o32[row * 9 + 4 + t] = pack_bf16(o[4] * i0, o[5] * i0);
        o32[(row + 8) * 9 + 4 + t] = pack_bf16(o[6] * i1, o[7] * i1);
        if (t == 0) { o32[row * 9 + 8] = pack_bf16(o[8] * i0, o[9] * i0); o32[(row + 8) * 9 + 8] = pack_bf16(o[10] * i1, o[11] * i1); }
    }
}

constexpr int O_THREADS = 416;
constexpr int O_OFF_STAT = P_A_BYTES + P_NST * P_B_STAGE + 256;
constexpr int O_SMEM = O_OFF_STAT + 9 * 64 * 8;

__global__ void __cluster_dims__(3, 1, 1) __launch_bounds__(O_THREADS, 1)
k_oproj(const __grid_constant__ CUtensorMap tmO, const __grid_constant__ CUtensorMap tmWo, const __grid_constant__ CUtensorMap tmX2, const __grid_constant__ CUtensorMap tmH, const __nv_bfloat16* __restrict__ x, const __nv_bfloat16* __restrict__ w1) {
    extern __shared__ __align__(1024) uint8_t smem[];
    const uint32_t sA = smem_u32(smem), sB = sA + P_A_BYTES, bars = sB + P_NST * P_B_STAGE;
    const uint32_t fullB = bars, emptyB = bars + 64, fullA = bars + 128;
    const int tid = threadIdx.x, warp = __shfl_sync(~0u, tid >> 5, 0), lane = tid & 31;
    const int m = blockIdx.x / 3, cg = blockIdx.x % 3;
    check_smem_base(sA);
    if (tid == 0) {
        prefetch_map(&tmO); prefetch_map(&tmWo); prefetch_map(&tmX2); prefetch_map(&tmH);
        for (int i = 0; i < P_NST; i++) { mbar_init(fullB + i * 8, 1); mbar_init(emptyB + i * 8, 12); }
        for (int i = 0; i < 9; i++) mbar_init(fullA + i * 8, 1);
        bar_init_fence();
        for (int kb = 0; kb < 9; kb++) mbar_expect(fullA + kb * 8, 8192);
    }
    __syncthreads();
    pdl_launch();
    if (warp == 12) {
        if (elect_one()) {
            for (int kb = 0; kb < 9; kb++) {
                const int s = kb >= P_NST ? kb - P_NST : kb;
                if (kb == 2) {
                    pdl_wait();
                    for (int ka = 0; ka < 9; ka++) tma_2d(sA + ka * 8192, &tmO, ka * 64, m * 64, fullA + ka * 8);
                }
                if (kb >= P_NST) mbar_wait(emptyB + s * 8, 0);
                mbar_expect(fullB + s * 8, P_B_STAGE);
                for (int a = 0; a < 3; a++) tma_2d(sB + s * P_B_STAGE + a * 8192, &tmWo, cg * 192 + a * 64, kb * 64, fullB + s * 8);
            }
            for (int i = 0; i < 6; i++) prefetch_l2(reinterpret_cast<const char*>(w1) + (size_t)blockIdx.x * (FF * DM * 2 / 96) + i * 9216, 9216);
        }
        return;
    }
    const int wg = warp >> 2, w = warp & 3, g = lane >> 2, t = lane & 3;
    uint32_t xr[16];
    {
        const uint32_t* x32 = reinterpret_cast<const uint32_t*>(x) + (((m * 64 + w * 16 + g) * DM + cg * 192 + wg * 64 + 2 * t) >> 1);
#pragma unroll
        for (int b = 0; b < 8; b++) { xr[2 * b] = __ldg(x32 + b * 4); xr[2 * b + 1] = __ldg(x32 + b * 4 + 4 * DM); }
    }
    float acc[32];
    proj_mma(acc, wg, fullB, emptyB, fullA, true, lane);
    named_sync(1, 384);
    float s0 = 0.f, q0 = 0.f, s1 = 0.f, q1 = 0.f;
#pragma unroll
    for (int b = 0; b < 8; b++) {
        const uint32_t xa = xr[2 * b], xb = xr[2 * b + 1];
        const uint32_t ha = pack_bf16(acc[4 * b] + bf_lo(xa), acc[4 * b + 1] + bf_hi(xa));
        const uint32_t hb = pack_bf16(acc[4 * b + 2] + bf_lo(xb), acc[4 * b + 3] + bf_hi(xb));
        xr[2 * b] = ha; xr[2 * b + 1] = hb;
        const float a = bf_lo(ha), c = bf_hi(ha), d = bf_lo(hb), e = bf_hi(hb);
        s0 += a + c; q0 = fmaf(a, a, fmaf(c, c, q0));
        s1 += d + e; q1 = fmaf(d, d, fmaf(e, e, q1));
    }
    s0 += __shfl_xor_sync(~0u, s0, 1); s0 += __shfl_xor_sync(~0u, s0, 2);
    q0 += __shfl_xor_sync(~0u, q0, 1); q0 += __shfl_xor_sync(~0u, q0, 2);
    s1 += __shfl_xor_sync(~0u, s1, 1); s1 += __shfl_xor_sync(~0u, s1, 2);
    q1 += __shfl_xor_sync(~0u, q1, 1); q1 += __shfl_xor_sync(~0u, q1, 2);
    const int r = w * 16 + g;
    const uint32_t sStat = sA + O_OFF_STAT;
    if (t < 3) {
        uint32_t dst;
        asm("mapa.shared::cluster.u32 %0, %1, %2;" : "=r"(dst) : "r"(sStat + ((cg * 3 + wg) * 64 + r) * 8), "r"(t));
        asm volatile("st.shared::cluster.v2.f32 [%0], {%1, %2};" ::"r"(dst), "f"(s0), "f"(q0) : "memory");
        asm volatile("st.shared::cluster.v2.f32 [%0], {%1, %2};" ::"r"(dst + 64), "f"(s1), "f"(q1) : "memory");
    }
    cluster_arrive();
    stage_tile<8>(xr, sA + wg * 8192, w, lane);
    proxy_fence();
    named_sync(2 + wg, 128);
    const bool leader = w == 0 && elect_one();
    if (leader) { tma_st_2d(&tmH, cg * 192 + wg * 64, m * 64, sA + wg * 8192); bulk_commit(); }
    cluster_wait();
    s0 = q0 = s1 = q1 = 0.f;
#pragma unroll
    for (int p = 0; p < 9; p++) {
        float a, b, c, d;
        asm volatile("ld.shared.v2.f32 {%0, %1}, [%2];" : "=f"(a), "=f"(b) : "r"(sStat + (p * 64 + r) * 8));
        asm volatile("ld.shared.v2.f32 {%0, %1}, [%2];" : "=f"(c), "=f"(d) : "r"(sStat + (p * 64 + r + 8) * 8));
        s0 += a; q0 += b; s1 += c; q1 += d;
    }
    const float m0 = s0 * (1.0f / DM), m1 = s1 * (1.0f / DM);
    const float rs0 = rsqrtf(fmaxf(q0 * (1.0f / DM) - m0 * m0, 0.f) + LN_EPS), rs1 = rsqrtf(fmaxf(q1 * (1.0f / DM) - m1 * m1, 0.f) + LN_EPS);
    const float sc0 = 0.5f * rs0, sc1 = 0.5f * rs1, n0 = -m0 * sc0, n1 = -m1 * sc1;
#pragma unroll
    for (int b = 0; b < 8; b++) {
        xr[2 * b] = pack_bf16(fmaf(bf_lo(xr[2 * b]), sc0, n0), fmaf(bf_hi(xr[2 * b]), sc0, n0));
        xr[2 * b + 1] = pack_bf16(fmaf(bf_lo(xr[2 * b + 1]), sc1, n1), fmaf(bf_hi(xr[2 * b + 1]), sc1, n1));
    }
    stage_tile<8>(xr, sA + (3 + wg) * 8192, w, lane);
    proxy_fence();
    named_sync(2 + wg, 128);
    if (leader) {
        tma_st_2d(&tmX2, cg * 192 + wg * 64, m * 64, sA + (3 + wg) * 8192);
        bulk_commit();
        bulk_wait_all();
    }
}

constexpr int F_THREADS = 384;
constexpr int F_NST = 6;
constexpr int F_STAGE = 96 * 128;
constexpr int F_X_BYTES = 9 * 16384;
constexpr int F_OFF_ST = F_X_BYTES;
constexpr int F_OFF_BAR = F_OFF_ST + F_NST * F_STAGE;
constexpr int F_SMEM = F_OFF_BAR + 256;

__device__ __forceinline__ float tanh_hw(float x) { float y; asm("tanh.approx.f32 %0, %1;" : "=f"(y) : "f"(x)); return y; }
__host__ __device__ constexpr int piece_begin(int p) { return p == 0 ? 0 : 3 * p + 1; }
template <int P>
__device__ __forceinline__ void silu_s1(const float (&acc)[32], float (&tmp)[8]) {
#pragma unroll
    for (int i = 2 * piece_begin(P); i < 2 * piece_begin(P + 1); i++) tmp[i - 2 * piece_begin(P)] = tanh_hw(acc[i]);
}
template <int C, int P>
__device__ __forceinline__ void silu_s2(const float (&acc)[32], const float (&tmp)[8], uint32_t (&h1)[144]) {
#pragma unroll
    for (int i = piece_begin(P); i < piece_begin(P + 1); i++) {
        const int k = 2 * (i - piece_begin(P));
        h1[C * 16 + i] = pack_bf16(fmaf(acc[2 * i], tmp[k], acc[2 * i]), fmaf(acc[2 * i + 1], tmp[k + 1], acc[2 * i + 1]));
    }
}
template <int J>
__device__ __forceinline__ void silu_slot_last(const float (&prev)[32], float (&tmp)[2][8], uint32_t (&h1)[144]) {
    if constexpr (J >= 1 && J <= 4) {
#pragma unroll
        for (int i = 0; i < 4; i++) {
            const int q = 4 * (J - 1) + i;
            h1[128 + q] = pack_bf16(fmaf(prev[2 * q], tmp[(J - 1) & 1][2 * i], prev[2 * q]), fmaf(prev[2 * q + 1], tmp[(J - 1) & 1][2 * i + 1], prev[2 * q + 1]));
        }
    }
    if constexpr (J <= 3) {
#pragma unroll
        for (int i = 0; i < 8; i++) tmp[J & 1][i] = tanh_hw(prev[8 * J + i]);
        pin(tmp[J & 1]);
    }
}
template <int C, int J>
__device__ __forceinline__ void silu_slot(const float (&prev)[32], float (&tmp)[2][8], uint32_t (&h1)[144]) {
    if constexpr (J >= 1) silu_s2<C, J - 1>(prev, tmp[(J - 1) & 1], h1);
    if constexpr (J <= 4) { silu_s1<J>(prev, tmp[J & 1]); pin(tmp[J & 1]); }
}

struct FfnPipe {
    uint32_t full, empty;
    int lane;
    __device__ __forceinline__ void acquire(int s, uint32_t ph) const { mbar_wait(full + s * 8, ph); }
    __device__ __forceinline__ void release(int s) const { if (lane == 0) mbar_arrive(empty + s * 8); }
};

template <int C>
__device__ __forceinline__ void ffn_phase1_chunk(float (&cur)[32], float (&prev)[32], uint32_t (&h1)[144], const FfnPipe& pp, uint64_t dx, uint32_t fullX) {
    float tmp[2][8];
    const uint64_t dw = cdesc(F_OFF_ST, 8192, 1024, 1) + blockIdx.y * (C + 1);
    dx += blockIdx.y * C;
#pragma unroll
    for (int j = 0; j < 6; j++) {
        if (C == 0) { mbar_wait(fullX + ((6 * j) >> 2) * 8, 0); mbar_wait(fullX + ((6 * j + 5) >> 2) * 8, 0); }
        pp.acquire(j, C & 1);
        if (j == 0) pin(cur);
        wg_fence();
#pragma unroll
        for (int i = 0; i < 6; i++) {
            const int ks = 6 * j + i;
            wgmma_ss_n64<1>(cur, dx + ((ks >> 2) * 1024 + (ks & 3) * 2), dw + ((j * F_STAGE + i * 2048) >> 4), ks != 0);
        }
        wg_commit();
        if (C > 0 || j > 0) { wg_wait<1>(); pp.release((j + 5) % 6); }
        if (C > 0) {
            constexpr int CP = C > 0 ? C - 1 : 0;
            pin(prev);
            if (j == 0) silu_slot<CP, 0>(prev, tmp, h1);
            if (j == 1) silu_slot<CP, 1>(prev, tmp, h1);
            if (j == 2) silu_slot<CP, 2>(prev, tmp, h1);
            if (j == 3) silu_slot<CP, 3>(prev, tmp, h1);
            if (j == 4) silu_slot<CP, 4>(prev, tmp, h1);
            if (j == 5) silu_slot<CP, 5>(prev, tmp, h1);
        }
    }
}

__device__ __forceinline__ void ffn_stage_chunk(const float (&acc)[32], uint32_t stg, int w, int lane, bool resid, uint32_t fullH) {
    uint32_t pk[16];
    if (resid) {
        mbar_wait(fullH, 0);
        const int r = w * 16 + (lane & 7) + ((lane >> 3) & 1) * 8;
#pragma unroll
        for (int b = 0; b < 8; b += 2) {
            uint32_t h0, h1, h2, h3;
            asm volatile("ldmatrix.sync.aligned.m8n8.x4.shared.b16 {%0, %1, %2, %3}, [%4];" : "=r"(h0), "=r"(h1), "=r"(h2), "=r"(h3) : "r"(stg + r * 128 + (((b + (lane >> 4)) ^ (r & 7)) << 4)) : "memory");
            pk[2 * b] = pack_bf16(acc[4 * b] + bf_lo(h0), acc[4 * b + 1] + bf_hi(h0));
            pk[2 * b + 1] = pack_bf16(acc[4 * b + 2] + bf_lo(h1), acc[4 * b + 3] + bf_hi(h1));
            pk[2 * b + 2] = pack_bf16(acc[4 * b + 4] + bf_lo(h2), acc[4 * b + 5] + bf_hi(h2));
            pk[2 * b + 3] = pack_bf16(acc[4 * b + 6] + bf_lo(h3), acc[4 * b + 7] + bf_hi(h3));
        }
    } else {
#pragma unroll
        for (int i = 0; i < 16; i++) pk[i] = pack_bf16(acc[2 * i], acc[2 * i + 1]);
    }
    stage_tile<8>(pk, stg, w, lane);
}
__device__ __forceinline__ void ffn_reduce_chunk(const CUtensorMap* tmOut, uint32_t stg, int col, int row, int w, int wgid, bool leader) {
    proxy_fence();
    if (w != 0) {
        asm volatile("bar.arrive %0, 128;" ::"r"(2 + wgid) : "memory");
    } else {
        named_sync(2 + wgid, 128);
        if (leader) { tma_red_2d(tmOut, col, row, stg); bulk_commit(); }
    }
}

__device__ __forceinline__ void ffn_load_residual(float (&acc)[32], uint32_t stg, int w, int lane, uint32_t fullH) {
    mbar_wait(fullH, 0);
    const int r = w * 16 + (lane & 7) + ((lane >> 3) & 1) * 8;
#pragma unroll
    for (int b = 0; b < 8; b += 2) {
        uint32_t h0, h1, h2, h3;
        asm volatile("ldmatrix.sync.aligned.m8n8.x4.shared.b16 {%0, %1, %2, %3}, [%4];" : "=r"(h0), "=r"(h1), "=r"(h2), "=r"(h3) : "r"(stg + r * 128 + (((b + (lane >> 4)) ^ (r & 7)) << 4)) : "memory");
        acc[4 * b] = bf_lo(h0); acc[4 * b + 1] = bf_hi(h0); acc[4 * b + 2] = bf_lo(h1); acc[4 * b + 3] = bf_hi(h1);
        acc[4 * b + 4] = bf_lo(h2); acc[4 * b + 5] = bf_hi(h2); acc[4 * b + 6] = bf_lo(h3); acc[4 * b + 7] = bf_hi(h3);
    }
}

template <int MODE>
__device__ __forceinline__ void ffn_phase2_chunk(float (&cur)[32], float (&prev)[32], uint32_t (&h1)[144], const FfnPipe& pp, uint32_t ph, const CUtensorMap* tmOut, uint32_t stg_prev, int col_prev, int row, int w, int lane, int wgid, bool leader,
                                                 uint32_t fullH, uint32_t stg_res) {
    const uint64_t dw = cdesc(F_OFF_ST, 8192, 1024, 1) + blockIdx.y * col_prev;
    float tmp[2][8];
#pragma unroll
    for (int j = 0; j < 6; j++) {
        pp.acquire(j, ph);
        if (j == 0) pin(cur);
        if (MODE == 0 && j == 5) pin(h1);
        wg_fence();
#pragma unroll
        for (int i = 0; i < 6; i++) {
            const int f = (6 * j + i) * 4;
            wgmma_rs_n64<1>(cur, h1[f], h1[f + 1], h1[f + 2], h1[f + 3], dw + ((j * F_STAGE + i * 2048) >> 4), (j | i) != 0);
        }
        wg_commit();
        wg_wait<1>();
        pp.release((j + 5) % 6);
        if (MODE == 0) {
            pin(prev);
            if (j == 0) silu_slot_last<0>(prev, tmp, h1);
            if (j == 1) silu_slot_last<1>(prev, tmp, h1);
            if (j == 2) silu_slot_last<2>(prev, tmp, h1);
            if (j == 3) silu_slot_last<3>(prev, tmp, h1);
            if (j == 4) silu_slot_last<4>(prev, tmp, h1);
        } else {
            if (j == 0) { pin(prev); ffn_stage_chunk(prev, stg_prev, w, lane, false, fullH); }
            if (j == 1) ffn_reduce_chunk(tmOut, stg_prev, col_prev, row, w, wgid, leader);
            if (MODE == 2 && j == 2) { ffn_load_residual(prev, stg_res, w, lane, fullH); pin(prev); }
        }
    }
}

template <int HALF, int J>
__device__ __forceinline__ void ffn_half_group(float (&cur)[32], uint32_t (&h1)[144], const FfnPipe& pp, uint64_t dw) {
    if (HALF == 0) pp.acquire(J, 1);
    wg_fence();
#pragma unroll
    for (int i = 0; i < 6; i++) {
        const int f = (6 * J + i) * 4;
        wgmma_rs_n32_of32<1, HALF * 16>(cur, h1[f], h1[f + 1], h1[f + 2], h1[f + 3], dw + (((J * F_STAGE + i * 2048) >> 4) + HALF * 4), 1);
    }
    wg_commit();
}
template <int HALF>
__device__ __forceinline__ void ffn_store_half(float (&acc)[32], const CUtensorMap* tmHalf, uint32_t stg, int col, int row, int w, int lane, int wgid, bool leader) {
    const int r = w * 16 + (lane & 7) + ((lane >> 3) & 1) * 8;
#pragma unroll
    for (int i = 0; i < 16; i++) asm volatile("" : "+f"(acc[HALF * 16 + i])::"memory");
#pragma unroll
    for (int b = 0; b < 4; b += 2) {
        const int q = HALF * 16 + 4 * b;
        stmatrix_x4(stg + r * 64 + (((b + (lane >> 4)) ^ ((r >> 1) & 3)) << 4), pack_bf16(acc[q], acc[q + 1]), pack_bf16(acc[q + 2], acc[q + 3]),
                    pack_bf16(acc[q + 4], acc[q + 5]), pack_bf16(acc[q + 6], acc[q + 7]));
    }
    ffn_reduce_chunk(tmHalf, stg, col + HALF * 32, row, w, wgid, leader);
}

__global__ void __launch_bounds__(F_THREADS, 1)
k_ffn(const __grid_constant__ CUtensorMap tmX2, const __grid_constant__ CUtensorMap tmW1, const __grid_constant__ CUtensorMap tmW2, const __grid_constant__ CUtensorMap tmOut,
      const __grid_constant__ CUtensorMap tmRes, const __grid_constant__ CUtensorMap tmHalf, const __nv_bfloat16* __restrict__ w2) {
    extern __shared__ __align__(1024) uint8_t smem[];
    const uint32_t sX = smem_u32(smem), sSt = sX + F_OFF_ST, bars = sX + F_OFF_BAR;
    const uint32_t full = bars, empty = bars + 64, fullX = bars + 128, fullH = bars + 208;
    const int tid = threadIdx.x, warp = __shfl_sync(~0u, tid >> 5, 0), lane = tid & 31;
    const int m = blockIdx.x >> 3, fs = blockIdx.x & 7;
    check_smem_base(sX);
    if (tid == 0) {
        prefetch_map(&tmW1); prefetch_map(&tmX2); prefetch_map(&tmW2); prefetch_map(&tmOut); prefetch_map(&tmRes); prefetch_map(&tmHalf);
        for (int i = 0; i < F_NST; i++) { mbar_init(full + i * 8, 1); mbar_init(empty + i * 8, 8); }
        for (int i = 0; i < 9; i++) mbar_init(fullX + i * 8, 1);
        mbar_init(fullH, 1); mbar_init(fullH + 8, 1);
        bar_init_fence();
        for (int kb = 0; kb < 9; kb++) mbar_expect(fullX + kb * 8, 16384);
    }
    __syncthreads();
    if (warp < 4) {
        asm volatile("setmaxnreg.dec.sync.aligned.u32 24;");
        if (warp == 1 && lane < 9) prefetch_l2(reinterpret_cast<const char*>(w2) + ((size_t)fs * 576 + m * 36 + lane * 4) * (DM * 2), 4 * DM * 2);
        if (warp == 0 && elect_one()) {
#pragma unroll 1
            for (int c = 0; c < 18; c++) {
                int col = c - 9 + fs;
                if (col >= 9) col -= 9;
#pragma unroll 1
                for (int j = 0; j < 6; j++) {
                    mbar_wait(empty + j * 8, (c & 1) ^ 1);
                    mbar_expect(full + j * 8, F_STAGE);
                    if (c < 9) tma_2d(sSt + j * F_STAGE, &tmW1, fs * 576 + c * 64, j * 96, full + j * 8);
                    else tma_2d(sSt + j * F_STAGE, &tmW2, col * 64, fs * 576 + j * 96, full + j * 8);
                }
            }
        }
    } else {
        asm volatile("setmaxnreg.inc.sync.aligned.u32 240;");
        const int wgid = (warp >> 2) - 1, w = warp & 3;
        pdl_wait();
        if (warp == 4 && elect_one()) {
            for (int kb = 0; kb < 9; kb++) tma_2d(sX + kb * 16384, &tmX2, kb * 64, m * 128, fullX + kb * 8);
        }
        __syncwarp();
        FfnPipe pp{full, empty, lane};
        const uint64_t xlo = cdesc(0, 16, 1024, 1) + wgid * 512;
        uint32_t h1[144];
        float acc0[32], acc1[32];
        ffn_phase1_chunk<0>(acc0, acc1, h1, pp, xlo, fullX);
        ffn_phase1_chunk<1>(acc1, acc0, h1, pp, xlo, fullX);
        ffn_phase1_chunk<2>(acc0, acc1, h1, pp, xlo, fullX);
        ffn_phase1_chunk<3>(acc1, acc0, h1, pp, xlo, fullX);
        ffn_phase1_chunk<4>(acc0, acc1, h1, pp, xlo, fullX);
        ffn_phase1_chunk<5>(acc1, acc0, h1, pp, xlo, fullX);
        ffn_phase1_chunk<6>(acc0, acc1, h1, pp, xlo, fullX);
        ffn_phase1_chunk<7>(acc1, acc0, h1, pp, xlo, fullX);
        ffn_phase1_chunk<8>(acc0, acc1, h1, pp, xlo, fullX);
        const int row = m * 128 + wgid * 64;
        const uint32_t stg = sX + wgid * 8192;
        int c = fs, cprev = 0;
        const bool leader = w == 0 && elect_one();
        const uint32_t myH = fullH + wgid * 8;
        ffn_phase2_chunk<0>(acc1, acc0, h1, pp, 1, &tmOut, 0, 0, row, w, lane, wgid, leader, myH, 0);
        if (leader) {
            const int c8 = fs == 0 ? 8 : fs - 1;
            mbar_expect(myH, fs == 0 ? 16384 : 8192);
            tma_2d(stg + 8 * 16384, &tmRes, c8 * 64, row, myH);
            if (fs == 0) tma_2d(stg + 7 * 16384, &tmRes, 7 * 64, row, myH);
        }
        cprev = c; if (++c == 9) c = 0;
#pragma unroll 1
        for (int j = 1; j < 7; j += 2) {
            ffn_phase2_chunk<1>(acc0, acc1, h1, pp, 0, &tmOut, stg + (j - 1) * 16384, cprev * 64, row, w, lane, wgid, leader, myH, 0);
            cprev = c; if (++c == 9) c = 0;
            ffn_phase2_chunk<1>(acc1, acc0, h1, pp, 1, &tmOut, stg + j * 16384, cprev * 64, row, w, lane, wgid, leader, myH, 0);
            cprev = c; if (++c == 9) c = 0;
        }
        ffn_phase2_chunk<2>(acc0, acc1, h1, pp, 0, &tmOut, stg + 6 * 16384, cprev * 64, row, w, lane, wgid, leader, myH, stg + 8 * 16384);
        cprev = c; if (++c == 9) c = 0;
        {
            const uint64_t dw = cdesc(F_OFF_ST, 8192, 1024, 1) + blockIdx.y * (c + 1);
            pin(acc1);
            ffn_half_group<0, 0>(acc1, h1, pp, dw);
            wg_wait<1>();
            pp.release(5);
            pin(acc0);
            ffn_stage_chunk(acc0, stg + 7 * 16384, w, lane, fs == 0, myH);
            ffn_half_group<0, 1>(acc1, h1, pp, dw);
            wg_wait<2>();
            ffn_reduce_chunk(&tmOut, stg + 7 * 16384, cprev * 64, row, w, wgid, leader);
            ffn_half_group<0, 2>(acc1, h1, pp, dw);
            ffn_half_group<0, 3>(acc1, h1, pp, dw);
            ffn_half_group<0, 4>(acc1, h1, pp, dw);
            ffn_half_group<0, 5>(acc1, h1, pp, dw);
            ffn_half_group<1, 0>(acc1, h1, pp, dw);
            ffn_half_group<1, 1>(acc1, h1, pp, dw);
            wg_wait<2>();
            ffn_store_half<0>(acc1, &tmHalf, stg + 8 * 16384, c * 64, row, w, lane, wgid, leader);
            ffn_half_group<1, 2>(acc1, h1, pp, dw);
            ffn_half_group<1, 3>(acc1, h1, pp, dw);
            ffn_half_group<1, 4>(acc1, h1, pp, dw);
            ffn_half_group<1, 5>(acc1, h1, pp, dw);
            wg_wait<0>();
            pin(acc1);
            ffn_store_half<1>(acc1, &tmHalf, stg + 8 * 16384 + 4096, c * 64, row, w, lane, wgid, leader);
        }
        if (leader) bulk_wait_all();
    }
}

typedef CUresult (*EncodeFn)(CUtensorMap*, CUtensorMapDataType, cuuint32_t, void*, const cuuint64_t*, const cuuint64_t*, const cuuint32_t*, const cuuint32_t*,
                             CUtensorMapInterleave, CUtensorMapSwizzle, CUtensorMapL2promotion, CUtensorMapFloatOOBfill);

CUtensorMap make_map(EncodeFn enc, const void* base, int rows, int cols, int box_rows, int box_cols = 64) {
    CUtensorMap tm;
    cuuint64_t dims[2] = {(cuuint64_t)cols, (cuuint64_t)rows};
    cuuint64_t strides[1] = {(cuuint64_t)cols * 2};
    cuuint32_t box[2] = {(cuuint32_t)box_cols, (cuuint32_t)box_rows};
    cuuint32_t es[2] = {1, 1};
    enc(&tm, CU_TENSOR_MAP_DATA_TYPE_BFLOAT16, 2, const_cast<void*>(base), dims, strides, box, es, CU_TENSOR_MAP_INTERLEAVE_NONE,
        box_cols == 64 ? CU_TENSOR_MAP_SWIZZLE_128B : CU_TENSOR_MAP_SWIZZLE_64B, CU_TENSOR_MAP_L2_PROMOTION_L2_256B, CU_TENSOR_MAP_FLOAT_OOB_FILL_NONE);
    return tm;
}

template <typename... KArgs, typename... Args>
void launch(void (*kern)(KArgs...), int grid, int block, int smem, bool pdl, Args... args) {
    cudaLaunchConfig_t cfg = {};
    cfg.gridDim = dim3(grid); cfg.blockDim = dim3(block); cfg.dynamicSmemBytes = smem; cfg.stream = cudaStreamPerThread;
    cudaLaunchAttribute at[1];
    at[0].id = cudaLaunchAttributeProgrammaticStreamSerialization;
    at[0].val.programmaticStreamSerializationAllowed = 1;
    cfg.attrs = at; cfg.numAttrs = pdl ? 1 : 0;
    cudaLaunchKernelEx(&cfg, kern, KArgs(args)...);
}

}

extern "C" void kernel_launch(void* const* d_in, const int* in_sizes, int n_in, void* d_out, int out_size) {
    const __nv_bfloat16* x = (const __nv_bfloat16*)d_in[0];
    const __nv_bfloat16* wq = (const __nv_bfloat16*)d_in[1];
    const __nv_bfloat16* wk = (const __nv_bfloat16*)d_in[2];
    const __nv_bfloat16* wv = (const __nv_bfloat16*)d_in[3];
    const __nv_bfloat16* wo = (const __nv_bfloat16*)d_in[4];
    const __nv_bfloat16* w1 = (const __nv_bfloat16*)d_in[6];
    const __nv_bfloat16* w2 = (const __nv_bfloat16*)d_in[7];
    __nv_bfloat16* out = (__nv_bfloat16*)d_out;

    static EncodeFn enc = nullptr;
    static void *p_o = nullptr, *p_x2 = nullptr, *p_q = nullptr, *p_res = nullptr;
    if (!enc) {
        cudaDriverEntryPointQueryResult qr;
        cudaGetDriverEntryPoint("cuTensorMapEncodeTiled", (void**)&enc, cudaEnableDefault, &qr);
        cudaGetSymbolAddress(&p_o, g_o);
        cudaGetSymbolAddress(&p_x2, g_x2);
        cudaGetSymbolAddress(&p_res, g_h);
        cudaGetSymbolAddress(&p_q, g_q);
        cudaFuncSetAttribute(k_qkv, cudaFuncAttributeMaxDynamicSharedMemorySize, Q_SMEM);
        cudaFuncSetAttribute(k_attn, cudaFuncAttributeMaxDynamicSharedMemorySize, A_SMEM);
        cudaFuncSetAttribute(k_oproj, cudaFuncAttributeMaxDynamicSharedMemorySize, O_SMEM);
        cudaFuncSetAttribute(k_ffn, cudaFuncAttributeMaxDynamicSharedMemorySize, F_SMEM);
    }
    const CUtensorMap tmWq = make_map(enc, wq, DM, DM, 192);
    const CUtensorMap tmWo = make_map(enc, wo, DM, DM, 64);
    const CUtensorMap tmO = make_map(enc, p_o, SEQ, DM, 64);
    const CUtensorMap tmX2st = make_map(enc, p_x2, SEQ, DM, 64);
    const CUtensorMap tmX2ld = make_map(enc, p_x2, SEQ, DM, 128);
    const CUtensorMap tmRes = make_map(enc, p_res, SEQ, DM, 64);
    const CUtensorMap tmQ = make_map(enc, p_q, SEQ, DM, 64);
    const CUtensorMap tmW1 = make_map(enc, w1, DM, FF, 96);
    const CUtensorMap tmW2 = make_map(enc, w2, FF, DM, 96);
    const CUtensorMap tmOut = make_map(enc, out, SEQ, DM, 64);
    const CUtensorMap tmHalf = make_map(enc, out, SEQ, DM, 64, 32);

    launch(k_qkv, 128, Q_THREADS, Q_SMEM, false, tmWq, tmQ, x, wk, wv);
    launch(k_attn, 128, A_THREADS, A_SMEM, true, out);
    launch(k_oproj, 96, O_THREADS, O_SMEM, true, tmO, tmWo, tmX2st, tmRes, x, w1);
    launch(k_ffn, 128, F_THREADS, F_SMEM, true, tmX2ld, tmW1, tmW2, tmOut, tmRes, tmHalf, w2);
}
```
